```python
import torch

def _softmax(x, axis=-1):
    return torch.softmax(x, dim=axis)
def _gelu(x):
    return torch.nn.functional.gelu(x, approximate="tanh")
def _silu(x):
    return torch.nn.functional.silu(x)
def _sigmoid(x):
    return torch.sigmoid(x)
def _layernorm(x, axis=-1, eps=1e-5):
    m = x.mean(dim=axis, keepdim=True)
    v = x.var(dim=axis, keepdim=True, unbiased=False)
    return (x - m) / torch.sqrt(v + eps)
def _scatter_add(tgt, idx, src, axis=0):
    return tgt.clone().index_add_(axis, idx, src)
def _segment_sum(src, seg, n):
    out = torch.zeros((n,) + src.shape[1:], dtype=src.dtype)
    return out.index_add_(0, seg, src)
def _pad(x, pw):
    flat = tuple(v for pair in reversed(pw) for v in pair)
    return torch.nn.functional.pad(x, flat)

kernel_name = 'interleave_layers__sliding_block__sliding_local_dilated__prompt'

def setup_inputs():

    _w = (lambda a: (lambda t: t.to(torch.bfloat16) if t.is_floating_point() else t)(torch.as_tensor(a)))
    def _A_setup():
        B, S, D = 1, 2048, 1024
        return {
            "x": _w((lambda *s: torch.randn(*s, dtype=torch.bfloat16) * 0.05)(B, S, D)),
            "wqkv": _w((lambda *s: torch.randn(*s, dtype=torch.bfloat16) * 0.05)(D, 3 * D)),
            "wo": _w((lambda *s: torch.randn(*s, dtype=torch.bfloat16) * 0.05)(D, D)),
        }
    _A_in = _A_setup()

    def _B_setup():
        B, S, D = 1, 2048, 1024
        return {
            "x": _w((lambda *s: torch.randn(*s, dtype=torch.bfloat16) * 0.05)(B, S, D)),
            "wqkv": _w((lambda *s: torch.randn(*s, dtype=torch.bfloat16) * 0.05)(D, 3 * D)),
            "wo": _w((lambda *s: torch.randn(*s, dtype=torch.bfloat16) * 0.05)(D, D)),
        }
    _B_in = _B_setup()

    return {
        "A_x": _A_in["x"],
        "A_wqkv": _A_in["wqkv"],
        "A_wo": _A_in["wo"],
        "B_x": _B_in["x"],
        "B_wqkv": _B_in["wqkv"],
        "B_wo": _B_in["wo"],
    }

def reference(A_x, A_wqkv, A_wo, B_x, B_wqkv, B_wo):
    def _A_ref(x, wqkv, wo):
        B, S, D = x.shape
        H = 32; Dh = D // H; W = 256
        qkv = (lambda x, *d: x.permute(*d))((x @ wqkv).reshape(B, S, 3, H, Dh), 2, 0, 3, 1, 4)
        q, k, v = qkv[0], qkv[1], qkv[2]
        scores = torch.einsum("bhqd,bhkd->bhqk", q, k) * (Dh ** -0.5)
        idx = torch.arange(S)
        mask = (idx[:, None] - idx[None, :] >= 0) & (idx[:, None] - idx[None, :] < W)
        scores = torch.where(mask[None, None], scores, -1e9)
        p = _softmax(scores, axis=-1)
        o = torch.einsum("bhqk,bhkd->bhqd", p, v)
        return (lambda x, *d: x.permute(*d))(o, 0, 2, 1, 3).reshape(B, S, D) @ wo

    def _B_ref(x, wqkv, wo):
        B, S, D = x.shape
        H = 32; Dh = D // H
        W, dil = 8, 2
        qkv = (lambda x, *d: x.permute(*d))((x @ wqkv).reshape(B, S, 3, H, Dh), 2, 0, 3, 1, 4)
        q, k, v = qkv[0], qkv[1], qkv[2]
        scale = Dh ** -0.5
        pos = torch.arange(S)
        off = torch.arange(W) * dil
        idx = pos[:, None] - off[None, :]
        mask = idx >= 0
        idx_c = torch.where(mask, idx, 0).reshape(-1)
        kg = k[:, :, idx_c, :].reshape(B, H, S, W, Dh)
        vg = v[:, :, idx_c, :].reshape(B, H, S, W, Dh)
        logits = torch.einsum("bhsd,bhswd->bhsw", q, kg) * scale
        logits = torch.where(mask[None, None, :, :], logits, -1e9)
        attn = _softmax(logits, axis=-1)
        o = torch.einsum("bhsw,bhswd->bhsd", attn, vg)
        return (lambda x, *d: x.permute(*d))(o, 0, 2, 1, 3).reshape(B, S, D) @ wo

    x = A_x
    x = x + _A_ref(_layernorm(x, axis=-1), A_wqkv, A_wo)
    x = x + _B_ref(_layernorm(x, axis=-1), B_wqkv, B_wo)
    x = x + _A_ref(_layernorm(x, axis=-1), A_wqkv, A_wo)
    x = x + _B_ref(_layernorm(x, axis=-1), B_wqkv, B_wo)
    return x
```

```cpp
#include <cuda_runtime.h>
#include <cuda_bf16.h>
#include <cuda.h>
#include <stdint.h>

namespace {

constexpr int S_LEN = 2048;
constexpr int DM = 1024;
constexpr int NQKV = 3072;
constexpr int NCTA = 128;

__device__ __align__(1024) uint8_t g_kvA[2][16][16][2][16384];
__device__ __align__(1024) uint8_t g_kvB[2][16][16][4096];
__device__ __align__(1024) uint8_t g_zero[16384];
__device__ __align__(1024) __nv_bfloat16 g_o[S_LEN * DM];
__device__ __align__(1024) __nv_bfloat16 g_x[S_LEN * DM];
__device__ __align__(1024) float4 g_stats[4][8][S_LEN];
__device__ __align__(1024) float4 g_cs[2][16][8][64];
constexpr int F_X = 0;
constexpr int XSTR = 32, OSTR = 32, KSTR = 32;
constexpr int F_O = F_X + 16 * XSTR;
constexpr int F_KV = F_O + 32 * OSTR;
constexpr int F_DONE = F_KV + 256 * KSTR;
__device__ __align__(1024) unsigned g_flags[F_DONE + 32];

constexpr uint32_t SBASE = 1024;
constexpr int UNIT = 8192;
constexpr int NUNITS = 20;
constexpr int OFF_SLOT = NUNITS * UNIT;
constexpr int OFF_BAR = OFF_SLOT + 4 * 16384;
constexpr int OFF_EPOCH = OFF_BAR + 280;
constexpr int OFF_CS = OFF_BAR + 288;
constexpr int OFF_RS = OFF_CS + 1536;
constexpr int SMEM_BYTES = OFF_RS + 1024;
constexpr int B_FULL = 0, B_EMPTY = 8, B_PREP = 16, B_HALO = 18, B_REL = 22, B_AFREE = 25, B_TURN = 26, B_XRDY = 28,
              B_CS = 30, B_CSD = 31, B_GO = 32, B_PRE = 33;

__device__ __forceinline__ uint32_t smem_u32(const void* p) { return (uint32_t)__cvta_generic_to_shared(p); }

__device__ __forceinline__ void mbar_init(uint32_t bar, uint32_t cnt) {
  asm volatile("mbarrier.init.shared::cta.b64 [%0], %1;" ::"r"(bar), "r"(cnt));
}
__device__ __forceinline__ void mbar_expect_tx(uint32_t bar, uint32_t bytes) {
  asm volatile("mbarrier.arrive.expect_tx.shared::cta.b64 _, [%0], %1;" ::"r"(bar), "r"(bytes) : "memory");
}
__device__ __forceinline__ void mbar_arrive(uint32_t bar) {
  asm volatile("mbarrier.arrive.shared::cta.b64 _, [%0];" ::"r"(bar) : "memory");
}
__device__ __forceinline__ bool mbar_try_wait(uint32_t bar, uint32_t parity) {
  uint32_t ok;
  asm volatile(
      "{\n.reg .pred p;\nmbarrier.try_wait.parity.shared::cta.b64 p, [%1], %2;\nselp.b32 %0, 1, 0, p;\n}\n"
      : "=r"(ok)
      : "r"(bar), "r"(parity)
      : "memory");
  return ok != 0;
}
__device__ __forceinline__ bool mbar_test(uint32_t bar, uint32_t parity) {
  uint32_t ok;
  asm volatile(
      "{\n.reg .pred p;\nmbarrier.test_wait.parity.shared::cta.b64 p, [%1], %2;\nselp.b32 %0, 1, 0, p;\n}\n"
      : "=r"(ok)
      : "r"(bar), "r"(parity)
      : "memory");
  return ok != 0;
}
__device__ __forceinline__ void mbar_wait(uint32_t bar, uint32_t parity) {
#pragma unroll 1
  for (uint32_t it = 0; it < (1u << 18); ++it) {
    if (mbar_try_wait(bar, parity)) return;
  }
}
__device__ __forceinline__ void mbar_pace(uint32_t bar, uint32_t parity) {
#pragma unroll 1
  for (uint32_t it = 0; it < 24; ++it) {
    if (mbar_try_wait(bar, parity)) return;
  }
}
template <int NS>
__device__ __forceinline__ void mbar_wait_lazy(uint32_t bar, uint32_t parity) {
#pragma unroll 1
  for (uint32_t it = 0; it < (1u << 18); ++it) {
    if (mbar_try_wait(bar, parity)) return;
    __nanosleep(NS);
  }
}
__device__ __forceinline__ bool elect_one() {
  uint32_t ok;
  asm volatile("{\n.reg .pred p;\nelect.sync _|p, 0xffffffff;\nselp.b32 %0, 1, 0, p;\n}\n" : "=r"(ok));
  return ok != 0;
}
__device__ __forceinline__ void fence_barrier_init() { asm volatile("fence.mbarrier_init.release.cluster;" ::: "memory"); }
__device__ __forceinline__ void fence_proxy_async_smem() { asm volatile("fence.proxy.async.shared::cta;" ::: "memory"); }
__device__ __forceinline__ void fence_proxy_async_all() { asm volatile("fence.proxy.async.global;" ::: "memory"); }

__device__ __forceinline__ void tma_load_2d(uint32_t dst, const CUtensorMap* map, uint32_t bar, int c0, int c1) {
  asm volatile(
      "cp.async.bulk.tensor.2d.shared::cluster.global.mbarrier::complete_tx::bytes [%0], [%1, {%3, %4}], [%2];" ::"r"(dst),
      "l"(map), "r"(bar), "r"(c0), "r"(c1)
      : "memory");
}
__device__ __forceinline__ void bulk_load(uint32_t dst, const void* src, uint32_t bytes, uint32_t bar) {
  asm volatile("cp.async.bulk.shared::cluster.global.mbarrier::complete_tx::bytes [%0], [%1], %2, [%3];" ::"r"(dst),
               "l"(src), "r"(bytes), "r"(bar)
               : "memory");
}
__device__ __forceinline__ void bulk_store(void* dst, uint32_t src, uint32_t bytes) {
  asm volatile("cp.async.bulk.global.shared::cta.bulk_group [%0], [%1], %2;" ::"l"(dst), "r"(src), "r"(bytes) : "memory");
}
__device__ __forceinline__ void tma_store_2d(const CUtensorMap* map, uint32_t src, int c0, int c1) {
  asm volatile("cp.async.bulk.tensor.2d.global.shared::cta.bulk_group [%0, {%2, %3}], [%1];" ::"l"(map), "r"(src),
               "r"(c0), "r"(c1)
               : "memory");
}
__device__ __forceinline__ void bulk_commit() { asm volatile("cp.async.bulk.commit_group;" ::: "memory"); }
__device__ __forceinline__ void bulk_wait_read0() { asm volatile("cp.async.bulk.wait_group.read 0;" ::: "memory"); }
__device__ __forceinline__ void bulk_wait0() { asm volatile("cp.async.bulk.wait_group 0;" ::: "memory"); }
__device__ __forceinline__ void named_bar_sync(int id, int nthreads) {
  asm volatile("bar.sync %0, %1;" ::"r"(id), "r"(nthreads) : "memory");
}
__device__ __forceinline__ void named_bar_arrive(int id, int nthreads) {
  asm volatile("bar.arrive %0, %1;" ::"r"(id), "r"(nthreads) : "memory");
}

__device__ __forceinline__ void wgmma_fence() { asm volatile("wgmma.fence.sync.aligned;\n" ::: "memory"); }
__device__ __forceinline__ void wgmma_commit() { asm volatile("wgmma.commit_group.sync.aligned;\n" ::: "memory"); }
template <int N>
__device__ __forceinline__ void wgmma_wait() {
  asm volatile("wgmma.wait_group.sync.aligned %0;\n" ::"n"(N) : "memory");
}
template <int R>
__device__ __forceinline__ void setmaxnreg_inc() { asm volatile("setmaxnreg.inc.sync.aligned.u32 %0;\n" ::"n"(R)); }
template <int R>
__device__ __forceinline__ void setmaxnreg_dec() { asm volatile("setmaxnreg.dec.sync.aligned.u32 %0;\n" ::"n"(R)); }
template <int N>
__device__ __forceinline__ void reg_fence(float* r) {
#pragma unroll
  for (int i = 0; i < N; i++) asm volatile("" : "+f"(r[i])::"memory");
}

template <int N>
__device__ __forceinline__ void reg_define(float* r) {
#pragma unroll
  for (int i = 0; i < N; i++) r[i] = 0.f;
}

__device__ __forceinline__ uint64_t desc_lo(uint32_t lo) {
  uint64_t d;
  asm("mov.b64 %0, {%1, %2};" : "=l"(d) : "r"(lo), "r"(0x40000040u));
  return d;
}
__device__ __forceinline__ uint64_t make_desc(uint32_t addr, uint32_t lbo_bytes) {
  return desc_lo((addr >> 4) + ((lbo_bytes >> 4) << 16));
}

__device__ __forceinline__ void wgmma_n192_ss_ta0_tb1(float* d, uint64_t descA, uint64_t descB, int scaleD) {
  asm volatile("{\n.reg .pred p;\nsetp.ne.b32 p, %98, 0;\n"
    "wgmma.mma_async.sync.aligned.m64n192k16.f32.bf16.bf16 {%0, %1, %2, %3, %4, %5, %6, %7, %8, %9, %10, %11, %12, %13, %14, %15, %16, %17, %18, %19, %20, %21, %22, %23, %24, %25, %26, %27, %28, %29, %30, %31, %32, %33, %34, %35, %36, %37, %38, %39, %40, %41, %42, %43, %44, %45, %46, %47, %48, %49, %50, %51, %52, %53, %54, %55, %56, %57, %58, %59, %60, %61, %62, %63, %64, %65, %66, %67, %68, %69, %70, %71, %72, %73, %74, %75, %76, %77, %78, %79, %80, %81, %82, %83, %84, %85, %86, %87, %88, %89, %90, %91, %92, %93, %94, %95}, %96, %97, p, 1, 1, 0, 1;\n}\n"
    : "+f"(d[0]), "+f"(d[1]), "+f"(d[2]), "+f"(d[3]), "+f"(d[4]), "+f"(d[5]), "+f"(d[6]), "+f"(d[7]), "+f"(d[8]), "+f"(d[9]), "+f"(d[10]), "+f"(d[11]), "+f"(d[12]), "+f"(d[13]), "+f"(d[14]), "+f"(d[15]), "+f"(d[16]), "+f"(d[17]), "+f"(d[18]), "+f"(d[19]), "+f"(d[20]), "+f"(d[21]), "+f"(d[22]), "+f"(d[23]), "+f"(d[24]), "+f"(d[25]), "+f"(d[26]), "+f"(d[27]), "+f"(d[28]), "+f"(d[29]), "+f"(d[30]), "+f"(d[31]), "+f"(d[32]), "+f"(d[33]), "+f"(d[34]), "+f"(d[35]), "+f"(d[36]), "+f"(d[37]), "+f"(d[38]), "+f"(d[39]), "+f"(d[40]), "+f"(d[41]), "+f"(d[42]), "+f"(d[43]), "+f"(d[44]), "+f"(d[45]), "+f"(d[46]), "+f"(d[47]), "+f"(d[48]), "+f"(d[49]), "+f"(d[50]), "+f"(d[51]), "+f"(d[52]), "+f"(d[53]), "+f"(d[54]), "+f"(d[55]), "+f"(d[56]), "+f"(d[57]), "+f"(d[58]), "+f"(d[59]), "+f"(d[60]), "+f"(d[61]), "+f"(d[62]), "+f"(d[63]), "+f"(d[64]), "+f"(d[65]), "+f"(d[66]), "+f"(d[67]), "+f"(d[68]), "+f"(d[69]), "+f"(d[70]), "+f"(d[71]), "+f"(d[72]), "+f"(d[73]), "+f"(d[74]), "+f"(d[75]), "+f"(d[76]), "+f"(d[77]), "+f"(d[78]), "+f"(d[79]), "+f"(d[80]), "+f"(d[81]), "+f"(d[82]), "+f"(d[83]), "+f"(d[84]), "+f"(d[85]), "+f"(d[86]), "+f"(d[87]), "+f"(d[88]), "+f"(d[89]), "+f"(d[90]), "+f"(d[91]), "+f"(d[92]), "+f"(d[93]), "+f"(d[94]), "+f"(d[95])
    : "l"(descA), "l"(descB), "r"(scaleD));
}

__device__ __forceinline__ void wgmma_n128_ss_ta0_tb1(float* d, uint64_t descA, uint64_t descB, int scaleD) {
  asm volatile("{\n.reg .pred p;\nsetp.ne.b32 p, %66, 0;\n"
    "wgmma.mma_async.sync.aligned.m64n128k16.f32.bf16.bf16 {%0, %1, %2, %3, %4, %5, %6, %7, %8, %9, %10, %11, %12, %13, %14, %15, %16, %17, %18, %19, %20, %21, %22, %23, %24, %25, %26, %27, %28, %29, %30, %31, %32, %33, %34, %35, %36, %37, %38, %39, %40, %41, %42, %43, %44, %45, %46, %47, %48, %49, %50, %51, %52, %53, %54, %55, %56, %57, %58, %59, %60, %61, %62, %63}, %64, %65, p, 1, 1, 0, 1;\n}\n"
    : "+f"(d[0]), "+f"(d[1]), "+f"(d[2]), "+f"(d[3]), "+f"(d[4]), "+f"(d[5]), "+f"(d[6]), "+f"(d[7]), "+f"(d[8]), "+f"(d[9]), "+f"(d[10]), "+f"(d[11]), "+f"(d[12]), "+f"(d[13]), "+f"(d[14]), "+f"(d[15]), "+f"(d[16]), "+f"(d[17]), "+f"(d[18]), "+f"(d[19]), "+f"(d[20]), "+f"(d[21]), "+f"(d[22]), "+f"(d[23]), "+f"(d[24]), "+f"(d[25]), "+f"(d[26]), "+f"(d[27]), "+f"(d[28]), "+f"(d[29]), "+f"(d[30]), "+f"(d[31]), "+f"(d[32]), "+f"(d[33]), "+f"(d[34]), "+f"(d[35]), "+f"(d[36]), "+f"(d[37]), "+f"(d[38]), "+f"(d[39]), "+f"(d[40]), "+f"(d[41]), "+f"(d[42]), "+f"(d[43]), "+f"(d[44]), "+f"(d[45]), "+f"(d[46]), "+f"(d[47]), "+f"(d[48]), "+f"(d[49]), "+f"(d[50]), "+f"(d[51]), "+f"(d[52]), "+f"(d[53]), "+f"(d[54]), "+f"(d[55]), "+f"(d[56]), "+f"(d[57]), "+f"(d[58]), "+f"(d[59]), "+f"(d[60]), "+f"(d[61]), "+f"(d[62]), "+f"(d[63])
    : "l"(descA), "l"(descB), "r"(scaleD));
}

__device__ __forceinline__ void wgmma_n192_ssz_ta0_tb1(float* d, uint64_t descA, uint64_t descB) {
  asm volatile("{\n.reg .pred p;\nsetp.ne.b32 p, 0, 0;\n"
    "wgmma.mma_async.sync.aligned.m64n192k16.f32.bf16.bf16 {%0, %1, %2, %3, %4, %5, %6, %7, %8, %9, %10, %11, %12, %13, %14, %15, %16, %17, %18, %19, %20, %21, %22, %23, %24, %25, %26, %27, %28, %29, %30, %31, %32, %33, %34, %35, %36, %37, %38, %39, %40, %41, %42, %43, %44, %45, %46, %47, %48, %49, %50, %51, %52, %53, %54, %55, %56, %57, %58, %59, %60, %61, %62, %63, %64, %65, %66, %67, %68, %69, %70, %71, %72, %73, %74, %75, %76, %77, %78, %79, %80, %81, %82, %83, %84, %85, %86, %87, %88, %89, %90, %91, %92, %93, %94, %95}, %96, %97, p, 1, 1, 0, 1;\n}\n"
    : "=f"(d[0]), "=f"(d[1]), "=f"(d[2]), "=f"(d[3]), "=f"(d[4]), "=f"(d[5]), "=f"(d[6]), "=f"(d[7]), "=f"(d[8]), "=f"(d[9]), "=f"(d[10]), "=f"(d[11]), "=f"(d[12]), "=f"(d[13]), "=f"(d[14]), "=f"(d[15]), "=f"(d[16]), "=f"(d[17]), "=f"(d[18]), "=f"(d[19]), "=f"(d[20]), "=f"(d[21]), "=f"(d[22]), "=f"(d[23]), "=f"(d[24]), "=f"(d[25]), "=f"(d[26]), "=f"(d[27]), "=f"(d[28]), "=f"(d[29]), "=f"(d[30]), "=f"(d[31]), "=f"(d[32]), "=f"(d[33]), "=f"(d[34]), "=f"(d[35]), "=f"(d[36]), "=f"(d[37]), "=f"(d[38]), "=f"(d[39]), "=f"(d[40]), "=f"(d[41]), "=f"(d[42]), "=f"(d[43]), "=f"(d[44]), "=f"(d[45]), "=f"(d[46]), "=f"(d[47]), "=f"(d[48]), "=f"(d[49]), "=f"(d[50]), "=f"(d[51]), "=f"(d[52]), "=f"(d[53]), "=f"(d[54]), "=f"(d[55]), "=f"(d[56]), "=f"(d[57]), "=f"(d[58]), "=f"(d[59]), "=f"(d[60]), "=f"(d[61]), "=f"(d[62]), "=f"(d[63]), "=f"(d[64]), "=f"(d[65]), "=f"(d[66]), "=f"(d[67]), "=f"(d[68]), "=f"(d[69]), "=f"(d[70]), "=f"(d[71]), "=f"(d[72]), "=f"(d[73]), "=f"(d[74]), "=f"(d[75]), "=f"(d[76]), "=f"(d[77]), "=f"(d[78]), "=f"(d[79]), "=f"(d[80]), "=f"(d[81]), "=f"(d[82]), "=f"(d[83]), "=f"(d[84]), "=f"(d[85]), "=f"(d[86]), "=f"(d[87]), "=f"(d[88]), "=f"(d[89]), "=f"(d[90]), "=f"(d[91]), "=f"(d[92]), "=f"(d[93]), "=f"(d[94]), "=f"(d[95])
    : "l"(descA), "l"(descB));
}

__device__ __forceinline__ void wgmma_n128_ssz_ta0_tb1(float* d, uint64_t descA, uint64_t descB) {
  asm volatile("{\n.reg .pred p;\nsetp.ne.b32 p, 0, 0;\n"
    "wgmma.mma_async.sync.aligned.m64n128k16.f32.bf16.bf16 {%0, %1, %2, %3, %4, %5, %6, %7, %8, %9, %10, %11, %12, %13, %14, %15, %16, %17, %18, %19, %20, %21, %22, %23, %24, %25, %26, %27, %28, %29, %30, %31, %32, %33, %34, %35, %36, %37, %38, %39, %40, %41, %42, %43, %44, %45, %46, %47, %48, %49, %50, %51, %52, %53, %54, %55, %56, %57, %58, %59, %60, %61, %62, %63}, %64, %65, p, 1, 1, 0, 1;\n}\n"
    : "=f"(d[0]), "=f"(d[1]), "=f"(d[2]), "=f"(d[3]), "=f"(d[4]), "=f"(d[5]), "=f"(d[6]), "=f"(d[7]), "=f"(d[8]), "=f"(d[9]), "=f"(d[10]), "=f"(d[11]), "=f"(d[12]), "=f"(d[13]), "=f"(d[14]), "=f"(d[15]), "=f"(d[16]), "=f"(d[17]), "=f"(d[18]), "=f"(d[19]), "=f"(d[20]), "=f"(d[21]), "=f"(d[22]), "=f"(d[23]), "=f"(d[24]), "=f"(d[25]), "=f"(d[26]), "=f"(d[27]), "=f"(d[28]), "=f"(d[29]), "=f"(d[30]), "=f"(d[31]), "=f"(d[32]), "=f"(d[33]), "=f"(d[34]), "=f"(d[35]), "=f"(d[36]), "=f"(d[37]), "=f"(d[38]), "=f"(d[39]), "=f"(d[40]), "=f"(d[41]), "=f"(d[42]), "=f"(d[43]), "=f"(d[44]), "=f"(d[45]), "=f"(d[46]), "=f"(d[47]), "=f"(d[48]), "=f"(d[49]), "=f"(d[50]), "=f"(d[51]), "=f"(d[52]), "=f"(d[53]), "=f"(d[54]), "=f"(d[55]), "=f"(d[56]), "=f"(d[57]), "=f"(d[58]), "=f"(d[59]), "=f"(d[60]), "=f"(d[61]), "=f"(d[62]), "=f"(d[63])
    : "l"(descA), "l"(descB));
}

__device__ __forceinline__ void wgmma_n64_rs_tb0(float* d, const uint32_t* a, uint64_t descB, int scaleD) {
  asm volatile("{\n.reg .pred p;\nsetp.ne.b32 p, %37, 0;\n"
    "wgmma.mma_async.sync.aligned.m64n64k16.f32.bf16.bf16 {%0, %1, %2, %3, %4, %5, %6, %7, %8, %9, %10, %11, %12, %13, %14, %15, %16, %17, %18, %19, %20, %21, %22, %23, %24, %25, %26, %27, %28, %29, %30, %31}, {%32, %33, %34, %35}, %36, p, 1, 1, 0;\n}\n"
    : "+f"(d[0]), "+f"(d[1]), "+f"(d[2]), "+f"(d[3]), "+f"(d[4]), "+f"(d[5]), "+f"(d[6]), "+f"(d[7]), "+f"(d[8]), "+f"(d[9]), "+f"(d[10]), "+f"(d[11]), "+f"(d[12]), "+f"(d[13]), "+f"(d[14]), "+f"(d[15]), "+f"(d[16]), "+f"(d[17]), "+f"(d[18]), "+f"(d[19]), "+f"(d[20]), "+f"(d[21]), "+f"(d[22]), "+f"(d[23]), "+f"(d[24]), "+f"(d[25]), "+f"(d[26]), "+f"(d[27]), "+f"(d[28]), "+f"(d[29]), "+f"(d[30]), "+f"(d[31])
    : "r"(a[0]), "r"(a[1]), "r"(a[2]), "r"(a[3]), "l"(descB), "r"(scaleD));
}

__device__ __forceinline__ void wgmma_n80_ss_ta0_tb0(float* d, uint64_t descA, uint64_t descB, int scaleD) {
  asm volatile("{\n.reg .pred p;\nsetp.ne.b32 p, %42, 0;\n"
    "wgmma.mma_async.sync.aligned.m64n80k16.f32.bf16.bf16 {%0, %1, %2, %3, %4, %5, %6, %7, %8, %9, %10, %11, %12, %13, %14, %15, %16, %17, %18, %19, %20, %21, %22, %23, %24, %25, %26, %27, %28, %29, %30, %31, %32, %33, %34, %35, %36, %37, %38, %39}, %40, %41, p, 1, 1, 0, 0;\n}\n"
    : "+f"(d[0]), "+f"(d[1]), "+f"(d[2]), "+f"(d[3]), "+f"(d[4]), "+f"(d[5]), "+f"(d[6]), "+f"(d[7]), "+f"(d[8]), "+f"(d[9]), "+f"(d[10]), "+f"(d[11]), "+f"(d[12]), "+f"(d[13]), "+f"(d[14]), "+f"(d[15]), "+f"(d[16]), "+f"(d[17]), "+f"(d[18]), "+f"(d[19]), "+f"(d[20]), "+f"(d[21]), "+f"(d[22]), "+f"(d[23]), "+f"(d[24]), "+f"(d[25]), "+f"(d[26]), "+f"(d[27]), "+f"(d[28]), "+f"(d[29]), "+f"(d[30]), "+f"(d[31]), "+f"(d[32]), "+f"(d[33]), "+f"(d[34]), "+f"(d[35]), "+f"(d[36]), "+f"(d[37]), "+f"(d[38]), "+f"(d[39])
    : "l"(descA), "l"(descB), "r"(scaleD));
}

__device__ __forceinline__ void wgmma_n32_rs_tb1(float* d, const uint32_t* a, uint64_t descB, int scaleD) {
  asm volatile("{\n.reg .pred p;\nsetp.ne.b32 p, %21, 0;\n"
    "wgmma.mma_async.sync.aligned.m64n32k16.f32.bf16.bf16 {%0, %1, %2, %3, %4, %5, %6, %7, %8, %9, %10, %11, %12, %13, %14, %15}, {%16, %17, %18, %19}, %20, p, 1, 1, 1;\n}\n"
    : "+f"(d[0]), "+f"(d[1]), "+f"(d[2]), "+f"(d[3]), "+f"(d[4]), "+f"(d[5]), "+f"(d[6]), "+f"(d[7]), "+f"(d[8]), "+f"(d[9]), "+f"(d[10]), "+f"(d[11]), "+f"(d[12]), "+f"(d[13]), "+f"(d[14]), "+f"(d[15])
    : "r"(a[0]), "r"(a[1]), "r"(a[2]), "r"(a[3]), "l"(descB), "r"(scaleD));
}

__device__ __forceinline__ uint32_t pack_bf16x2(float lo, float hi) {
  uint32_t r;
  asm("cvt.rn.bf16x2.f32 %0, %1, %2;" : "=r"(r) : "f"(hi), "f"(lo));
  return r;
}
__device__ __forceinline__ float bf_lo(uint32_t p) { return __uint_as_float(p << 16); }
__device__ __forceinline__ float bf_hi(uint32_t p) { return __uint_as_float(p & 0xffff0000u); }
__device__ __forceinline__ float bf16_round(float v) { return __bfloat162float(__float2bfloat16_rn(v)); }
__device__ __forceinline__ float ex2_approx(float x) {
  float r;
  asm("ex2.approx.ftz.f32 %0, %1;" : "=f"(r) : "f"(x));
  return r;
}
__device__ __forceinline__ float rcp_fast(float x) {
  float r;
  asm("rcp.approx.ftz.f32 %0, %1;" : "=f"(r) : "f"(x));
  return r;
}
__device__ __forceinline__ void ldmatrix_x4(uint32_t (&r)[4], uint32_t addr) {
  asm volatile("ldmatrix.sync.aligned.m8n8.x4.shared.b16 {%0,%1,%2,%3}, [%4];"
               : "=r"(r[0]), "=r"(r[1]), "=r"(r[2]), "=r"(r[3])
               : "r"(addr)
               : "memory");
}
__device__ __forceinline__ void stmatrix_x4(uint32_t addr, uint32_t r0, uint32_t r1, uint32_t r2, uint32_t r3) {
  asm volatile("stmatrix.sync.aligned.m8n8.x4.shared.b16 [%0], {%1,%2,%3,%4};" ::"r"(addr), "r"(r0), "r"(r1), "r"(r2),
               "r"(r3));
}
__device__ __forceinline__ uint32_t add_bf16x2(uint32_t a, uint32_t b) {
  uint32_t r;
  asm("add.rn.bf16x2 %0, %1, %2;" : "=r"(r) : "r"(a), "r"(b));
  return r;
}
__device__ __forceinline__ uint4 lds128(uint32_t addr) {
  uint4 v;
  asm volatile("ld.shared.v4.b32 {%0,%1,%2,%3}, [%4];" : "=r"(v.x), "=r"(v.y), "=r"(v.z), "=r"(v.w) : "r"(addr) : "memory");
  return v;
}
__device__ __forceinline__ uint32_t lds32(uint32_t addr) {
  uint32_t v;
  asm volatile("ld.shared.b32 %0, [%1];" : "=r"(v) : "r"(addr) : "memory");
  return v;
}
__device__ __forceinline__ void sts32(uint32_t addr, uint32_t v) {
  asm volatile("st.shared.b32 [%0], %1;" ::"r"(addr), "r"(v) : "memory");
}

__device__ __forceinline__ unsigned ld_acquire_u32(const unsigned* p) {
  unsigned v;
  asm volatile("ld.acquire.gpu.global.u32 %0, [%1];" : "=r"(v) : "l"(p) : "memory");
  return v;
}
__device__ __forceinline__ void red_relaxed_add(unsigned* p, unsigned v) {
  asm volatile("red.relaxed.gpu.global.add.u32 [%0], %1;" ::"l"(p), "r"(v) : "memory");
}
__device__ __forceinline__ void wait_ge(const unsigned* p, unsigned target) {
#pragma unroll 1
  for (uint32_t it = 0; it < (1u << 17); ++it) {
    if ((int)(ld_acquire_u32(p) - target) >= 0) return;
  }
}

template <bool SLOW>
__device__ __forceinline__ void wait_mask(const unsigned* f, int cnt, unsigned target, uint32_t need, uint32_t& seen, int lane) {
  if ((seen & need) == need) return;
  const unsigned* fp = f + (lane & (cnt - 1));
#pragma unroll 1
  for (uint32_t it = 0; it < (1u << 17); ++it) {
    seen = __ballot_sync(0xffffffffu, (int)(ld_acquire_u32(fp) - target) >= 0);
    if ((seen & need) == need) break;
    if (SLOW) __nanosleep(400);
  }
  fence_proxy_async_all();
}
__device__ __forceinline__ float4 ld_rec(const float4* p) {
  float4 v;
  asm volatile("ld.relaxed.gpu.global.v4.f32 {%0,%1,%2,%3}, [%4];" : "=f"(v.x), "=f"(v.y), "=f"(v.z), "=f"(v.w) : "l"(p) : "memory");
  return v;
}
__device__ __forceinline__ void st_rec(float4* p, float a, float b, float c, unsigned tag) {
  asm volatile("st.relaxed.gpu.global.v4.f32 [%0], {%1,%2,%3,%4};" ::"l"(p), "f"(a), "f"(b), "f"(c), "f"(__uint_as_float(tag)) : "memory");
}
template <int N>
__device__ __forceinline__ float4 sum_recs(const float4* p, int stride, unsigned tag) {
  float4 s;
#pragma unroll 1
  for (uint32_t it = 0; it < (1u << 17); ++it) {
    float4 v[N];
#pragma unroll
    for (int t = 0; t < N; t++) v[t] = ld_rec(p + t * stride);
    bool ok = true;
    s = make_float4(0.f, 0.f, 0.f, 0.f);
#pragma unroll
    for (int t = 0; t < N; t++) {
      ok &= __float_as_uint(v[t].w) == tag;
      s.x += v[t].x;
      s.y += v[t].y;
      s.z += v[t].z;
    }
    if (ok) break;
    __nanosleep(200);
  }
  return s;
}

__device__ __forceinline__ int fresh_tid() {
  int t;
  asm volatile("mov.u32 %0, %%tid.x;" : "=r"(t));
  return t;
}
#define PHASE_IDS                                  \
  const int tid_ = fresh_tid();                    \
  const int lane = tid_ & 31, wwarp = __shfl_sync(0xffffffffu, (tid_ >> 5) & 3, 0), tid = tid_ & 127; \
  const int g = lane >> 2, c = lane & 3;           \
  (void)tid; (void)g; (void)c; (void)wwarp;

#define GTL(i) do { } while (0)
#define GTLX(c, i) do { } while (0)
#define TGET(v) do { } while (0)
#define TPUT(c, i, v) do { } while (0)

constexpr float SM_C = 0.17677669529663687f * 1.4426950408889634f;

__device__ __forceinline__ void sched_fence(uint32_t never) {
  asm volatile("{\n.reg .pred p;\nSF%=:\nsetp.ne.u32 p, %0, 0;\n@p nanosleep.u32 32;\n@p bra.uni SF%=;\n}\n" ::"r"(never) : "memory");
}

__device__ __forceinline__ void attn_soft(float (&s)[32], float (&mneg)[2], int i, bool valid, int dbase) {
  if ((i & 3) == 0) {
   if (i == 0) {
#pragma unroll
    for (int k = 0; k < 32; k++)
      if (8 * (k >> 2) + (k & 1) - 8 * ((k >> 1) & 1) > dbase) s[k] = -INFINITY;
#pragma unroll
    for (int r = 0; r < 2; r++) {
      float mx = fmaxf(fmaxf(fmaxf(s[2 * r], s[2 * r + 1]), fmaxf(s[4 + 2 * r], s[4 + 2 * r + 1])),
                       fmaxf(fmaxf(s[8 + 2 * r], s[8 + 2 * r + 1]), fmaxf(s[12 + 2 * r], s[12 + 2 * r + 1])));
      mx = fmaxf(mx, __shfl_xor_sync(0xffffffffu, mx, 1));
      mx = fmaxf(mx, __shfl_xor_sync(0xffffffffu, mx, 2));
      mneg[r] = -SM_C * mx;
    }
   } else {
#pragma unroll
    for (int k = 0; k < 32; k++)
      if (8 * (k >> 2) + (k & 1) - 8 * ((k >> 1) & 1) <= dbase) s[k] = -INFINITY;
   }
  }
  const float m0 = valid ? mneg[0] : -INFINITY, m1 = valid ? mneg[1] : -INFINITY;
#pragma unroll
  for (int k = 0; k < 32; k++) s[k] = ex2_approx(fmaf(s[k], SM_C, (k & 2) ? m1 : m0));
}

template <bool NEXT>
__device__ __forceinline__ void attn_mma(float (&s)[32], float (&o)[16], float (&l)[2], uint32_t vdesc,
                                         const uint32_t (&q)[2][4], uint32_t kdesc) {
  uint32_t p[4][4];
#pragma unroll
  for (int k = 0; k < 16; k++) p[k >> 2][k & 3] = pack_bf16x2(s[2 * k], s[2 * k + 1]);
  wgmma_fence();
  if (NEXT) {
    wgmma_n64_rs_tb0(s, q[0], desc_lo(kdesc), 0);
    wgmma_n64_rs_tb0(s, q[1], desc_lo(kdesc + 2), 1);
    wgmma_commit();
  }
#pragma unroll
  for (int k = 0; k < 4; k++) wgmma_n32_rs_tb1(o, p[k], desc_lo(vdesc + k * 128), 1);
  wgmma_commit();
#pragma unroll
  for (int r = 0; r < 2; r++) {
    const uint32_t t0 = add_bf16x2(add_bf16x2(p[0][r], p[0][2 + r]), add_bf16x2(p[1][r], p[1][2 + r]));
    const uint32_t t1 = add_bf16x2(add_bf16x2(p[2][r], p[2][2 + r]), add_bf16x2(p[3][r], p[3][2 + r]));
    l[r] += (bf_lo(t0) + bf_hi(t0)) + (bf_lo(t1) + bf_hi(t1));
  }
}

__device__ __forceinline__ void attn_a_slow(const uint8_t* __restrict__ kvimg, int L, int gb, int hp,
                                         int hh, int wwarp, int lane) {
  constexpr uint32_t sq = SBASE + OFF_SLOT + 3 * 16384;
  wait_ge(g_flags + F_KV + (gb * 16 + hp) * KSTR, 8u * ((*(volatile unsigned*)(g_flags + F_DONE)) / NCTA) + 2u * L + 2u);
#pragma unroll 1
  for (int t = 0; t < 32; t++) {
    const int row = (t >> 4) * 64 + wwarp * 16 + (t & 15);
    const int qpos = gb * 128 + row;
    const uint32_t qaddr = sq + row * 128;
    float mx = -INFINITY, sum = 0.f, acc = 0.f;
#pragma unroll 1
    for (int pass = 0; pass < 2; pass++) {
#pragma unroll 1
      for (int j = 0; j < 8; j++) {
        const int kp = qpos - (lane + 32 * j);
        const uint8_t* kr = kvimg + ((size_t)((kp >> 7) * 16 + hp) * 2 + ((kp >> 6) & 1)) * 16384 + (kp & 63) * 128;
        float d = -INFINITY;
        if (kp >= 0) {
          d = 0.f;
#pragma unroll 1
          for (int q = 0; q < 4; q++) {
            const uint4 kv = __ldcg(reinterpret_cast<const uint4*>(kr + (((hh * 4 + q) ^ (kp & 7)) << 4)));
            const uint4 qv = lds128(qaddr + (((hh * 4 + q) ^ (row & 7)) << 4));
            const uint32_t kw[4] = {kv.x, kv.y, kv.z, kv.w}, qw[4] = {qv.x, qv.y, qv.z, qv.w};
#pragma unroll
            for (int e = 0; e < 4; e++) d = fmaf(bf_lo(kw[e]), bf_lo(qw[e]), fmaf(bf_hi(kw[e]), bf_hi(qw[e]), d));
          }
        }
        if (pass == 0) {
          mx = fmaxf(mx, d);
        } else {
          const float ev = ex2_approx((d - mx) * SM_C);
          sum += ev;
          const float pv = bf16_round(ev);
#pragma unroll 1
          for (int kk = 0; kk < 32; kk++) {
            const float pk = __shfl_sync(0xffffffffu, pv, kk);
            const int k2 = qpos - (kk + 32 * j);
            if (k2 >= 0) {
              const uint8_t* vr = kvimg + ((size_t)((k2 >> 7) * 16 + hp) * 2 + ((k2 >> 6) & 1)) * 16384 + 8192 + (k2 & 63) * 128;
              const unsigned short vv =
                  __ldcg(reinterpret_cast<const unsigned short*>(vr + (((hh * 4 + (lane >> 3)) ^ (k2 & 7)) << 4) + (lane & 7) * 2));
              acc = fmaf(pk, __uint_as_float((uint32_t)vv << 16), acc);
            }
          }
        }
      }
      if (pass == 0) {
#pragma unroll
        for (int o = 16; o > 0; o >>= 1) mx = fmaxf(mx, __shfl_xor_sync(0xffffffffu, mx, o));
      }
    }
#pragma unroll
    for (int o = 16; o > 0; o >>= 1) sum += __shfl_xor_sync(0xffffffffu, sum, o);
    acc *= rcp_fast(sum);
    const float hi = __shfl_down_sync(0xffffffffu, acc, 1);
    __syncwarp();
    if ((lane & 1) == 0) sts32(qaddr + (((hh * 4 + (lane >> 3)) ^ (row & 7)) << 4) + (lane & 7) * 2, pack_bf16x2(acc, hi));
    __syncwarp();
  }
}

__device__ __forceinline__ void store_o(const float (&o)[16], const float (&inv)[2], uint32_t rowaddr, int hh, int lane) {
  const int mat = lane >> 3, r7 = lane & 7;
#pragma unroll
  for (int jp = 0; jp < 2; jp++)
    stmatrix_x4(rowaddr + (((hh * 4 + 2 * jp + (mat >> 1)) ^ r7) << 4),
                pack_bf16x2(o[8 * jp] * inv[0], o[8 * jp + 1] * inv[0]),
                pack_bf16x2(o[8 * jp + 2] * inv[1], o[8 * jp + 3] * inv[1]),
                pack_bf16x2(o[8 * jp + 4] * inv[0], o[8 * jp + 5] * inv[0]),
                pack_bf16x2(o[8 * jp + 6] * inv[1], o[8 * jp + 7] * inv[1]));
}

__device__ __forceinline__ void attention_a(int HH, int L, int gb, int hp, uint32_t par0, uint32_t parA, int wwarp, int lane,
                                            uint32_t zero) {
  constexpr uint32_t bars = SBASE + OFF_BAR;
  const uint32_t dslot = ((SBASE + OFF_SLOT) >> 4) + 0x10000u + HH * 4;
  const int db = 16 * wwarp + (lane >> 2) - 2 * (lane & 3);
  float s[32], o[2][16], l[2][2], mneg[2][2];
  uint32_t q[2][2][4];
  const uint32_t ra = SBASE + OFF_SLOT + 3 * 16384 + (wwarp * 16 + ((lane >> 3) & 1) * 8 + (lane & 7)) * 128;
#pragma unroll
  for (int h = 0; h < 2; h++) {
#pragma unroll
    for (int ks = 0; ks < 2; ks++) ldmatrix_x4(q[h][ks], ra + h * 8192 + (((HH * 4 + ks * 2 + (lane >> 4)) ^ (lane & 7)) << 4));
#pragma unroll
    for (int i = 0; i < 16; i++) o[h][i] = 0.f;
    l[h][0] = l[h][1] = 0.f;
    mneg[h][0] = mneg[h][1] = 0.f;
  }
  reg_define<32>(s);
  const int nmax = 2 * gb + 1;
  uint32_t d1 = dslot + 1024, d0 = dslot;
#pragma unroll 1
  for (int i = 0; i < 5; i++) {
    attn_mma<true>(s, o[0], l[0], d1 + 512, q[1], d1);
    if (i >= 1) mbar_wait(bars + 8u * (B_HALO - 1) + 8u * i, i == 1 ? par0 : parA);
    wgmma_wait<1>();
    reg_fence<32>(s);
    attn_soft(s, mneg[1], i, i <= nmax, db);
    wgmma_wait<0>();
    attn_mma<true>(s, o[1], l[1], d1 + 512, q[0], d0);
    wgmma_wait<1>();
    reg_fence<32>(s);
    attn_soft(s, mneg[0], i, i + 1 <= nmax, db);
    d1 = d0;
    d0 = d0 == dslot ? dslot + 2048 : d0 - 1024;
    sched_fence(zero);
    wgmma_wait<0>();
    if (i < 3 && lane == 0) mbar_arrive(bars + 8u * B_REL + 8u * i);
  }
  attn_mma<false>(s, o[0], l[0], dslot + 2048 + 512, q[0], 0u);
  wgmma_wait<0>();
  reg_fence<16>(o[0]);
  reg_fence<16>(o[1]);
  float inv[2][2];
  bool bad = false;
#pragma unroll
  for (int h = 0; h < 2; h++)
#pragma unroll
    for (int r = 0; r < 2; r++) {
      float v = l[h][r];
      v += __shfl_xor_sync(0xffffffffu, v, 1);
      v += __shfl_xor_sync(0xffffffffu, v, 2);
      bad |= !(v <= 1.152921504606846976e18f);
      inv[h][r] = rcp_fast(v);
    }
  if (HH == 0) GTL(45);
  if (__any_sync(0xffffffffu, bad)) {
    attn_a_slow(g_kvA[L >> 1][0][0][0], L, gb, hp, HH, wwarp, lane);
  } else {
    store_o(o[0], inv[0], ra, HH, lane);
    store_o(o[1], inv[1], ra + 8192, HH, lane);
  }
}

constexpr uint32_t KB_ROW0 = SBASE + OFF_SLOT + 2048, VB_ROW0 = SBASE + OFF_SLOT + 24576 + 2048;

__device__ __forceinline__ void attnB_soft(const float (&s)[40], int wwarp, int D, bool edge, bool odd,
                                           uint32_t (&p)[5][4], float (&sum)[2]) {
  float z[2][3];
#define GATHER_(W)                                                                                  \
  _Pragma("unroll") for (int r = 0; r < 2; r++) _Pragma("unroll") for (int t = 0; t < 3; t++)       \
      z[r][t] = odd ? s[4 * (2 * W + r + t) + 2 * r + 1] : s[4 * (2 * W + r + t) + 2 * r];
  if (wwarp < 2) {
    if (wwarp == 0) { GATHER_(0) } else { GATHER_(1) }
  } else {
    if (wwarp == 2) { GATHER_(2) } else { GATHER_(3) }
  }
#undef GATHER_
  float y[2];
  y[0] = D >= 2 ? z[0][0] : z[0][2];
  y[1] = D >= 2 ? z[1][0] : z[1][2];
  if (edge) {
    z[0][1] = -INFINITY;
    if (D >= 2) y[0] = y[1] = -INFINITY;
  }
  float m0 = fmaxf(z[0][1], y[0]), m1 = fmaxf(z[1][1], y[1]);
  m0 = fmaxf(m0, __shfl_xor_sync(0xffffffffu, m0, 1));
  m1 = fmaxf(m1, __shfl_xor_sync(0xffffffffu, m1, 1));
  m0 = -SM_C * fmaxf(m0, __shfl_xor_sync(0xffffffffu, m0, 2));
  m1 = -SM_C * fmaxf(m1, __shfl_xor_sync(0xffffffffu, m1, 2));
  const float e00 = ex2_approx(fmaf(z[0][1], SM_C, m0)), e01 = ex2_approx(fmaf(y[0], SM_C, m0));
  const float e10 = ex2_approx(fmaf(z[1][1], SM_C, m1)), e11 = ex2_approx(fmaf(y[1], SM_C, m1));
  sum[0] = e00 + e01;
  sum[1] = e10 + e11;
  const int sh = odd ? 16 : 0;
  const uint32_t a0 = pack_bf16x2(e00, 0.f) << sh, a1 = pack_bf16x2(e10, 0.f) << sh;
  const uint32_t b0 = pack_bf16x2(e01, 0.f) << sh, b1 = pack_bf16x2(e11, 0.f) << sh;
  const int kb = wwarp + (D >= 2 ? 0 : 1);
#pragma unroll
  for (int k = 0; k < 5; k++) {
    p[k][0] = k == kb ? b0 : 0u;
    p[k][1] = k == wwarp + 1 ? a1 : 0u;
    p[k][2] = k == wwarp ? a0 : 0u;
    p[k][3] = k == kb ? b1 : 0u;
#pragma unroll
    for (int q = 0; q < 4; q++) asm volatile("" : "+r"(p[k][q]));
  }
}

__device__ __forceinline__ void attnB_s(float (&s)[40], int HH, int h) {
  constexpr uint32_t sq = SBASE + OFF_SLOT + 3 * 16384;
#pragma unroll
  for (int ks = 0; ks < 2; ks++)
    wgmma_n80_ss_ta0_tb0(s, make_desc(sq + h * 8192 + HH * 64 + ks * 32, 16),
                         make_desc(KB_ROW0 + h * 8192 - 2048 + HH * 64 + ks * 32, 16), ks);
}
__device__ __forceinline__ void attnB_pv(float (&o)[16], const uint32_t (&p)[5][4], int HH, int h) {
#pragma unroll
  for (int k = 0; k < 5; k++)
    wgmma_n32_rs_tb1(o, p[k], make_desc(VB_ROW0 + h * 8192 - 2048 + k * 2048 + HH * 64, 16), k);
}

__device__ __forceinline__ void attention_b(int HH, int gb, uint32_t par0, int wwarp, int lane) {
  constexpr uint32_t bars = SBASE + OFF_BAR, sq = SBASE + OFF_SLOT + 3 * 16384;
  float s[40];
  reg_define<40>(s);
  wgmma_fence();
  attnB_s(s, HH, 1);
  wgmma_commit();
  const int g = lane >> 2;
  const bool odd = g & 1;
  const int D = 2 * (lane & 3) + (g & 1) - g;
  const uint32_t ra = sq + (wwarp * 16 + ((lane >> 3) & 1) * 8 + (lane & 7)) * 128;
  wgmma_wait<0>();
  reg_fence<40>(s);
#pragma unroll 1
  for (int h = 1; h >= 0; h--) {
    float o[16], inv[2];
    uint32_t p[5][4];
    reg_define<16>(o);
    attnB_soft(s, wwarp, D, h == 0 && gb == 0 && wwarp == 0, odd, p, inv);
    if (h == 1) {
      mbar_wait(bars + 8u * B_HALO, par0);
      wgmma_fence();
      attnB_s(s, HH, 0);
    }
    wgmma_fence();
    attnB_pv(o, p, HH, h);
    wgmma_commit();
#pragma unroll
    for (int r = 0; r < 2; r++) {
      inv[r] += __shfl_xor_sync(0xffffffffu, inv[r], 1);
      inv[r] += __shfl_xor_sync(0xffffffffu, inv[r], 2);
      inv[r] = rcp_fast(inv[r]);
    }
    wgmma_wait<0>();
    reg_fence<40>(s);
    reg_fence<16>(o);
    store_o(o, inv, ra + h * 8192, HH, lane);
  }
}

#define KTQM 0
#define TRICKLE 300
#define CSPF 4
#define WTURN 15
#define QTURN 2
struct Params {
  CUtensorMap x_in, x, o, out_map, wqkv[2], wo[2];
  const __nv_bfloat16* in_x;
  const __nv_bfloat16* wqkv_p[2];
  const __nv_bfloat16* wo_p[2];
  __nv_bfloat16* out;
  uint32_t zero;
};

__device__ __forceinline__ void colsum_part(const CUtensorMap* wmap, int ty, int qr, int hp) {
  constexpr uint32_t bars = SBASE + OFF_BAR, slots = SBASE + OFF_SLOT;
  PHASE_IDS
  const unsigned ep1 = (*(volatile unsigned*)(g_flags + F_DONE)) / NCTA + 1u;
  if (wwarp == 0 && elect_one()) {
    mbar_expect_tx(bars + 8u * B_CS, 6 * UNIT);
#pragma unroll 1
    for (int j = 0; j < 6; j++) {
      if (ty == 0) mbar_pace(bars + 8u * (B_EMPTY + j), 0);
      else __nanosleep(400);
      tma_load_2d(slots + j * UNIT, wmap, bars + 8u * B_CS, (j >> 1) * 1024 + hp * 64, qr * 128 + (j & 1) * 64);
    }
  }
  mbar_wait(bars + 8u * B_CS, ty);
  const uint32_t src = slots + (tid >> 3) * 128 + (((tid & 7) ^ ((tid >> 3) & 7)) << 4);
#pragma unroll 1
  for (int p = 0; p < 3; p++) {
    float s[8];
#pragma unroll
    for (int e = 0; e < 8; e++) s[e] = 0.f;
#pragma unroll
    for (int j = 0; j < 8; j++) {
      const uint4 v = lds128(src + p * 2 * UNIT + j * 2048);
      const uint32_t x[4] = {v.x, v.y, v.z, v.w};
#pragma unroll
      for (int e = 0; e < 4; e++) {
        s[2 * e] += bf_lo(x[e]);
        s[2 * e + 1] += bf_hi(x[e]);
      }
    }
#pragma unroll
    for (int st = 0; st < 2; st++) {
      const bool up = (lane >> (st + 3)) & 1;
#pragma unroll
      for (int e = 0; e < (4 >> st); e++) {
        const float keep = up ? s[e + (4 >> st)] : s[e], give = up ? s[e] : s[e + (4 >> st)];
        s[e] = keep + __shfl_xor_sync(0xffffffffu, give, 8 << st);
      }
    }
    const uint32_t dst = slots + 6 * UNIT + ((wwarp * 3 + p) * 64 + (lane & 7) * 8 + ((lane >> 3) & 1) * 4 + (lane >> 4) * 2) * 4;
    sts32(dst, __float_as_uint(s[0]));
    sts32(dst + 4, __float_as_uint(s[1]));
  }
  named_bar_sync(6, 128);
  if (tid < 64) {
    float r[3] = {0.f, 0.f, 0.f};
#pragma unroll
    for (int e = 0; e < 12; e++) r[e % 3] += __uint_as_float(lds32(slots + 6 * UNIT + (e * 64 + tid) * 4));
    st_rec(&g_cs[ty][hp][qr][tid], r[0], r[1], r[2], ep1);
  }
  named_bar_sync(6, 128);
}

__device__ __forceinline__ int cs_pos(int col) { return (col & ~15) + ((col & 7) >> 1) * 4 + ((col >> 3) & 1) * 2 + (col & 1); }

__device__ __forceinline__ uint32_t ln_params(float s1, float s2) {
  const float mean = s1 * (1.0f / DM);
  const float var = fmaxf(fmaf(-mean, mean, s2 * (1.0f / DM)), 0.f);
  float sd;
  asm("sqrt.approx.f32 %0, %1;" : "=f"(sd) : "f"(bf16_round(bf16_round(var) + 1e-5f)));
  return pack_bf16x2(mean, sd);
}

__host__ __device__ constexpr void w_units(int u, int& ua, int& ub) {
  ua = u == 18 ? 0 : u;
  ub = u == 18 ? 18 : (u == 19 ? 0 : u + 1);
}

struct RingProd {
  int used = 20, tail_n = 12, cnt = 4;
  uint32_t fifo = 0x5555u;
  __device__ __forceinline__ void acquire(int need) {
    while (used + need > NUNITS) {
      mbar_wait_lazy<60>(SBASE + OFF_BAR + 8u * (B_EMPTY + (tail_n & 7)), (tail_n >> 3) & 1);
      used -= fifo & 15u;
      fifo >>= 4;
      cnt--;
      tail_n++;
    }
    used += need;
    fifo |= (uint32_t)need << (4 * cnt);
    cnt++;
  }
};

constexpr int NSEG = 20;
__host__ __device__ constexpr int SEGQ(int ch, int L, int k0, int k1) { return ch | (L << 2) | ((k0 / 4) << 4) | ((k1 / 4 - 1) << 6); }
__host__ __device__ constexpr int SEGW(int ch, int L) { return ch | 2 | (L << 2); }
__host__ __device__ constexpr unsigned long long pack8(int a, int b, int c, int d, int e, int f, int g, int h) {
  return (unsigned long long)a | ((unsigned long long)b << 8) | ((unsigned long long)c << 16) | ((unsigned long long)d << 24) |
         ((unsigned long long)e << 32) | ((unsigned long long)f << 40) | ((unsigned long long)g << 48) | ((unsigned long long)h << 56);
}
#define SP2 12
#define SP3 12
#define SP4 12
#define SP6 12
__device__ __forceinline__ int seg_code(int sg) {
  constexpr unsigned long long T0 = pack8(SEGQ(0, 0, 0, 16), SEGQ(1, 0, 0, 16), SEGW(0, 0), SEGQ(0, 1, 0, SP2), SEGW(1, 0),
                                          SEGQ(0, 1, SP2, 16), SEGQ(1, 1, 0, SP3), SEGW(0, 1));
  constexpr unsigned long long T1 = pack8(SEGQ(1, 1, SP3, 16), SEGQ(0, 2, 0, SP4), SEGW(1, 1), SEGQ(0, 2, SP4, 16),
                                          SEGQ(1, 2, 0, 16), SEGW(0, 2), SEGQ(0, 3, 0, SP6), SEGW(1, 2));
  constexpr unsigned long long T2 = pack8(SEGQ(0, 3, SP6, 16), SEGQ(1, 3, 0, 16), SEGW(0, 3), SEGW(1, 3), 0, 0, 0, 0);
  return (int)(((sg < 8 ? T0 : (sg < 16 ? T1 : T2)) >> (8 * (sg & 7))) & 255ull);
}
__device__ __forceinline__ int q_first(int inst) { return (int)((pack8(0, 16, 49, 82, 115, 148, 181, 214) >> (8 * inst)) & 255ull); }
__device__ __forceinline__ int w_first(int inst) {
  return (int)((pack8(32, 49 + SP2, 82 + SP3, 115 + SP4, 164, 181 + SP6, 230, 247) >> (8 * inst)) & 255ull);
}
#define PREMASK 0x2Cu
#define PRE0 3
#define PRESH 2
__host__ __device__ constexpr int pre_idx(int kt) {
  const int d = kt - PRE0;
  return (d >= 0 && (d & ((1 << PRESH) - 1)) == 0 && (d >> PRESH) < 4) ? d >> PRESH : -1;
}
__device__ __forceinline__ bool w_pre(int inst) { return (PREMASK >> inst) & 1u; }
__device__ __forceinline__ int q_split(int inst) { return (int)(((0x40400044u | ((SP2 / 4) << 8) | ((SP3 / 4) << 12) | ((SP4 / 4) << 16) | ((SP6 / 4) << 24)) >> (4 * inst)) & 15u); }

__global__ void __launch_bounds__(512, 1) fused_kernel(const __grid_constant__ Params P) {
  extern __shared__ __align__(1024) uint8_t smem_raw[];
  constexpr uint32_t base = SBASE, bars = base + OFF_BAR, slots = base + OFF_SLOT;
  if (smem_u32(smem_raw) != base) __trap();
  const int warp = __shfl_sync(0xffffffffu, threadIdx.x >> 5, 0), lane = threadIdx.x & 31;
  const int b = blockIdx.x;
#define QS 0
#define WS 1
  const int qr = ((b & ((8 << QS) - 1)) >> QS) ^ (((b >> (3 + QS)) & 1) * 7);
  const int hp = ((b >> (3 + QS)) << QS) + (b & ((1 << QS) - 1));
  const int rt = ((b & ((16 << WS) - 1)) >> WS) ^ (((b >> (4 + WS)) & 1) * 15);
  const int ct = ((b >> (4 + WS)) << WS) + (b & ((1 << WS) - 1));

  if (warp == 12) {
    if (elect_one()) {
#pragma unroll
      for (int s = 0; s < 8; s++) {
        mbar_init(bars + 8u * (B_FULL + s), 2);
        mbar_init(bars + 8u * (B_EMPTY + s), 4);
      }
      mbar_init(bars + 8u * B_GO, 1);
      fence_barrier_init();
    }
    __syncwarp();
    named_bar_arrive(0, 512);
  }
  if (threadIdx.x == 0) {
    mbar_init(bars + 8u * B_PREP, 1);
    mbar_init(bars + 8u * (B_PREP + 1), 1);
    for (int s = 0; s < 4; s++) mbar_init(bars + 8u * (B_HALO + s), 1);
    for (int s = 0; s < 3; s++) mbar_init(bars + 8u * (B_REL + s), 8);
    mbar_init(bars + 8u * B_AFREE, 2);
    mbar_init(bars + 8u * B_TURN, 4);
    mbar_init(bars + 8u * (B_TURN + 1), 4);
    mbar_init(bars + 8u * B_CS, 1);
    mbar_init(bars + 8u * B_PRE, 1);
    mbar_init(bars + 8u * B_CSD, 4);
    mbar_init(bars + 8u * B_XRDY, 1);
    mbar_init(bars + 8u * (B_XRDY + 1), 1);
    fence_barrier_init();
  }
  if (warp != 12) named_bar_sync(0, 512);

  if (warp >= 12) {
    setmaxnreg_dec<32>();
    if (warp == 12) {
      if (elect_one()) {
#pragma unroll 1
        for (int s = 0; s < 16; s++) {
          const uint32_t fb = bars + 8u * (B_FULL + (s & 7)), sa = base + (s & 3) * 5 * UNIT;
          if (s >= 4) mbar_wait(bars + 8u * (B_EMPTY + ((s - 4) & 7)), ((s - 4) >> 3) & 1);
          mbar_expect_tx(fb, 5 * UNIT);
          mbar_arrive(fb);
          tma_load_2d(sa, &P.x_in, fb, s * 64, qr * 128);
          tma_load_2d(sa + UNIT, &P.x_in, fb, s * 64, qr * 128 + 64);
#pragma unroll
          for (int j = 0; j < 3; j++) tma_load_2d(sa + (2 + j) * UNIT, &P.wqkv[0], fb, j * 1024 + hp * 64, s * 64);
        }
        mbar_arrive(bars + 8u * B_GO);
        RingProd rp;
        int n = 16, u = 0;
#pragma unroll 1
        for (int sg = 1; sg < NSEG; sg++) {
          const int code = seg_code(sg);
          const int ty = (code >> 2) & 1;
          if ((code & 2) == 0) {
            const int k0 = (code >> 2) & 12, k1 = ((code >> 4) & 12) + 4;
#pragma unroll 1
            for (int kt = k0; kt < k1; kt++, n++) {
              rp.acquire(5);
              const uint32_t fb = bars + 8u * (B_FULL + (n & 7));
              mbar_expect_tx(fb, 3 * UNIT);
#pragma unroll
              for (int j = 0; j < 3; j++) tma_load_2d(base + (u + 2 + j) * UNIT, &P.wqkv[ty], fb, j * 1024 + hp * 64, kt * 64);
              u = u == 15 ? 0 : u + 5;
            }
          } else {
#pragma unroll 1
            for (int kt = 0; kt < 16; kt++, n++) {
              rp.acquire(3);
              int ua, ub;
              w_units(u, ua, ub);
              const uint32_t fb = bars + 8u * (B_FULL + (n & 7));
              if (pre_idx(kt) >= 0 && w_pre(((code >> 1) & 6) | (code & 1))) {
                mbar_arrive(fb);
              } else {
                mbar_expect_tx(fb, 2 * UNIT);
#pragma unroll
                for (int j = 0; j < 2; j++) tma_load_2d(base + (ub + j) * UNIT, &P.wo[ty], fb, ct * 128 + j * 64, kt * 64);
              }
              u = u >= 17 ? u - 17 : u + 3;
            }
            rp.acquire(2);
            mbar_arrive(bars + 8u * (B_FULL + (n & 7)));
            n++;
            u = u >= 18 ? u - 18 : u + 2;
          }
        }
      }
    } else if (warp == 13) {
      RingProd rp;
      int n = 16, u = 0;
      unsigned ep1 = 0;
      mbar_wait(bars + 8u * B_GO, 0);
#pragma unroll 1
      for (int sg = 1; sg < NSEG; sg++) {
        const int code = seg_code(sg);
        const int L = (code >> 2) & 3, ch = code & 1;
        const CUtensorMap* tx = L == 0 ? &P.x_in : &P.x;
        uint32_t seen = 0;
        if ((code & 2) == 0) {
          const int k0 = (code >> 2) & 12, k1 = ((code >> 4) & 12) + 4;
          if (L == 0 || mbar_test(bars + 8u * (B_XRDY + ch), (L & 1) ^ 1)) {
            seen = 0xFFu;
            fence_proxy_async_all();
          }
          if (sg == 1) ep1 = (*(volatile unsigned*)(g_flags + F_DONE)) / NCTA + 1u;
          const int m0 = ch * 1024 + qr * 128;
#pragma unroll 1
          for (int kt = k0; kt < k1; kt++, n++) {
            wait_mask<false>(g_flags + F_X + (ch * 8 + qr) * XSTR, 8, 6u * ep1 - 6u + 2u * L, 1u << (kt >> 1), seen, lane);
            TGET(t38);
            rp.acquire(5);
            TGET(t39);
            if (elect_one()) {
              const uint32_t fb = bars + 8u * (B_FULL + (n & 7));
              mbar_expect_tx(fb, 2 * UNIT);
              tma_load_2d(base + u * UNIT, tx, fb, kt * 64, m0);
              tma_load_2d(base + (u + 1) * UNIT, tx, fb, kt * 64, m0 + 64);
            }
            if (L == 3 && kt == 0 && lane == 0) { TPUT(ch, 38, t38); TPUT(ch, 39, t39); }
            u = u == 15 ? 0 : u + 5;
          }
        } else {
          const int m0 = ch * 1024 + rt * 64;
#pragma unroll 1
          for (int kt = 0; kt < 16; kt++, n++) {
            wait_mask<false>(g_flags + F_O + (ch * 16 + rt) * OSTR, 16, 4u * ep1 - 3u + L, 1u << kt, seen, lane);
            rp.acquire(3);
            int ua, ub;
            w_units(u, ua, ub);
            if (elect_one()) {
              const uint32_t fb = bars + 8u * (B_FULL + (n & 7));
              mbar_expect_tx(fb, UNIT);
              tma_load_2d(base + ua * UNIT, &P.o, fb, kt * 64, m0);
            }
            u = u >= 17 ? u - 17 : u + 3;
          }
          rp.acquire(2);
          if (elect_one()) {
            const uint32_t fb = bars + 8u * (B_FULL + (n & 7));
            mbar_expect_tx(fb, 2 * UNIT);
            tma_load_2d(base + u * UNIT, tx, fb, ct * 128, m0);
            tma_load_2d(base + (u + 1) * UNIT, tx, fb, ct * 128 + 64, m0);
          }
          n++;
          u = u >= 18 ? u - 18 : u + 2;
        }
      }
    } else if (warp == 14) {
      const unsigned ep1 = (*(volatile unsigned*)(g_flags + F_DONE)) / NCTA + 1u;
#pragma unroll 1
      for (int inst = 0; inst < 8; inst++) {
        const int L = inst >> 1, ch = inst & 1, gb = ch * 8 + qr;
        unsigned* kvf = g_flags + F_KV;
        const unsigned kvt = 8u * ep1 - 6u + 2u * L;
        named_bar_sync(3, 160);
        if (elect_one()) {
          if ((L & 1) == 0) {
            bulk_store(g_kvA[L >> 1][gb][hp][1], slots + 16384, 16384);
          } else {
            bulk_store(g_kvB[L >> 1][gb][hp], KB_ROW0 + 112 * 128, 2048);
            bulk_store(g_kvB[L >> 1][gb][hp] + 2048, VB_ROW0 + 112 * 128, 2048);
          }
          bulk_commit();
          bulk_wait0();
          fence_proxy_async_all();
          red_relaxed_add(kvf + (gb * 16 + hp) * KSTR, (L & 1) + 1u);
        }
        __syncwarp();
        if (L & 1) named_bar_arrive(7, 160);
        else named_bar_sync(7, 160);
        if (elect_one()) {
          if ((L & 1) == 0) {
            bulk_store(g_kvA[L >> 1][gb][hp][0], slots, 16384);
            bulk_commit();
            bulk_wait0();
            fence_proxy_async_all();
            red_relaxed_add(kvf + (gb * 16 + hp) * KSTR, 1u);
          }
          if (gb >= 1) {
            wait_ge(kvf + ((gb - 1) * 16 + hp) * KSTR, kvt - 1u);
            fence_proxy_async_all();
          }
          if ((L & 1) == 0) {
            const uint32_t parA = ((L >> 1) * 2 + ch) & 1;
            const uint8_t* s1 = gb >= 1 ? g_kvA[L >> 1][gb - 1][hp][0] : g_zero;
            mbar_expect_tx(bars + 8u * B_HALO, 16384);
            bulk_load(slots + 2 * 16384, gb >= 1 ? s1 + 16384 : s1, 16384, bars + 8u * B_HALO);
            if (gb >= 1) {
              wait_ge(kvf + ((gb - 1) * 16 + hp) * KSTR, kvt);
              fence_proxy_async_all();
            }
            mbar_wait_lazy<100>(bars + 8u * B_REL, parA);
            mbar_expect_tx(bars + 8u * (B_HALO + 1), 16384);
            bulk_load(slots + 16384, s1, 16384, bars + 8u * (B_HALO + 1));
            if (gb >= 2) {
              wait_ge(kvf + ((gb - 2) * 16 + hp) * KSTR, kvt);
              fence_proxy_async_all();
            }
            const uint8_t* s2 = gb >= 2 ? g_kvA[L >> 1][gb - 2][hp][0] : g_zero;
            mbar_wait_lazy<100>(bars + 8u * (B_REL + 1), parA);
            mbar_expect_tx(bars + 8u * (B_HALO + 2), 16384);
            bulk_load(slots, gb >= 2 ? s2 + 16384 : s2, 16384, bars + 8u * (B_HALO + 2));
            mbar_wait_lazy<100>(bars + 8u * (B_REL + 2), parA);
            mbar_expect_tx(bars + 8u * (B_HALO + 3), 16384);
            bulk_load(slots + 2 * 16384, s2, 16384, bars + 8u * (B_HALO + 3));
          } else {
            const uint8_t* s1 = gb >= 1 ? g_kvB[L >> 1][gb - 1][hp] : g_zero;
            mbar_expect_tx(bars + 8u * B_HALO, 4096);
            bulk_load(KB_ROW0 - 2048, s1, 2048, bars + 8u * B_HALO);
            bulk_load(VB_ROW0 - 2048, s1 + 2048, 2048, bars + 8u * B_HALO);
          }
          if (w_pre(inst)) {
            mbar_wait(bars + 8u * B_AFREE, (inst & 1) ^ 1);
            if (inst == 1) mbar_wait(bars + 8u * B_CSD, 0);
            mbar_expect_tx(bars + 8u * B_PRE, 8 * UNIT);
#pragma unroll 1
            for (int j = 0; j < 8; j++) {
              tma_load_2d(slots + j * UNIT, &P.wo[L & 1], bars + 8u * B_PRE, ct * 128 + (j & 1) * 64, (PRE0 + ((j >> 1) << PRESH)) * 64);
              __nanosleep(100);
            }
          }
        }
        __syncwarp();
      }
    } else {
      const unsigned ep1 = (*(volatile unsigned*)(g_flags + F_DONE)) / NCTA + 1u;
      mbar_wait(bars + 8u * B_GO, 0);
#pragma unroll 1
      for (int i = 0; i < 20; i++) {
        const char* src = i < 4 ? reinterpret_cast<const char*>(P.wo_p[0]) + (size_t)b * 16384 + i * 4096
                                : (i < 16 ? reinterpret_cast<const char*>(P.wqkv_p[1]) + (size_t)b * 49152 + (i - 4) * 4096
                                          : reinterpret_cast<const char*>(P.wo_p[1]) + (size_t)b * 16384 + (i - 16) * 4096);
        asm volatile("prefetch.global.L2 [%0];" ::"l"(src + lane * 128));
        __nanosleep(TRICKLE);
      }
#pragma unroll 1
      for (int inst = 2; inst < 8; inst++) {
        const int L = inst >> 1, ch = inst & 1, gb = ch * 8 + qr;
        uint32_t seen = 0;
        wait_mask<true>(g_flags + F_X + gb * XSTR, 8, 6u * ep1 - 6u + 2u * L, 0xFFu, seen, lane);
        if (lane == 0) mbar_arrive(bars + 8u * (B_XRDY + ch));
#pragma unroll 1
        for (int h = 0; h < 4; h++) {
          const float4* sp = &g_stats[L][0][gb * 128 + h * 32 + lane];
          const float4 s0 = sum_recs<4>(sp, S_LEN, ep1), s1 = sum_recs<4>(sp + 4 * S_LEN, S_LEN, ep1);
          sts32(base + OFF_RS + (ch * 128 + h * 32 + lane) * 4, ln_params(s0.x + s1.x, s0.y + s1.y));
        }
        if (inst == 2) {
          mbar_wait(bars + 8u * B_CSD, 0);
#pragma unroll 1
          for (int hf = 0; hf < 2; hf++) {
            const float4* cp = &g_cs[1][hp][0][hf * 32 + lane];
            const float4 s0 = sum_recs<4>(cp, 64, ep1), s1 = sum_recs<4>(cp + 4 * 64, 64, ep1);
            const uint32_t ca = base + OFF_CS + (192 + cs_pos(hf * 32 + lane)) * 4;
            sts32(ca, __float_as_uint(s0.x + s1.x));
            sts32(ca + 256, __float_as_uint(s0.y + s1.y));
            sts32(ca + 512, __float_as_uint(s0.z + s1.z));
          }
        }
        __syncwarp();
        if (lane == 0) mbar_arrive(bars + 8u * (B_PREP + ch));
      }
    }
  } else {
    const bool asst = warp >= 8;
    const bool lane0 = lane == 0;
    uint32_t tpar = 0;
    GTL(0);
    if (asst) {
      colsum_part(&P.wqkv[0], 0, qr, hp);
      if ((threadIdx.x & 127) < 2) mbar_arrive(bars + 8u * B_AFREE);
    } else if (warp >= 4) {
      PHASE_IDS
      {
        const unsigned ep1 = (*(volatile unsigned*)(g_flags + F_DONE)) / NCTA + 1u;
        const int row = b * 16 + (tid >> 3);
        const uint4* src = reinterpret_cast<const uint4*>(P.in_x + (size_t)row * DM) + (tid & 7);
        float s1 = 0.f, s2 = 0.f;
#pragma unroll 1
        for (int k = 0; k < 4; k++) {
          mbar_pace(bars + 8u * (B_EMPTY + 2 * k), 0);
          uint4 v[4];
#pragma unroll
          for (int j = 0; j < 4; j++) v[j] = __ldg(src + (k * 4 + j) * 8);
#pragma unroll
          for (int j = 0; j < 4; j++) {
            const uint32_t w[4] = {v[j].x, v[j].y, v[j].z, v[j].w};
#pragma unroll
            for (int e = 0; e < 4; e++) {
              const float x0 = bf_lo(w[e]), x1 = bf_hi(w[e]);
              s1 += x0 + x1;
              s2 = fmaf(x0, x0, fmaf(x1, x1, s2));
            }
          }
        }
#pragma unroll
        for (int o = 1; o < 8; o <<= 1) {
          s1 += __shfl_xor_sync(0xffffffffu, s1, o);
          s2 += __shfl_xor_sync(0xffffffffu, s2, o);
        }
        if ((tid & 7) == 0) st_rec(&g_stats[0][0][row], s1, s2, 0.f, ep1);
        if (tid == 0) sts32(base + OFF_EPOCH, ep1);
        if (tid < 64) {
          const float4 s0 = sum_recs<8>(&g_cs[0][hp][0][tid], 64, ep1);
          sts32(base + OFF_CS + cs_pos(tid) * 4, __float_as_uint(s0.x));
          sts32(base + OFF_CS + cs_pos(tid) * 4 + 256, __float_as_uint(s0.y));
          sts32(base + OFF_CS + cs_pos(tid) * 4 + 512, __float_as_uint(s0.z));
        }
#pragma unroll 1
        for (int cc = 0; cc < 2; cc++) {
          const float4 s0 = sum_recs<1>(&g_stats[0][0][(cc * 8 + qr) * 128 + tid], 0, ep1);
          sts32(base + OFF_RS + (cc * 128 + tid) * 4, ln_params(s0.x, s0.y));
        }
        named_bar_sync(2, 128);
        if (tid < 2) mbar_arrive(bars + 8u * (B_PREP + tid));
      }
    }
#pragma unroll 1
    for (int inst = asst ? 0 : warp >> 2; inst < 8; inst += asst ? 1 : 2) {
      const int L = inst >> 1, ch = inst & 1, gb = ch * 8 + qr;
      if (asst) {
        setmaxnreg_dec<24>();
        named_bar_sync(4, 256);
        setmaxnreg_inc<128>();
      } else {
      setmaxnreg_inc<224>();
      {
        float acc[2][96];
        const int ksp = q_split(inst);
        int n = q_first(inst);
        uint32_t dlt = (ch == 0 && L > 0) ? 10u * (UNIT >> 4) : 0u;
        if (inst != 0 && inst != 2 && inst != 6) {
          mbar_wait_lazy<100>(bars + 8u * (B_TURN + ch), tpar);
          tpar ^= 1u;
        }
        if (L == 3) GTL(37);
        mbar_wait(bars + 8u * (B_FULL + (n & 7)), (n >> 3) & 1);
        GTL(1 + L * 8);
        {
          const uint32_t da = (base >> 4) + 0x10000u + dlt;
          const uint64_t db = desc_lo(da - 0x10000u + ((UNIT >> 4) << 16) + 2 * (UNIT >> 4));
          wgmma_fence();
          wgmma_n192_ssz_ta0_tb1(acc[0], desc_lo(da), db);
          wgmma_commit();
          wgmma_n192_ssz_ta0_tb1(acc[1], desc_lo(da + (UNIT >> 4)), db);
          wgmma_commit();
        }
#pragma unroll 1
        for (int k4 = 0; k4 < 4; k4++) {
          const bool brk = k4 + 1 == ksp && k4 < 3;
#pragma unroll
          for (int ks = 0; ks < 4; ks++, n++) {
            const uint32_t da = ((base + ks * 5 * UNIT) >> 4) + 0x10000u + (ks < 2 ? dlt : 0u - dlt);
            const uint32_t dbb = da - 0x10000u + ((UNIT >> 4) << 16) + 2 * (UNIT >> 4);
#pragma unroll
            for (int k16 = 0; k16 < 4; k16++) {
              if (ks == 0 && k16 == 0 && k4 == 0) continue;
              const uint64_t db = desc_lo(dbb + k16 * 128);
              wgmma_fence();
              wgmma_n192_ss_ta0_tb1(acc[0], desc_lo(da + k16 * 2), db, 1);
              wgmma_commit();
              wgmma_wait<1>();
              if (k16 == 0 && lane0 && (ks != 0 || k4 != ksp)) mbar_arrive(bars + 8u * (B_EMPTY + ((n - 1) & 7)));
              wgmma_fence();
              wgmma_n192_ss_ta0_tb1(acc[1], desc_lo(da + (UNIT >> 4) + k16 * 2), db, 1);
              wgmma_commit();
              bool ok = true;
              if (k16 == 2) ok = mbar_test(bars + 8u * (B_FULL + ((n + 1) & 7)), ((n + 1) >> 3) & 1) || (ks == 3 && (k4 == 3 || brk));
              if (k16 == QTURN && ks == 3 && (k4 == 3 || brk) && lane0) mbar_arrive(bars + 8u * (B_TURN + (ch ^ 1)));
              if (ks < 3 || k16 < 3) wgmma_wait<1>();
              if (k16 == 2 && !ok) mbar_wait(bars + 8u * (B_FULL + ((n + 1) & 7)), ((n + 1) >> 3) & 1);
            }
          }
          if (brk) {
            wgmma_wait<0>();
            if (lane0) mbar_arrive(bars + 8u * (B_EMPTY + ((n - 1) & 7)));
            n += 17;
            dlt ^= 10u * (UNIT >> 4);
            mbar_wait_lazy<100>(bars + 8u * (B_TURN + ch), tpar);
            tpar ^= 1u;
            mbar_wait(bars + 8u * (B_FULL + (n & 7)), (n >> 3) & 1);
          }
        }
        PHASE_IDS
        mbar_wait(bars + 8u * (B_PREP + ch), L & 1);
        const bool afree = mbar_test(bars + 8u * B_AFREE, inst & 1);
        float nmean[2][2], rinv[2][2];
        const uint32_t csa = base + OFF_CS + ((L & 1) * 192 + 4 * c) * 4;
        uint4 cs[20];
        {
          uint32_t v[4];
#pragma unroll
          for (int i = 0; i < 4; i++)
            v[i] = lds32(base + OFF_RS + (ch * 128 + (i >> 1) * 64 + wwarp * 16 + g + 8 * (i & 1)) * 4);
#pragma unroll
          for (int t = 0; t < 2; t++) cs[t] = lds128(csa + (t + 4) * 64);
#pragma unroll
          for (int i = 0; i < 4; i++) {
            nmean[i >> 1][i & 1] = -bf_lo(v[i]);
            rinv[i >> 1][i & 1] = rcp_fast(bf_hi(v[i]));
            asm volatile("" : "+f"(rinv[i >> 1][i & 1]), "+f"(nmean[i >> 1][i & 1]));
          }
        }
        const int mat = lane >> 3;
        const uint32_t soff = (wwarp * 16 + (mat & 1) * 8 + (lane & 7)) * 128;
        const uint32_t kdst = ((L & 1) ? KB_ROW0 : slots) + soff, vdst = ((L & 1) ? VB_ROW0 : slots + 8192) + soff;
        const uint32_t hs = (L & 1) ? 8192 : 16384;
        wgmma_wait<0>();
        reg_fence<96>(acc[0]);
        reg_fence<96>(acc[1]);
        if (lane0) mbar_arrive(bars + 8u * (B_EMPTY + ((n - 1) & 7)));
        GTL(2 + L * 8);
        if (!afree) mbar_wait(bars + 8u * B_AFREE, inst & 1);
#pragma unroll
        for (int t = 2; t < CSPF; t++) cs[t] = lds128(csa + (t + 4) * 64);
#pragma unroll
        for (int t = 0; t < 20; t++) {
          const int p = t >= 16 ? 0 : ((t >> 2) & 1) + 1, jp = t & 3;
          if (t + CSPF < 20) {
            const int tn = t + CSPF, jn = tn >= 16 ? tn - 16 : (tn & 7) + 4;
            cs[tn] = lds128(csa + jn * 64);
          }
          const int j = p * 8 + 2 * jp;
          const float2 cs0 = make_float2(__uint_as_float(cs[t].x), __uint_as_float(cs[t].y));
          const float2 cs1 = make_float2(__uint_as_float(cs[t].z), __uint_as_float(cs[t].w));
          const uint32_t sw = ((2 * jp + (mat >> 1)) ^ (lane & 7)) << 4;
#pragma unroll
          for (int h = 0; h < 2; h++) {
            if (t < 16 && h != (t < 8 ? 1 : 0)) continue;
            const float* a = &acc[h][4 * j];
            const uint32_t r0 = pack_bf16x2(fmaf(nmean[h][0], cs0.x, a[0]) * rinv[h][0], fmaf(nmean[h][0], cs0.y, a[1]) * rinv[h][0]);
            const uint32_t r1 = pack_bf16x2(fmaf(nmean[h][1], cs0.x, a[2]) * rinv[h][1], fmaf(nmean[h][1], cs0.y, a[3]) * rinv[h][1]);
            const uint32_t r2 = pack_bf16x2(fmaf(nmean[h][0], cs1.x, a[4]) * rinv[h][0], fmaf(nmean[h][0], cs1.y, a[5]) * rinv[h][0]);
            const uint32_t r3 = pack_bf16x2(fmaf(nmean[h][1], cs1.x, a[6]) * rinv[h][1], fmaf(nmean[h][1], cs1.y, a[7]) * rinv[h][1]);
            const uint32_t dst = p == 0 ? slots + 3 * 16384 + soff + h * 8192 : (p == 1 ? kdst : vdst) + h * hs;
            stmatrix_x4(dst + sw, r0, r1, r2, r3);
          }
          if (t == 7 || t == 15) {
            fence_proxy_async_smem();
            named_bar_arrive(t == 7 ? 3 : 7, 160);
          }
        }
      }
      fence_proxy_async_smem();
      setmaxnreg_dec<128>();
      named_bar_sync(4, 256);
      }
      GTL(3 + L * 8);
      {
        PHASE_IDS
        if ((L & 1) == 0) attention_a(asst, L, gb, hp, inst & 1, ch, wwarp, lane, P.zero);
        else attention_b(asst, gb, inst & 1, wwarp, lane);
        GTL(4 + L * 8);
        fence_proxy_async_smem();
      }
      if (asst) {
        named_bar_arrive(5, 256);
        if (inst == 1) {
          mbar_wait(bars + 8u * B_AFREE, 0);
          colsum_part(&P.wqkv[1], 1, qr, hp);
          if (lane0) mbar_arrive(bars + 8u * B_CSD);
        }
        continue;
      }
      {
        named_bar_sync(5, 256);
        const int wwarp = warp & 3;
        if (wwarp < 2 && elect_one()) {
          tma_store_2d(&P.o, slots + 3 * 16384 + wwarp * 8192, hp * 64, gb * 128 + wwarp * 64);
          bulk_commit();
          bulk_wait0();
          mbar_arrive(bars + 8u * B_AFREE);
          fence_proxy_async_all();
          red_relaxed_add(g_flags + F_O + (gb * 2 + wwarp) * OSTR + hp, 1u);
        }
        __syncwarp();
      }
      GTL(5 + L * 8);

      {
        float acc[64];
        const int n0 = w_first(inst);
        const bool pre = w_pre(inst);
        mbar_wait_lazy<100>(bars + 8u * (B_TURN + ch), tpar);
        tpar ^= 1u;
        mbar_wait(bars + 8u * (B_FULL + (n0 & 7)), (n0 >> 3) & 1);
        GTL(6 + L * 8);
#pragma unroll
        for (int kt = 0; kt < 16; kt++) {
          const int n = n0 + kt;
          int ua0, ub0, ua1, ub1;
          w_units((3 * kt) % 20, ua0, ub0);
          w_units((3 * kt + 10) % 20, ua1, ub1);
          const uint32_t da = (ch ? (base + ua1 * UNIT) >> 4 : (base + ua0 * UNIT) >> 4) + 0x10000u;
          uint32_t db = (ch ? (base + ub1 * UNIT) >> 4 : (base + ub0 * UNIT) >> 4);
          if (pre_idx(kt) >= 0) db = pre ? (slots + pre_idx(kt) * 2 * UNIT) >> 4 : db;
          db += (UNIT >> 4) << 16;
          if (kt == PRE0 && pre) mbar_wait(bars + 8u * B_PRE, __popc(PREMASK & ((1u << inst) - 1u)) & 1);
          if (kt == WTURN && lane0 && (inst & 3) != 0) mbar_arrive(bars + 8u * (B_TURN + (ch ^ 1)));
          wgmma_fence();
          if (kt == 0) wgmma_n128_ssz_ta0_tb1(acc, desc_lo(da), desc_lo(db));
#pragma unroll
          for (int k16 = kt == 0 ? 1 : 0; k16 < 4; k16++) wgmma_n128_ss_ta0_tb1(acc, desc_lo(da + 2 * k16), desc_lo(db + 128 * k16), 1);
          wgmma_commit();
          const bool ok = mbar_test(bars + 8u * (B_FULL + ((n + 1) & 7)), ((n + 1) >> 3) & 1);
          if (kt > 0) {
            wgmma_wait<1>();
            if (lane0) mbar_arrive(bars + 8u * (B_EMPTY + ((n - 1) & 7)));
          }
          if (!ok) mbar_wait(bars + 8u * (B_FULL + ((n + 1) & 7)), ((n + 1) >> 3) & 1);
        }
        const int u = ch ? 18 : 8;
        PHASE_IDS
        const uint32_t xb = base + u * UNIT;
        const int mat = lane >> 3;
        const uint32_t xrow = xb + (wwarp * 16 + (mat & 1) * 8 + (lane & 7)) * 128;
        uint32_t xv[8][4];
#pragma unroll
        for (int jp = 0; jp < 8; jp++)
          ldmatrix_x4(xv[jp], xrow + (jp >> 2) * UNIT + (((2 * (jp & 3) + (mat >> 1)) ^ (lane & 7)) << 4));
        wgmma_wait<0>();
        reg_fence<64>(acc);
        if (lane0) mbar_arrive(bars + 8u * (B_EMPTY + ((n0 + 15) & 7)));
        GTL(7 + L * 8);
        const int nx = n0 + 16;
#pragma unroll
        for (int jp = 0; jp < 8; jp++) {
#pragma unroll
          for (int q = 0; q < 4; q++) xv[jp][q] = add_bf16x2(xv[jp][q], pack_bf16x2(acc[8 * jp + 2 * q], acc[8 * jp + 2 * q + 1]));
          stmatrix_x4(xrow + (jp >> 2) * UNIT + (((2 * (jp & 3) + (mat >> 1)) ^ (lane & 7)) << 4), xv[jp][0], xv[jp][1],
                      xv[jp][2], xv[jp][3]);
        }
        fence_proxy_async_smem();
        named_bar_sync(1 + ch, 128);
        const int grow = ch * 1024 + rt * 64;
        if (wwarp == 0) {
          if (elect_one()) {
            const CUtensorMap* to = L == 3 ? &P.out_map : &P.x;
            tma_store_2d(to, xb, ct * 128, grow);
            tma_store_2d(to, xb + UNIT, ct * 128 + 64, grow);
            bulk_commit();
            bulk_wait_read0();
            mbar_arrive(bars + 8u * (B_EMPTY + (nx & 7)));
            bulk_wait0();
            TGET(t35);
            fence_proxy_async_all();
            if (L < 3) red_relaxed_add(g_flags + F_X + (ch * 8 + (rt >> 1)) * XSTR + ct, 1u);
            if (L == 2) TPUT(ch, 35, t35);
          }
          __syncwarp();
        } else if (lane == 0) {
          mbar_arrive(bars + 8u * (B_EMPTY + (nx & 7)));
        }
        if (L < 3) {
          const unsigned ep1 = lds32(base + OFF_EPOCH);
          float s1[2] = {0.f, 0.f}, s2[2] = {0.f, 0.f};
#pragma unroll
          for (int jp = 0; jp < 8; jp++)
#pragma unroll
            for (int q = 0; q < 4; q++) {
              const float x0 = bf_lo(xv[jp][q]), x1 = bf_hi(xv[jp][q]);
              s1[q & 1] += x0 + x1;
              s2[q & 1] = fmaf(x0, x0, fmaf(x1, x1, s2[q & 1]));
            }
#pragma unroll
          for (int r = 0; r < 2; r++) {
            s1[r] += __shfl_xor_sync(0xffffffffu, s1[r], 1);
            s2[r] += __shfl_xor_sync(0xffffffffu, s2[r], 1);
            s1[r] += __shfl_xor_sync(0xffffffffu, s1[r], 2);
            s2[r] += __shfl_xor_sync(0xffffffffu, s2[r], 2);
            if (c == 0) st_rec(&g_stats[L + 1][ct][grow + wwarp * 16 + g + 8 * r], s1[r], s2[r], 0.f, ep1);
          }
        }
        GTL(8 + L * 8);
      }
    }
    if (threadIdx.x == 128) atomicAdd(g_flags + F_DONE, 1u);
  }
}

typedef CUresult (*PFN_tmEncode)(CUtensorMap*, CUtensorMapDataType, cuuint32_t, void*, const cuuint64_t*,
                                 const cuuint64_t*, const cuuint32_t*, const cuuint32_t*, CUtensorMapInterleave,
                                 CUtensorMapSwizzle, CUtensorMapL2promotion, CUtensorMapFloatOOBfill);

PFN_tmEncode get_encode_fn() {
  static PFN_tmEncode fn = nullptr;
  if (!fn) {
    cudaDriverEntryPointQueryResult qr;
    void* p = nullptr;
    cudaGetDriverEntryPoint("cuTensorMapEncodeTiled", &p, cudaEnableDefault, &qr);
    fn = (PFN_tmEncode)p;
  }
  return fn;
}

CUtensorMap make_map(const void* ptr, int rows, int cols) {
  CUtensorMap m;
  cuuint64_t gdim[2] = {(cuuint64_t)cols, (cuuint64_t)rows};
  cuuint64_t gstr[1] = {(cuuint64_t)cols * 2};
  cuuint32_t box[2] = {64, 64};
  cuuint32_t estr[2] = {1, 1};
  get_encode_fn()(&m, CU_TENSOR_MAP_DATA_TYPE_BFLOAT16, 2, const_cast<void*>(ptr), gdim, gstr, box, estr,
                  CU_TENSOR_MAP_INTERLEAVE_NONE, CU_TENSOR_MAP_SWIZZLE_128B, CU_TENSOR_MAP_L2_PROMOTION_L2_128B,
                  CU_TENSOR_MAP_FLOAT_OOB_FILL_NONE);
  return m;
}

}

extern "C" void kernel_launch(void* const* d_in, const int* in_sizes, int n_in, void* d_out, int out_size) {
  (void)in_sizes; (void)n_in; (void)out_size;
  void *p_o, *p_x;
  cudaGetSymbolAddress(&p_o, g_o);
  cudaGetSymbolAddress(&p_x, g_x);
  static bool attr_done = false;
  if (!attr_done) {
    cudaFuncSetAttribute(fused_kernel, cudaFuncAttributeMaxDynamicSharedMemorySize, SMEM_BYTES);
    attr_done = true;
  }
  Params P;
  P.in_x = (const __nv_bfloat16*)d_in[0];
  P.wqkv_p[0] = (const __nv_bfloat16*)d_in[1];
  P.wo_p[0] = (const __nv_bfloat16*)d_in[2];
  P.wqkv_p[1] = (const __nv_bfloat16*)d_in[4];
  P.wo_p[1] = (const __nv_bfloat16*)d_in[5];
  P.out = (__nv_bfloat16*)d_out;
  P.zero = 0;
  P.x_in = make_map(P.in_x, S_LEN, DM);
  P.x = make_map(p_x, S_LEN, DM);
  P.o = make_map(p_o, S_LEN, DM);
  P.out_map = make_map(d_out, S_LEN, DM);
  for (int t = 0; t < 2; t++) {
    P.wqkv[t] = make_map(P.wqkv_p[t], DM, NQKV);
    P.wo[t] = make_map(P.wo_p[t], DM, DM);
  }
  fused_kernel<<<NCTA, 512, SMEM_BYTES>>>(P);
}
```

```cpp
#include <cuda_runtime.h>
#include <cuda_bf16.h>
#include <cuda.h>
#include <stdint.h>

namespace {

constexpr int S_LEN = 2048;
constexpr int DM = 1024;
constexpr int NQKV = 3072;
constexpr int NCTA = 128;

__device__ __align__(1024) uint8_t g_kvA[2][16][16][2][16384];
__device__ __align__(1024) uint8_t g_kvB[2][16][16][4096];
__device__ __align__(1024) uint8_t g_zero[16384];
__device__ __align__(1024) __nv_bfloat16 g_o[S_LEN * DM];
__device__ __align__(1024) __nv_bfloat16 g_x[3][S_LEN * DM];
__device__ __align__(1024) float4 g_stats[4][8][S_LEN];
__device__ __align__(1024) float4 g_cs[2][16][8][64];
constexpr int F_X = 0;
constexpr int XSTR = 32, OSTR = 32;
constexpr int F_O = F_X + 16 * XSTR;
constexpr int F_DONE = F_O + 32 * OSTR;
__device__ __align__(1024) unsigned g_flags[F_DONE + 32];

constexpr uint32_t SBASE = 1024;
constexpr int UNIT = 8192;
constexpr int NUNITS = 20;
constexpr int OFF_SLOT = NUNITS * UNIT;
constexpr int OFF_BAR = OFF_SLOT + 4 * 16384;
constexpr int OFF_EPOCH = OFF_BAR + 408;
constexpr int OFF_LSB = OFF_BAR + 416;
constexpr int OFF_CS = OFF_BAR + 480;
constexpr int OFF_RS = OFF_CS + 1536;
constexpr int SMEM_BYTES = OFF_RS + 1024;
constexpr int B_QF = 0, B_WF = 4, B_RF = 12, B_E = 13, B_PREP = 26, B_LOC = 28, B_HALO = 29, B_REL = 33, B_AFREE = 36,
              B_TURN = 37, B_XRDY = 39, B_CS = 41, B_CSD = 42, B_GO = 43, B_PRE = 44, B_HL = 45, B_REDO = 46,
              B_RDONE = 48, B_PRE2 = 49;
static_assert(SMEM_BYTES <= 232448, "shared memory");

__device__ __forceinline__ uint32_t smem_u32(const void* p) { return (uint32_t)__cvta_generic_to_shared(p); }

__device__ __forceinline__ void mbar_init(uint32_t bar, uint32_t cnt) {
  asm volatile("mbarrier.init.shared::cta.b64 [%0], %1;" ::"r"(bar), "r"(cnt));
}
__device__ __forceinline__ void mbar_expect_tx(uint32_t bar, uint32_t bytes) {
  asm volatile("mbarrier.arrive.expect_tx.shared::cta.b64 _, [%0], %1;" ::"r"(bar), "r"(bytes) : "memory");
}
__device__ __forceinline__ void mbar_arrive(uint32_t bar) {
  asm volatile("mbarrier.arrive.shared::cta.b64 _, [%0];" ::"r"(bar) : "memory");
}
__device__ __forceinline__ bool mbar_try_wait(uint32_t bar, uint32_t parity) {
  uint32_t ok;
  asm volatile(
      "{\n.reg .pred p;\nmbarrier.try_wait.parity.shared::cta.b64 p, [%1], %2;\nselp.b32 %0, 1, 0, p;\n}\n"
      : "=r"(ok)
      : "r"(bar), "r"(parity)
      : "memory");
  return ok != 0;
}
__device__ __forceinline__ bool mbar_test(uint32_t bar, uint32_t parity) {
  uint32_t ok;
  asm volatile(
      "{\n.reg .pred p;\nmbarrier.test_wait.parity.shared::cta.b64 p, [%1], %2;\nselp.b32 %0, 1, 0, p;\n}\n"
      : "=r"(ok)
      : "r"(bar), "r"(parity)
      : "memory");
  return ok != 0;
}
__device__ __forceinline__ void mbar_wait(uint32_t bar, uint32_t parity) {
#pragma unroll 1
  for (uint32_t it = 0; it < (1u << 18); ++it) {
    if (mbar_try_wait(bar, parity)) return;
  }
}
__device__ __forceinline__ void mbar_pace(uint32_t bar, uint32_t parity) {
#pragma unroll 1
  for (uint32_t it = 0; it < 24; ++it) {
    if (mbar_try_wait(bar, parity)) return;
  }
}
template <int NS>
__device__ __forceinline__ void mbar_wait_lazy(uint32_t bar, uint32_t parity) {
#pragma unroll 1
  for (uint32_t it = 0; it < (1u << 18); ++it) {
    if (mbar_try_wait(bar, parity)) return;
    __nanosleep(NS);
  }
}
__device__ __forceinline__ bool elect_one() {
  uint32_t ok;
  asm volatile("{\n.reg .pred p;\nelect.sync _|p, 0xffffffff;\nselp.b32 %0, 1, 0, p;\n}\n" : "=r"(ok));
  return ok != 0;
}
__device__ __forceinline__ void fence_barrier_init() { asm volatile("fence.mbarrier_init.release.cluster;" ::: "memory"); }
__device__ __forceinline__ void fence_proxy_async_smem() { asm volatile("fence.proxy.async.shared::cta;" ::: "memory"); }
__device__ __forceinline__ void fence_proxy_async_all() { asm volatile("fence.proxy.async.global;" ::: "memory"); }

__device__ __forceinline__ void tma_load_2d(uint32_t dst, const CUtensorMap* map, uint32_t bar, int c0, int c1) {
  asm volatile(
      "cp.async.bulk.tensor.2d.shared::cluster.global.mbarrier::complete_tx::bytes [%0], [%1, {%3, %4}], [%2];" ::"r"(dst),
      "l"(map), "r"(bar), "r"(c0), "r"(c1)
      : "memory");
}
__device__ __forceinline__ void tma_load_3d(uint32_t dst, const CUtensorMap* map, uint32_t bar, int c0, int c1) {
  asm volatile(
      "cp.async.bulk.tensor.3d.shared::cluster.global.mbarrier::complete_tx::bytes [%0], [%1, {%3, %4, %5}], [%2];" ::"r"(dst),
      "l"(map), "r"(bar), "r"(c0), "r"(c1), "r"(0)
      : "memory");
}
__device__ __forceinline__ void tma_load_5d(uint32_t dst, const CUtensorMap* map, uint32_t bar, int c0, int c4) {
  asm volatile(
      "cp.async.bulk.tensor.5d.shared::cluster.global.mbarrier::complete_tx::bytes [%0], [%1, {%3, %5, %5, %5, %4}], [%2];" ::"r"(dst),
      "l"(map), "r"(bar), "r"(c0), "r"(c4), "r"(0)
      : "memory");
}
__device__ __forceinline__ void bulk_load(uint32_t dst, const void* src, uint32_t bytes, uint32_t bar) {
  asm volatile("cp.async.bulk.shared::cluster.global.mbarrier::complete_tx::bytes [%0], [%1], %2, [%3];" ::"r"(dst),
               "l"(src), "r"(bytes), "r"(bar)
               : "memory");
}
__device__ __forceinline__ void bulk_store(void* dst, uint32_t src, uint32_t bytes) {
  asm volatile("cp.async.bulk.global.shared::cta.bulk_group [%0], [%1], %2;" ::"l"(dst), "r"(src), "r"(bytes) : "memory");
}
__device__ __forceinline__ void tma_store_2d(const CUtensorMap* map, uint32_t src, int c0, int c1) {
  asm volatile("cp.async.bulk.tensor.2d.global.shared::cta.bulk_group [%0, {%2, %3}], [%1];" ::"l"(map), "r"(src),
               "r"(c0), "r"(c1)
               : "memory");
}
__device__ __forceinline__ void bulk_commit() { asm volatile("cp.async.bulk.commit_group;" ::: "memory"); }
__device__ __forceinline__ void bulk_wait_read0() { asm volatile("cp.async.bulk.wait_group.read 0;" ::: "memory"); }
__device__ __forceinline__ void bulk_wait0() { asm volatile("cp.async.bulk.wait_group 0;" ::: "memory"); }
__device__ __forceinline__ void named_bar_sync(int id, int nthreads) {
  asm volatile("bar.sync %0, %1;" ::"r"(id), "r"(nthreads) : "memory");
}
__device__ __forceinline__ void named_bar_arrive(int id, int nthreads) {
  asm volatile("bar.arrive %0, %1;" ::"r"(id), "r"(nthreads) : "memory");
}

__device__ __forceinline__ bool named_bar_or(int id, int nthreads, bool v) {
  uint32_t r;
  asm volatile("{\n.reg .pred p, q;\nsetp.ne.b32 q, %3, 0;\nbar.red.or.pred p, %1, %2, q;\nselp.b32 %0, 1, 0, p;\n}\n"
               : "=r"(r) : "r"(id), "r"(nthreads), "r"((int)v) : "memory");
  return __any_sync(0xffffffffu, r != 0);
}

__device__ __forceinline__ void wgmma_fence() { asm volatile("wgmma.fence.sync.aligned;\n" ::: "memory"); }
__device__ __forceinline__ void wgmma_commit() { asm volatile("wgmma.commit_group.sync.aligned;\n" ::: "memory"); }
template <int N>
__device__ __forceinline__ void wgmma_wait() {
  asm volatile("wgmma.wait_group.sync.aligned %0;\n" ::"n"(N) : "memory");
}
template <int R>
__device__ __forceinline__ void setmaxnreg_inc() { asm volatile("setmaxnreg.inc.sync.aligned.u32 %0;\n" ::"n"(R)); }
template <int R>
__device__ __forceinline__ void setmaxnreg_dec() { asm volatile("setmaxnreg.dec.sync.aligned.u32 %0;\n" ::"n"(R)); }
template <int N>
__device__ __forceinline__ void reg_fence(float* r) {
#pragma unroll
  for (int i = 0; i < N; i++) asm volatile("" : "+f"(r[i])::"memory");
}

template <int N>
__device__ __forceinline__ void reg_define(float* r) {
#pragma unroll
  for (int i = 0; i < N; i++) r[i] = 0.f;
}

__device__ __forceinline__ uint64_t desc_lo(uint32_t lo) {
  uint64_t d;
  asm("mov.b64 %0, {%1, %2};" : "=l"(d) : "r"(lo), "r"(0x40000040u));
  return d;
}
__device__ __forceinline__ uint64_t make_desc(uint32_t addr, uint32_t lbo_bytes) {
  return desc_lo((addr >> 4) + ((lbo_bytes >> 4) << 16));
}

__device__ __forceinline__ void wgmma_n192_ss_ta0_tb1(float* d, uint64_t descA, uint64_t descB, int scaleD) {
  asm volatile("{\n.reg .pred p;\nsetp.ne.b32 p, %98, 0;\n"
    "wgmma.mma_async.sync.aligned.m64n192k16.f32.bf16.bf16 {%0, %1, %2, %3, %4, %5, %6, %7, %8, %9, %10, %11, %12, %13, %14, %15, %16, %17, %18, %19, %20, %21, %22, %23, %24, %25, %26, %27, %28, %29, %30, %31, %32, %33, %34, %35, %36, %37, %38, %39, %40, %41, %42, %43, %44, %45, %46, %47, %48, %49, %50, %51, %52, %53, %54, %55, %56, %57, %58, %59, %60, %61, %62, %63, %64, %65, %66, %67, %68, %69, %70, %71, %72, %73, %74, %75, %76, %77, %78, %79, %80, %81, %82, %83, %84, %85, %86, %87, %88, %89, %90, %91, %92, %93, %94, %95}, %96, %97, p, 1, 1, 0, 1;\n}\n"
    : "+f"(d[0]), "+f"(d[1]), "+f"(d[2]), "+f"(d[3]), "+f"(d[4]), "+f"(d[5]), "+f"(d[6]), "+f"(d[7]), "+f"(d[8]), "+f"(d[9]), "+f"(d[10]), "+f"(d[11]), "+f"(d[12]), "+f"(d[13]), "+f"(d[14]), "+f"(d[15]), "+f"(d[16]), "+f"(d[17]), "+f"(d[18]), "+f"(d[19]), "+f"(d[20]), "+f"(d[21]), "+f"(d[22]), "+f"(d[23]), "+f"(d[24]), "+f"(d[25]), "+f"(d[26]), "+f"(d[27]), "+f"(d[28]), "+f"(d[29]), "+f"(d[30]), "+f"(d[31]), "+f"(d[32]), "+f"(d[33]), "+f"(d[34]), "+f"(d[35]), "+f"(d[36]), "+f"(d[37]), "+f"(d[38]), "+f"(d[39]), "+f"(d[40]), "+f"(d[41]), "+f"(d[42]), "+f"(d[43]), "+f"(d[44]), "+f"(d[45]), "+f"(d[46]), "+f"(d[47]), "+f"(d[48]), "+f"(d[49]), "+f"(d[50]), "+f"(d[51]), "+f"(d[52]), "+f"(d[53]), "+f"(d[54]), "+f"(d[55]), "+f"(d[56]), "+f"(d[57]), "+f"(d[58]), "+f"(d[59]), "+f"(d[60]), "+f"(d[61]), "+f"(d[62]), "+f"(d[63]), "+f"(d[64]), "+f"(d[65]), "+f"(d[66]), "+f"(d[67]), "+f"(d[68]), "+f"(d[69]), "+f"(d[70]), "+f"(d[71]), "+f"(d[72]), "+f"(d[73]), "+f"(d[74]), "+f"(d[75]), "+f"(d[76]), "+f"(d[77]), "+f"(d[78]), "+f"(d[79]), "+f"(d[80]), "+f"(d[81]), "+f"(d[82]), "+f"(d[83]), "+f"(d[84]), "+f"(d[85]), "+f"(d[86]), "+f"(d[87]), "+f"(d[88]), "+f"(d[89]), "+f"(d[90]), "+f"(d[91]), "+f"(d[92]), "+f"(d[93]), "+f"(d[94]), "+f"(d[95])
    : "l"(descA), "l"(descB), "r"(scaleD));
}

__device__ __forceinline__ void wgmma_n128_ss_ta0_tb1(float* d, uint64_t descA, uint64_t descB, int scaleD) {
  asm volatile("{\n.reg .pred p;\nsetp.ne.b32 p, %66, 0;\n"
    "wgmma.mma_async.sync.aligned.m64n128k16.f32.bf16.bf16 {%0, %1, %2, %3, %4, %5, %6, %7, %8, %9, %10, %11, %12, %13, %14, %15, %16, %17, %18, %19, %20, %21, %22, %23, %24, %25, %26, %27, %28, %29, %30, %31, %32, %33, %34, %35, %36, %37, %38, %39, %40, %41, %42, %43, %44, %45, %46, %47, %48, %49, %50, %51, %52, %53, %54, %55, %56, %57, %58, %59, %60, %61, %62, %63}, %64, %65, p, 1, 1, 0, 1;\n}\n"
    : "+f"(d[0]), "+f"(d[1]), "+f"(d[2]), "+f"(d[3]), "+f"(d[4]), "+f"(d[5]), "+f"(d[6]), "+f"(d[7]), "+f"(d[8]), "+f"(d[9]), "+f"(d[10]), "+f"(d[11]), "+f"(d[12]), "+f"(d[13]), "+f"(d[14]), "+f"(d[15]), "+f"(d[16]), "+f"(d[17]), "+f"(d[18]), "+f"(d[19]), "+f"(d[20]), "+f"(d[21]), "+f"(d[22]), "+f"(d[23]), "+f"(d[24]), "+f"(d[25]), "+f"(d[26]), "+f"(d[27]), "+f"(d[28]), "+f"(d[29]), "+f"(d[30]), "+f"(d[31]), "+f"(d[32]), "+f"(d[33]), "+f"(d[34]), "+f"(d[35]), "+f"(d[36]), "+f"(d[37]), "+f"(d[38]), "+f"(d[39]), "+f"(d[40]), "+f"(d[41]), "+f"(d[42]), "+f"(d[43]), "+f"(d[44]), "+f"(d[45]), "+f"(d[46]), "+f"(d[47]), "+f"(d[48]), "+f"(d[49]), "+f"(d[50]), "+f"(d[51]), "+f"(d[52]), "+f"(d[53]), "+f"(d[54]), "+f"(d[55]), "+f"(d[56]), "+f"(d[57]), "+f"(d[58]), "+f"(d[59]), "+f"(d[60]), "+f"(d[61]), "+f"(d[62]), "+f"(d[63])
    : "l"(descA), "l"(descB), "r"(scaleD));
}

__device__ __forceinline__ void wgmma_n192_ssz_ta0_tb1(float* d, uint64_t descA, uint64_t descB) {
  asm volatile("{\n.reg .pred p;\nsetp.ne.b32 p, 0, 0;\n"
    "wgmma.mma_async.sync.aligned.m64n192k16.f32.bf16.bf16 {%0, %1, %2, %3, %4, %5, %6, %7, %8, %9, %10, %11, %12, %13, %14, %15, %16, %17, %18, %19, %20, %21, %22, %23, %24, %25, %26, %27, %28, %29, %30, %31, %32, %33, %34, %35, %36, %37, %38, %39, %40, %41, %42, %43, %44, %45, %46, %47, %48, %49, %50, %51, %52, %53, %54, %55, %56, %57, %58, %59, %60, %61, %62, %63, %64, %65, %66, %67, %68, %69, %70, %71, %72, %73, %74, %75, %76, %77, %78, %79, %80, %81, %82, %83, %84, %85, %86, %87, %88, %89, %90, %91, %92, %93, %94, %95}, %96, %97, p, 1, 1, 0, 1;\n}\n"
    : "=f"(d[0]), "=f"(d[1]), "=f"(d[2]), "=f"(d[3]), "=f"(d[4]), "=f"(d[5]), "=f"(d[6]), "=f"(d[7]), "=f"(d[8]), "=f"(d[9]), "=f"(d[10]), "=f"(d[11]), "=f"(d[12]), "=f"(d[13]), "=f"(d[14]), "=f"(d[15]), "=f"(d[16]), "=f"(d[17]), "=f"(d[18]), "=f"(d[19]), "=f"(d[20]), "=f"(d[21]), "=f"(d[22]), "=f"(d[23]), "=f"(d[24]), "=f"(d[25]), "=f"(d[26]), "=f"(d[27]), "=f"(d[28]), "=f"(d[29]), "=f"(d[30]), "=f"(d[31]), "=f"(d[32]), "=f"(d[33]), "=f"(d[34]), "=f"(d[35]), "=f"(d[36]), "=f"(d[37]), "=f"(d[38]), "=f"(d[39]), "=f"(d[40]), "=f"(d[41]), "=f"(d[42]), "=f"(d[43]), "=f"(d[44]), "=f"(d[45]), "=f"(d[46]), "=f"(d[47]), "=f"(d[48]), "=f"(d[49]), "=f"(d[50]), "=f"(d[51]), "=f"(d[52]), "=f"(d[53]), "=f"(d[54]), "=f"(d[55]), "=f"(d[56]), "=f"(d[57]), "=f"(d[58]), "=f"(d[59]), "=f"(d[60]), "=f"(d[61]), "=f"(d[62]), "=f"(d[63]), "=f"(d[64]), "=f"(d[65]), "=f"(d[66]), "=f"(d[67]), "=f"(d[68]), "=f"(d[69]), "=f"(d[70]), "=f"(d[71]), "=f"(d[72]), "=f"(d[73]), "=f"(d[74]), "=f"(d[75]), "=f"(d[76]), "=f"(d[77]), "=f"(d[78]), "=f"(d[79]), "=f"(d[80]), "=f"(d[81]), "=f"(d[82]), "=f"(d[83]), "=f"(d[84]), "=f"(d[85]), "=f"(d[86]), "=f"(d[87]), "=f"(d[88]), "=f"(d[89]), "=f"(d[90]), "=f"(d[91]), "=f"(d[92]), "=f"(d[93]), "=f"(d[94]), "=f"(d[95])
    : "l"(descA), "l"(descB));
}

__device__ __forceinline__ void wgmma_n80_rs_tb0(float* d, const uint32_t* a, uint64_t descB, int scaleD) {
  asm volatile("{\n.reg .pred p;\nsetp.ne.b32 p, %45, 0;\n"
    "wgmma.mma_async.sync.aligned.m64n80k16.f32.bf16.bf16 {%0, %1, %2, %3, %4, %5, %6, %7, %8, %9, %10, %11, %12, %13, %14, %15, %16, %17, %18, %19, %20, %21, %22, %23, %24, %25, %26, %27, %28, %29, %30, %31, %32, %33, %34, %35, %36, %37, %38, %39}, {%40, %41, %42, %43}, %44, p, 1, 1, 0;\n}\n"
    : "+f"(d[0]), "+f"(d[1]), "+f"(d[2]), "+f"(d[3]), "+f"(d[4]), "+f"(d[5]), "+f"(d[6]), "+f"(d[7]), "+f"(d[8]), "+f"(d[9]), "+f"(d[10]), "+f"(d[11]), "+f"(d[12]), "+f"(d[13]), "+f"(d[14]), "+f"(d[15]), "+f"(d[16]), "+f"(d[17]), "+f"(d[18]), "+f"(d[19]), "+f"(d[20]), "+f"(d[21]), "+f"(d[22]), "+f"(d[23]), "+f"(d[24]), "+f"(d[25]), "+f"(d[26]), "+f"(d[27]), "+f"(d[28]), "+f"(d[29]), "+f"(d[30]), "+f"(d[31]), "+f"(d[32]), "+f"(d[33]), "+f"(d[34]), "+f"(d[35]), "+f"(d[36]), "+f"(d[37]), "+f"(d[38]), "+f"(d[39])
    : "r"(a[0]), "r"(a[1]), "r"(a[2]), "r"(a[3]), "l"(descB), "r"(scaleD));
}

__device__ __forceinline__ void wgmma_n80_rsz_tb0(float* d, const uint32_t* a, uint64_t descB) {
  asm volatile("{\n.reg .pred p;\nsetp.ne.b32 p, 0, 0;\n"
    "wgmma.mma_async.sync.aligned.m64n80k16.f32.bf16.bf16 {%0, %1, %2, %3, %4, %5, %6, %7, %8, %9, %10, %11, %12, %13, %14, %15, %16, %17, %18, %19, %20, %21, %22, %23, %24, %25, %26, %27, %28, %29, %30, %31, %32, %33, %34, %35, %36, %37, %38, %39}, {%40, %41, %42, %43}, %44, p, 1, 1, 0;\n}\n"
    : "=f"(d[0]), "=f"(d[1]), "=f"(d[2]), "=f"(d[3]), "=f"(d[4]), "=f"(d[5]), "=f"(d[6]), "=f"(d[7]), "=f"(d[8]), "=f"(d[9]), "=f"(d[10]), "=f"(d[11]), "=f"(d[12]), "=f"(d[13]), "=f"(d[14]), "=f"(d[15]), "=f"(d[16]), "=f"(d[17]), "=f"(d[18]), "=f"(d[19]), "=f"(d[20]), "=f"(d[21]), "=f"(d[22]), "=f"(d[23]), "=f"(d[24]), "=f"(d[25]), "=f"(d[26]), "=f"(d[27]), "=f"(d[28]), "=f"(d[29]), "=f"(d[30]), "=f"(d[31]), "=f"(d[32]), "=f"(d[33]), "=f"(d[34]), "=f"(d[35]), "=f"(d[36]), "=f"(d[37]), "=f"(d[38]), "=f"(d[39])
    : "r"(a[0]), "r"(a[1]), "r"(a[2]), "r"(a[3]), "l"(descB));
}

__device__ __forceinline__ void wgmma_n32_rs_tb1(float* d, const uint32_t* a, uint64_t descB, int scaleD) {
  asm volatile("{\n.reg .pred p;\nsetp.ne.b32 p, %21, 0;\n"
    "wgmma.mma_async.sync.aligned.m64n32k16.f32.bf16.bf16 {%0, %1, %2, %3, %4, %5, %6, %7, %8, %9, %10, %11, %12, %13, %14, %15}, {%16, %17, %18, %19}, %20, p, 1, 1, 1;\n}\n"
    : "+f"(d[0]), "+f"(d[1]), "+f"(d[2]), "+f"(d[3]), "+f"(d[4]), "+f"(d[5]), "+f"(d[6]), "+f"(d[7]), "+f"(d[8]), "+f"(d[9]), "+f"(d[10]), "+f"(d[11]), "+f"(d[12]), "+f"(d[13]), "+f"(d[14]), "+f"(d[15])
    : "r"(a[0]), "r"(a[1]), "r"(a[2]), "r"(a[3]), "l"(descB), "r"(scaleD));
}

__device__ __forceinline__ void wgmma_n32_rsz_tb1(float* d, const uint32_t* a, uint64_t descB) {
  asm volatile("{\n.reg .pred p;\nsetp.ne.b32 p, 0, 0;\n"
    "wgmma.mma_async.sync.aligned.m64n32k16.f32.bf16.bf16 {%0, %1, %2, %3, %4, %5, %6, %7, %8, %9, %10, %11, %12, %13, %14, %15}, {%16, %17, %18, %19}, %20, p, 1, 1, 1;\n}\n"
    : "=f"(d[0]), "=f"(d[1]), "=f"(d[2]), "=f"(d[3]), "=f"(d[4]), "=f"(d[5]), "=f"(d[6]), "=f"(d[7]), "=f"(d[8]), "=f"(d[9]), "=f"(d[10]), "=f"(d[11]), "=f"(d[12]), "=f"(d[13]), "=f"(d[14]), "=f"(d[15])
    : "r"(a[0]), "r"(a[1]), "r"(a[2]), "r"(a[3]), "l"(descB));
}

__device__ __forceinline__ void wgmma_n32_rs_tb0(float* d, const uint32_t* a, uint64_t descB, int scaleD) {
  asm volatile("{\n.reg .pred p;\nsetp.ne.b32 p, %21, 0;\n"
    "wgmma.mma_async.sync.aligned.m64n32k16.f32.bf16.bf16 {%0, %1, %2, %3, %4, %5, %6, %7, %8, %9, %10, %11, %12, %13, %14, %15}, {%16, %17, %18, %19}, %20, p, 1, 1, 0;\n}\n"
    : "+f"(d[0]), "+f"(d[1]), "+f"(d[2]), "+f"(d[3]), "+f"(d[4]), "+f"(d[5]), "+f"(d[6]), "+f"(d[7]), "+f"(d[8]), "+f"(d[9]), "+f"(d[10]), "+f"(d[11]), "+f"(d[12]), "+f"(d[13]), "+f"(d[14]), "+f"(d[15])
    : "r"(a[0]), "r"(a[1]), "r"(a[2]), "r"(a[3]), "l"(descB), "r"(scaleD));
}

__device__ __forceinline__ void wgmma_n32_rsz_tb0(float* d, const uint32_t* a, uint64_t descB) {
  asm volatile("{\n.reg .pred p;\nsetp.ne.b32 p, 0, 0;\n"
    "wgmma.mma_async.sync.aligned.m64n32k16.f32.bf16.bf16 {%0, %1, %2, %3, %4, %5, %6, %7, %8, %9, %10, %11, %12, %13, %14, %15}, {%16, %17, %18, %19}, %20, p, 1, 1, 0;\n}\n"
    : "=f"(d[0]), "=f"(d[1]), "=f"(d[2]), "=f"(d[3]), "=f"(d[4]), "=f"(d[5]), "=f"(d[6]), "=f"(d[7]), "=f"(d[8]), "=f"(d[9]), "=f"(d[10]), "=f"(d[11]), "=f"(d[12]), "=f"(d[13]), "=f"(d[14]), "=f"(d[15])
    : "r"(a[0]), "r"(a[1]), "r"(a[2]), "r"(a[3]), "l"(descB));
}

__device__ __forceinline__ uint32_t pack_bf16x2(float lo, float hi) {
  uint32_t r;
  asm("cvt.rn.bf16x2.f32 %0, %1, %2;" : "=r"(r) : "f"(hi), "f"(lo));
  return r;
}
__device__ __forceinline__ float bf_lo(uint32_t p) { return __uint_as_float(p << 16); }
__device__ __forceinline__ float bf_hi(uint32_t p) { return __uint_as_float(p & 0xffff0000u); }
__device__ __forceinline__ float bf16_round(float v) { return __bfloat162float(__float2bfloat16_rn(v)); }
__device__ __forceinline__ float ex2_approx(float x) {
  float r;
  asm("ex2.approx.ftz.f32 %0, %1;" : "=f"(r) : "f"(x));
  return r;
}
__device__ __forceinline__ float rcp_fast(float x) {
  float r;
  asm("rcp.approx.ftz.f32 %0, %1;" : "=f"(r) : "f"(x));
  return r;
}
__device__ __forceinline__ void ldmatrix_x4(uint32_t (&r)[4], uint32_t addr) {
  asm volatile("ldmatrix.sync.aligned.m8n8.x4.shared.b16 {%0,%1,%2,%3}, [%4];"
               : "=r"(r[0]), "=r"(r[1]), "=r"(r[2]), "=r"(r[3])
               : "r"(addr)
               : "memory");
}
__device__ __forceinline__ void stmatrix_x4(uint32_t addr, uint32_t r0, uint32_t r1, uint32_t r2, uint32_t r3) {
  asm volatile("stmatrix.sync.aligned.m8n8.x4.shared.b16 [%0], {%1,%2,%3,%4};" ::"r"(addr), "r"(r0), "r"(r1), "r"(r2),
               "r"(r3));
}
__device__ __forceinline__ uint32_t add_bf16x2(uint32_t a, uint32_t b) {
  uint32_t r;
  asm("add.rn.bf16x2 %0, %1, %2;" : "=r"(r) : "r"(a), "r"(b));
  return r;
}
__device__ __forceinline__ uint4 lds128(uint32_t addr) {
  uint4 v;
  asm volatile("ld.shared.v4.b32 {%0,%1,%2,%3}, [%4];" : "=r"(v.x), "=r"(v.y), "=r"(v.z), "=r"(v.w) : "r"(addr) : "memory");
  return v;
}
__device__ __forceinline__ uint32_t lds32(uint32_t addr) {
  uint32_t v;
  asm volatile("ld.shared.b32 %0, [%1];" : "=r"(v) : "r"(addr) : "memory");
  return v;
}
__device__ __forceinline__ void sts32(uint32_t addr, uint32_t v) {
  asm volatile("st.shared.b32 [%0], %1;" ::"r"(addr), "r"(v) : "memory");
}

__device__ __forceinline__ unsigned ld_acquire_u32(const unsigned* p) {
  unsigned v;
  asm volatile("ld.acquire.gpu.global.u32 %0, [%1];" : "=r"(v) : "l"(p) : "memory");
  return v;
}
__device__ __forceinline__ unsigned ld_relaxed_u32(const void* p) {
  unsigned v;
  asm volatile("ld.relaxed.gpu.global.u32 %0, [%1];" : "=r"(v) : "l"(p) : "memory");
  return v;
}
__device__ __forceinline__ void red_announce(unsigned* p, unsigned v) {
  asm volatile("red.relaxed.gpu.global.add.u32 [%0], %1;" ::"l"(p), "r"(v) : "memory");
}
__device__ __forceinline__ uint32_t set_tag(uint32_t w, uint32_t m, uint32_t tag) { return (w & ~m) | (tag & m); }
__device__ __forceinline__ uint32_t o_tag(int L) { return (L + 1) & 1; }
__device__ __forceinline__ uint32_t x_tag(unsigned ep1, int L) { return ep1 & 1; }

template <bool SLOW>
__device__ __forceinline__ void wait_mask(const unsigned* f, int cnt, unsigned target, uint32_t need, uint32_t& seen, int lane) {
  if ((seen & need) == need) return;
  const unsigned* fp = f + (lane & (cnt - 1));
#pragma unroll 1
  for (uint32_t it = 0; it < (1u << 17); ++it) {
    seen = __ballot_sync(0xffffffffu, (int)(ld_acquire_u32(fp) - target) >= 0);
    if ((seen & need) == need) break;
    if (SLOW) __nanosleep(400);
  }
  fence_proxy_async_all();
}
__device__ __forceinline__ float4 ld_rec(const float4* p) {
  float4 v;
  asm volatile("ld.relaxed.gpu.global.v4.f32 {%0,%1,%2,%3}, [%4];" : "=f"(v.x), "=f"(v.y), "=f"(v.z), "=f"(v.w) : "l"(p) : "memory");
  return v;
}
__device__ __forceinline__ void st_rec(float4* p, float a, float b, float c, unsigned tag) {
  asm volatile("st.relaxed.gpu.global.v4.f32 [%0], {%1,%2,%3,%4};" ::"l"(p), "f"(a), "f"(b), "f"(c), "f"(__uint_as_float(tag)) : "memory");
}
template <int N>
__device__ __forceinline__ float4 sum_recs(const float4* p, int stride, unsigned tag) {
  float4 s;
#pragma unroll 1
  for (uint32_t it = 0; it < (1u << 17); ++it) {
    float4 v[N];
#pragma unroll
    for (int t = 0; t < N; t++) v[t] = ld_rec(p + t * stride);
    bool ok = true;
    s = make_float4(0.f, 0.f, 0.f, 0.f);
#pragma unroll
    for (int t = 0; t < N; t++) {
      ok &= __float_as_uint(v[t].w) == tag;
      s.x += v[t].x;
      s.y += v[t].y;
      s.z += v[t].z;
    }
    if (ok) break;
    __nanosleep(200);
  }
  return s;
}

__device__ __forceinline__ int fresh_tid() {
  int t;
  asm volatile("mov.u32 %0, %%tid.x;" : "=r"(t));
  return t;
}
#define PHASE_IDS                                  \
  const int tid_ = fresh_tid();                    \
  const int lane = tid_ & 31, wwarp = __shfl_sync(0xffffffffu, (tid_ >> 5) & 3, 0), tid = tid_ & 127; \
  const int g = lane >> 2, c = lane & 3;           \
  (void)tid; (void)g; (void)c; (void)wwarp;

#define PHASE_IDS_W                                \
  const int lane = fresh_tid() & 31, wwarp = warp & 3; \
  const int g = lane >> 2, c = lane & 3;

#define GTL(i) do { } while (0)
#define GTLX(c, i) do { } while (0)
#define TGET(v) do { } while (0)
#define TPUT(c, i, v) do { } while (0)

constexpr float SM_C = 0.17677669529663687f * 1.4426950408889634f;

__device__ __forceinline__ void stmatrix_x4_if(bool ok, uint32_t addr, uint32_t r0, uint32_t r1, uint32_t r2, uint32_t r3) {
  asm volatile("{\n.reg .pred p;\nsetp.ne.b32 p, %5, 0;\n@p stmatrix.sync.aligned.m8n8.x4.shared.b16 [%0], {%1,%2,%3,%4};\n}\n" ::"r"(addr),
               "r"(r0), "r"(r1), "r"(r2), "r"(r3), "r"((int)ok));
}

__device__ __forceinline__ void attn_a_slow(const uint8_t* __restrict__ kvimg, int L, int gb, int hp, uint32_t bad,
                                            int row0, int lane) {
  constexpr uint32_t sq = SBASE + OFF_SLOT + 3 * 16384;
#pragma unroll 1
  for (int j = 0; j < 8; j++) {
    const uint8_t* tp = kvimg + (size_t)(gb * 16 + hp) * 32768 + (j * 32 + lane) * 128 + ((lane & 7) << 4);
#pragma unroll 1
    for (uint32_t it = 0; it < (1u << 17); ++it)
      if (((ld_relaxed_u32(tp) ^ lds32(SBASE + OFF_EPOCH)) & 1u) == 0u) break;
  }
  __syncwarp();
#pragma unroll 1
  for (int t = 0; t < 32; t++) {
    const int hh = t >> 4, row = row0 + (t & 7) + (t & 8) * 4;
    if (!((bad >> hh) & 1u)) continue;
    const int qpos = gb * 128 + row;
    const uint32_t qaddr = sq + row * 128;
    float mx = -INFINITY, sum = 0.f, acc = 0.f;
#pragma unroll 1
    for (int pass = 0; pass < 2; pass++) {
#pragma unroll 1
      for (int j = 0; j < 8; j++) {
        const int kp = qpos - (lane + 32 * j);
        const uint8_t* kr = kvimg + ((size_t)((kp >> 7) * 16 + hp) * 2 + ((kp >> 6) & 1)) * 16384 + (kp & 63) * 128;
        float d = -INFINITY;
        if (kp >= 0) {
          d = 0.f;
#pragma unroll 1
          for (int q = 0; q < 4; q++) {
            const uint4 kv = __ldcg(reinterpret_cast<const uint4*>(kr + (((hh * 4 + q) ^ (kp & 7)) << 4)));
            const uint4 qv = lds128(qaddr + (((hh * 4 + q) ^ (row & 7)) << 4));
            const uint32_t kw[4] = {kv.x, kv.y, kv.z, kv.w}, qw[4] = {qv.x, qv.y, qv.z, qv.w};
#pragma unroll
            for (int e = 0; e < 4; e++) d = fmaf(bf_lo(kw[e]), bf_lo(qw[e]), fmaf(bf_hi(kw[e]), bf_hi(qw[e]), d));
          }
        }
        if (pass == 0) {
          mx = fmaxf(mx, d);
        } else {
          const float ev = ex2_approx(d - mx);
          sum += ev;
          const float pv = bf16_round(ev);
#pragma unroll 1
          for (int kk = 0; kk < 32; kk++) {
            const float pk = __shfl_sync(0xffffffffu, pv, kk);
            const int k2 = qpos - (kk + 32 * j);
            if (k2 >= 0) {
              const uint8_t* vr = kvimg + ((size_t)((k2 >> 7) * 16 + hp) * 2 + ((k2 >> 6) & 1)) * 16384 + 8192 + (k2 & 63) * 128;
              const unsigned short vv =
                  __ldcg(reinterpret_cast<const unsigned short*>(vr + (((hh * 4 + (lane >> 3)) ^ (k2 & 7)) << 4) + (lane & 7) * 2));
              acc = fmaf(pk, __uint_as_float((uint32_t)vv << 16), acc);
            }
          }
        }
      }
      if (pass == 0) {
#pragma unroll
        for (int o = 16; o > 0; o >>= 1) mx = fmaxf(mx, __shfl_xor_sync(0xffffffffu, mx, o));
      }
    }
#pragma unroll
    for (int o = 16; o > 0; o >>= 1) sum += __shfl_xor_sync(0xffffffffu, sum, o);
    acc *= rcp_fast(sum);
    const float hi = __shfl_down_sync(0xffffffffu, acc, 1);
    __syncwarp();
    if ((lane & 1) == 0) sts32(qaddr + (((hh * 4 + (lane >> 3)) ^ (row & 7)) << 4) + (lane & 7) * 2,
                               set_tag(pack_bf16x2(acc, hi), hh == 0 && lane == 0, o_tag(L)));
    __syncwarp();
  }
}

template <int HH>
__device__ __forceinline__ void store_o(const float (&o)[16], const float (&inv)[2], uint32_t ra, uint32_t tag, bool ok) {
  const uint32_t m = HH == 0 && (fresh_tid() & 3) == 0;
#pragma unroll
  for (int jp = 0; jp < 2; jp++) {
    uint32_t w0 = pack_bf16x2(o[8 * jp] * inv[0], o[8 * jp + 1] * inv[0]);
    uint32_t w1 = pack_bf16x2(o[8 * jp + 2] * inv[1], o[8 * jp + 3] * inv[1]);
    if (HH == 0 && jp == 0) {
      w0 = set_tag(w0, m, tag);
      w1 = set_tag(w1, m, tag);
    }
    stmatrix_x4_if(ok, ra ^ ((HH * 4 + 2 * jp) << 4), w0, w1, pack_bf16x2(o[8 * jp + 4] * inv[0], o[8 * jp + 5] * inv[0]),
                   pack_bf16x2(o[8 * jp + 6] * inv[1], o[8 * jp + 7] * inv[1]));
  }
}
__device__ __forceinline__ int tile_row(bool B, int w, int r, int g) { return (B ? 16 * w + 8 * r : 8 * w + 32 * r) + g; }
__device__ __forceinline__ uint32_t q_row_addr(bool B, int R, int w, int lane) {
  return SBASE + OFF_SLOT + 3 * 16384 + R * 8192 + tile_row(B, w, (lane >> 3) & 1, lane & 7) * 128 + (((lane >> 4) ^ (lane & 7)) << 4);
}

struct AttnA {
  float s[2][16], o[2][16], l[2][2], sh[2][3];
  uint32_t p[2][4], t[2], me[4], ra, bad, zero;
};
#define ATS_(i) do { } while (0)
template <int V>
__device__ __forceinline__ void attn_sum(AttnA& a, int nv) {
  constexpr int hh = (V >> 1) & 1, kh = V & 1, i = V >> 2;
#pragma unroll
  for (int r = 0; r < 2; r++) {
    const uint32_t t1 = add_bf16x2(add_bf16x2(a.p[0][r], a.p[0][2 + r]), add_bf16x2(a.p[1][r], a.p[1][2 + r]));
    if (kh == 0) {
      a.t[r] = t1;
    } else {
      uint32_t tt = add_bf16x2(a.t[r], t1);
      if (i > 0) tt = i <= nv ? tt : 0u;
      const float v = bf_lo(tt) + bf_hi(tt);
      a.l[hh][r] = i == 0 ? v : a.l[hh][r] + v;
    }
  }
}
template <int HH>
__device__ __forceinline__ void attn_shfl(AttnA& a) {
#pragma unroll
  for (int r = 0; r < 2; r++)
#pragma unroll
    for (int j = 0; j < 3; j++) a.sh[r][j] = __shfl_xor_sync(0xffffffffu, a.l[HH][r], j + 1);
}
template <int HH>
__device__ __forceinline__ void attn_fin(AttnA& a) {
  bool bad = false;
  float inv[2];
#pragma unroll
  for (int r = 0; r < 2; r++) {
    const float v = (a.l[HH][r] + a.sh[r][0]) + (a.sh[r][1] + a.sh[r][2]);
    bad |= !(v <= 1.152921504606846976e18f && v >= 8.673617379884035e-19f);
    inv[r] = rcp_fast(v);
  }
  bad = __any_sync(0xffffffffu, bad);
  if (HH == 1) wgmma_wait<0>();
  reg_fence<16>(a.o[HH]);
  store_o<HH>(a.o[HH], inv, a.ra, o_tag(0), !bad);
  a.bad = (HH == 0 ? 0u : a.bad) | (bad ? 1u << HH : 0u);
}
__device__ __forceinline__ void attn_masks(AttnA& a, int wr) {
  const int lane = fresh_tid() & 31, d = (lane >> 2) - 2 * (lane & 3);
  const uint32_t tri = d >= 1 ? 0xffffffffu : (d == 0 ? 0xffffu : 0u);
#pragma unroll
  for (int t = 0; t < 4; t++) a.me[t] = wr > t ? 0xffffffffu : (wr == t ? tri : 0u);
}
template <int V, int K>
__device__ __forceinline__ uint32_t attn_exp(AttnA& a) {
  constexpr int i = V >> 2, kh = V & 1, r = K & 1;
  if ((i == 0 && kh > r) || (i == 4 && kh < r)) return 0u;
  const uint32_t w = pack_bf16x2(ex2_approx(a.s[V & 1][2 * K]), ex2_approx(a.s[V & 1][2 * K + 1]));
  if (i == 0 && kh == r) return w & a.me[K >> 1];
  if (i == 4 && kh == r) return w & ~a.me[K >> 1];
  return w;
}
template <int V>
__device__ __forceinline__ void attn_unit(AttnA& a, const uint32_t (&q)[2][2][4], uint64_t dcur, uint64_t dnext, int R, int wr, int nv,
                                          uint32_t hbar, uint32_t hpar, uint32_t rbar, bool rel) {
  constexpr int hh = (V >> 1) & 1, kh = V & 1, i = V >> 2;
  ATS_(V + 1);
  asm volatile("" : "+l"(dcur), "+l"(dnext));
  wgmma_wait<1>();
  reg_fence<16>(a.s[V & 1]);
  bool hok = true;
  if ((V & 3) == 2 && V < 16) hok = mbar_test(hbar, hpar);
  const uint64_t d0 = ((V & 3) >= 2 ? dnext : dcur) + ((hh ^ 1) * 4 + kh * 256), d1 = ((V & 3) >= 2 ? dnext : dcur) + ((hh ^ 1) * 4 + kh * 256 + 2);
  const uint64_t d2 = dcur + (512 + hh * 4 + kh * 256), d3 = dcur + (640 + hh * 4 + kh * 256);
  if ((V & 3) == 1 && V > 4 && rel) mbar_arrive(rbar);
  if (V > 0) attn_sum<V - 1>(a, nv);
  if (V == 15) attn_masks(a, wr);
  if (V == 18) {
    attn_shfl<0>(a);
    a.ra = q_row_addr(false, R, wr, fresh_tid() & 31);
  }
  if (V == 19) attn_fin<0>(a);
  uint32_t p[2][4];
  p[0][0] = attn_exp<V, 0>(a);
  p[0][1] = attn_exp<V, 1>(a);
  p[0][2] = attn_exp<V, 2>(a);
  p[0][3] = attn_exp<V, 3>(a);
  p[1][0] = attn_exp<V, 4>(a);
  p[1][1] = attn_exp<V, 5>(a);
  p[1][2] = attn_exp<V, 6>(a);
  p[1][3] = attn_exp<V, 7>(a);
  if (V > 0) {
#pragma unroll
    for (int r = 0; r < 2; r++) p[1][r] ^= (kh ? a.t[r] : __float_as_uint(a.l[hh ^ 1][r])) & a.zero;
  }
#pragma unroll
  for (int k = 0; k < 8; k++) {
    asm volatile("" : "+r"(p[k >> 2][k & 3]));
    a.p[k >> 2][k & 3] = p[k >> 2][k & 3];
  }
  if (!hok) mbar_wait(hbar, hpar);
  wgmma_fence();
  if (V < 18) wgmma_n32_rsz_tb0(a.s[V & 1], q[hh ^ 1][0], d0);
  if (i == 0 && kh == 0) wgmma_n32_rsz_tb1(a.o[hh], a.p[0], d2);
  else wgmma_n32_rs_tb1(a.o[hh], a.p[0], d2, 1);
  if (V < 18) wgmma_n32_rs_tb0(a.s[V & 1], q[hh ^ 1][1], d1, 1);
  wgmma_n32_rs_tb1(a.o[hh], a.p[1], d3, 1);
  wgmma_commit();
}
template <int I>
__device__ __forceinline__ void attn_step(AttnA& a, const uint32_t (&q)[2][2][4], uint64_t dcur, uint64_t dnext, int R, int wr, int nv,
                                          uint32_t hbar, uint32_t hpar, uint32_t rbar, bool rel) {
  attn_unit<4 * I>(a, q, dcur, dnext, R, wr, nv, hbar, hpar, rbar, rel);
  attn_unit<4 * I + 1>(a, q, dcur, dnext, R, wr, nv, hbar, hpar, rbar, rel);
  attn_unit<4 * I + 2>(a, q, dcur, dnext, R, wr, nv, hbar, hpar, rbar, rel);
  attn_unit<4 * I + 3>(a, q, dcur, dnext, R, wr, nv, hbar, hpar, rbar, rel);
}

__device__ __forceinline__ void attention_a(const uint32_t (&q)[2][2][4], int R, int L, int gb, int hp, uint32_t par0, uint32_t parA,
                                            int wr, uint32_t zero) {
  constexpr uint32_t bars = SBASE + OFF_BAR;
  constexpr uint32_t dslot = ((SBASE + OFF_SLOT) >> 4) + 0x10000u;
  auto next = [&](uint64_t d) { return desc_lo((uint32_t)d == dslot ? dslot + 2048 : (uint32_t)d - 1024) + zero; };
  uint64_t d0 = desc_lo(dslot + R * 1024) + zero, d1 = next(d0);
  AttnA a;
  ATS_(0);
  wgmma_fence();
#pragma unroll
  for (int v = 0; v < 2; v++) {
    wgmma_n32_rsz_tb0(a.s[v], q[0][0], d0 + v * 256);
    wgmma_n32_rs_tb0(a.s[v], q[0][1], d0 + (v * 256 + 2), 1);
    wgmma_commit();
  }
  a.zero = zero;
  const bool lane0 = (fresh_tid() & 31) == 0;
  attn_masks(a, wr);
  const int nv = 2 * gb + R;
  const uint32_t hb = bars + 8u * (B_HALO - R), rb = bars + 8u * (B_REL - R);
  attn_step<0>(a, q, d0, d1, R, wr, nv, hb, par0, 0, false);
  d0 = next(d1);
  attn_step<1>(a, q, d1, d0, R, wr, nv, hb + 8, R ? par0 : parA, rb + 8, lane0);
  d1 = next(d0);
  attn_step<2>(a, q, d0, d1, R, wr, nv, hb + 16, parA, rb + 16, lane0);
  d0 = next(d1);
  attn_step<3>(a, q, d1, d0, R, wr, nv, hb + 24, parA, rb + 24, lane0 && R);
  attn_step<4>(a, q, d0, d0, R, wr, nv, 0, 0, rb, false);
  ATS_(21);
  attn_sum<19>(a, nv);
  attn_shfl<1>(a);
  attn_fin<1>(a);
  if (a.bad != 0u) attn_a_slow(g_kvA[L >> 1][0][0][0], L, gb, hp, a.bad, R * 64 + wr * 8, fresh_tid() & 31);
}

constexpr uint32_t KB_ROW0 = SBASE + OFF_SLOT + 2048, VB_ROW0 = SBASE + OFF_SLOT + 24576 + 2048;

__device__ __forceinline__ void attention_b(const uint32_t (&q)[2][2][4], int R, int gb, uint32_t par0, int wr) {
  constexpr uint32_t bars = SBASE + OFF_BAR;
  const uint32_t dk = ((KB_ROW0 - 2048) >> 4) + 0x10000u + R * 512, dv = dk + ((VB_ROW0 - KB_ROW0) >> 4);
  float s[2][40];
  mbar_wait(bars + 8u * (B_HALO - R), par0);
  wgmma_fence();
#pragma unroll
  for (int hh = 0; hh < 2; hh++) {
    wgmma_n80_rsz_tb0(s[hh], q[hh][0], desc_lo(dk + hh * 4));
    wgmma_n80_rs_tb0(s[hh], q[hh][1], desc_lo(dk + hh * 4 + 2), 1);
  }
  wgmma_commit();
  const int lane = fresh_tid() & 31, g = lane >> 2;
  const bool odd = g & 1, edge = R == 0 && gb == 0 && wr == 0;
  const int D = 2 * (lane & 3) + (g & 1) - g;
  const uint32_t ra = q_row_addr(true, R, wr, lane);
  wgmma_wait<0>();
  reg_fence<40>(s[0]);
  reg_fence<40>(s[1]);
  float z[2][2], y[2][2];
#define GATHER_(W)                                                                                          \
  _Pragma("unroll") for (int hh = 0; hh < 2; hh++) _Pragma("unroll") for (int r = 0; r < 2; r++) {          \
    const float* e = &s[hh][4 * (2 * W + r) + 2 * r];                                                       \
    z[hh][r] = odd ? e[5] : e[4];                                                                           \
    y[hh][r] = D >= 2 ? (odd ? e[1] : e[0]) : (odd ? e[9] : e[8]);                                          \
  }
  if (wr < 2) {
    if (wr == 0) { GATHER_(0) } else { GATHER_(1) }
  } else {
    if (wr == 2) { GATHER_(2) } else { GATHER_(3) }
  }
#undef GATHER_
  float o[2][16], inv[2][2];
  uint32_t p[2][5][4];
  const int sh = odd ? 16 : 0, kb = wr + (D >= 2 ? 0 : 1);
#pragma unroll
  for (int hh = 0; hh < 2; hh++) {
    if (edge) {
      z[hh][0] = -INFINITY;
      if (D >= 2) y[hh][0] = y[hh][1] = -INFINITY;
    }
    uint32_t ab[2][2];
#pragma unroll
    for (int r = 0; r < 2; r++) {
      float m = fmaxf(z[hh][r], y[hh][r]);
      m = fmaxf(m, __shfl_xor_sync(0xffffffffu, m, 1));
      m = fmaxf(m, __shfl_xor_sync(0xffffffffu, m, 2));
      const float e0 = ex2_approx(z[hh][r] - m), e1 = ex2_approx(y[hh][r] - m);
      inv[hh][r] = e0 + e1;
      ab[r][0] = pack_bf16x2(e0, 0.f) << sh;
      ab[r][1] = pack_bf16x2(e1, 0.f) << sh;
    }
#pragma unroll
    for (int k = 0; k < 5; k++) {
      p[hh][k][0] = k == kb ? ab[0][1] : 0u;
      p[hh][k][1] = k == wr + 1 ? ab[1][0] : 0u;
      p[hh][k][2] = k == wr ? ab[0][0] : 0u;
      p[hh][k][3] = k == kb ? ab[1][1] : 0u;
#pragma unroll
      for (int j = 0; j < 4; j++) asm volatile("" : "+r"(p[hh][k][j]));
    }
  }
  wgmma_fence();
#pragma unroll
  for (int hh = 0; hh < 2; hh++) {
    wgmma_n32_rsz_tb1(o[hh], p[hh][0], desc_lo(dv + hh * 4));
#pragma unroll
    for (int k = 1; k < 5; k++) wgmma_n32_rs_tb1(o[hh], p[hh][k], desc_lo(dv + hh * 4 + k * 128), 1);
  }
  wgmma_commit();
#pragma unroll
  for (int hh = 0; hh < 2; hh++)
#pragma unroll
    for (int r = 0; r < 2; r++) {
      inv[hh][r] += __shfl_xor_sync(0xffffffffu, inv[hh][r], 1);
      inv[hh][r] += __shfl_xor_sync(0xffffffffu, inv[hh][r], 2);
      inv[hh][r] = rcp_fast(inv[hh][r]);
    }
  wgmma_wait<0>();
  reg_fence<16>(o[0]);
  reg_fence<16>(o[1]);
  store_o<0>(o[0], inv[0], ra, o_tag(1), true);
  store_o<1>(o[1], inv[1], ra, o_tag(1), true);
}

#define KTQM 0
#define TRICKLE 300
#define CSPF 4
#define WTURN 15
#define CSPF2 2
#define QEARLY 0
#define PRESLEEP 200
#define QTURN 2
struct Params {
  CUtensorMap x[5], xq[4], o, wqkv[2], wqkv3[2], wo3[2];
  const __nv_bfloat16* in_x;
  const __nv_bfloat16* wqkv_p[2];
  const __nv_bfloat16* wo_p[2];
  __nv_bfloat16* out;
  uint32_t zero;
};

__device__ __forceinline__ void colsum_part(const CUtensorMap* wmap, int ty, int qr, int hp) {
  constexpr uint32_t bars = SBASE + OFF_BAR, slots = SBASE + OFF_SLOT;
  PHASE_IDS
  const unsigned ep1 = (*(volatile unsigned*)(g_flags + F_DONE)) / NCTA + 1u;
  if (wwarp == 0 && elect_one()) {
    mbar_expect_tx(bars + 8u * B_CS, 6 * UNIT);
#pragma unroll 1
    for (int j = 0; j < 6; j++) {
      if (ty == 0) mbar_pace(bars + 8u * (B_QF + B_E + (j & 3)), j >> 2);
      else __nanosleep(400);
      tma_load_2d(slots + j * UNIT, wmap, bars + 8u * B_CS, (j >> 1) * 1024 + hp * 64, qr * 128 + (j & 1) * 64);
    }
  }
  mbar_wait(bars + 8u * B_CS, ty);
  const uint32_t src = slots + (tid >> 3) * 128 + (((tid & 7) ^ ((tid >> 3) & 7)) << 4);
#pragma unroll 1
  for (int p = 0; p < 3; p++) {
    float s[8];
#pragma unroll
    for (int e = 0; e < 8; e++) s[e] = 0.f;
#pragma unroll
    for (int j = 0; j < 8; j++) {
      const uint4 v = lds128(src + p * 2 * UNIT + j * 2048);
      const uint32_t x[4] = {v.x, v.y, v.z, v.w};
#pragma unroll
      for (int e = 0; e < 4; e++) {
        s[2 * e] += bf_lo(x[e]);
        s[2 * e + 1] += bf_hi(x[e]);
      }
    }
#pragma unroll
    for (int st = 0; st < 2; st++) {
      const bool up = (lane >> (st + 3)) & 1;
#pragma unroll
      for (int e = 0; e < (4 >> st); e++) {
        const float keep = up ? s[e + (4 >> st)] : s[e], give = up ? s[e] : s[e + (4 >> st)];
        s[e] = keep + __shfl_xor_sync(0xffffffffu, give, 8 << st);
      }
    }
    const uint32_t dst = slots + 6 * UNIT + ((wwarp * 3 + p) * 64 + (lane & 7) * 8 + ((lane >> 3) & 1) * 4 + (lane >> 4) * 2) * 4;
    sts32(dst, __float_as_uint(s[0]));
    sts32(dst + 4, __float_as_uint(s[1]));
  }
  named_bar_sync(6, 128);
  if (tid < 64) {
    float r[3] = {0.f, 0.f, 0.f};
#pragma unroll
    for (int e = 0; e < 12; e++) r[e % 3] += __uint_as_float(lds32(slots + 6 * UNIT + (e * 64 + tid) * 4));
    st_rec(&g_cs[ty][hp][qr][tid], r[0], r[1], r[2], ep1);
  }
  named_bar_sync(6, 128);
}

__device__ __forceinline__ int cs_pos(int col) { return (col & ~15) + ((col & 7) >> 1) * 4 + ((col >> 3) & 1) * 2 + (col & 1); }

__device__ __forceinline__ uint32_t ln_params(float s1, float s2) {
  const float mean = s1 * (1.0f / DM);
  const float var = fmaxf(fmaf(-mean, mean, s2 * (1.0f / DM)), 0.f);
  float sd;
  asm("sqrt.approx.f32 %0, %1;" : "=f"(sd) : "f"(bf16_round(bf16_round(var) + 1e-5f)));
  return pack_bf16x2(mean, sd);
}

struct RingProd {
  uint32_t rel = ((B_QF << 1) | 1) * 0x01010101u + 0x06040200u;
  int st = 0;
  __device__ __forceinline__ uint32_t next(uint32_t bar, uint32_t par, bool wait) {
    const uint32_t e = (rel >> (8 * st)) & 255u, a = SBASE + st * 5 * UNIT;
    if (wait) mbar_wait(SBASE + OFF_BAR + 8u * B_E + 8u * (e >> 1), e & 1u);
    rel ^= (e ^ ((bar << 1) | par)) << (8 * st);
    st = (st + 1) & 3;
    return a;
  }
};

#define SP1 15
#define SP2 14
#define SP3 12
#define SP4 12
#define SP5 15
#define SP6 14
#define SP7 16
__device__ __forceinline__ int q_split(int inst) {
  constexpr uint32_t T = 15u | ((SP1 - 1) << 4) | ((SP2 - 1) << 8) | ((SP3 - 1) << 12) | ((SP4 - 1) << 16) | ((SP5 - 1) << 20) |
                         ((SP6 - 1) << 24) | ((uint32_t)(SP7 - 1) << 28);
  return (int)((T >> (4 * inst)) & 15u) + 1;
}
__host__ __device__ constexpr uint32_t turn_par(int kind) {
  const int sp[8] = {16, SP1, SP2, SP3, SP4, SP5, SP6, SP7};
  int cnt[2] = {0, 0};
  uint32_t m = 0;
  for (int i = 0; i < 8; i++)
    for (int k = 0; k < 3; k++) {
      if (k == kind) m |= (uint32_t)(cnt[i & 1] & 1) << i;
      if (k == 0 ? (i == 1 || (i > 1 && sp[i - 1] < 16)) : (k == 2 || sp[i] < 16)) cnt[i & 1]++;
    }
  return m;
}
#define PREMASK 0xBDu
__device__ __forceinline__ bool w_pre(int inst) { return (PREMASK >> inst) & 1u; }
__global__ void __launch_bounds__(512, 1) fused_kernel(const __grid_constant__ Params P) {
  extern __shared__ __align__(1024) uint8_t smem_raw[];
  constexpr uint32_t base = SBASE, bars = base + OFF_BAR, slots = base + OFF_SLOT;
  if (smem_u32(smem_raw) != base) __trap();
  const int warp = __shfl_sync(0xffffffffu, threadIdx.x >> 5, 0), lane = threadIdx.x & 31;
  const int b = blockIdx.x;
#define QS 0
#define WS 1
  const int qr = ((b & ((8 << QS) - 1)) >> QS) ^ (((b >> (3 + QS)) & 1) * 7);
  const int hp = ((b >> (3 + QS)) << QS) + (b & ((1 << QS) - 1));
  const int rt = ((b & ((16 << WS) - 1)) >> WS) ^ (((b >> (4 + WS)) & 1) * 15);
  const int ct = ((b >> (4 + WS)) << WS) + (b & ((1 << WS) - 1));

  if (warp == 12) {
    if (elect_one()) {
#pragma unroll
      for (int s = 0; s < 4; s++) {
        mbar_init(bars + 8u * (B_QF + s), 2);
        mbar_init(bars + 8u * (B_QF + B_E + s), 4);
      }
      mbar_init(bars + 8u * B_GO, 1);
      fence_barrier_init();
    }
    __syncwarp();
    named_bar_arrive(0, 512);
  }
  if (threadIdx.x == 0) {
    for (int s = B_WF; s <= B_RF; s++) {
      mbar_init(bars + 8u * s, s == B_RF ? 1 : 2);
      mbar_init(bars + 8u * (s + B_E), 4);
    }
    mbar_init(bars + 8u * B_PREP, 1);
    mbar_init(bars + 8u * (B_PREP + 1), 1);
    mbar_init(bars + 8u * B_HL, 1);
    for (int s = 0; s < 4; s++) mbar_init(bars + 8u * (B_HALO + s), 1);
    for (int s = 0; s < 3; s++) mbar_init(bars + 8u * (B_REL + s), s == 0 ? 4 : 8);
    mbar_init(bars + 8u * B_LOC, 4);
    mbar_init(bars + 8u * B_AFREE, 2);
    mbar_init(bars + 8u * B_TURN, 4);
    mbar_init(bars + 8u * (B_TURN + 1), 4);
    mbar_init(bars + 8u * B_CS, 1);
    mbar_init(bars + 8u * B_PRE, 1);
    mbar_init(bars + 8u * B_PRE2, 1);
    mbar_init(bars + 8u * B_RDONE, 4);
    mbar_init(bars + 8u * B_CSD, 4);
    mbar_init(bars + 8u * B_XRDY, 1);
    mbar_init(bars + 8u * (B_XRDY + 1), 1);
    fence_barrier_init();
  }
  if (warp != 12) named_bar_sync(0, 512);

  if (warp >= 12) {
    setmaxnreg_dec<32>();
    if (warp == 12) {
      if (elect_one()) {
#pragma unroll 1
        for (int s = 0; s < 16; s++) {
          const uint32_t fb = bars + 8u * (B_QF + (s & 3)), sa = base + (s & 3) * 5 * UNIT;
          if (s >= 4) mbar_wait(fb + 8u * B_E, ((s >> 2) & 1) ^ 1);
          mbar_expect_tx(fb, 5 * UNIT);
          mbar_arrive(fb);
          tma_load_5d(sa, &P.xq[0], fb, s * 64, qr * 2);
          tma_load_3d(sa + 2 * UNIT, &P.wqkv3[0], fb, hp * 64, s * 64);
        }
        mbar_arrive(bars + 8u * B_GO);
        RingProd rp;
#pragma unroll 1
        for (int sg = 4; sg < 34; sg++) {
          const int part = sg & 3, inst = (sg >> 2) - (part & 1);
          if (part == 3 || inst == 8) continue;
          const int ty = (inst >> 1) & 1;
          if (part != 1) {
            const int k0 = part ? q_split(inst) : 0, k1 = part ? 16 : q_split(inst);
#pragma unroll 1
            for (int kt = k0; kt < k1; kt++) {
              const uint32_t sa = rp.next(B_QF + (kt & 3), (kt >> 2) & 1, true), fb = bars + 8u * (B_QF + (kt & 3));
              mbar_expect_tx(fb, 3 * UNIT);
              tma_load_3d(sa + 2 * UNIT, &P.wqkv3[ty], fb, hp * 64, kt * 64);
            }
          } else {
            const bool pre = w_pre(inst);
            const int lag = pre ? 8 : 5;
            uint32_t sa = 0;
#pragma unroll 1
            for (int kt = 0; kt < 16; kt++) {
              const int i = kt & 3;
              const uint32_t fb = bars + 8u * (B_WF + (kt & 7));
              if (i == 1) sa += 2 * UNIT;
              else if (i != 3 || !pre) sa = rp.next(kt == 14 ? B_RF : B_WF + ((kt | 1) & 7), kt == 14 ? inst & 1 : kt >> 3, kt < lag) + ((0x21 >> (2 * i)) & 3) * UNIT;
              if (kt >= lag) mbar_wait(bars + 8u * (B_WF + B_E + ((kt - lag) & 7)), (kt - lag) >> 3);
              if (i == 3 && pre) {
                mbar_arrive(fb);
              } else {
                mbar_expect_tx(fb, 2 * UNIT);
                tma_load_3d(sa, &P.wo3[ty], fb, ct * 128, kt * 64);
              }
            }
          }
        }
      }
    } else if (warp == 13) {
      RingProd rp;
      unsigned ep1 = 0;
      mbar_wait(bars + 8u * B_GO, 0);
#pragma unroll 1
      for (int sg = 4; sg < 34; sg++) {
        const int part = sg & 3, inst = (sg >> 2) - (part & 1);
        if (part == 3 || inst == 8) continue;
        const int L = inst >> 1, ch = inst & 1;
        uint32_t seen = 0;
        if (part != 1) {
          const CUtensorMap* tx = &P.xq[L];
          const int k0 = part ? q_split(inst) : 0, k1 = part ? 16 : q_split(inst);
          if (L == 0 || mbar_test(bars + 8u * (B_XRDY + ch), (L & 1) ^ 1)) {
            seen = 0xFFu;
            fence_proxy_async_all();
          }
          if (sg == 4) ep1 = (*(volatile unsigned*)(g_flags + F_DONE)) / NCTA + 1u;
          const int m0 = ch * 16 + qr * 2;
#pragma unroll 1
          for (int kt = k0; kt < k1; kt++) {
            wait_mask<false>(g_flags + F_X + (ch * 8 + qr) * XSTR, 8, 6u * ep1 - 6u + 2u * L, 1u << (kt >> 1), seen, lane);
            TGET(t38);
            const uint32_t sa = rp.next(B_QF + (kt & 3), (kt >> 2) & 1, true);
            TGET(t39);
            if (elect_one()) {
              const uint32_t fb = bars + 8u * (B_QF + (kt & 3));
              mbar_expect_tx(fb, 2 * UNIT);
              tma_load_5d(sa, tx, fb, kt * 64, m0);
            }
            if (L == 3 && kt == 0 && lane == 0) { TPUT(ch, 38, t38); TPUT(ch, 39, t39); }
          }
        } else {
          const int m0 = ch * 1024 + rt * 64;
          const bool pre = w_pre(inst);
          const int lag = pre ? 8 : 5;
          uint32_t sa = 0;
#pragma unroll 1
          for (int kt = 0; kt < 16; kt++) {
            const int i = kt & 3;
            const uint32_t fb = bars + 8u * (B_WF + (kt & 7));
            wait_mask<false>(g_flags + F_O + (ch * 16 + rt) * OSTR, 16, 4u * ep1 - 3u + L, 1u << kt, seen, lane);
            if (i < 2) sa = rp.next(kt == 13 ? B_RF : B_WF + (kt & 7) + i + 1, kt == 13 ? inst & 1 : kt >> 3, kt < lag);
            else sa += (2 * i - 3) * UNIT;
            if (kt >= lag) mbar_wait(bars + 8u * (B_WF + B_E + ((kt - lag) & 7)), (kt - lag) >> 3);
            if (elect_one()) {
              mbar_expect_tx(fb, UNIT);
              tma_load_2d(sa, &P.o, fb, kt * 64, m0);
            }
            if (i == 3 && !pre) rp.next(B_WF + (kt & 7), kt >> 3, false);
          }
        }
      }
    } else if (warp == 14) {
      const unsigned ep1 = (*(volatile unsigned*)(g_flags + F_DONE)) / NCTA + 1u;
      uint32_t hpar = 0;
#pragma unroll 1
      for (int inst = 0; inst < 8; inst++) {
        const int L = inst >> 1, ch = inst & 1, gb = ch * 8 + qr;
        named_bar_sync(3, 160);
        if ((L & 1) == 0) {
          uint8_t* img = g_kvA[L >> 1][gb][hp][0];
          if (elect_one()) {
            bulk_store(img + 16384, slots + 16384, 16384);
            bulk_commit();
          }
          bool pub = false;
#pragma unroll 1
          for (int j = 0; j < 4; j++) {
            const bool real = gb > (j >> 1);
            const uint8_t* src = real ? img - ((j >> 1) + 1) * (16 * 32768) + (~j & 1) * 16384 : g_zero;
            const uint32_t dst = slots + (j == 3 ? 2 : 2 - j) * 16384;
            if (j == 1 && elect_one()) bulk_wait_read0();
            if (j >= 1) mbar_wait_lazy<100>(bars + 8u * (B_REL - 1) + 8u * j, ch);
#pragma unroll 1
            for (int tries = 0; tries < 64; tries++) {
              bool go = false;
#pragma unroll 1
              for (uint32_t it = 0; it < (1u << 17) && !(go && pub); ++it) {
                if (!pub && mbar_test(bars + 8u * B_LOC, inst & 1)) {
                  pub = true;
                  if (elect_one()) {
                    bulk_store(img, slots, 16384);
                    bulk_commit();
                  }
                }
                if (!go && (!real || ((ld_relaxed_u32(src + 16384 - 16) ^ ep1) & 1u) == 0u)) {
                  go = true;
                  fence_proxy_async_all();
                  if (elect_one()) {
                    mbar_expect_tx(bars + 8u * B_HL, 16384);
                    bulk_load(dst, src, 16384, bars + 8u * B_HL);
                  }
                }
              }
              mbar_wait(bars + 8u * B_HL, hpar);
              hpar ^= 1u;
              uint32_t t = 0;
#pragma unroll
              for (int k = 0; k < 4; k++) t |= lds32(dst + (k * 32 + lane) * 128 + ((lane & 7) << 4)) ^ ep1;
              if (!real || !__any_sync(0xffffffffu, t & 1u)) break;
              fence_proxy_async_smem();
            }
            if (lane == 0) mbar_arrive(bars + 8u * B_HALO + 8u * j);
          }
        } else {
          uint8_t* img = g_kvB[L >> 1][gb][hp];
          if (elect_one()) {
            bulk_store(img, KB_ROW0 + 112 * 128, 2048);
            bulk_store(img + 2048, VB_ROW0 + 112 * 128, 2048);
            bulk_commit();
            bulk_wait_read0();
          }
          const uint8_t* src = gb >= 1 ? img - 16 * 4096 : g_zero;
#pragma unroll 1
          for (uint32_t it = 0; it < (1u << 17); ++it) {
            fence_proxy_async_all();
            if (elect_one()) {
              mbar_expect_tx(bars + 8u * B_HL, 4096);
              bulk_load(KB_ROW0 - 2048, src, 2048, bars + 8u * B_HL);
              bulk_load(VB_ROW0 - 2048, src + 2048, 2048, bars + 8u * B_HL);
            }
            mbar_wait(bars + 8u * B_HL, hpar);
            hpar ^= 1u;
            const uint32_t t = lds32((lane < 16 ? KB_ROW0 - 2048 : VB_ROW0 - 4096) + lane * 128 + ((lane & 7) << 4)) ^ ep1;
            if (gb == 0 || !__any_sync(0xffffffffu, t & 1u)) break;
            fence_proxy_async_smem();
          }
          if (lane == 0) mbar_arrive(bars + 8u * B_HALO);
        }
        if (elect_one()) {
          mbar_wait(bars + 8u * B_AFREE, inst & 1);
          mbar_expect_tx(bars + 8u * B_RF, 2 * UNIT);
          tma_load_2d(slots + 6 * UNIT, &P.x[L], bars + 8u * B_RF, ct * 128, ch * 1024 + rt * 64);
          tma_load_2d(slots + 7 * UNIT, &P.x[L], bars + 8u * B_RF, ct * 128 + 64, ch * 1024 + rt * 64);
          if (w_pre(inst)) {
            if (inst == 1) mbar_wait(bars + 8u * B_CSD, 0);
            mbar_expect_tx(bars + 8u * B_PRE, 6 * UNIT);
            mbar_expect_tx(bars + 8u * B_PRE2, 2 * UNIT);
#pragma unroll 1
            for (int j = 0; j < 4; j++) {
              __nanosleep(PRESLEEP);
              if (j == 3) mbar_wait(bars + 8u * B_RDONE, (inst & 1) ^ 1);
              tma_load_3d(slots + j * 2 * UNIT, &P.wo3[L & 1], bars + 8u * (j == 3 ? B_PRE2 : B_PRE), ct * 128, (4 * j + 3) * 64);
            }
          }
        }
        __syncwarp();
      }
    } else {
      const unsigned ep1 = (*(volatile unsigned*)(g_flags + F_DONE)) / NCTA + 1u;
      mbar_wait(bars + 8u * B_GO, 0);
#pragma unroll 1
      for (int i = 0; i < 20; i++) {
        const char* src = i < 4 ? reinterpret_cast<const char*>(P.wo_p[0]) + (size_t)b * 16384 + i * 4096
                                : (i < 16 ? reinterpret_cast<const char*>(P.wqkv_p[1]) + (size_t)b * 49152 + (i - 4) * 4096
                                          : reinterpret_cast<const char*>(P.wo_p[1]) + (size_t)b * 16384 + (i - 16) * 4096);
        asm volatile("prefetch.global.L2 [%0];" ::"l"(src + lane * 128));
        __nanosleep(TRICKLE);
      }
#pragma unroll 1
      for (int inst = 2; inst < 8; inst++) {
        const int L = inst >> 1, ch = inst & 1, gb = ch * 8 + qr;
        uint32_t seen = 0;
        wait_mask<true>(g_flags + F_X + gb * XSTR, 8, 6u * ep1 - 6u + 2u * L, 0xFFu, seen, lane);
        if (lane == 0) mbar_arrive(bars + 8u * (B_XRDY + ch));
#pragma unroll 1
        for (int h = 0; h < 4; h++) {
          const float4* sp = &g_stats[L][0][gb * 128 + h * 32 + lane];
          const float4 s0 = sum_recs<4>(sp, S_LEN, ep1), s1 = sum_recs<4>(sp + 4 * S_LEN, S_LEN, ep1);
          sts32(base + OFF_RS + (ch * 128 + h * 32 + lane) * 4, ln_params(s0.x + s1.x, s0.y + s1.y));
        }
        if (inst == 2) {
          mbar_wait(bars + 8u * B_CSD, 0);
#pragma unroll 1
          for (int hf = 0; hf < 2; hf++) {
            const float4* cp = &g_cs[1][hp][0][hf * 32 + lane];
            const float4 s0 = sum_recs<4>(cp, 64, ep1), s1 = sum_recs<4>(cp + 4 * 64, 64, ep1);
            const uint32_t ca = base + OFF_CS + (192 + cs_pos(hf * 32 + lane)) * 4;
            sts32(ca, __float_as_uint(s0.x + s1.x));
            sts32(ca + 256, __float_as_uint(s0.y + s1.y));
            sts32(ca + 512, __float_as_uint(s0.z + s1.z));
          }
        }
        __syncwarp();
        if (lane == 0) mbar_arrive(bars + 8u * (B_PREP + ch));
      }
    }
  } else {
    const bool asst = warp >= 8;
    GTL(0);
    if (asst) {
      colsum_part(&P.wqkv[0], 0, qr, hp);
      if ((threadIdx.x & 127) < 4) mbar_arrive(bars + 8u * B_RDONE);
    } else if (warp >= 4) {
      PHASE_IDS
      {
        const unsigned ep1 = (*(volatile unsigned*)(g_flags + F_DONE)) / NCTA + 1u;
        const int row = b * 16 + (tid >> 3);
        const uint4* src = reinterpret_cast<const uint4*>(P.in_x + (size_t)row * DM) + (tid & 7);
        float s1 = 0.f, s2 = 0.f;
#pragma unroll 1
        for (int k = 0; k < 4; k++) {
          mbar_pace(bars + 8u * (B_QF + B_E + ((2 * k) & 3)), k >> 1);
          uint4 v[4];
#pragma unroll
          for (int j = 0; j < 4; j++) v[j] = __ldg(src + (k * 4 + j) * 8);
#pragma unroll
          for (int j = 0; j < 4; j++) {
            const uint32_t w[4] = {v[j].x, v[j].y, v[j].z, v[j].w};
#pragma unroll
            for (int e = 0; e < 4; e++) {
              const float x0 = bf_lo(w[e]), x1 = bf_hi(w[e]);
              s1 += x0 + x1;
              s2 = fmaf(x0, x0, fmaf(x1, x1, s2));
            }
          }
        }
#pragma unroll
        for (int o = 1; o < 8; o <<= 1) {
          s1 += __shfl_xor_sync(0xffffffffu, s1, o);
          s2 += __shfl_xor_sync(0xffffffffu, s2, o);
        }
        if ((tid & 7) == 0) st_rec(&g_stats[0][0][row], s1, s2, 0.f, ep1);
        if (tid == 0) sts32(base + OFF_EPOCH, ep1);
        if (tid < 64) {
          const float4 s0 = sum_recs<8>(&g_cs[0][hp][0][tid], 64, ep1);
          sts32(base + OFF_CS + cs_pos(tid) * 4, __float_as_uint(s0.x));
          sts32(base + OFF_CS + cs_pos(tid) * 4 + 256, __float_as_uint(s0.y));
          sts32(base + OFF_CS + cs_pos(tid) * 4 + 512, __float_as_uint(s0.z));
        }
#pragma unroll 1
        for (int cc = 0; cc < 2; cc++) {
          const float4 s0 = sum_recs<1>(&g_stats[0][0][(cc * 8 + qr) * 128 + tid], 0, ep1);
          sts32(base + OFF_RS + (cc * 128 + tid) * 4, ln_params(s0.x, s0.y));
        }
        named_bar_sync(2, 128);
        if (tid < 2) mbar_arrive(bars + 8u * (B_PREP + tid));
      }
    }
#pragma unroll 1
    for (int inst = asst ? 0 : warp >> 2; inst < 8; inst += asst ? 1 : 2) {
      const int L = inst >> 1, ch = inst & 1, gb = ch * 8 + qr;
      uint32_t q[2][2][4];
      if (asst) {
        setmaxnreg_dec<24>();
        named_bar_sync(4, 256);
        setmaxnreg_inc<128>();
        const uint32_t ra = q_row_addr(L & 1, 1, warp & 3, fresh_tid() & 31);
#pragma unroll
        for (int j = 0; j < 4; j++) ldmatrix_x4(q[j >> 1][j & 1], ra ^ (j << 5));
      } else {
      setmaxnreg_inc<224>();
      {
        float acc[2][96];
        const int ksp = q_split(inst);
        const int kturn = inst == 0 ? 15 : ksp - 1 - QEARLY;
        constexpr uint32_t STG = 5 * (UNIT >> 4), D0 = (base >> 4) + 0x10000u;
        constexpr uint32_t DB = ((UNIT >> 4) << 16) - 0x10000u + 2 * (UNIT >> 4);
        uint32_t sd = D0;
        uint32_t tand = 1u, tor = 0u, tw = 0u;
        const uint32_t toff = ((fresh_tid() & 127) << 7) + ((fresh_tid() & 7) << 4);
        bool lane0 = (toff & 0xf80u) == 0u;
        if (inst == 1 || (inst > 1 && q_split(inst - 1) < 16)) mbar_wait_lazy<100>(bars + 8u * (B_TURN + ch), (turn_par(0) >> inst) & 1u);
        if (L == 3) GTL(37);
        mbar_wait(bars + 8u * B_QF, 0);
        GTL(1 + L * 8);
        {
          const uint64_t da = desc_lo(sd) + P.zero;
          wgmma_fence();
          wgmma_n192_ssz_ta0_tb1(acc[1], da + (UNIT >> 4), da + DB);
          wgmma_commit();
          wgmma_n192_ssz_ta0_tb1(acc[0], da, da + DB);
          wgmma_commit();
        }
#pragma unroll 1
        for (int kt = 0; kt < 16; kt++) {
          const bool last = kt + 1 == ksp || kt == 15;
          const uint64_t da = desc_lo(sd) + P.zero;
          const uint32_t fn = bars + 8u * (B_QF + ((kt + 1) & 3)), pn = ((kt + 1) >> 2) & 1;
#pragma unroll
          for (int k16 = 0; k16 < 4; k16++) {
            if (k16 == 0 && kt == 0) continue;
            wgmma_fence();
            wgmma_n192_ss_ta0_tb1(acc[1], da + ((UNIT >> 4) + k16 * 2), da + (DB + k16 * 128), 1);
            wgmma_commit();
            wgmma_wait<1>();
            if (k16 == 0 && lane0 && kt != ksp) mbar_arrive(bars + 8u * (B_QF + B_E + ((kt - 1) & 3)));
            wgmma_fence();
            wgmma_n192_ss_ta0_tb1(acc[0], da + k16 * 2, da + (DB + k16 * 128), 1);
            wgmma_commit();
            if (k16 == 1) tw = lds32(((sd & 0xffffu) << 4) + toff);
            if (k16 == 2) {
              tand &= tw;
              tor |= tw;
            }
            bool ok = true;
            if (k16 == 2) ok = mbar_test(fn, pn) || last;
            if (k16 == QTURN && (kt == kturn || (kt == 15 && ksp != 16)) && lane0) mbar_arrive(bars + 8u * (B_TURN + (ch ^ 1)));
            if (k16 < 3) wgmma_wait<1>();
            if (k16 == 2 && !ok) mbar_wait(fn, pn);
          }
          if (kt < 15) sd = sd == D0 + 3 * STG ? D0 : sd + STG;
          if (last && kt < 15) {
            wgmma_wait<0>();
            if (lane0) mbar_arrive(bars + 8u * (B_QF + B_E + (kt & 3)));
            mbar_wait_lazy<100>(bars + 8u * (B_TURN + ch), (turn_par(1) >> inst) & 1u);
            mbar_wait(fn, pn);
          }
        }
        mbar_wait(bars + 8u * (B_PREP + ch), L & 1);
        const uint32_t ep1 = __shfl_sync(0xffffffffu, lds32(base + OFF_EPOCH), 0);
        const bool redo = named_bar_or(1 + ch, 128, L > 0 && (((x_tag(ep1, L) ? ~tand : tor) & 1u) != 0u));
        if (redo) {
          wgmma_wait<0>();
          const uint32_t sa = (sd & 0xffffu) << 4, rb = bars + 8u * (B_REDO + ch);
          if (toff == 0) {
            mbar_init(rb, 1);
            fence_barrier_init();
          }
          uint32_t rpar = 0;
#pragma unroll 1
          for (int kt = 0, tries = 0; kt < 16;) {
            fence_proxy_async_smem();
            named_bar_sync(1 + ch, 128);
            if ((warp & 3) == 0 && elect_one()) {
              fence_proxy_async_all();
              mbar_expect_tx(rb, 5 * UNIT);
              tma_load_5d(sa, &P.xq[L], rb, kt * 64, gb * 2);
              tma_load_3d(sa + 2 * UNIT, &P.wqkv3[L & 1], rb, hp * 64, kt * 64);
            }
            mbar_wait(rb, rpar);
            rpar ^= 1u;
            if (named_bar_or(1 + ch, 128, (lds32(sa + toff) ^ x_tag(ep1, L)) & 1u) && ++tries < 4096) continue;
            wgmma_fence();
#pragma unroll
            for (int k16 = 0; k16 < 4; k16++) {
              const uint64_t db = make_desc(sa + 2 * UNIT + k16 * 2048, UNIT);
              wgmma_n192_ss_ta0_tb1(acc[1], make_desc(sa + UNIT + k16 * 32, 16), db, kt | k16);
              wgmma_n192_ss_ta0_tb1(acc[0], make_desc(sa + k16 * 32, 16), db, kt | k16);
            }
            wgmma_commit();
            wgmma_wait<0>();
            kt++;
          }
        }
        PHASE_IDS_W
        lane0 = lane == 0;
        if (ksp < 16) mbar_wait(bars + 8u * (B_WF + B_E + 7), 1);
        const bool afree = mbar_test(bars + 8u * B_RDONE, inst & 1);
        const uint32_t csa = base + OFF_CS + ((L & 1) * 192 + 4 * c) * 4;
        uint4 cs[24];
        uint32_t rs[2][2];
        const uint32_t rsa = base + OFF_RS + (ch * 128 + tile_row(L & 1, wwarp, 0, g)) * 4, rsd = (L & 1) ? 32 : 128;
#pragma unroll
        for (int r = 0; r < 2; r++) rs[1][r] = lds32(rsa + 256 + r * rsd);
#pragma unroll
        for (int t = 0; t < 2; t++) cs[t] = lds128(csa + (t + 4) * 64);
        float nmean[2], rinv[2];
#pragma unroll
        for (int r = 0; r < 2; r++) {
          nmean[r] = -bf_lo(rs[1][r]);
          rinv[r] = rcp_fast(bf_hi(rs[1][r]));
          asm volatile("" : "+f"(rinv[r]), "+f"(nmean[r]));
        }
        const uint32_t soff = tile_row(L & 1, wwarp, (lane >> 3) & 1, lane & 7) * 128 + (((lane >> 4) ^ (lane & 7)) << 4);
        const uint32_t kdst = ((L & 1) ? KB_ROW0 : slots) + soff, vdst = ((L & 1) ? VB_ROW0 : slots + 8192) + soff;
        const uint32_t hs = (L & 1) ? 8192 : 16384;
        wgmma_wait<0>();
        reg_fence<96>(acc[0]);
        reg_fence<96>(acc[1]);
        if (lane0) mbar_arrive(bars + 8u * (B_QF + B_E + 3));
        GTL(2 + L * 8);
        if (!afree) mbar_wait(bars + 8u * B_RDONE, inst & 1);
#pragma unroll
        for (int t = 2; t < CSPF; t++) cs[t] = lds128(csa + (t + 4) * 64);
#pragma unroll
        for (int t = 0; t < 24; t++) {
          const int h = t < 12 ? 1 : 0, p = ((t % 12) / 4 + 1) % 3, jp = t & 3;
          if (t < 12 ? t + CSPF < 12 : t + CSPF2 < 24) {
            const int tn = t < 12 ? t + CSPF : t + CSPF2;
            cs[tn] = lds128(csa + (tn % 12 + 4) % 12 * 64);
          }
          if (t == 4) {
#pragma unroll
            for (int r = 0; r < 2; r++) rs[0][r] = lds32(rsa + r * rsd);
          }
          if (t == 8 || t == 20) {
            rinv[0] *= SM_C;
            rinv[1] *= SM_C;
          }
          const float2 cs0 = make_float2(__uint_as_float(cs[t].x), __uint_as_float(cs[t].y));
          const float2 cs1 = make_float2(__uint_as_float(cs[t].z), __uint_as_float(cs[t].w));
          const float* a = &acc[h][4 * (p * 8 + 2 * jp)];
          uint32_t r0 = pack_bf16x2(fmaf(nmean[0], cs0.x, a[0]) * rinv[0], fmaf(nmean[0], cs0.y, a[1]) * rinv[0]);
          uint32_t r1 = pack_bf16x2(fmaf(nmean[1], cs0.x, a[2]) * rinv[1], fmaf(nmean[1], cs0.y, a[3]) * rinv[1]);
          if (p != 0 && jp == 0) {
            r0 = set_tag(r0, c == 0, ep1);
            r1 = set_tag(r1, c == 0, ep1);
          }
          const uint32_t r2 = pack_bf16x2(fmaf(nmean[0], cs1.x, a[4]) * rinv[0], fmaf(nmean[0], cs1.y, a[5]) * rinv[0]);
          const uint32_t r3 = pack_bf16x2(fmaf(nmean[1], cs1.x, a[6]) * rinv[1], fmaf(nmean[1], cs1.y, a[7]) * rinv[1]);
          const uint32_t dst = p == 0 ? slots + 3 * 16384 + soff + h * 8192 : (p == 1 ? kdst : vdst) + h * hs;
          stmatrix_x4(dst ^ (jp << 5), r0, r1, r2, r3);
          if (t >= 20) {
            q[jp >> 1][jp & 1][0] = r0;
            q[jp >> 1][jp & 1][1] = r1;
            q[jp >> 1][jp & 1][2] = r2;
            q[jp >> 1][jp & 1][3] = r3;
          }
          if (t == 7 || t == 19) {
            fence_proxy_async_smem();
            if (t == 7) {
              named_bar_arrive(3, 160);
            } else {
              __syncwarp();
              if (lane0) mbar_arrive(bars + 8u * B_LOC);
            }
          }
          if (t == 11) {
            setmaxnreg_dec<128>();
            named_bar_arrive(4, 256);
#pragma unroll
            for (int u = 0; u < CSPF2; u++) cs[12 + u] = lds128(csa + (u + 4) * 64);
#pragma unroll
            for (int r = 0; r < 2; r++) {
              nmean[r] = -bf_lo(rs[0][r]);
              rinv[r] = rcp_fast(bf_hi(rs[0][r]));
            }
          }
        }
        mbar_wait(bars + 8u * B_LOC, inst & 1);
      }
      }
      GTL(3 + L * 8);
      if ((L & 1) == 0) attention_a(q, asst, L, gb, hp, inst & 1, ch, warp & 3, P.zero);
      else attention_b(q, asst, gb, inst & 1, warp & 3);
      GTL(4 + L * 8);
      fence_proxy_async_smem();
      named_bar_sync(asst ? 6 : 1 + ch, 128);
      if ((warp & 3) == 0) {
        if (elect_one()) {
          tma_store_2d(&P.o, slots + 3 * 16384 + asst * 8192, hp * 64, gb * 128 + asst * 64);
          bulk_commit();
          bulk_wait0();
          mbar_arrive(bars + 8u * B_AFREE);
          fence_proxy_async_all();
          red_announce(g_flags + F_O + (gb * 2 + asst) * OSTR + hp, 1u);
        }
        __syncwarp();
      }
      if (asst) {
        if (inst == 1) {
          mbar_wait(bars + 8u * B_RDONE, 0);
          colsum_part(&P.wqkv[1], 1, qr, hp);
          if ((fresh_tid() & 31) == 0) mbar_arrive(bars + 8u * B_CSD);
        }
        continue;
      }
      GTL(5 + L * 8);

      {
        float acc[64];
        const int sp = inst < 7 ? q_split(inst + 1) : 0;
        int st = sp & 3;
        const bool pre = w_pre(inst);
        uint32_t tbad = 0u;
        const uint32_t toff = ((fresh_tid() & 63) << 7) + ((fresh_tid() & 7) << 4);
        const bool lane0 = (toff & 0xf80u) == 0u;
        constexpr uint32_t U4 = UNIT >> 4, LA = 0x10000u, LB = U4 << 16;
        reg_define<64>(acc);
        reg_fence<64>(acc);
        uint32_t xv[8][4];
        {
          PHASE_IDS_W
          const uint32_t xr = slots + 6 * UNIT + (wwarp * 16 + (lane & 15)) * 128 + (((lane >> 4) ^ (lane & 7)) << 4);
          mbar_wait(bars + 8u * B_RF, inst & 1);
#pragma unroll
          for (int jp = 0; jp < 8; jp++) ldmatrix_x4(xv[jp], (xr ^ ((jp & 3) << 5)) + (jp >> 2) * UNIT);
          fence_proxy_async_smem();
          __syncwarp();
          if (lane0) mbar_arrive(bars + 8u * B_RDONE);
          if (L > 0) {
            uint32_t lsb;
            asm volatile("ld.shared.u8 %0, [%1];" : "=r"(lsb) : "r"(base + OFF_LSB + ch * 32 + wwarp * 8 + g) : "memory");
#pragma unroll
            for (int k = 0; k < 4; k++) xv[(k >> 1) * 4][k & 1] = set_tag(xv[(k >> 1) * 4][k & 1], c == 0, lsb >> k);
          }
        }
        uint64_t d0 = desc_lo((base >> 4) + st * 5 * U4) + P.zero;
        if (inst < 7 || SP7 == 16) mbar_wait_lazy<100>(bars + 8u * (B_TURN + ch), (turn_par(2) >> inst) & 1u);
        mbar_wait(bars + 8u * B_WF, 0);
        GTL(6 + L * 8);
        uint32_t s1 = 0;
#pragma unroll 1
        for (int m = 0; m < 4; m++) {
          const uint32_t s0 = base + st * 5 * UNIT, fb = bars + 8u * (B_WF + 4 * (m & 1));
          s1 = base + ((st + 1) & 3) * 5 * UNIT;
          const uint64_t d1 = desc_lo(s1 >> 4) + P.zero;
          const uint64_t d2 = desc_lo((pre ? slots + m * 2 * UNIT : base + ((st + 2) & 3) * 5 * UNIT) >> 4) + P.zero;
          st = (st + (pre ? 2 : 3)) & 3;
#pragma unroll
          for (int i = 0; i < 4; i++) {
            const uint64_t da = (i == 0 ? d0 : d1) + (LA + (i == 2 ? 1 : (i == 3 ? 4 : 0)) * U4);
            const uint64_t db = (i < 2 ? d0 : (i == 2 ? d1 : d2)) + (LB + (i == 0 ? 1 : (i == 1 ? 3 : (i == 2 ? 2 : 0))) * U4);
            if (i == 3 && (m == 0 || m == 3) && pre) mbar_wait(bars + 8u * (m ? B_PRE2 : B_PRE), __popc(PREMASK & ((1u << inst) - 1u)) & 1);
            if (i == (WTURN & 3) && m == 3 && lane0 && (sp < 16 || inst == 6)) mbar_arrive(bars + 8u * (B_TURN + (ch ^ 1)));
            wgmma_fence();
#pragma unroll
            for (int k16 = 0; k16 < 4; k16++) wgmma_n128_ss_ta0_tb1(acc, da + 2 * k16, db + 128 * k16, 1);
            wgmma_commit();
            if (i == 2) d0 = desc_lo((base >> 4) + st * 5 * U4) + P.zero;
            tbad |= lds32((i == 0 ? s0 : s1) + (i == 2 ? 1 : (i == 3 ? 4 : 0)) * UNIT + toff) ^ o_tag(L);
            const uint32_t fn = i < 3 ? fb + 8u * (i + 1) : fb ^ 96u;
            const uint32_t pn = i < 3 ? m >> 1 : m > 0;
            const bool ok = mbar_test(fn, pn) || (i == 3 && m == 3);
            wgmma_wait<1>();
            if (lane0 && (i > 0 || m > 0)) mbar_arrive((i > 0 ? fb + 8u * (i - 1) : (fb ^ 96u) + 24u) + 8u * B_E);
            if (!ok) mbar_wait(fn, pn);
          }
        }
        const uint32_t xb = s1;
        const bool redo = named_bar_or(1 + ch, 128, tbad & 1u);
        if (redo) {
          wgmma_wait<0>();
          const uint32_t sa = s1 + 4 * UNIT, sb = s1 + 2 * UNIT;
          const uint32_t rb = bars + 8u * (B_REDO + ch);
          if ((fresh_tid() & 127) == 0) {
            mbar_init(rb, 1);
            fence_barrier_init();
          }
          uint32_t rpar = 0;
#pragma unroll 1
          for (int kt = 0, tries = 0; kt < 16;) {
            fence_proxy_async_smem();
            named_bar_sync(1 + ch, 128);
            if ((warp & 3) == 0 && elect_one()) {
              fence_proxy_async_all();
              mbar_expect_tx(rb, 3 * UNIT);
              tma_load_2d(sa, &P.o, rb, kt * 64, ch * 1024 + rt * 64);
              tma_load_3d(sb, &P.wo3[L & 1], rb, ct * 128, kt * 64);
            }
            mbar_wait(rb, rpar);
            rpar ^= 1u;
            if (named_bar_or(1 + ch, 128, (lds32(sa + toff) ^ o_tag(L)) & 1u) && ++tries < 4096) continue;
            wgmma_fence();
#pragma unroll
            for (int k16 = 0; k16 < 4; k16++)
              wgmma_n128_ss_ta0_tb1(acc, make_desc(sa + k16 * 32, 16), make_desc(sb + k16 * 2048, UNIT), kt | k16);
            wgmma_commit();
            wgmma_wait<0>();
            kt++;
          }
        }
        PHASE_IDS_W
        const uint32_t xrow = xb + (wwarp * 16 + (lane & 15)) * 128 + (((lane >> 4) ^ (lane & 7)) << 4);
        const unsigned ep1 = __shfl_sync(0xffffffffu, lds32(base + OFF_EPOCH), 0);
        const uint32_t tm = c == 0, lsa = base + OFF_LSB + ch * 32 + wwarp * 8 + g;
        wgmma_wait<0>();
        reg_fence<64>(acc);
        if (lane0) mbar_arrive(bars + 8u * (B_WF + B_E + 7));
        GTL(7 + L * 8);
        const uint32_t tmx = L < 3 ? tm : 0u, xt = x_tag(ep1, L + 1);
#pragma unroll
        for (int jp = 0; jp < 8; jp++) {
#pragma unroll
          for (int q = 0; q < 4; q++) xv[jp][q] = add_bf16x2(xv[jp][q], pack_bf16x2(acc[8 * jp + 2 * q], acc[8 * jp + 2 * q + 1]));
          const bool tg = (jp & 3) == 0;
          stmatrix_x4((xrow ^ ((jp & 3) << 5)) + (jp >> 2) * UNIT,
                      tg ? set_tag(xv[jp][0], tmx, xt) : xv[jp][0], tg ? set_tag(xv[jp][1], tmx, xt) : xv[jp][1], xv[jp][2], xv[jp][3]);
        }
        fence_proxy_async_smem();
        named_bar_sync(1 + ch, 128);
        const int grow = ch * 1024 + rt * 64;
        if (wwarp == 0) {
          if (elect_one()) {
            const CUtensorMap* to = &P.x[L + 1];
            tma_store_2d(to, xb, ct * 128, grow);
            tma_store_2d(to, xb + UNIT, ct * 128 + 64, grow);
            bulk_commit();
            bulk_wait_read0();
            mbar_arrive(bars + 8u * (B_RF + B_E));
            bulk_wait0();
            TGET(t35);
            fence_proxy_async_all();
            if (L < 3) red_announce(g_flags + F_X + (ch * 8 + (rt >> 1)) * XSTR + ct, 1u);
            if (L == 2) TPUT(ch, 35, t35);
          }
          __syncwarp();
        } else if (lane == 0) {
          mbar_arrive(bars + 8u * (B_RF + B_E));
        }
        if (L < 3) {
          if (c == 0)
            asm volatile("st.shared.u8 [%0], %1;" ::"r"(lsa),
                         "r"((xv[0][0] & 1u) | ((xv[0][1] & 1u) << 1) | ((xv[4][0] & 1u) << 2) | ((xv[4][1] & 1u) << 3)) : "memory");
          float s1[2] = {0.f, 0.f}, s2[2] = {0.f, 0.f};
#pragma unroll
          for (int jp = 0; jp < 8; jp++)
#pragma unroll
            for (int q = 0; q < 4; q++) {
              const float x0 = bf_lo(xv[jp][q]), x1 = bf_hi(xv[jp][q]);
              s1[q & 1] += x0 + x1;
              s2[q & 1] = fmaf(x0, x0, fmaf(x1, x1, s2[q & 1]));
            }
#pragma unroll
          for (int r = 0; r < 2; r++) {
            s1[r] += __shfl_xor_sync(0xffffffffu, s1[r], 1);
            s2[r] += __shfl_xor_sync(0xffffffffu, s2[r], 1);
            s1[r] += __shfl_xor_sync(0xffffffffu, s1[r], 2);
            s2[r] += __shfl_xor_sync(0xffffffffu, s2[r], 2);
            if (c == 0) st_rec(&g_stats[L + 1][ct][grow + wwarp * 16 + g + 8 * r], s1[r], s2[r], 0.f, ep1);
          }
        }
        GTL(8 + L * 8);
      }
    }
    if (threadIdx.x == 128) atomicAdd(g_flags + F_DONE, 1u);
  }
}

typedef CUresult (*PFN_tmEncode)(CUtensorMap*, CUtensorMapDataType, cuuint32_t, void*, const cuuint64_t*,
                                 const cuuint64_t*, const cuuint32_t*, const cuuint32_t*, CUtensorMapInterleave,
                                 CUtensorMapSwizzle, CUtensorMapL2promotion, CUtensorMapFloatOOBfill);

PFN_tmEncode get_encode_fn() {
  static PFN_tmEncode fn = nullptr;
  if (!fn) {
    cudaDriverEntryPointQueryResult qr;
    void* p = nullptr;
    cudaGetDriverEntryPoint("cuTensorMapEncodeTiled", &p, cudaEnableDefault, &qr);
    fn = (PFN_tmEncode)p;
  }
  return fn;
}

CUtensorMap make_map(const void* ptr, int rows, int cols) {
  CUtensorMap m;
  cuuint64_t gdim[2] = {(cuuint64_t)cols, (cuuint64_t)rows};
  cuuint64_t gstr[1] = {(cuuint64_t)cols * 2};
  cuuint32_t box[2] = {64, 64};
  cuuint32_t estr[2] = {1, 1};
  get_encode_fn()(&m, CU_TENSOR_MAP_DATA_TYPE_BFLOAT16, 2, const_cast<void*>(ptr), gdim, gstr, box, estr,
                  CU_TENSOR_MAP_INTERLEAVE_NONE, CU_TENSOR_MAP_SWIZZLE_128B, CU_TENSOR_MAP_L2_PROMOTION_L2_128B,
                  CU_TENSOR_MAP_FLOAT_OOB_FILL_NONE);
  return m;
}

CUtensorMap make_map3(const void* ptr, int rows, int cols, int n, int step) {
  CUtensorMap m;
  cuuint64_t gdim[3] = {(cuuint64_t)(cols - (n - 1) * step), (cuuint64_t)rows, (cuuint64_t)n};
  cuuint64_t gstr[2] = {(cuuint64_t)cols * 2, (cuuint64_t)step * 2};
  cuuint32_t box[3] = {64, 64, (cuuint32_t)n};
  cuuint32_t estr[3] = {1, 1, 1};
  get_encode_fn()(&m, CU_TENSOR_MAP_DATA_TYPE_BFLOAT16, 3, const_cast<void*>(ptr), gdim, gstr, box, estr,
                  CU_TENSOR_MAP_INTERLEAVE_NONE, CU_TENSOR_MAP_SWIZZLE_128B, CU_TENSOR_MAP_L2_PROMOTION_L2_128B,
                  CU_TENSOR_MAP_FLOAT_OOB_FILL_NONE);
  return m;
}

CUtensorMap make_map_q(const void* ptr, int sw, int sr) {
  CUtensorMap m;
  cuuint64_t gdim[5] = {DM, 8, 2, 4, S_LEN / 64};
  cuuint64_t gstr[4] = {DM * 2, (cuuint64_t)sr * DM * 2, (cuuint64_t)sw * DM * 2, 64 * DM * 2};
  cuuint32_t box[5] = {64, 8, 2, 4, 2};
  cuuint32_t estr[5] = {1, 1, 1, 1, 1};
  get_encode_fn()(&m, CU_TENSOR_MAP_DATA_TYPE_BFLOAT16, 5, const_cast<void*>(ptr), gdim, gstr, box, estr,
                  CU_TENSOR_MAP_INTERLEAVE_NONE, CU_TENSOR_MAP_SWIZZLE_128B, CU_TENSOR_MAP_L2_PROMOTION_L2_128B,
                  CU_TENSOR_MAP_FLOAT_OOB_FILL_NONE);
  return m;
}

}

extern "C" void kernel_launch(void* const* d_in, const int* in_sizes, int n_in, void* d_out, int out_size) {
  (void)in_sizes; (void)n_in; (void)out_size;
  void *p_o, *p_x;
  cudaGetSymbolAddress(&p_o, g_o);
  cudaGetSymbolAddress(&p_x, g_x);
  static bool attr_done = false;
  if (!attr_done) {
    cudaFuncSetAttribute(fused_kernel, cudaFuncAttributeMaxDynamicSharedMemorySize, SMEM_BYTES);
    attr_done = true;
  }
  Params P;
  P.in_x = (const __nv_bfloat16*)d_in[0];
  P.wqkv_p[0] = (const __nv_bfloat16*)d_in[1];
  P.wo_p[0] = (const __nv_bfloat16*)d_in[2];
  P.wqkv_p[1] = (const __nv_bfloat16*)d_in[4];
  P.wo_p[1] = (const __nv_bfloat16*)d_in[5];
  P.out = (__nv_bfloat16*)d_out;
  P.zero = 0;
  for (int L = 0; L < 5; L++) {
    const void* px = L == 0 ? (const void*)P.in_x : (L == 4 ? d_out : (const void*)((__nv_bfloat16*)p_x + (size_t)(L - 1) * S_LEN * DM));
    P.x[L] = make_map(px, S_LEN, DM);
    if (L < 4) P.xq[L] = (L & 1) ? make_map_q(px, 16, 8) : make_map_q(px, 8, 32);
  }
  P.o = make_map(p_o, S_LEN, DM);
  for (int t = 0; t < 2; t++) {
    P.wqkv[t] = make_map(P.wqkv_p[t], DM, NQKV);
    P.wqkv3[t] = make_map3(P.wqkv_p[t], DM, NQKV, 3, 1024);
    P.wo3[t] = make_map3(P.wo_p[t], DM, DM, 2, 64);
  }
  fused_kernel<<<NCTA, 512, SMEM_BYTES>>>(P);
}
```

```cpp
#include <cuda_runtime.h>
#include <cuda_bf16.h>
#include <cuda.h>
#include <stdint.h>

namespace {

constexpr int S_LEN = 2048;
constexpr int DM = 1024;
constexpr int NQKV = 3072;
constexpr int NCTA = 128;

__device__ __align__(1024) uint8_t g_kvA[2][16][16][2][16384];
__device__ __align__(1024) uint8_t g_kvB[2][16][16][4096];
__device__ __align__(1024) uint8_t g_zero[16384];
__device__ __align__(1024) __nv_bfloat16 g_o[S_LEN * DM];
__device__ __align__(1024) __nv_bfloat16 g_x[S_LEN * DM];
__device__ __align__(1024) float4 g_stats[4][8][S_LEN];
__device__ __align__(1024) float4 g_cs[2][16][8][64];
__device__ __align__(128) unsigned g_fx[16][32];
__device__ __align__(128) unsigned g_fo[32][32];
__device__ __align__(128) unsigned g_done[32];

constexpr uint32_t SBASE = 1024;
constexpr int UNIT = 8192;
constexpr int NUNITS = 20;
constexpr int OFF_SLOT = NUNITS * UNIT;
constexpr int OFF_BAR = OFF_SLOT + 4 * 16384;
constexpr int OFF_EPOCH = OFF_BAR + 424;
constexpr int OFF_LSB = OFF_BAR + 432;
constexpr int OFF_CS = OFF_BAR + 496;
constexpr int OFF_RS = OFF_CS + 1536;
constexpr int SMEM_BYTES = OFF_RS + 1024;
constexpr int B_QF = 0, B_WF = 4, B_RF = 12, B_E = 13, B_PREP = 26, B_LOC = 28, B_HALO = 29, B_REL = 33, B_AFREE = 36,
              B_TURN = 37, B_XRDY = 39, B_CS = 41, B_CSD = 42, B_GO = 43, B_PRE = 44, B_HV = 45, B_REDO = 46,
              B_RDONE = 48, B_PRE2 = 49, B_HL = 50;
static_assert(SMEM_BYTES <= 232448, "shared memory");

__device__ __forceinline__ uint32_t smem_u32(const void* p) { return (uint32_t)__cvta_generic_to_shared(p); }

__device__ __forceinline__ void mbar_init(uint32_t bar, uint32_t cnt) {
  asm volatile("mbarrier.init.shared::cta.b64 [%0], %1;" ::"r"(bar), "r"(cnt));
}
__device__ __forceinline__ void mbar_expect_tx(uint32_t bar, uint32_t bytes) {
  asm volatile("mbarrier.arrive.expect_tx.shared::cta.b64 _, [%0], %1;" ::"r"(bar), "r"(bytes) : "memory");
}
__device__ __forceinline__ void mbar_arrive(uint32_t bar) {
  asm volatile("mbarrier.arrive.shared::cta.b64 _, [%0];" ::"r"(bar) : "memory");
}
__device__ __forceinline__ bool mbar_try_wait(uint32_t bar, uint32_t parity) {
  uint32_t ok;
  asm volatile(
      "{\n.reg .pred p;\nmbarrier.try_wait.parity.shared::cta.b64 p, [%1], %2;\nselp.b32 %0, 1, 0, p;\n}\n"
      : "=r"(ok)
      : "r"(bar), "r"(parity)
      : "memory");
  return ok != 0;
}
__device__ __forceinline__ bool mbar_test(uint32_t bar, uint32_t parity) {
  uint32_t ok;
  asm volatile(
      "{\n.reg .pred p;\nmbarrier.test_wait.parity.shared::cta.b64 p, [%1], %2;\nselp.b32 %0, 1, 0, p;\n}\n"
      : "=r"(ok)
      : "r"(bar), "r"(parity)
      : "memory");
  return ok != 0;
}
__device__ __forceinline__ void mbar_wait(uint32_t bar, uint32_t parity) {
#pragma unroll 1
  for (uint32_t it = 0; it < (1u << 18); ++it) {
    if (mbar_try_wait(bar, parity)) return;
  }
}
__device__ __forceinline__ void mbar_pace(uint32_t bar, uint32_t parity) {
#pragma unroll 1
  for (uint32_t it = 0; it < 24; ++it) {
    if (mbar_try_wait(bar, parity)) return;
  }
}
template <int NS>
__device__ __forceinline__ void mbar_wait_lazy(uint32_t bar, uint32_t parity) {
#pragma unroll 1
  for (uint32_t it = 0; it < (1u << 18); ++it) {
    if (mbar_try_wait(bar, parity)) return;
    __nanosleep(NS);
  }
}
__device__ __forceinline__ bool elect_one() {
  uint32_t ok;
  asm volatile("{\n.reg .pred p;\nelect.sync _|p, 0xffffffff;\nselp.b32 %0, 1, 0, p;\n}\n" : "=r"(ok));
  return ok != 0;
}
__device__ __forceinline__ void fence_barrier_init() { asm volatile("fence.mbarrier_init.release.cluster;" ::: "memory"); }
__device__ __forceinline__ void fence_proxy_async_smem() { asm volatile("fence.proxy.async.shared::cta;" ::: "memory"); }
__device__ __forceinline__ void fence_proxy_async_all() { asm volatile("fence.proxy.async.global;" ::: "memory"); }

__device__ __forceinline__ void tma_load_2d(uint32_t dst, const CUtensorMap* map, uint32_t bar, int c0, int c1) {
  asm volatile(
      "cp.async.bulk.tensor.2d.shared::cluster.global.mbarrier::complete_tx::bytes [%0], [%1, {%3, %4}], [%2];" ::"r"(dst),
      "l"(map), "r"(bar), "r"(c0), "r"(c1)
      : "memory");
}
__device__ __forceinline__ void tma_load_3d(uint32_t dst, const CUtensorMap* map, uint32_t bar, int c0, int c1) {
  asm volatile(
      "cp.async.bulk.tensor.3d.shared::cluster.global.mbarrier::complete_tx::bytes [%0], [%1, {%3, %4, %5}], [%2];" ::"r"(dst),
      "l"(map), "r"(bar), "r"(c0), "r"(c1), "r"(0)
      : "memory");
}
__device__ __forceinline__ void tma_load_5d(uint32_t dst, const CUtensorMap* map, uint32_t bar, int c0, int c4) {
  asm volatile(
      "cp.async.bulk.tensor.5d.shared::cluster.global.mbarrier::complete_tx::bytes [%0], [%1, {%3, %5, %5, %5, %4}], [%2];" ::"r"(dst),
      "l"(map), "r"(bar), "r"(c0), "r"(c4), "r"(0)
      : "memory");
}
__device__ __forceinline__ void bulk_load(uint32_t dst, const void* src, uint32_t bytes, uint32_t bar) {
  asm volatile("cp.async.bulk.shared::cluster.global.mbarrier::complete_tx::bytes [%0], [%1], %2, [%3];" ::"r"(dst),
               "l"(src), "r"(bytes), "r"(bar)
               : "memory");
}
__device__ __forceinline__ void bulk_store(void* dst, uint32_t src, uint32_t bytes) {
  asm volatile("cp.async.bulk.global.shared::cta.bulk_group [%0], [%1], %2;" ::"l"(dst), "r"(src), "r"(bytes) : "memory");
}
__device__ __forceinline__ void tma_store_2d(const CUtensorMap* map, uint32_t src, int c0, int c1) {
  asm volatile("cp.async.bulk.tensor.2d.global.shared::cta.bulk_group [%0, {%2, %3}], [%1];" ::"l"(map), "r"(src),
               "r"(c0), "r"(c1)
               : "memory");
}
__device__ __forceinline__ void bulk_commit() { asm volatile("cp.async.bulk.commit_group;" ::: "memory"); }
__device__ __forceinline__ void bulk_wait_read0() { asm volatile("cp.async.bulk.wait_group.read 0;" ::: "memory"); }
__device__ __forceinline__ void bulk_wait0() { asm volatile("cp.async.bulk.wait_group 0;" ::: "memory"); }
__device__ __forceinline__ void named_bar_sync(int id, int nthreads) {
  asm volatile("bar.sync %0, %1;" ::"r"(id), "r"(nthreads) : "memory");
}
__device__ __forceinline__ void named_bar_arrive(int id, int nthreads) {
  asm volatile("bar.arrive %0, %1;" ::"r"(id), "r"(nthreads) : "memory");
}

__device__ __forceinline__ bool named_bar_or(int id, int nthreads, bool v) {
  uint32_t r;
  asm volatile("{\n.reg .pred p, q;\nsetp.ne.b32 q, %3, 0;\nbar.red.or.pred p, %1, %2, q;\nselp.b32 %0, 1, 0, p;\n}\n"
               : "=r"(r) : "r"(id), "r"(nthreads), "r"((int)v) : "memory");
  return __any_sync(0xffffffffu, r != 0);
}

__device__ __forceinline__ void wgmma_fence() { asm volatile("wgmma.fence.sync.aligned;\n" ::: "memory"); }
__device__ __forceinline__ void wgmma_commit() { asm volatile("wgmma.commit_group.sync.aligned;\n" ::: "memory"); }
template <int N>
__device__ __forceinline__ void wgmma_wait() {
  asm volatile("wgmma.wait_group.sync.aligned %0;\n" ::"n"(N) : "memory");
}
template <int R>
__device__ __forceinline__ void setmaxnreg_inc() { asm volatile("setmaxnreg.inc.sync.aligned.u32 %0;\n" ::"n"(R)); }
template <int R>
__device__ __forceinline__ void setmaxnreg_dec() { asm volatile("setmaxnreg.dec.sync.aligned.u32 %0;\n" ::"n"(R)); }
template <int N>
__device__ __forceinline__ void reg_fence(float* r) {
#pragma unroll
  for (int i = 0; i < N; i++) asm volatile("" : "+f"(r[i])::"memory");
}

template <int N>
__device__ __forceinline__ void reg_define(float* r) {
#pragma unroll
  for (int i = 0; i < N; i++) r[i] = 0.f;
}

__device__ __forceinline__ uint64_t desc_lo(uint32_t lo) {
  uint64_t d;
  asm("mov.b64 %0, {%1, %2};" : "=l"(d) : "r"(lo), "r"(0x40000040u));
  return d;
}
__device__ __forceinline__ uint64_t make_desc(uint32_t addr, uint32_t lbo_bytes) {
  return desc_lo((addr >> 4) + ((lbo_bytes >> 4) << 16));
}

__device__ __forceinline__ void wgmma_n192_ss_ta0_tb1(float* d, uint64_t descA, uint64_t descB, int scaleD) {
  asm volatile("{\n.reg .pred p;\nsetp.ne.b32 p, %98, 0;\n"
    "wgmma.mma_async.sync.aligned.m64n192k16.f32.bf16.bf16 {%0, %1, %2, %3, %4, %5, %6, %7, %8, %9, %10, %11, %12, %13, %14, %15, %16, %17, %18, %19, %20, %21, %22, %23, %24, %25, %26, %27, %28, %29, %30, %31, %32, %33, %34, %35, %36, %37, %38, %39, %40, %41, %42, %43, %44, %45, %46, %47, %48, %49, %50, %51, %52, %53, %54, %55, %56, %57, %58, %59, %60, %61, %62, %63, %64, %65, %66, %67, %68, %69, %70, %71, %72, %73, %74, %75, %76, %77, %78, %79, %80, %81, %82, %83, %84, %85, %86, %87, %88, %89, %90, %91, %92, %93, %94, %95}, %96, %97, p, 1, 1, 0, 1;\n}\n"
    : "+f"(d[0]), "+f"(d[1]), "+f"(d[2]), "+f"(d[3]), "+f"(d[4]), "+f"(d[5]), "+f"(d[6]), "+f"(d[7]), "+f"(d[8]), "+f"(d[9]), "+f"(d[10]), "+f"(d[11]), "+f"(d[12]), "+f"(d[13]), "+f"(d[14]), "+f"(d[15]), "+f"(d[16]), "+f"(d[17]), "+f"(d[18]), "+f"(d[19]), "+f"(d[20]), "+f"(d[21]), "+f"(d[22]), "+f"(d[23]), "+f"(d[24]), "+f"(d[25]), "+f"(d[26]), "+f"(d[27]), "+f"(d[28]), "+f"(d[29]), "+f"(d[30]), "+f"(d[31]), "+f"(d[32]), "+f"(d[33]), "+f"(d[34]), "+f"(d[35]), "+f"(d[36]), "+f"(d[37]), "+f"(d[38]), "+f"(d[39]), "+f"(d[40]), "+f"(d[41]), "+f"(d[42]), "+f"(d[43]), "+f"(d[44]), "+f"(d[45]), "+f"(d[46]), "+f"(d[47]), "+f"(d[48]), "+f"(d[49]), "+f"(d[50]), "+f"(d[51]), "+f"(d[52]), "+f"(d[53]), "+f"(d[54]), "+f"(d[55]), "+f"(d[56]), "+f"(d[57]), "+f"(d[58]), "+f"(d[59]), "+f"(d[60]), "+f"(d[61]), "+f"(d[62]), "+f"(d[63]), "+f"(d[64]), "+f"(d[65]), "+f"(d[66]), "+f"(d[67]), "+f"(d[68]), "+f"(d[69]), "+f"(d[70]), "+f"(d[71]), "+f"(d[72]), "+f"(d[73]), "+f"(d[74]), "+f"(d[75]), "+f"(d[76]), "+f"(d[77]), "+f"(d[78]), "+f"(d[79]), "+f"(d[80]), "+f"(d[81]), "+f"(d[82]), "+f"(d[83]), "+f"(d[84]), "+f"(d[85]), "+f"(d[86]), "+f"(d[87]), "+f"(d[88]), "+f"(d[89]), "+f"(d[90]), "+f"(d[91]), "+f"(d[92]), "+f"(d[93]), "+f"(d[94]), "+f"(d[95])
    : "l"(descA), "l"(descB), "r"(scaleD));
}

__device__ __forceinline__ void wgmma_n128_ss_ta0_tb1(float* d, uint64_t descA, uint64_t descB, int scaleD) {
  asm volatile("{\n.reg .pred p;\nsetp.ne.b32 p, %66, 0;\n"
    "wgmma.mma_async.sync.aligned.m64n128k16.f32.bf16.bf16 {%0, %1, %2, %3, %4, %5, %6, %7, %8, %9, %10, %11, %12, %13, %14, %15, %16, %17, %18, %19, %20, %21, %22, %23, %24, %25, %26, %27, %28, %29, %30, %31, %32, %33, %34, %35, %36, %37, %38, %39, %40, %41, %42, %43, %44, %45, %46, %47, %48, %49, %50, %51, %52, %53, %54, %55, %56, %57, %58, %59, %60, %61, %62, %63}, %64, %65, p, 1, 1, 0, 1;\n}\n"
    : "+f"(d[0]), "+f"(d[1]), "+f"(d[2]), "+f"(d[3]), "+f"(d[4]), "+f"(d[5]), "+f"(d[6]), "+f"(d[7]), "+f"(d[8]), "+f"(d[9]), "+f"(d[10]), "+f"(d[11]), "+f"(d[12]), "+f"(d[13]), "+f"(d[14]), "+f"(d[15]), "+f"(d[16]), "+f"(d[17]), "+f"(d[18]), "+f"(d[19]), "+f"(d[20]), "+f"(d[21]), "+f"(d[22]), "+f"(d[23]), "+f"(d[24]), "+f"(d[25]), "+f"(d[26]), "+f"(d[27]), "+f"(d[28]), "+f"(d[29]), "+f"(d[30]), "+f"(d[31]), "+f"(d[32]), "+f"(d[33]), "+f"(d[34]), "+f"(d[35]), "+f"(d[36]), "+f"(d[37]), "+f"(d[38]), "+f"(d[39]), "+f"(d[40]), "+f"(d[41]), "+f"(d[42]), "+f"(d[43]), "+f"(d[44]), "+f"(d[45]), "+f"(d[46]), "+f"(d[47]), "+f"(d[48]), "+f"(d[49]), "+f"(d[50]), "+f"(d[51]), "+f"(d[52]), "+f"(d[53]), "+f"(d[54]), "+f"(d[55]), "+f"(d[56]), "+f"(d[57]), "+f"(d[58]), "+f"(d[59]), "+f"(d[60]), "+f"(d[61]), "+f"(d[62]), "+f"(d[63])
    : "l"(descA), "l"(descB), "r"(scaleD));
}

__device__ __forceinline__ void wgmma_n192_ssz_ta0_tb1(float* d, uint64_t descA, uint64_t descB) {
  asm volatile("{\n.reg .pred p;\nsetp.ne.b32 p, 0, 0;\n"
    "wgmma.mma_async.sync.aligned.m64n192k16.f32.bf16.bf16 {%0, %1, %2, %3, %4, %5, %6, %7, %8, %9, %10, %11, %12, %13, %14, %15, %16, %17, %18, %19, %20, %21, %22, %23, %24, %25, %26, %27, %28, %29, %30, %31, %32, %33, %34, %35, %36, %37, %38, %39, %40, %41, %42, %43, %44, %45, %46, %47, %48, %49, %50, %51, %52, %53, %54, %55, %56, %57, %58, %59, %60, %61, %62, %63, %64, %65, %66, %67, %68, %69, %70, %71, %72, %73, %74, %75, %76, %77, %78, %79, %80, %81, %82, %83, %84, %85, %86, %87, %88, %89, %90, %91, %92, %93, %94, %95}, %96, %97, p, 1, 1, 0, 1;\n}\n"
    : "=f"(d[0]), "=f"(d[1]), "=f"(d[2]), "=f"(d[3]), "=f"(d[4]), "=f"(d[5]), "=f"(d[6]), "=f"(d[7]), "=f"(d[8]), "=f"(d[9]), "=f"(d[10]), "=f"(d[11]), "=f"(d[12]), "=f"(d[13]), "=f"(d[14]), "=f"(d[15]), "=f"(d[16]), "=f"(d[17]), "=f"(d[18]), "=f"(d[19]), "=f"(d[20]), "=f"(d[21]), "=f"(d[22]), "=f"(d[23]), "=f"(d[24]), "=f"(d[25]), "=f"(d[26]), "=f"(d[27]), "=f"(d[28]), "=f"(d[29]), "=f"(d[30]), "=f"(d[31]), "=f"(d[32]), "=f"(d[33]), "=f"(d[34]), "=f"(d[35]), "=f"(d[36]), "=f"(d[37]), "=f"(d[38]), "=f"(d[39]), "=f"(d[40]), "=f"(d[41]), "=f"(d[42]), "=f"(d[43]), "=f"(d[44]), "=f"(d[45]), "=f"(d[46]), "=f"(d[47]), "=f"(d[48]), "=f"(d[49]), "=f"(d[50]), "=f"(d[51]), "=f"(d[52]), "=f"(d[53]), "=f"(d[54]), "=f"(d[55]), "=f"(d[56]), "=f"(d[57]), "=f"(d[58]), "=f"(d[59]), "=f"(d[60]), "=f"(d[61]), "=f"(d[62]), "=f"(d[63]), "=f"(d[64]), "=f"(d[65]), "=f"(d[66]), "=f"(d[67]), "=f"(d[68]), "=f"(d[69]), "=f"(d[70]), "=f"(d[71]), "=f"(d[72]), "=f"(d[73]), "=f"(d[74]), "=f"(d[75]), "=f"(d[76]), "=f"(d[77]), "=f"(d[78]), "=f"(d[79]), "=f"(d[80]), "=f"(d[81]), "=f"(d[82]), "=f"(d[83]), "=f"(d[84]), "=f"(d[85]), "=f"(d[86]), "=f"(d[87]), "=f"(d[88]), "=f"(d[89]), "=f"(d[90]), "=f"(d[91]), "=f"(d[92]), "=f"(d[93]), "=f"(d[94]), "=f"(d[95])
    : "l"(descA), "l"(descB));
}

__device__ __forceinline__ void wgmma_n192_rs_tb1(float* d, const uint32_t* a, uint64_t descB, int scaleD) {
  asm volatile("{\n.reg .pred p;\nsetp.ne.b32 p, %101, 0;\n"
    "wgmma.mma_async.sync.aligned.m64n192k16.f32.bf16.bf16 {%0, %1, %2, %3, %4, %5, %6, %7, %8, %9, %10, %11, %12, %13, %14, %15, %16, %17, %18, %19, %20, %21, %22, %23, %24, %25, %26, %27, %28, %29, %30, %31, %32, %33, %34, %35, %36, %37, %38, %39, %40, %41, %42, %43, %44, %45, %46, %47, %48, %49, %50, %51, %52, %53, %54, %55, %56, %57, %58, %59, %60, %61, %62, %63, %64, %65, %66, %67, %68, %69, %70, %71, %72, %73, %74, %75, %76, %77, %78, %79, %80, %81, %82, %83, %84, %85, %86, %87, %88, %89, %90, %91, %92, %93, %94, %95}, {%96, %97, %98, %99}, %100, p, 1, 1, 1;\n}\n"
    : "+f"(d[0]), "+f"(d[1]), "+f"(d[2]), "+f"(d[3]), "+f"(d[4]), "+f"(d[5]), "+f"(d[6]), "+f"(d[7]), "+f"(d[8]), "+f"(d[9]), "+f"(d[10]), "+f"(d[11]), "+f"(d[12]), "+f"(d[13]), "+f"(d[14]), "+f"(d[15]), "+f"(d[16]), "+f"(d[17]), "+f"(d[18]), "+f"(d[19]), "+f"(d[20]), "+f"(d[21]), "+f"(d[22]), "+f"(d[23]), "+f"(d[24]), "+f"(d[25]), "+f"(d[26]), "+f"(d[27]), "+f"(d[28]), "+f"(d[29]), "+f"(d[30]), "+f"(d[31]), "+f"(d[32]), "+f"(d[33]), "+f"(d[34]), "+f"(d[35]), "+f"(d[36]), "+f"(d[37]), "+f"(d[38]), "+f"(d[39]), "+f"(d[40]), "+f"(d[41]), "+f"(d[42]), "+f"(d[43]), "+f"(d[44]), "+f"(d[45]), "+f"(d[46]), "+f"(d[47]), "+f"(d[48]), "+f"(d[49]), "+f"(d[50]), "+f"(d[51]), "+f"(d[52]), "+f"(d[53]), "+f"(d[54]), "+f"(d[55]), "+f"(d[56]), "+f"(d[57]), "+f"(d[58]), "+f"(d[59]), "+f"(d[60]), "+f"(d[61]), "+f"(d[62]), "+f"(d[63]), "+f"(d[64]), "+f"(d[65]), "+f"(d[66]), "+f"(d[67]), "+f"(d[68]), "+f"(d[69]), "+f"(d[70]), "+f"(d[71]), "+f"(d[72]), "+f"(d[73]), "+f"(d[74]), "+f"(d[75]), "+f"(d[76]), "+f"(d[77]), "+f"(d[78]), "+f"(d[79]), "+f"(d[80]), "+f"(d[81]), "+f"(d[82]), "+f"(d[83]), "+f"(d[84]), "+f"(d[85]), "+f"(d[86]), "+f"(d[87]), "+f"(d[88]), "+f"(d[89]), "+f"(d[90]), "+f"(d[91]), "+f"(d[92]), "+f"(d[93]), "+f"(d[94]), "+f"(d[95])
    : "r"(a[0]), "r"(a[1]), "r"(a[2]), "r"(a[3]), "l"(descB), "r"(scaleD));
}

__device__ __forceinline__ void wgmma_n80_rs_tb0(float* d, const uint32_t* a, uint64_t descB, int scaleD) {
  asm volatile("{\n.reg .pred p;\nsetp.ne.b32 p, %45, 0;\n"
    "wgmma.mma_async.sync.aligned.m64n80k16.f32.bf16.bf16 {%0, %1, %2, %3, %4, %5, %6, %7, %8, %9, %10, %11, %12, %13, %14, %15, %16, %17, %18, %19, %20, %21, %22, %23, %24, %25, %26, %27, %28, %29, %30, %31, %32, %33, %34, %35, %36, %37, %38, %39}, {%40, %41, %42, %43}, %44, p, 1, 1, 0;\n}\n"
    : "+f"(d[0]), "+f"(d[1]), "+f"(d[2]), "+f"(d[3]), "+f"(d[4]), "+f"(d[5]), "+f"(d[6]), "+f"(d[7]), "+f"(d[8]), "+f"(d[9]), "+f"(d[10]), "+f"(d[11]), "+f"(d[12]), "+f"(d[13]), "+f"(d[14]), "+f"(d[15]), "+f"(d[16]), "+f"(d[17]), "+f"(d[18]), "+f"(d[19]), "+f"(d[20]), "+f"(d[21]), "+f"(d[22]), "+f"(d[23]), "+f"(d[24]), "+f"(d[25]), "+f"(d[26]), "+f"(d[27]), "+f"(d[28]), "+f"(d[29]), "+f"(d[30]), "+f"(d[31]), "+f"(d[32]), "+f"(d[33]), "+f"(d[34]), "+f"(d[35]), "+f"(d[36]), "+f"(d[37]), "+f"(d[38]), "+f"(d[39])
    : "r"(a[0]), "r"(a[1]), "r"(a[2]), "r"(a[3]), "l"(descB), "r"(scaleD));
}

__device__ __forceinline__ void wgmma_n80_rsz_tb0(float* d, const uint32_t* a, uint64_t descB) {
  asm volatile("{\n.reg .pred p;\nsetp.ne.b32 p, 0, 0;\n"
    "wgmma.mma_async.sync.aligned.m64n80k16.f32.bf16.bf16 {%0, %1, %2, %3, %4, %5, %6, %7, %8, %9, %10, %11, %12, %13, %14, %15, %16, %17, %18, %19, %20, %21, %22, %23, %24, %25, %26, %27, %28, %29, %30, %31, %32, %33, %34, %35, %36, %37, %38, %39}, {%40, %41, %42, %43}, %44, p, 1, 1, 0;\n}\n"
    : "=f"(d[0]), "=f"(d[1]), "=f"(d[2]), "=f"(d[3]), "=f"(d[4]), "=f"(d[5]), "=f"(d[6]), "=f"(d[7]), "=f"(d[8]), "=f"(d[9]), "=f"(d[10]), "=f"(d[11]), "=f"(d[12]), "=f"(d[13]), "=f"(d[14]), "=f"(d[15]), "=f"(d[16]), "=f"(d[17]), "=f"(d[18]), "=f"(d[19]), "=f"(d[20]), "=f"(d[21]), "=f"(d[22]), "=f"(d[23]), "=f"(d[24]), "=f"(d[25]), "=f"(d[26]), "=f"(d[27]), "=f"(d[28]), "=f"(d[29]), "=f"(d[30]), "=f"(d[31]), "=f"(d[32]), "=f"(d[33]), "=f"(d[34]), "=f"(d[35]), "=f"(d[36]), "=f"(d[37]), "=f"(d[38]), "=f"(d[39])
    : "r"(a[0]), "r"(a[1]), "r"(a[2]), "r"(a[3]), "l"(descB));
}

__device__ __forceinline__ void wgmma_n32_rs_tb1(float* d, const uint32_t* a, uint64_t descB, int scaleD) {
  asm volatile("{\n.reg .pred p;\nsetp.ne.b32 p, %21, 0;\n"
    "wgmma.mma_async.sync.aligned.m64n32k16.f32.bf16.bf16 {%0, %1, %2, %3, %4, %5, %6, %7, %8, %9, %10, %11, %12, %13, %14, %15}, {%16, %17, %18, %19}, %20, p, 1, 1, 1;\n}\n"
    : "+f"(d[0]), "+f"(d[1]), "+f"(d[2]), "+f"(d[3]), "+f"(d[4]), "+f"(d[5]), "+f"(d[6]), "+f"(d[7]), "+f"(d[8]), "+f"(d[9]), "+f"(d[10]), "+f"(d[11]), "+f"(d[12]), "+f"(d[13]), "+f"(d[14]), "+f"(d[15])
    : "r"(a[0]), "r"(a[1]), "r"(a[2]), "r"(a[3]), "l"(descB), "r"(scaleD));
}

__device__ __forceinline__ void wgmma_n32_rsz_tb1(float* d, const uint32_t* a, uint64_t descB) {
  asm volatile("{\n.reg .pred p;\nsetp.ne.b32 p, 0, 0;\n"
    "wgmma.mma_async.sync.aligned.m64n32k16.f32.bf16.bf16 {%0, %1, %2, %3, %4, %5, %6, %7, %8, %9, %10, %11, %12, %13, %14, %15}, {%16, %17, %18, %19}, %20, p, 1, 1, 1;\n}\n"
    : "=f"(d[0]), "=f"(d[1]), "=f"(d[2]), "=f"(d[3]), "=f"(d[4]), "=f"(d[5]), "=f"(d[6]), "=f"(d[7]), "=f"(d[8]), "=f"(d[9]), "=f"(d[10]), "=f"(d[11]), "=f"(d[12]), "=f"(d[13]), "=f"(d[14]), "=f"(d[15])
    : "r"(a[0]), "r"(a[1]), "r"(a[2]), "r"(a[3]), "l"(descB));
}

__device__ __forceinline__ void wgmma_n32_rs_tb0(float* d, const uint32_t* a, uint64_t descB, int scaleD) {
  asm volatile("{\n.reg .pred p;\nsetp.ne.b32 p, %21, 0;\n"
    "wgmma.mma_async.sync.aligned.m64n32k16.f32.bf16.bf16 {%0, %1, %2, %3, %4, %5, %6, %7, %8, %9, %10, %11, %12, %13, %14, %15}, {%16, %17, %18, %19}, %20, p, 1, 1, 0;\n}\n"
    : "+f"(d[0]), "+f"(d[1]), "+f"(d[2]), "+f"(d[3]), "+f"(d[4]), "+f"(d[5]), "+f"(d[6]), "+f"(d[7]), "+f"(d[8]), "+f"(d[9]), "+f"(d[10]), "+f"(d[11]), "+f"(d[12]), "+f"(d[13]), "+f"(d[14]), "+f"(d[15])
    : "r"(a[0]), "r"(a[1]), "r"(a[2]), "r"(a[3]), "l"(descB), "r"(scaleD));
}

__device__ __forceinline__ void wgmma_n32_rsz_tb0(float* d, const uint32_t* a, uint64_t descB) {
  asm volatile("{\n.reg .pred p;\nsetp.ne.b32 p, 0, 0;\n"
    "wgmma.mma_async.sync.aligned.m64n32k16.f32.bf16.bf16 {%0, %1, %2, %3, %4, %5, %6, %7, %8, %9, %10, %11, %12, %13, %14, %15}, {%16, %17, %18, %19}, %20, p, 1, 1, 0;\n}\n"
    : "=f"(d[0]), "=f"(d[1]), "=f"(d[2]), "=f"(d[3]), "=f"(d[4]), "=f"(d[5]), "=f"(d[6]), "=f"(d[7]), "=f"(d[8]), "=f"(d[9]), "=f"(d[10]), "=f"(d[11]), "=f"(d[12]), "=f"(d[13]), "=f"(d[14]), "=f"(d[15])
    : "r"(a[0]), "r"(a[1]), "r"(a[2]), "r"(a[3]), "l"(descB));
}

__device__ __forceinline__ uint32_t pack_bf16x2(float lo, float hi) {
  uint32_t r;
  asm("cvt.rn.bf16x2.f32 %0, %1, %2;" : "=r"(r) : "f"(hi), "f"(lo));
  return r;
}
__device__ __forceinline__ float bf_lo(uint32_t p) { return __uint_as_float(p << 16); }
__device__ __forceinline__ float bf_hi(uint32_t p) { return __uint_as_float(p & 0xffff0000u); }
__device__ __forceinline__ float bf16_round(float v) { return __bfloat162float(__float2bfloat16_rn(v)); }
__device__ __forceinline__ float ex2_approx(float x) {
  float r;
  asm("ex2.approx.ftz.f32 %0, %1;" : "=f"(r) : "f"(x));
  return r;
}
__device__ __forceinline__ float rcp_fast(float x) {
  float r;
  asm("rcp.approx.ftz.f32 %0, %1;" : "=f"(r) : "f"(x));
  return r;
}
__device__ __forceinline__ void ldmatrix_x4(uint32_t (&r)[4], uint32_t addr) {
  asm volatile("ldmatrix.sync.aligned.m8n8.x4.shared.b16 {%0,%1,%2,%3}, [%4];"
               : "=r"(r[0]), "=r"(r[1]), "=r"(r[2]), "=r"(r[3])
               : "r"(addr)
               : "memory");
}
__device__ __forceinline__ void stmatrix_x4(uint32_t addr, uint32_t r0, uint32_t r1, uint32_t r2, uint32_t r3) {
  asm volatile("stmatrix.sync.aligned.m8n8.x4.shared.b16 [%0], {%1,%2,%3,%4};" ::"r"(addr), "r"(r0), "r"(r1), "r"(r2),
               "r"(r3));
}
__device__ __forceinline__ uint32_t add_bf16x2(uint32_t a, uint32_t b) {
  uint32_t r;
  asm("add.rn.bf16x2 %0, %1, %2;" : "=r"(r) : "r"(a), "r"(b));
  return r;
}
__device__ __forceinline__ uint4 lds128(uint32_t addr) {
  uint4 v;
  asm volatile("ld.shared.v4.b32 {%0,%1,%2,%3}, [%4];" : "=r"(v.x), "=r"(v.y), "=r"(v.z), "=r"(v.w) : "r"(addr) : "memory");
  return v;
}
__device__ __forceinline__ uint32_t lds32(uint32_t addr) {
  uint32_t v;
  asm volatile("ld.shared.b32 %0, [%1];" : "=r"(v) : "r"(addr) : "memory");
  return v;
}
__device__ __forceinline__ void sts32(uint32_t addr, uint32_t v) {
  asm volatile("st.shared.b32 [%0], %1;" ::"r"(addr), "r"(v) : "memory");
}

__device__ __forceinline__ unsigned ld_relaxed_u32(const void* p) {
  unsigned v;
  asm volatile("ld.relaxed.gpu.global.u32 %0, [%1];" : "=r"(v) : "l"(p) : "memory");
  return v;
}
__device__ __forceinline__ unsigned launch_epoch() { return (*(volatile unsigned*)g_done) / NCTA + 1u; }
__device__ __forceinline__ void red_announce(unsigned* p) {
  asm volatile("red.relaxed.gpu.global.add.u32 [%0], %1;" ::"l"(p), "r"(1u) : "memory");
}
__device__ __forceinline__ uint32_t set_tag(uint32_t w, uint32_t m, uint32_t tag) { return (w & ~m) | (tag & m); }
__device__ __forceinline__ uint32_t o_tag(int L) { return (L + 1) & 1; }
__device__ __forceinline__ uint32_t x_tag(unsigned ep1, int L) { return (ep1 + L + 1) & 1; }

__device__ __forceinline__ void wait_count(const unsigned* f, unsigned target, int i, uint32_t& seen, int lane) {
  if ((seen >> i) & 1u) return;
#pragma unroll 1
  for (uint32_t it = 0; it < (1u << 17); ++it) {
    seen = __ballot_sync(0xffffffffu, (int)(ld_relaxed_u32(f + (lane & 15)) - target) >= 0);
    if ((seen >> i) & 1u) break;
  }
  fence_proxy_async_all();
}
__device__ __forceinline__ float4 ld_rec(const float4* p) {
  float4 v;
  asm volatile("ld.relaxed.gpu.global.v4.f32 {%0,%1,%2,%3}, [%4];" : "=f"(v.x), "=f"(v.y), "=f"(v.z), "=f"(v.w) : "l"(p) : "memory");
  return v;
}
__device__ __forceinline__ void st_rec(float4* p, float a, float b, float c, unsigned tag) {
  asm volatile("st.relaxed.gpu.global.v4.f32 [%0], {%1,%2,%3,%4};" ::"l"(p), "f"(a), "f"(b), "f"(c), "f"(__uint_as_float(tag)) : "memory");
}
template <int N>
__device__ __forceinline__ float4 sum_recs(const float4* p, int stride, unsigned tag) {
  float4 s;
#pragma unroll 1
  for (uint32_t it = 0; it < (1u << 17); ++it) {
    float4 v[N];
#pragma unroll
    for (int t = 0; t < N; t++) v[t] = ld_rec(p + t * stride);
    bool ok = true;
    s = make_float4(0.f, 0.f, 0.f, 0.f);
#pragma unroll
    for (int t = 0; t < N; t++) {
      ok &= __float_as_uint(v[t].w) == tag;
      s.x += v[t].x;
      s.y += v[t].y;
      s.z += v[t].z;
    }
    if (ok) break;
    __nanosleep(200);
  }
  return s;
}

__device__ __forceinline__ int fresh_tid() {
  int t;
  asm volatile("mov.u32 %0, %%tid.x;" : "=r"(t));
  return t;
}
#define PHASE_IDS                                  \
  const int tid_ = fresh_tid();                    \
  const int lane = tid_ & 31, wwarp = __shfl_sync(0xffffffffu, (tid_ >> 5) & 3, 0), tid = tid_ & 127; \
  const int g = lane >> 2, c = lane & 3;           \
  (void)tid; (void)g; (void)c; (void)wwarp;

#define PHASE_IDS_W                                \
  const int lane = fresh_tid() & 31, wwarp = warp & 3; \
  const int g = lane >> 2, c = lane & 3;

#define GTL(i) do { } while (0)
#define TGET(v) do { } while (0)
#define TPUT(c, i, v) do { } while (0)

constexpr float SM_C = 0.17677669529663687f * 1.4426950408889634f;

__device__ __forceinline__ void stmatrix_x4_if(bool ok, uint32_t addr, uint32_t r0, uint32_t r1, uint32_t r2, uint32_t r3) {
  asm volatile("{\n.reg .pred p;\nsetp.ne.b32 p, %5, 0;\n@p stmatrix.sync.aligned.m8n8.x4.shared.b16 [%0], {%1,%2,%3,%4};\n}\n" ::"r"(addr),
               "r"(r0), "r"(r1), "r"(r2), "r"(r3), "r"((int)ok));
}

__device__ __forceinline__ void attn_a_slow(const uint8_t* __restrict__ kvimg, int L, int gb, int hp, uint32_t bad,
                                            int row0, int lane) {
  constexpr uint32_t sq = SBASE + OFF_SLOT + 3 * 16384;
#pragma unroll 1
  for (int j = 0; j < 8; j++) {
    const uint8_t* tp = kvimg + (size_t)(gb * 16 + hp) * 32768 + (j * 32 + lane) * 128 + ((lane & 7) << 4);
#pragma unroll 1
    for (uint32_t it = 0; it < (1u << 17); ++it)
      if (((ld_relaxed_u32(tp) ^ lds32(SBASE + OFF_EPOCH)) & 1u) == 0u) break;
  }
  __syncwarp();
#pragma unroll 1
  for (int t = 0; t < 32; t++) {
    const int hh = t >> 4, row = row0 + (t & 7) + (t & 8) * 4;
    if (!((bad >> hh) & 1u)) continue;
    const int qpos = gb * 128 + row;
    const uint32_t qaddr = sq + row * 128;
    float mx = -INFINITY, sum = 0.f, acc = 0.f;
#pragma unroll 1
    for (int pass = 0; pass < 2; pass++) {
#pragma unroll 1
      for (int j = 0; j < 8; j++) {
        const int kp = qpos - (lane + 32 * j);
        const uint8_t* kr = kvimg + ((size_t)((kp >> 7) * 16 + hp) * 2 + ((kp >> 6) & 1)) * 16384 + (kp & 63) * 128;
        float d = -INFINITY;
        if (kp >= 0) {
          d = 0.f;
#pragma unroll 1
          for (int q = 0; q < 4; q++) {
            const uint4 kv = __ldcg(reinterpret_cast<const uint4*>(kr + (((hh * 4 + q) ^ (kp & 7)) << 4)));
            const uint4 qv = lds128(qaddr + (((hh * 4 + q) ^ (row & 7)) << 4));
            const uint32_t kw[4] = {kv.x, kv.y, kv.z, kv.w}, qw[4] = {qv.x, qv.y, qv.z, qv.w};
#pragma unroll
            for (int e = 0; e < 4; e++) d = fmaf(bf_lo(kw[e]), bf_lo(qw[e]), fmaf(bf_hi(kw[e]), bf_hi(qw[e]), d));
          }
        }
        if (pass == 0) {
          mx = fmaxf(mx, d);
        } else {
          const float ev = ex2_approx(d - mx);
          sum += ev;
          const float pv = bf16_round(ev);
#pragma unroll 1
          for (int kk = 0; kk < 32; kk++) {
            const float pk = __shfl_sync(0xffffffffu, pv, kk);
            const int k2 = qpos - (kk + 32 * j);
            if (k2 >= 0) {
              const uint8_t* vr = kvimg + ((size_t)((k2 >> 7) * 16 + hp) * 2 + ((k2 >> 6) & 1)) * 16384 + 8192 + (k2 & 63) * 128;
              const unsigned short vv =
                  __ldcg(reinterpret_cast<const unsigned short*>(vr + (((hh * 4 + (lane >> 3)) ^ (k2 & 7)) << 4) + (lane & 7) * 2));
              acc = fmaf(pk, __uint_as_float((uint32_t)vv << 16), acc);
            }
          }
        }
      }
      if (pass == 0) {
#pragma unroll
        for (int o = 16; o > 0; o >>= 1) mx = fmaxf(mx, __shfl_xor_sync(0xffffffffu, mx, o));
      }
    }
#pragma unroll
    for (int o = 16; o > 0; o >>= 1) sum += __shfl_xor_sync(0xffffffffu, sum, o);
    acc *= rcp_fast(sum);
    const float hi = __shfl_down_sync(0xffffffffu, acc, 1);
    __syncwarp();
    if ((lane & 1) == 0) sts32(qaddr + (((hh * 4 + (lane >> 3)) ^ (row & 7)) << 4) + (lane & 7) * 2,
                               set_tag(pack_bf16x2(acc, hi), hh == 0 && lane == 0, o_tag(L)));
    __syncwarp();
  }
}

template <int HH>
__device__ __forceinline__ void store_o(const float (&o)[16], const float (&inv)[2], uint32_t ra, uint32_t tag, bool ok) {
  const uint32_t m = HH == 0 && (fresh_tid() & 3) == 0;
#pragma unroll
  for (int jp = 0; jp < 2; jp++) {
    uint32_t w0 = pack_bf16x2(o[8 * jp] * inv[0], o[8 * jp + 1] * inv[0]);
    uint32_t w1 = pack_bf16x2(o[8 * jp + 2] * inv[1], o[8 * jp + 3] * inv[1]);
    if (HH == 0 && jp == 0) {
      w0 = set_tag(w0, m, tag);
      w1 = set_tag(w1, m, tag);
    }
    stmatrix_x4_if(ok, ra ^ ((HH * 4 + 2 * jp) << 4), w0, w1, pack_bf16x2(o[8 * jp + 4] * inv[0], o[8 * jp + 5] * inv[0]),
                   pack_bf16x2(o[8 * jp + 6] * inv[1], o[8 * jp + 7] * inv[1]));
  }
}
__device__ __forceinline__ int tile_row(bool B, int w, int r, int g) { return (B ? 16 * w + 8 * r : 8 * w + 32 * r) + g; }
__device__ __forceinline__ uint32_t q_row_addr(bool B, int R, int w, int lane) {
  return SBASE + OFF_SLOT + 3 * 16384 + R * 8192 + tile_row(B, w, (lane >> 3) & 1, lane & 7) * 128 + (((lane >> 4) ^ (lane & 7)) << 4);
}

struct AttnA {
  float s[2][16], o[2][16], l[2][2], sh[2][3];
  uint32_t p[2][4], t[2], me[4], ra, bad, zero;
};
#define ATS_(i) do { } while (0)
template <int V>
__device__ __forceinline__ void attn_sum(AttnA& a, int nv) {
  constexpr int hh = (V >> 1) & 1, kh = V & 1, i = V >> 2;
#pragma unroll
  for (int r = 0; r < 2; r++) {
    const uint32_t t1 = add_bf16x2(add_bf16x2(a.p[0][r], a.p[0][2 + r]), add_bf16x2(a.p[1][r], a.p[1][2 + r]));
    if (kh == 0) {
      a.t[r] = t1;
    } else {
      uint32_t tt = add_bf16x2(a.t[r], t1);
      if (i > 0) tt = i <= nv ? tt : 0u;
      const float v = bf_lo(tt) + bf_hi(tt);
      a.l[hh][r] = i == 0 ? v : a.l[hh][r] + v;
    }
  }
}
template <int HH>
__device__ __forceinline__ void attn_shfl(AttnA& a) {
#pragma unroll
  for (int r = 0; r < 2; r++)
#pragma unroll
    for (int j = 0; j < 3; j++) a.sh[r][j] = __shfl_xor_sync(0xffffffffu, a.l[HH][r], j + 1);
}
template <int HH>
__device__ __forceinline__ void attn_fin(AttnA& a) {
  bool bad = false;
  float inv[2];
#pragma unroll
  for (int r = 0; r < 2; r++) {
    const float v = (a.l[HH][r] + a.sh[r][0]) + (a.sh[r][1] + a.sh[r][2]);
    bad |= !(v <= 1.152921504606846976e18f && v >= 8.673617379884035e-19f);
    inv[r] = rcp_fast(v);
  }
  bad = __any_sync(0xffffffffu, bad);
  if (HH == 1) wgmma_wait<0>();
  reg_fence<16>(a.o[HH]);
  store_o<HH>(a.o[HH], inv, a.ra, o_tag(0), !bad);
  a.bad = (HH == 0 ? 0u : a.bad) | (bad ? 1u << HH : 0u);
}
__device__ __forceinline__ void attn_masks(AttnA& a, int wr) {
  const int lane = fresh_tid() & 31, d = (lane >> 2) - 2 * (lane & 3);
  const uint32_t tri = d >= 1 ? 0xffffffffu : (d == 0 ? 0xffffu : 0u);
#pragma unroll
  for (int t = 0; t < 4; t++) a.me[t] = wr > t ? 0xffffffffu : (wr == t ? tri : 0u);
}
template <int V, int K>
__device__ __forceinline__ uint32_t attn_exp(AttnA& a) {
  constexpr int i = V >> 2, kh = V & 1, r = K & 1;
  if ((i == 0 && kh > r) || (i == 4 && kh < r)) return 0u;
  const uint32_t w = pack_bf16x2(ex2_approx(a.s[V & 1][2 * K]), ex2_approx(a.s[V & 1][2 * K + 1]));
  if (i == 0 && kh == r) return w & a.me[K >> 1];
  if (i == 4 && kh == r) return w & ~a.me[K >> 1];
  return w;
}
template <int V>
__device__ __forceinline__ void attn_unit(AttnA& a, const uint32_t (&q)[2][2][4], uint64_t dcur, uint64_t dnext, int R, int wr, int nv,
                                          uint32_t hbar, uint32_t hpar, uint32_t rbar, bool rel) {
  constexpr int hh = (V >> 1) & 1, kh = V & 1, i = V >> 2;
  ATS_(V + 1);
  asm volatile("" : "+l"(dcur), "+l"(dnext));
  wgmma_wait<1>();
  reg_fence<16>(a.s[V & 1]);
  bool hok = true;
  if (V == 4) hbar = SBASE + OFF_BAR + 8u * (R ? B_LOC : B_HV);
  if (((V & 3) == 2 && V < 16) || V == 4) hok = mbar_test(hbar, hpar);
  const uint64_t d0 = ((V & 3) >= 2 ? dnext : dcur) + ((hh ^ 1) * 4 + kh * 256), d1 = ((V & 3) >= 2 ? dnext : dcur) + ((hh ^ 1) * 4 + kh * 256 + 2);
  const uint64_t d2 = dcur + (512 + hh * 4 + kh * 256), d3 = dcur + (640 + hh * 4 + kh * 256);
  if ((V & 3) == 1 && V > 4 && rel) mbar_arrive(rbar);
  if (V > 0) attn_sum<V - 1>(a, nv);
  if (V == 15) attn_masks(a, wr);
  if (V == 18) {
    attn_shfl<0>(a);
    a.ra = q_row_addr(false, R, wr, fresh_tid() & 31);
  }
  if (V == 19) attn_fin<0>(a);
  uint32_t p[2][4];
  p[0][0] = attn_exp<V, 0>(a);
  p[0][1] = attn_exp<V, 1>(a);
  p[0][2] = attn_exp<V, 2>(a);
  p[0][3] = attn_exp<V, 3>(a);
  p[1][0] = attn_exp<V, 4>(a);
  p[1][1] = attn_exp<V, 5>(a);
  p[1][2] = attn_exp<V, 6>(a);
  p[1][3] = attn_exp<V, 7>(a);
  if (V > 0) {
#pragma unroll
    for (int r = 0; r < 2; r++) p[1][r] ^= (kh ? a.t[r] : __float_as_uint(a.l[hh ^ 1][r])) & a.zero;
  }
#pragma unroll
  for (int k = 0; k < 8; k++) {
    asm volatile("" : "+r"(p[k >> 2][k & 3]));
    a.p[k >> 2][k & 3] = p[k >> 2][k & 3];
  }
  if (!hok) mbar_wait(hbar, hpar);
  wgmma_fence();
  if (V < 18) wgmma_n32_rsz_tb0(a.s[V & 1], q[hh ^ 1][0], d0);
  if (i == 0 && kh == 0) wgmma_n32_rsz_tb1(a.o[hh], a.p[0], d2);
  else wgmma_n32_rs_tb1(a.o[hh], a.p[0], d2, 1);
  if (V < 18) wgmma_n32_rs_tb0(a.s[V & 1], q[hh ^ 1][1], d1, 1);
  wgmma_n32_rs_tb1(a.o[hh], a.p[1], d3, 1);
  wgmma_commit();
}
template <int I>
__device__ __forceinline__ void attn_step(AttnA& a, const uint32_t (&q)[2][2][4], uint64_t dcur, uint64_t dnext, int R, int wr, int nv,
                                          uint32_t hbar, uint32_t hpar, uint32_t rbar, bool rel) {
  attn_unit<4 * I>(a, q, dcur, dnext, R, wr, nv, hbar, hpar, rbar, rel);
  attn_unit<4 * I + 1>(a, q, dcur, dnext, R, wr, nv, hbar, hpar, rbar, rel);
  attn_unit<4 * I + 2>(a, q, dcur, dnext, R, wr, nv, hbar, hpar, rbar, rel);
  attn_unit<4 * I + 3>(a, q, dcur, dnext, R, wr, nv, hbar, hpar, rbar, rel);
}

__device__ __forceinline__ void attention_a(const uint32_t (&q)[2][2][4], int R, int L, int gb, int hp, uint32_t par, int wr,
                                            uint32_t zero) {
  constexpr uint32_t bars = SBASE + OFF_BAR;
  constexpr uint32_t dslot = ((SBASE + OFF_SLOT) >> 4) + 0x10000u;
  auto next = [&](uint64_t d) { return desc_lo((uint32_t)d == dslot ? dslot + 2048 : (uint32_t)d - 1024) + zero; };
  uint64_t d0 = desc_lo(dslot + R * 1024) + zero, d1 = next(d0);
  AttnA a;
  ATS_(0);
  wgmma_fence();
#pragma unroll
  for (int v = 0; v < 2; v++) {
    wgmma_n32_rsz_tb0(a.s[v], q[0][0], d0 + v * 256);
    wgmma_n32_rs_tb0(a.s[v], q[0][1], d0 + (v * 256 + 2), 1);
    wgmma_commit();
  }
  a.zero = zero;
  const bool lane0 = (fresh_tid() & 31) == 0;
  attn_masks(a, wr);
  const int nv = 2 * gb + R;
  const uint32_t hb = bars + 8u * (B_HALO - R), rb = bars + 8u * (B_REL - R);
  attn_step<0>(a, q, d0, d1, R, wr, nv, hb, par, 0, false);
  d0 = next(d1);
  attn_step<1>(a, q, d1, d0, R, wr, nv, R ? bars + 8u * B_HV : hb + 8, par, rb + 8, lane0);
  d1 = next(d0);
  attn_step<2>(a, q, d0, d1, R, wr, nv, hb + 16, par, rb + 16, lane0);
  d0 = next(d1);
  attn_step<3>(a, q, d1, d0, R, wr, nv, hb + 24, par, rb + 24, lane0 && R);
  attn_step<4>(a, q, d0, d0, R, wr, nv, 0, 0, rb, false);
  ATS_(21);
  attn_sum<19>(a, nv);
  attn_shfl<1>(a);
  attn_fin<1>(a);
  ATS_(22);
  if (a.bad != 0u) attn_a_slow(g_kvA[L >> 1][0][0][0], L, gb, hp, a.bad, R * 64 + wr * 8, fresh_tid() & 31);
}

constexpr uint32_t KB_ROW0 = SBASE + OFF_SLOT + 2048, VB_ROW0 = SBASE + OFF_SLOT + 24576 + 2048;

__device__ __forceinline__ void attention_b(const uint32_t (&q)[2][2][4], int R, int gb, uint32_t par0, int wr) {
  constexpr uint32_t bars = SBASE + OFF_BAR;
  const uint32_t dk = ((KB_ROW0 - 2048) >> 4) + 0x10000u + R * 512, dv = dk + ((VB_ROW0 - KB_ROW0) >> 4);
  float s[2][40];
  mbar_wait(bars + 8u * (B_HALO - R), par0);
  wgmma_fence();
#pragma unroll
  for (int hh = 0; hh < 2; hh++) {
    wgmma_n80_rsz_tb0(s[hh], q[hh][0], desc_lo(dk + hh * 4));
    wgmma_n80_rs_tb0(s[hh], q[hh][1], desc_lo(dk + hh * 4 + 2), 1);
  }
  wgmma_commit();
  const int lane = fresh_tid() & 31, g = lane >> 2;
  const bool odd = g & 1, edge = R == 0 && gb == 0 && wr == 0;
  const int D = 2 * (lane & 3) + (g & 1) - g;
  const uint32_t ra = q_row_addr(true, R, wr, lane);
  wgmma_wait<0>();
  reg_fence<40>(s[0]);
  reg_fence<40>(s[1]);
  float z[2][2], y[2][2];
#define GATHER_(W)                                                                                          \
  _Pragma("unroll") for (int hh = 0; hh < 2; hh++) _Pragma("unroll") for (int r = 0; r < 2; r++) {          \
    const float* e = &s[hh][4 * (2 * W + r) + 2 * r];                                                       \
    z[hh][r] = odd ? e[5] : e[4];                                                                           \
    y[hh][r] = D >= 2 ? (odd ? e[1] : e[0]) : (odd ? e[9] : e[8]);                                          \
  }
  if (wr < 2) {
    if (wr == 0) { GATHER_(0) } else { GATHER_(1) }
  } else {
    if (wr == 2) { GATHER_(2) } else { GATHER_(3) }
  }
#undef GATHER_
  float o[2][16], inv[2][2];
  uint32_t p[2][5][4];
  const int sh = odd ? 16 : 0, kb = wr + (D >= 2 ? 0 : 1);
#pragma unroll
  for (int hh = 0; hh < 2; hh++) {
    if (edge) {
      z[hh][0] = -INFINITY;
      if (D >= 2) y[hh][0] = y[hh][1] = -INFINITY;
    }
    uint32_t ab[2][2];
#pragma unroll
    for (int r = 0; r < 2; r++) {
      float m = fmaxf(z[hh][r], y[hh][r]);
      m = fmaxf(m, __shfl_xor_sync(0xffffffffu, m, 1));
      m = fmaxf(m, __shfl_xor_sync(0xffffffffu, m, 2));
      const float e0 = ex2_approx(z[hh][r] - m), e1 = ex2_approx(y[hh][r] - m);
      inv[hh][r] = e0 + e1;
      ab[r][0] = pack_bf16x2(e0, 0.f) << sh;
      ab[r][1] = pack_bf16x2(e1, 0.f) << sh;
    }
#pragma unroll
    for (int k = 0; k < 5; k++) {
      p[hh][k][0] = k == kb ? ab[0][1] : 0u;
      p[hh][k][1] = k == wr + 1 ? ab[1][0] : 0u;
      p[hh][k][2] = k == wr ? ab[0][0] : 0u;
      p[hh][k][3] = k == kb ? ab[1][1] : 0u;
#pragma unroll
      for (int j = 0; j < 4; j++) asm volatile("" : "+r"(p[hh][k][j]));
    }
  }
  wgmma_fence();
#pragma unroll
  for (int hh = 0; hh < 2; hh++) {
    wgmma_n32_rsz_tb1(o[hh], p[hh][0], desc_lo(dv + hh * 4));
#pragma unroll
    for (int k = 1; k < 5; k++) wgmma_n32_rs_tb1(o[hh], p[hh][k], desc_lo(dv + hh * 4 + k * 128), 1);
  }
  wgmma_commit();
#pragma unroll
  for (int hh = 0; hh < 2; hh++)
#pragma unroll
    for (int r = 0; r < 2; r++) {
      inv[hh][r] += __shfl_xor_sync(0xffffffffu, inv[hh][r], 1);
      inv[hh][r] += __shfl_xor_sync(0xffffffffu, inv[hh][r], 2);
      inv[hh][r] = rcp_fast(inv[hh][r]);
    }
  wgmma_wait<0>();
  reg_fence<16>(o[0]);
  reg_fence<16>(o[1]);
  store_o<0>(o[0], inv[0], ra, o_tag(1), true);
  store_o<1>(o[1], inv[1], ra, o_tag(1), true);
}

#define KTQM 0
#define TRICKLE 300
#define WTURN 15
#define QREL 8
#define PRESLEEP 200
#define VSLEEP 150
#define QTURN 2
struct Params {
  CUtensorMap x[5], xq[4], o, wqkv[2], wqkv3[2], wo3[2];
  const __nv_bfloat16* in_x;
  const __nv_bfloat16* wqkv_p[2];
  const __nv_bfloat16* wo_p[2];
  __nv_bfloat16* out;
  uint32_t zero;
};

__device__ __forceinline__ void colsum_part(const CUtensorMap* wmap, int ty, int qr, int hp) {
  constexpr uint32_t bars = SBASE + OFF_BAR, slots = SBASE + OFF_SLOT;
  PHASE_IDS
  const unsigned ep1 = launch_epoch();
  if (wwarp == 0 && elect_one()) {
    mbar_expect_tx(bars + 8u * B_CS, 6 * UNIT);
#pragma unroll 1
    for (int j = 0; j < 6; j++) {
      if (ty == 0) mbar_pace(bars + 8u * (B_QF + B_E + (j & 3)), j >> 2);
      else __nanosleep(400);
      tma_load_2d(slots + j * UNIT, wmap, bars + 8u * B_CS, (j >> 1) * 1024 + hp * 64, qr * 128 + (j & 1) * 64);
    }
  }
  mbar_wait(bars + 8u * B_CS, ty);
  const uint32_t src = slots + (tid >> 3) * 128 + (((tid & 7) ^ ((tid >> 3) & 7)) << 4);
#pragma unroll 1
  for (int p = 0; p < 3; p++) {
    float s[8];
#pragma unroll
    for (int e = 0; e < 8; e++) s[e] = 0.f;
#pragma unroll
    for (int j = 0; j < 8; j++) {
      const uint4 v = lds128(src + p * 2 * UNIT + j * 2048);
      const uint32_t x[4] = {v.x, v.y, v.z, v.w};
#pragma unroll
      for (int e = 0; e < 4; e++) {
        s[2 * e] += bf_lo(x[e]);
        s[2 * e + 1] += bf_hi(x[e]);
      }
    }
#pragma unroll
    for (int st = 0; st < 2; st++) {
      const bool up = (lane >> (st + 3)) & 1;
#pragma unroll
      for (int e = 0; e < (4 >> st); e++) {
        const float keep = up ? s[e + (4 >> st)] : s[e], give = up ? s[e] : s[e + (4 >> st)];
        s[e] = keep + __shfl_xor_sync(0xffffffffu, give, 8 << st);
      }
    }
    const uint32_t dst = slots + 6 * UNIT + ((wwarp * 3 + p) * 64 + (lane & 7) * 8 + ((lane >> 3) & 1) * 4 + (lane >> 4) * 2) * 4;
    sts32(dst, __float_as_uint(s[0]));
    sts32(dst + 4, __float_as_uint(s[1]));
  }
  named_bar_sync(6, 128);
  if (tid < 64) {
    float r[3] = {0.f, 0.f, 0.f};
#pragma unroll
    for (int e = 0; e < 12; e++) r[e % 3] += __uint_as_float(lds32(slots + 6 * UNIT + (e * 64 + tid) * 4));
    st_rec(&g_cs[ty][hp][qr][tid], r[0], r[1], r[2], ep1);
  }
  named_bar_sync(6, 128);
}

__device__ __forceinline__ void put_colsums(int ty, int col, const float4& s) {
  const float v[3] = {s.x, s.y, s.z};
#pragma unroll
  for (int p = 0; p < 3; p++) {
    const uint32_t a = SBASE + OFF_CS + (p * 8 + (col >> 3)) * 64 + ty * 32 + (col & 7) * 2;
    const float hi = bf16_round(v[p]);
    const uint32_t w = pack_bf16x2(hi, v[p] - hi);
    asm volatile("st.shared.b16 [%0], %1;" ::"r"(a), "h"((unsigned short)w) : "memory");
    asm volatile("st.shared.b16 [%0], %1;" ::"r"(a + 16), "h"((unsigned short)(w >> 16)) : "memory");
  }
}

__device__ __forceinline__ uint32_t ln_params(float s1, float s2) {
  const float mean = s1 * (1.0f / DM);
  const float var = fmaxf(fmaf(-mean, mean, s2 * (1.0f / DM)), 0.f);
  float sd;
  asm("sqrt.approx.f32 %0, %1;" : "=f"(sd) : "f"(bf16_round(bf16_round(var) + 1e-5f)));
  return pack_bf16x2(mean, sd);
}

struct RingProd {
  uint32_t rel = ((B_QF << 1) | 1) * 0x01010101u + 0x06040200u;
  int st = 0;
  __device__ __forceinline__ uint32_t next(uint32_t bar, uint32_t par, bool wait) {
    const uint32_t e = (rel >> (8 * st)) & 255u, a = SBASE + st * 5 * UNIT;
    if (wait) mbar_wait(SBASE + OFF_BAR + 8u * B_E + 8u * (e >> 1), e & 1u);
    rel ^= (e ^ ((bar << 1) | par)) << (8 * st);
    st = (st + 1) & 3;
    return a;
  }
};

#define SP1 15
#define SP2 14
#define SP3 12
#define SP4 12
#define SP5 15
#define SP6 14
#define SP7 16
__device__ __forceinline__ int q_split(int inst) {
  constexpr uint32_t T = 15u | ((SP1 - 1) << 4) | ((SP2 - 1) << 8) | ((SP3 - 1) << 12) | ((SP4 - 1) << 16) | ((SP5 - 1) << 20) |
                         ((SP6 - 1) << 24) | ((uint32_t)(SP7 - 1) << 28);
  return (int)((T >> (4 * inst)) & 15u) + 1;
}
__host__ __device__ constexpr uint32_t turn_par(int kind) {
  const int sp[8] = {16, SP1, SP2, SP3, SP4, SP5, SP6, SP7};
  int cnt[2] = {0, 0};
  uint32_t m = 0;
  for (int i = 0; i < 8; i++)
    for (int k = 0; k < 3; k++) {
      if (k == kind) m |= (uint32_t)(cnt[i & 1] & 1) << i;
      if (k == 0 ? (i == 1 || (i > 1 && sp[i - 1] < 16)) : (k == 2 || sp[i] < 16)) cnt[i & 1]++;
    }
  return m;
}
#define PREMASK 0xBDu
__device__ __forceinline__ bool w_pre(int inst) { return (PREMASK >> inst) & 1u; }
__global__ void __launch_bounds__(512, 1) fused_kernel(const __grid_constant__ Params P) {
  extern __shared__ __align__(1024) uint8_t smem_raw[];
  constexpr uint32_t base = SBASE, bars = base + OFF_BAR, slots = base + OFF_SLOT;
  if (smem_u32(smem_raw) != base) __trap();
  const int warp = __shfl_sync(0xffffffffu, threadIdx.x >> 5, 0), lane = threadIdx.x & 31;
  const int b = blockIdx.x;
#define QS 0
#define WS 1
  const int qr = ((b & ((8 << QS) - 1)) >> QS) ^ (((b >> (3 + QS)) & 1) * 7);
  const int hp = ((b >> (3 + QS)) << QS) + (b & ((1 << QS) - 1));
  const int rt = ((b & ((16 << WS) - 1)) >> WS) ^ (((b >> (4 + WS)) & 1) * 15);
  const int ct = ((b >> (4 + WS)) << WS) + (b & ((1 << WS) - 1));

  if (warp == 12) {
    if (elect_one()) {
#pragma unroll
      for (int s = 0; s < 4; s++) {
        mbar_init(bars + 8u * (B_QF + s), 2);
        mbar_init(bars + 8u * (B_QF + B_E + s), 4);
      }
      mbar_init(bars + 8u * B_GO, 1);
      fence_barrier_init();
    }
    __syncwarp();
    named_bar_arrive(0, 512);
  }
  if (threadIdx.x == 0) {
    for (int s = B_WF; s <= B_RF; s++) {
      mbar_init(bars + 8u * s, s == B_RF ? 1 : 2);
      mbar_init(bars + 8u * (s + B_E), 4);
    }
    mbar_init(bars + 8u * B_PREP, 1);
    mbar_init(bars + 8u * (B_PREP + 1), 1);
    mbar_init(bars + 8u * B_HL, 1);
    mbar_init(bars + 8u * (B_HL + 1), 1);
    mbar_init(bars + 8u * B_HV, 1);
    for (int s = 0; s < 4; s++) mbar_init(bars + 8u * (B_HALO + s), 1);
    for (int s = 0; s < 3; s++) mbar_init(bars + 8u * (B_REL + s), s == 0 ? 4 : 8);
    mbar_init(bars + 8u * B_LOC, 4);
    mbar_init(bars + 8u * B_AFREE, 2);
    mbar_init(bars + 8u * B_TURN, 4);
    mbar_init(bars + 8u * (B_TURN + 1), 4);
    mbar_init(bars + 8u * B_CS, 1);
    mbar_init(bars + 8u * B_PRE, 1);
    mbar_init(bars + 8u * B_PRE2, 1);
    mbar_init(bars + 8u * B_RDONE, 4);
    mbar_init(bars + 8u * B_CSD, 4);
    mbar_init(bars + 8u * B_XRDY, 1);
    mbar_init(bars + 8u * (B_XRDY + 1), 1);
    fence_barrier_init();
  }
  if (warp != 12) named_bar_sync(0, 512);

  if (warp >= 12) {
    setmaxnreg_dec<32>();
    if (warp == 12) {
      if (elect_one()) {
#pragma unroll 1
        for (int s = 0; s < 16; s++) {
          const uint32_t fb = bars + 8u * (B_QF + (s & 3)), sa = base + (s & 3) * 5 * UNIT;
          if (s >= 4) mbar_wait(fb + 8u * B_E, ((s >> 2) & 1) ^ 1);
          mbar_expect_tx(fb, 5 * UNIT);
          mbar_arrive(fb);
          tma_load_5d(sa, &P.xq[0], fb, s * 64, qr * 2);
          tma_load_3d(sa + 2 * UNIT, &P.wqkv3[0], fb, hp * 64, s * 64);
        }
        mbar_arrive(bars + 8u * B_GO);
        RingProd rp;
#pragma unroll 1
        for (int sg = 4; sg < 34; sg++) {
          const int part = sg & 3, inst = (sg >> 2) - (part & 1);
          if (part == 3 || inst == 8) continue;
          const int ty = (inst >> 1) & 1;
          if (part != 1) {
            const int k0 = part ? q_split(inst) : 0, k1 = part ? 16 : q_split(inst);
#pragma unroll 1
            for (int kt = k0; kt < k1; kt++) {
              const uint32_t sa = rp.next(B_QF + (kt & 3), (kt >> 2) & 1, true), fb = bars + 8u * (B_QF + (kt & 3));
              mbar_expect_tx(fb, 3 * UNIT);
              tma_load_3d(sa + 2 * UNIT, &P.wqkv3[ty], fb, hp * 64, kt * 64);
            }
          } else {
            const bool pre = w_pre(inst);
            const int lag = pre ? 8 : 5;
            uint32_t sa = 0;
#pragma unroll 1
            for (int kt = 0; kt < 16; kt++) {
              const int i = kt & 3;
              const uint32_t fb = bars + 8u * (B_WF + (kt & 7));
              if (i == 1) sa += 2 * UNIT;
              else if (i != 3 || !pre) sa = rp.next(kt == 14 ? B_RF : B_WF + ((kt | 1) & 7), kt == 14 ? inst & 1 : kt >> 3, kt < lag) + ((0x21 >> (2 * i)) & 3) * UNIT;
              if (kt >= lag) mbar_wait(bars + 8u * (B_WF + B_E + ((kt - lag) & 7)), (kt - lag) >> 3);
              if (i == 3 && pre) {
                mbar_arrive(fb);
              } else {
                mbar_expect_tx(fb, 2 * UNIT);
                tma_load_3d(sa, &P.wo3[ty], fb, ct * 128, kt * 64);
              }
            }
          }
        }
      }
    } else if (warp == 13) {
      RingProd rp;
      unsigned ep1 = 0;
      mbar_wait(bars + 8u * B_GO, 0);
#pragma unroll 1
      for (int sg = 4; sg < 34; sg++) {
        const int part = sg & 3, inst = (sg >> 2) - (part & 1);
        if (part == 3 || inst == 8) continue;
        const int L = inst >> 1, ch = inst & 1;
        uint32_t seen = 0;
        if (part != 1) {
          const CUtensorMap* tx = &P.xq[L];
          const int k0 = part ? q_split(inst) : 0, k1 = part ? 16 : q_split(inst);
          if (L == 0 || mbar_test(bars + 8u * (B_XRDY + ch), (L & 1) ^ 1)) {
            seen = 0xFFFFFFFFu;
            fence_proxy_async_all();
          }
          if (sg == 4) ep1 = launch_epoch();
          const int m0 = ch * 16 + qr * 2;
#pragma unroll 1
          for (int kt = k0; kt < k1; kt++) {
            wait_count(g_fx[ch * 8 + qr], 6u * ep1 - 6u + 2u * L, kt, seen, lane);
            TGET(t38);
            const uint32_t sa = rp.next(B_QF + (kt & 3), (kt >> 2) & 1, true);
            TGET(t39);
            if (elect_one()) {
              const uint32_t fb = bars + 8u * (B_QF + (kt & 3));
              mbar_expect_tx(fb, 2 * UNIT);
              tma_load_5d(sa, tx, fb, kt * 64, m0);
            }
            if (L == 3 && kt == 0 && lane == 0) { TPUT(ch, 38, t38); TPUT(ch, 39, t39); }
          }
        } else {
          const int m0 = ch * 1024 + rt * 64;
          const bool pre = w_pre(inst);
          const int lag = pre ? 8 : 5;
          uint32_t sa = 0;
#pragma unroll 1
          for (int kt = 0; kt < 16; kt++) {
            const int i = kt & 3;
            const uint32_t fb = bars + 8u * (B_WF + (kt & 7));
            wait_count(g_fo[ch * 16 + rt], 4u * ep1 - 3u + L, kt, seen, lane);
            if (i < 2) sa = rp.next(kt == 13 ? B_RF : B_WF + (kt & 7) + i + 1, kt == 13 ? inst & 1 : kt >> 3, kt < lag);
            else sa += (2 * i - 3) * UNIT;
            if (kt >= lag) mbar_wait(bars + 8u * (B_WF + B_E + ((kt - lag) & 7)), (kt - lag) >> 3);
            if (elect_one()) {
              mbar_expect_tx(fb, UNIT);
              tma_load_2d(sa, &P.o, fb, kt * 64, m0);
            }
            if (i == 3 && !pre) rp.next(B_WF + (kt & 7), kt >> 3, false);
          }
        }
      }
    } else if (warp == 14) {
      const unsigned ep1 = launch_epoch();
      uint32_t hpar = 0;
#pragma unroll 1
      for (int inst = 0; inst < 8; inst++) {
        const int L = inst >> 1, ch = inst & 1, gb = ch * 8 + qr;
        named_bar_sync(3, 160);
        if ((L & 1) == 0) {
          uint8_t* img = g_kvA[L >> 1][gb][hp][0];
          if (elect_one()) {
            bulk_store(img + 16384, slots + 16384, 16384);
            bulk_commit();
          }
          const uint32_t toff = lane * 128 + ((lane & 7) << 4);
          auto fresh = [&](const uint8_t* p) { return ((ld_relaxed_u32(p - 16) ^ ep1) & 1u) == 0u; };
          auto load = [&](uint32_t dst, const uint8_t* src, uint32_t bytes, uint32_t bar) {
            fence_proxy_async_all();
            if (elect_one()) {
              mbar_expect_tx(bar, bytes);
              bulk_load(dst, src, bytes, bar);
            }
          };
          {
            const uint8_t* src = gb > 0 ? img - 16 * 32768 + 16384 : g_zero;
            int go = -1;
            bool pub = false;
#pragma unroll 1
            for (uint32_t it = 0; it < (1u << 20) && !(go == 2 && pub); ++it) {
              if (go < 0) {
                if (gb == 0 || fresh(src + 8192)) {
                  load(slots + 32768, src, 8192, bars + 8u * B_HL);
                  __nanosleep(VSLEEP);
                  load(slots + 32768 + 8192, src + 8192, 8192, bars + 8u * B_HL + 8u);
                  go = 0;
                }
              } else if (go < 2 && mbar_test(bars + 8u * B_HL + 8u * go, (hpar >> go) & 1u)) {
                hpar ^= 1u << go;
                const uint32_t dst = slots + 32768 + go * 8192;
                uint32_t t = (lds32(dst + toff) ^ ep1) | (lds32(dst + toff + 4096) ^ ep1);
                if (gb == 0 || !__any_sync(0xffffffffu, t & 1u)) {
                  if (lane == 0) mbar_arrive(bars + 8u * (go ? B_HV : B_HALO));
                  go++;
                } else {
                  fence_proxy_async_smem();
                  load(dst, src + go * 8192, 8192, bars + 8u * B_HL + 8u * go);
                }
              }
              if (!pub && mbar_test(bars + 8u * B_LOC, inst & 1)) {
                pub = true;
                if (elect_one()) {
                  bulk_store(img, slots, 16384);
                  bulk_commit();
                }
              }
            }
          }
#pragma unroll 1
          for (int n = 1; n < 4; n++) {
            const bool real = gb > (n >> 1);
            const uint8_t* src = real ? img - ((n >> 1) + 1) * (16 * 32768) + (~n & 1) * 16384 : g_zero;
            const uint32_t dst = slots + (n == 3 ? 2 : 2 - n) * 16384;
#pragma unroll 1
            for (uint32_t it = 0; it < (1u << 17); ++it)
              if (!real || fresh(src + 16384)) break;
            if (n == 1 && elect_one()) bulk_wait_read0();
            mbar_wait(bars + 8u * (B_REL - 1) + 8u * n, ch);
#pragma unroll 1
            for (int tries = 0; tries < 4096; tries++) {
              load(dst, src, 16384, bars + 8u * B_HL);
              mbar_wait(bars + 8u * B_HL, hpar & 1u);
              hpar ^= 1u;
              uint32_t t = 0;
#pragma unroll
              for (int k = 0; k < 4; k++) t |= lds32(dst + toff + k * 4096) ^ ep1;
              if (!real || !__any_sync(0xffffffffu, t & 1u)) break;
              fence_proxy_async_smem();
            }
            if (lane == 0) mbar_arrive(bars + 8u * B_HALO + 8u * n);
          }
        } else {
          uint8_t* img = g_kvB[L >> 1][gb][hp];
          if (elect_one()) {
            bulk_store(img, KB_ROW0 + 112 * 128, 2048);
            bulk_store(img + 2048, VB_ROW0 + 112 * 128, 2048);
            bulk_commit();
            bulk_wait_read0();
          }
          const uint8_t* src = gb >= 1 ? img - 16 * 4096 : g_zero;
#pragma unroll 1
          for (uint32_t it = 0; it < (1u << 17); ++it) {
            fence_proxy_async_all();
            if (elect_one()) {
              mbar_expect_tx(bars + 8u * B_HL, 4096);
              bulk_load(KB_ROW0 - 2048, src, 2048, bars + 8u * B_HL);
              bulk_load(VB_ROW0 - 2048, src + 2048, 2048, bars + 8u * B_HL);
            }
            mbar_wait(bars + 8u * B_HL, hpar & 1u);
            hpar ^= 1u;
            const uint32_t t = lds32((lane < 16 ? KB_ROW0 - 2048 : VB_ROW0 - 4096) + lane * 128 + ((lane & 7) << 4)) ^ ep1;
            if (gb == 0 || !__any_sync(0xffffffffu, t & 1u)) break;
            fence_proxy_async_smem();
          }
          if (lane == 0) mbar_arrive(bars + 8u * B_HALO);
        }
        if (elect_one()) {
          mbar_wait(bars + 8u * B_AFREE, inst & 1);
          mbar_expect_tx(bars + 8u * B_RF, 2 * UNIT);
          tma_load_2d(slots + 6 * UNIT, &P.x[L], bars + 8u * B_RF, ct * 128, ch * 1024 + rt * 64);
          tma_load_2d(slots + 7 * UNIT, &P.x[L], bars + 8u * B_RF, ct * 128 + 64, ch * 1024 + rt * 64);
          if (w_pre(inst)) {
            if (inst == 1) mbar_wait(bars + 8u * B_CSD, 0);
            mbar_expect_tx(bars + 8u * B_PRE, 6 * UNIT);
            mbar_expect_tx(bars + 8u * B_PRE2, 2 * UNIT);
#pragma unroll 1
            for (int j = 0; j < 4; j++) {
              __nanosleep(PRESLEEP);
              if (j == 3) mbar_wait(bars + 8u * B_RDONE, (inst & 1) ^ 1);
              tma_load_3d(slots + j * 2 * UNIT, &P.wo3[L & 1], bars + 8u * (j == 3 ? B_PRE2 : B_PRE), ct * 128, (4 * j + 3) * 64);
            }
          }
        }
        __syncwarp();
      }
    } else {
      const unsigned ep1 = launch_epoch();
      mbar_wait(bars + 8u * B_GO, 0);
#pragma unroll 1
      for (int i = 0; i < 20; i++) {
        const char* src = i < 4 ? reinterpret_cast<const char*>(P.wo_p[0]) + (size_t)b * 16384 + i * 4096
                                : (i < 16 ? reinterpret_cast<const char*>(P.wqkv_p[1]) + (size_t)b * 49152 + (i - 4) * 4096
                                          : reinterpret_cast<const char*>(P.wo_p[1]) + (size_t)b * 16384 + (i - 16) * 4096);
        asm volatile("prefetch.global.L2 [%0];" ::"l"(src + lane * 128));
        __nanosleep(TRICKLE);
      }
#pragma unroll 1
      for (int inst = 2; inst < 8; inst++) {
        const int L = inst >> 1, ch = inst & 1, gb = ch * 8 + qr;
        mbar_wait_lazy<200>(bars + 8u * (B_RF + B_E), inst & 1);
#pragma unroll 1
        for (int h = 0; h < 4; h++) {
          const float4* sp = &g_stats[L][0][gb * 128 + h * 32 + lane];
          const float4 s0 = sum_recs<4>(sp, S_LEN, ep1), s1 = sum_recs<4>(sp + 4 * S_LEN, S_LEN, ep1);
          sts32(base + OFF_RS + (ch * 128 + h * 32 + lane) * 4, ln_params(s0.x + s1.x, s0.y + s1.y));
        }
        if (lane == 0) mbar_arrive(bars + 8u * (B_XRDY + ch));
        if (inst == 2) {
          mbar_wait(bars + 8u * B_CSD, 0);
#pragma unroll 1
          for (int hf = 0; hf < 2; hf++) {
            const float4* cp = &g_cs[1][hp][0][hf * 32 + lane];
            const float4 s0 = sum_recs<4>(cp, 64, ep1), s1 = sum_recs<4>(cp + 4 * 64, 64, ep1);
            put_colsums(1, hf * 32 + lane, make_float4(s0.x + s1.x, s0.y + s1.y, s0.z + s1.z, 0.f));
          }
        }
        fence_proxy_async_smem();
        __syncwarp();
        if (lane == 0) mbar_arrive(bars + 8u * (B_PREP + ch));
      }
    }
  } else {
    const bool asst = warp >= 8;
    GTL(0);
    if (asst) {
      colsum_part(&P.wqkv[0], 0, qr, hp);
      if ((threadIdx.x & 127) < 4) mbar_arrive(bars + 8u * B_RDONE);
    } else if (warp >= 4) {
      PHASE_IDS
      {
        const unsigned ep1 = launch_epoch();
        const int row = b * 16 + (tid >> 3);
        const uint4* src = reinterpret_cast<const uint4*>(P.in_x + (size_t)row * DM) + (tid & 7);
        float s1 = 0.f, s2 = 0.f;
#pragma unroll 1
        for (int k = 0; k < 4; k++) {
          mbar_pace(bars + 8u * (B_QF + B_E + ((2 * k) & 3)), k >> 1);
          uint4 v[4];
#pragma unroll
          for (int j = 0; j < 4; j++) v[j] = __ldg(src + (k * 4 + j) * 8);
#pragma unroll
          for (int j = 0; j < 4; j++) {
            const uint32_t w[4] = {v[j].x, v[j].y, v[j].z, v[j].w};
#pragma unroll
            for (int e = 0; e < 4; e++) {
              const float x0 = bf_lo(w[e]), x1 = bf_hi(w[e]);
              s1 += x0 + x1;
              s2 = fmaf(x0, x0, fmaf(x1, x1, s2));
            }
          }
        }
#pragma unroll
        for (int o = 1; o < 8; o <<= 1) {
          s1 += __shfl_xor_sync(0xffffffffu, s1, o);
          s2 += __shfl_xor_sync(0xffffffffu, s2, o);
        }
        if ((tid & 7) == 0) st_rec(&g_stats[0][0][row], s1, s2, 0.f, ep1);
        if (tid == 0) sts32(base + OFF_EPOCH, ep1);
        if (tid < 64) {
          const float4 s0 = sum_recs<8>(&g_cs[0][hp][0][tid], 64, ep1);
          put_colsums(0, tid, s0);
        } else {
          put_colsums(1, tid - 64, make_float4(0.f, 0.f, 0.f, 0.f));
        }
#pragma unroll 1
        for (int cc = 0; cc < 2; cc++) {
          const float4 s0 = sum_recs<1>(&g_stats[0][0][(cc * 8 + qr) * 128 + tid], 0, ep1);
          sts32(base + OFF_RS + (cc * 128 + tid) * 4, ln_params(s0.x, s0.y));
        }
        fence_proxy_async_smem();
        named_bar_sync(2, 128);
        if (tid < 2) mbar_arrive(bars + 8u * (B_PREP + tid));
      }
    }
#pragma unroll 1
    for (int inst = asst ? 0 : warp >> 2; inst < 8; inst += asst ? 1 : 2) {
      const int L = inst >> 1, ch = inst & 1, gb = ch * 8 + qr;
      uint32_t q[2][2][4];
      if (asst) {
        setmaxnreg_dec<24>();
        named_bar_sync(4, 256);
        setmaxnreg_inc<128>();
        const uint32_t ra = q_row_addr(L & 1, 1, warp & 3, fresh_tid() & 31);
#pragma unroll
        for (int j = 0; j < 4; j++) ldmatrix_x4(q[j >> 1][j & 1], ra ^ (j << 5));
      } else {
      setmaxnreg_inc<224>();
      {
        float acc[2][96];
        const int ksp = q_split(inst);
        constexpr uint32_t STG = 5 * (UNIT >> 4), D0 = (base >> 4) + 0x10000u;
        constexpr uint32_t DB = ((UNIT >> 4) << 16) - 0x10000u + 2 * (UNIT >> 4);
        uint32_t sd = D0;
        uint32_t tand = 1u, tor = 0u, tw = 0u;
        const uint32_t toff = ((fresh_tid() & 127) << 7) + ((fresh_tid() & 7) << 4);
        bool lane0 = (toff & 0xf80u) == 0u;
        if (inst == 1 || (inst > 1 && q_split(inst - 1) < 16)) mbar_wait_lazy<100>(bars + 8u * (B_TURN + ch), (turn_par(0) >> inst) & 1u);
        if (L == 3) GTL(37);
        mbar_wait(bars + 8u * B_QF, 0);
        GTL(1 + L * 8);
        {
          const uint64_t da = desc_lo(sd) + P.zero;
          wgmma_fence();
          wgmma_n192_ssz_ta0_tb1(acc[1], da + (UNIT >> 4), da + DB);
          wgmma_commit();
          wgmma_n192_ssz_ta0_tb1(acc[0], da, da + DB);
          wgmma_commit();
        }
#pragma unroll 1
        for (int kt = 0; kt < 15; kt++) {
          const bool last = kt + 1 == ksp;
          const uint64_t da = desc_lo(sd) + P.zero;
          const uint32_t fn = bars + 8u * (B_QF + ((kt + 1) & 3)), pn = ((kt + 1) >> 2) & 1;
#pragma unroll
          for (int k16 = 0; k16 < 4; k16++) {
            if (k16 == 0 && kt == 0) continue;
            wgmma_fence();
            wgmma_n192_ss_ta0_tb1(acc[1], da + ((UNIT >> 4) + k16 * 2), da + (DB + k16 * 128), 1);
            wgmma_commit();
            wgmma_wait<1>();
            if (k16 == 0 && lane0 && kt != ksp) mbar_arrive(bars + 8u * (B_QF + B_E + ((kt - 1) & 3)));
            wgmma_fence();
            wgmma_n192_ss_ta0_tb1(acc[0], da + k16 * 2, da + (DB + k16 * 128), 1);
            wgmma_commit();
            if (k16 == 1) tw = lds32(((sd & 0xffffu) << 4) + toff);
            if (k16 == 2) {
              tand &= tw;
              tor |= tw;
            }
            bool ok = true;
            if (k16 == 2) ok = mbar_test(fn, pn) || last;
            if (k16 == QTURN && last && lane0) mbar_arrive(bars + 8u * (B_TURN + (ch ^ 1)));
            if (k16 < 3) wgmma_wait<1>();
            if (k16 == 2 && !ok) mbar_wait(fn, pn);
          }
          sd = sd == D0 + 3 * STG ? D0 : sd + STG;
          if (last) {
            wgmma_wait<0>();
            if (lane0) mbar_arrive(bars + 8u * (B_QF + B_E + (kt & 3)));
            mbar_wait_lazy<100>(bars + 8u * (B_TURN + ch), (turn_par(1) >> inst) & 1u);
            mbar_wait(fn, pn);
          }
        }
        PHASE_IDS_W
        lane0 = lane == 0;
        constexpr uint32_t DL = D0 + 3 * STG;
        wgmma_fence();
#pragma unroll
        for (int k16 = 0; k16 < 4; k16++) wgmma_n192_ss_ta0_tb1(acc[1], desc_lo(DL + (UNIT >> 4) + k16 * 2), desc_lo(DL + DB + k16 * 128), 1);
        wgmma_commit();
        tw = lds32(((DL & 0xffffu) << 4) + toff);
        mbar_wait(bars + 8u * (B_PREP + ch), L & 1);
        const uint32_t rsa = base + OFF_RS + (ch * 128 + tile_row(L & 1, wwarp, 0, g)) * 4, rsd = (L & 1) ? 32 : 128;
        uint32_t rs[2][2];
        const uint32_t ep1 = __shfl_sync(0xffffffffu, lds32(base + OFF_EPOCH), 0);
        constexpr uint64_t DCS = (uint64_t)((base + OFF_CS) >> 4) | (4ull << 32);
        auto ln_mma = [&](float (&d)[96], uint32_t (&r)[2], int h) {
          uint32_t a[4];
#pragma unroll
          for (int i = 0; i < 2; i++) {
            r[i] = lds32(rsa + h * 256 + i * rsd);
            a[i] = c == (L & 1) ? __byte_perm(r[i], 0u, 0x1010) ^ 0x80008000u : 0u;
            a[i + 2] = r[i] & P.zero;
          }
#pragma unroll
          for (int i = 0; i < 4; i++) asm volatile("" : "+r"(a[i]));
          wgmma_fence();
          wgmma_n192_rs_tb1(d, a, DCS, 1);
          wgmma_commit();
        };
        wgmma_wait<1>();
        if (lane0 && ksp != 15) mbar_arrive(bars + 8u * (B_QF + B_E + 2));
        ln_mma(acc[1], rs[1], 1);
#pragma unroll
        for (int k16 = 0; k16 < 4; k16++) wgmma_n192_ss_ta0_tb1(acc[0], desc_lo(DL + k16 * 2), desc_lo(DL + DB + k16 * 128), 1);
        wgmma_commit();
        tand &= tw;
        tor |= tw;
        const bool redo = named_bar_or(1 + ch, 128, L > 0 && (((x_tag(ep1, L) ? ~tand : tor) & 1u) != 0u));
        if (ksp < 16) mbar_wait(bars + 8u * (B_WF + B_E + 7), 1);
        const bool afree = mbar_test(bars + 8u * B_RDONE, inst & 1);
        float rinv[2];
#pragma unroll
        for (int r = 0; r < 2; r++) rinv[r] = rcp_fast(bf_hi(rs[1][r]));
        const uint32_t soff = tile_row(L & 1, wwarp, (lane >> 3) & 1, lane & 7) * 128 + (((lane >> 4) ^ (lane & 7)) << 4);
        const uint32_t kdst = ((L & 1) ? KB_ROW0 : slots) + soff, vdst = ((L & 1) ? VB_ROW0 : slots + 8192) + soff;
        const uint32_t hs = (L & 1) ? 8192 : 16384;
        wgmma_wait<1>();
        if (lane0) mbar_arrive(bars + 8u * (B_TURN + (ch ^ 1)));
        if (redo) {
          wgmma_wait<0>();
          constexpr uint32_t sa = (DL & 0xffffu) << 4;
          const uint32_t rb = bars + 8u * (B_REDO + ch);
          if (toff == 0) {
            mbar_init(rb, 1);
            fence_barrier_init();
          }
          uint32_t rpar = 0;
#pragma unroll 1
          for (int kt = 0, tries = 0; kt < 16;) {
            fence_proxy_async_smem();
            named_bar_sync(1 + ch, 128);
            if ((warp & 3) == 0 && elect_one()) {
              fence_proxy_async_all();
              mbar_expect_tx(rb, 5 * UNIT);
              tma_load_5d(sa, &P.xq[L], rb, kt * 64, gb * 2);
              tma_load_3d(sa + 2 * UNIT, &P.wqkv3[L & 1], rb, hp * 64, kt * 64);
            }
            mbar_wait(rb, rpar);
            rpar ^= 1u;
            if (named_bar_or(1 + ch, 128, (lds32(sa + toff) ^ x_tag(ep1, L)) & 1u) && ++tries < 4096) continue;
            wgmma_fence();
#pragma unroll
            for (int k16 = 0; k16 < 4; k16++) {
              const uint64_t db = make_desc(sa + 2 * UNIT + k16 * 2048, UNIT);
              wgmma_n192_ss_ta0_tb1(acc[1], make_desc(sa + UNIT + k16 * 32, 16), db, kt | k16);
              wgmma_n192_ss_ta0_tb1(acc[0], make_desc(sa + k16 * 32, 16), db, kt | k16);
            }
            wgmma_commit();
            wgmma_wait<0>();
            kt++;
          }
          ln_mma(acc[1], rs[1], 1);
          wgmma_wait<0>();
        }
        ln_mma(acc[0], rs[0], 0);
        reg_fence<96>(acc[1]);
        GTL(2 + L * 8);
        if (!afree) mbar_wait(bars + 8u * B_RDONE, inst & 1);
#pragma unroll
        for (int t = 0; t < 24; t++) {
          const int h = t < 12 ? 1 : 0, p = ((t % 12) / 4 + 1) % 3, jp = t & 3;
          if (t == QREL) {
            wgmma_wait<0>();
            reg_fence<96>(acc[0]);
            if (lane0) mbar_arrive(bars + 8u * (B_QF + B_E + 3));
          }
          if (t == 8 || t == 20) {
            rinv[0] *= SM_C;
            rinv[1] *= SM_C;
          }
          const float* a = &acc[h][4 * (p * 8 + 2 * jp)];
          uint32_t r0 = pack_bf16x2(a[0] * rinv[0], a[1] * rinv[0]);
          uint32_t r1 = pack_bf16x2(a[2] * rinv[1], a[3] * rinv[1]);
          if (p != 0 && jp == 0) {
            r0 = set_tag(r0, c == 0, ep1);
            r1 = set_tag(r1, c == 0, ep1);
          }
          const uint32_t r2 = pack_bf16x2(a[4] * rinv[0], a[5] * rinv[0]);
          const uint32_t r3 = pack_bf16x2(a[6] * rinv[1], a[7] * rinv[1]);
          const uint32_t dst = p == 0 ? slots + 3 * 16384 + soff + h * 8192 : (p == 1 ? kdst : vdst) + h * hs;
          stmatrix_x4(dst ^ (jp << 5), r0, r1, r2, r3);
          if (t >= 20) {
            q[jp >> 1][jp & 1][0] = r0;
            q[jp >> 1][jp & 1][1] = r1;
            q[jp >> 1][jp & 1][2] = r2;
            q[jp >> 1][jp & 1][3] = r3;
          }
          if (t == 7 || t == 19) {
            fence_proxy_async_smem();
            if (t == 7) {
              named_bar_arrive(3, 160);
            } else {
              __syncwarp();
              if (lane0) mbar_arrive(bars + 8u * B_LOC);
            }
          }
          if (t == 11) {
            setmaxnreg_dec<128>();
            named_bar_arrive(4, 256);
#pragma unroll
            for (int r = 0; r < 2; r++) rinv[r] = rcp_fast(bf_hi(rs[0][r]));
          }
        }
        mbar_wait(bars + 8u * B_LOC, inst & 1);
      }
      }
      GTL(3 + L * 8);
      if ((L & 1) == 0) attention_a(q, asst, L, gb, hp, ch, warp & 3, P.zero);
      else attention_b(q, asst, gb, inst & 1, warp & 3);
      GTL(4 + L * 8);
      fence_proxy_async_smem();
      named_bar_sync(asst ? 6 : 1 + ch, 128);
      if ((warp & 3) == 0) {
        if (elect_one()) {
          tma_store_2d(&P.o, slots + 3 * 16384 + asst * 8192, hp * 64, gb * 128 + asst * 64);
          bulk_commit();
          bulk_wait0();
          red_announce(&g_fo[gb * 2 + asst][hp]);
          mbar_arrive(bars + 8u * B_AFREE);
        }
        __syncwarp();
      }
      if (asst) {
        if (inst == 1) {
          mbar_wait(bars + 8u * B_RDONE, 0);
          colsum_part(&P.wqkv[1], 1, qr, hp);
          if ((fresh_tid() & 31) == 0) mbar_arrive(bars + 8u * B_CSD);
        }
        continue;
      }
      GTL(5 + L * 8);

      {
        float acc[64];
        const int sp = inst < 7 ? q_split(inst + 1) : 0;
        int st = sp & 3;
        const bool pre = w_pre(inst);
        uint32_t tbad = 0u;
        const uint32_t toff = ((fresh_tid() & 63) << 7) + ((fresh_tid() & 7) << 4);
        const bool lane0 = (toff & 0xf80u) == 0u;
        constexpr uint32_t U4 = UNIT >> 4, LA = 0x10000u, LB = U4 << 16;
        reg_define<64>(acc);
        reg_fence<64>(acc);
        uint32_t xv[8][4];
        {
          PHASE_IDS_W
          const uint32_t xr = slots + 6 * UNIT + (wwarp * 16 + (lane & 15)) * 128 + (((lane >> 4) ^ (lane & 7)) << 4);
          mbar_wait(bars + 8u * B_RF, inst & 1);
#pragma unroll
          for (int jp = 0; jp < 8; jp++) ldmatrix_x4(xv[jp], (xr ^ ((jp & 3) << 5)) + (jp >> 2) * UNIT);
          fence_proxy_async_smem();
          __syncwarp();
          if (lane0) mbar_arrive(bars + 8u * B_RDONE);
          if (L > 0) {
            uint32_t lsb;
            asm volatile("ld.shared.u8 %0, [%1];" : "=r"(lsb) : "r"(base + OFF_LSB + ch * 32 + wwarp * 8 + g) : "memory");
#pragma unroll
            for (int k = 0; k < 4; k++) xv[(k >> 1) * 4][k & 1] = set_tag(xv[(k >> 1) * 4][k & 1], c == 0, lsb >> k);
          }
        }
        uint64_t d0 = desc_lo((base >> 4) + st * 5 * U4) + P.zero;
        if (inst < 7 || SP7 == 16) mbar_wait_lazy<100>(bars + 8u * (B_TURN + ch), (turn_par(2) >> inst) & 1u);
        mbar_wait(bars + 8u * B_WF, 0);
        GTL(6 + L * 8);
        uint32_t s1 = 0;
#pragma unroll 1
        for (int m = 0; m < 4; m++) {
          const uint32_t s0 = base + st * 5 * UNIT, fb = bars + 8u * (B_WF + 4 * (m & 1));
          s1 = base + ((st + 1) & 3) * 5 * UNIT;
          const uint64_t d1 = desc_lo(s1 >> 4) + P.zero;
          const uint64_t d2 = desc_lo((pre ? slots + m * 2 * UNIT : base + ((st + 2) & 3) * 5 * UNIT) >> 4) + P.zero;
          st = (st + (pre ? 2 : 3)) & 3;
#pragma unroll
          for (int i = 0; i < 4; i++) {
            const uint64_t da = (i == 0 ? d0 : d1) + (LA + (i == 2 ? 1 : (i == 3 ? 4 : 0)) * U4);
            const uint64_t db = (i < 2 ? d0 : (i == 2 ? d1 : d2)) + (LB + (i == 0 ? 1 : (i == 1 ? 3 : (i == 2 ? 2 : 0))) * U4);
            if (i == 3 && (m == 0 || m == 3) && pre) mbar_wait(bars + 8u * (m ? B_PRE2 : B_PRE), __popc(PREMASK & ((1u << inst) - 1u)) & 1);
            if (i == (WTURN & 3) && m == 3 && lane0 && (sp < 16 || inst == 6)) mbar_arrive(bars + 8u * (B_TURN + (ch ^ 1)));
            wgmma_fence();
#pragma unroll
            for (int k16 = 0; k16 < 4; k16++) wgmma_n128_ss_ta0_tb1(acc, da + 2 * k16, db + 128 * k16, 1);
            wgmma_commit();
            if (i == 2) d0 = desc_lo((base >> 4) + st * 5 * U4) + P.zero;
            tbad |= lds32((i == 0 ? s0 : s1) + (i == 2 ? 1 : (i == 3 ? 4 : 0)) * UNIT + toff) ^ o_tag(L);
            const uint32_t fn = i < 3 ? fb + 8u * (i + 1) : fb ^ 96u;
            const uint32_t pn = i < 3 ? m >> 1 : m > 0;
            const bool ok = mbar_test(fn, pn) || (i == 3 && m == 3);
            wgmma_wait<1>();
            if (lane0 && (i > 0 || m > 0)) mbar_arrive((i > 0 ? fb + 8u * (i - 1) : (fb ^ 96u) + 24u) + 8u * B_E);
            if (!ok) mbar_wait(fn, pn);
          }
        }
        const uint32_t xb = s1;
        const bool redo = named_bar_or(1 + ch, 128, tbad & 1u);
        if (redo) {
          wgmma_wait<0>();
          const uint32_t sa = s1 + 4 * UNIT, sb = s1 + 2 * UNIT;
          const uint32_t rb = bars + 8u * (B_REDO + ch);
          if ((fresh_tid() & 127) == 0) {
            mbar_init(rb, 1);
            fence_barrier_init();
          }
          uint32_t rpar = 0;
#pragma unroll 1
          for (int kt = 0, tries = 0; kt < 16;) {
            fence_proxy_async_smem();
            named_bar_sync(1 + ch, 128);
            if ((warp & 3) == 0 && elect_one()) {
              fence_proxy_async_all();
              mbar_expect_tx(rb, 3 * UNIT);
              tma_load_2d(sa, &P.o, rb, kt * 64, ch * 1024 + rt * 64);
              tma_load_3d(sb, &P.wo3[L & 1], rb, ct * 128, kt * 64);
            }
            mbar_wait(rb, rpar);
            rpar ^= 1u;
            if (named_bar_or(1 + ch, 128, (lds32(sa + toff) ^ o_tag(L)) & 1u) && ++tries < 4096) continue;
            wgmma_fence();
#pragma unroll
            for (int k16 = 0; k16 < 4; k16++)
              wgmma_n128_ss_ta0_tb1(acc, make_desc(sa + k16 * 32, 16), make_desc(sb + k16 * 2048, UNIT), kt | k16);
            wgmma_commit();
            wgmma_wait<0>();
            kt++;
          }
        }
        PHASE_IDS_W
        const uint32_t xrow = xb + (wwarp * 16 + (lane & 15)) * 128 + (((lane >> 4) ^ (lane & 7)) << 4);
        const unsigned ep1 = __shfl_sync(0xffffffffu, lds32(base + OFF_EPOCH), 0);
        const uint32_t tm = c == 0, lsa = base + OFF_LSB + ch * 32 + wwarp * 8 + g;
        wgmma_wait<0>();
        reg_fence<64>(acc);
        if (lane0) mbar_arrive(bars + 8u * (B_WF + B_E + 7));
        GTL(7 + L * 8);
        const uint32_t tmx = L < 3 ? tm : 0u, xt = x_tag(ep1, L + 1);
        const int grow = ch * 1024 + rt * 64;
#pragma unroll
        for (int jp = 0; jp < 8; jp++) {
#pragma unroll
          for (int q = 0; q < 4; q++) xv[jp][q] = add_bf16x2(xv[jp][q], pack_bf16x2(acc[8 * jp + 2 * q], acc[8 * jp + 2 * q + 1]));
          const bool tg = (jp & 3) == 0;
          stmatrix_x4((xrow ^ ((jp & 3) << 5)) + (jp >> 2) * UNIT,
                      tg ? set_tag(xv[jp][0], tmx, xt) : xv[jp][0], tg ? set_tag(xv[jp][1], tmx, xt) : xv[jp][1], xv[jp][2], xv[jp][3]);
          if ((jp & 3) == 3) {
            fence_proxy_async_smem();
            if (wwarp == jp >> 2) {
              named_bar_sync(8 + 2 * ch + (jp >> 2), 128);
              if (elect_one()) {
                tma_store_2d(&P.x[L + 1], xb + (jp >> 2) * UNIT, ct * 128 + (jp >> 2) * 64, grow);
                bulk_commit();
              }
              __syncwarp();
            } else {
              named_bar_arrive(8 + 2 * ch + (jp >> 2), 128);
            }
            if (L == 2 && jp == 3) GTL(36);
          }
        }
        if (elect_one()) {
          bulk_wait0();
          if (L < 3 && wwarp < 2) red_announce(&g_fx[ch * 8 + (rt >> 1)][ct * 2 + wwarp]);
          mbar_arrive(bars + 8u * (B_RF + B_E));
        }
        __syncwarp();
        if (L < 3) {
          if (c == 0)
            asm volatile("st.shared.u8 [%0], %1;" ::"r"(lsa),
                         "r"((xv[0][0] & 1u) | ((xv[0][1] & 1u) << 1) | ((xv[4][0] & 1u) << 2) | ((xv[4][1] & 1u) << 3)) : "memory");
          float s1[2] = {0.f, 0.f}, s2[2] = {0.f, 0.f};
#pragma unroll
          for (int jp = 0; jp < 8; jp++)
#pragma unroll
            for (int q = 0; q < 4; q++) {
              const float x0 = bf_lo(xv[jp][q]), x1 = bf_hi(xv[jp][q]);
              s1[q & 1] += x0 + x1;
              s2[q & 1] = fmaf(x0, x0, fmaf(x1, x1, s2[q & 1]));
            }
#pragma unroll
          for (int r = 0; r < 2; r++) {
            s1[r] += __shfl_xor_sync(0xffffffffu, s1[r], 1);
            s2[r] += __shfl_xor_sync(0xffffffffu, s2[r], 1);
            s1[r] += __shfl_xor_sync(0xffffffffu, s1[r], 2);
            s2[r] += __shfl_xor_sync(0xffffffffu, s2[r], 2);
            if (c == 0) st_rec(&g_stats[L + 1][ct][grow + wwarp * 16 + g + 8 * r], s1[r], s2[r], 0.f, ep1);
          }
        }
        GTL(8 + L * 8);
      }
    }
    if (threadIdx.x == 128) atomicAdd(g_done, 1u);
  }
}

typedef CUresult (*PFN_tmEncode)(CUtensorMap*, CUtensorMapDataType, cuuint32_t, void*, const cuuint64_t*,
                                 const cuuint64_t*, const cuuint32_t*, const cuuint32_t*, CUtensorMapInterleave,
                                 CUtensorMapSwizzle, CUtensorMapL2promotion, CUtensorMapFloatOOBfill);

PFN_tmEncode get_encode_fn() {
  static PFN_tmEncode fn = nullptr;
  if (!fn) {
    cudaDriverEntryPointQueryResult qr;
    void* p = nullptr;
    cudaGetDriverEntryPoint("cuTensorMapEncodeTiled", &p, cudaEnableDefault, &qr);
    fn = (PFN_tmEncode)p;
  }
  return fn;
}

CUtensorMap make_map(const void* ptr, int rows, int cols) {
  CUtensorMap m;
  cuuint64_t gdim[2] = {(cuuint64_t)cols, (cuuint64_t)rows};
  cuuint64_t gstr[1] = {(cuuint64_t)cols * 2};
  cuuint32_t box[2] = {64, 64};
  cuuint32_t estr[2] = {1, 1};
  get_encode_fn()(&m, CU_TENSOR_MAP_DATA_TYPE_BFLOAT16, 2, const_cast<void*>(ptr), gdim, gstr, box, estr,
                  CU_TENSOR_MAP_INTERLEAVE_NONE, CU_TENSOR_MAP_SWIZZLE_128B, CU_TENSOR_MAP_L2_PROMOTION_L2_128B,
                  CU_TENSOR_MAP_FLOAT_OOB_FILL_NONE);
  return m;
}

CUtensorMap make_map3(const void* ptr, int rows, int cols, int n, int step) {
  CUtensorMap m;
  cuuint64_t gdim[3] = {(cuuint64_t)(cols - (n - 1) * step), (cuuint64_t)rows, (cuuint64_t)n};
  cuuint64_t gstr[2] = {(cuuint64_t)cols * 2, (cuuint64_t)step * 2};
  cuuint32_t box[3] = {64, 64, (cuuint32_t)n};
  cuuint32_t estr[3] = {1, 1, 1};
  get_encode_fn()(&m, CU_TENSOR_MAP_DATA_TYPE_BFLOAT16, 3, const_cast<void*>(ptr), gdim, gstr, box, estr,
                  CU_TENSOR_MAP_INTERLEAVE_NONE, CU_TENSOR_MAP_SWIZZLE_128B, CU_TENSOR_MAP_L2_PROMOTION_L2_128B,
                  CU_TENSOR_MAP_FLOAT_OOB_FILL_NONE);
  return m;
}

CUtensorMap make_map_q(const void* ptr, int sw, int sr) {
  CUtensorMap m;
  cuuint64_t gdim[5] = {DM, 8, 2, 4, S_LEN / 64};
  cuuint64_t gstr[4] = {DM * 2, (cuuint64_t)sr * DM * 2, (cuuint64_t)sw * DM * 2, 64 * DM * 2};
  cuuint32_t box[5] = {64, 8, 2, 4, 2};
  cuuint32_t estr[5] = {1, 1, 1, 1, 1};
  get_encode_fn()(&m, CU_TENSOR_MAP_DATA_TYPE_BFLOAT16, 5, const_cast<void*>(ptr), gdim, gstr, box, estr,
                  CU_TENSOR_MAP_INTERLEAVE_NONE, CU_TENSOR_MAP_SWIZZLE_128B, CU_TENSOR_MAP_L2_PROMOTION_L2_128B,
                  CU_TENSOR_MAP_FLOAT_OOB_FILL_NONE);
  return m;
}

}

extern "C" void kernel_launch(void* const* d_in, const int* in_sizes, int n_in, void* d_out, int out_size) {
  (void)in_sizes; (void)n_in; (void)out_size;
  void *p_o, *p_x;
  cudaGetSymbolAddress(&p_o, g_o);
  cudaGetSymbolAddress(&p_x, g_x);
  static bool attr_done = false;
  if (!attr_done) {
    cudaFuncSetAttribute(fused_kernel, cudaFuncAttributeMaxDynamicSharedMemorySize, SMEM_BYTES);
    attr_done = true;
  }
  Params P;
  P.in_x = (const __nv_bfloat16*)d_in[0];
  P.wqkv_p[0] = (const __nv_bfloat16*)d_in[1];
  P.wo_p[0] = (const __nv_bfloat16*)d_in[2];
  P.wqkv_p[1] = (const __nv_bfloat16*)d_in[4];
  P.wo_p[1] = (const __nv_bfloat16*)d_in[5];
  P.out = (__nv_bfloat16*)d_out;
  P.zero = 0;
  for (int L = 0; L < 5; L++) {
    const void* px = L == 0 ? (const void*)P.in_x : (L == 4 ? d_out : p_x);
    P.x[L] = make_map(px, S_LEN, DM);
    if (L < 4) P.xq[L] = (L & 1) ? make_map_q(px, 16, 8) : make_map_q(px, 8, 32);
  }
  P.o = make_map(p_o, S_LEN, DM);
  for (int t = 0; t < 2; t++) {
    P.wqkv[t] = make_map(P.wqkv_p[t], DM, NQKV);
    P.wqkv3[t] = make_map3(P.wqkv_p[t], DM, NQKV, 3, 1024);
    P.wo3[t] = make_map3(P.wo_p[t], DM, DM, 2, 64);
  }
  fused_kernel<<<NCTA, 512, SMEM_BYTES>>>(P);
}
```

```cpp
#include <cuda_runtime.h>
#include <cuda_bf16.h>
#include <cuda.h>
#include <stdint.h>

namespace {

constexpr int S_LEN = 2048;
constexpr int DM = 1024;
constexpr int NQKV = 3072;
constexpr int NCTA = 128;

__device__ __align__(1024) uint8_t g_kvA[2][16][16][2][16384];
__device__ __align__(1024) uint8_t g_kvB[2][16][16][4096];
__device__ __align__(1024) uint8_t g_zero[16384];
__device__ __align__(1024) __nv_bfloat16 g_o[S_LEN * DM];
__device__ __align__(1024) __nv_bfloat16 g_x[S_LEN * DM];
__device__ __align__(1024) float4 g_stats[4][8][S_LEN];
__device__ __align__(1024) float4 g_cs[2][16][8][64];
__device__ __align__(128) unsigned g_fx[16][32];
__device__ __align__(128) unsigned g_fo[32][32];
__device__ __align__(128) unsigned g_fk[16][16][4];
__device__ __align__(128) unsigned g_done[32];

constexpr uint32_t SBASE = 1024;
constexpr int UNIT = 8192;
constexpr int NUNITS = 20;
constexpr int OFF_SLOT = NUNITS * UNIT;
constexpr int OFF_BAR = OFF_SLOT + 4 * 16384;
constexpr int OFF_EPOCH = OFF_BAR + 424;
constexpr int OFF_LSB = OFF_BAR + 432;
constexpr int OFF_CS = OFF_BAR + 496;
constexpr int OFF_RS = OFF_CS + 1536;
constexpr int OFF_ONE = OFF_RS + 1024;
constexpr int SMEM_BYTES = OFF_ONE + 16;
constexpr int B_QF = 0, B_WF = 4, B_RF = 12, B_E = 13, B_PREP = 26, B_LOC = 28, B_HALO = 29, B_REL = 33, B_AFREE = 36,
              B_TURN = 37, B_XRDY = 39, B_CS = 41, B_CSD = 42, B_GO = 43, B_PRE = 44, B_HV = 45, B_REDO = 46,
              B_RDONE = 48, B_PRE2 = 49, B_HL = 50;
static_assert(SMEM_BYTES <= 232448, "shared memory");

__device__ __forceinline__ uint32_t smem_u32(const void* p) { return (uint32_t)__cvta_generic_to_shared(p); }

__device__ __forceinline__ void mbar_init(uint32_t bar, uint32_t cnt) {
  asm volatile("mbarrier.init.shared::cta.b64 [%0], %1;" ::"r"(bar), "r"(cnt));
}
__device__ __forceinline__ void mbar_expect_tx(uint32_t bar, uint32_t bytes) {
  asm volatile("mbarrier.arrive.expect_tx.shared::cta.b64 _, [%0], %1;" ::"r"(bar), "r"(bytes) : "memory");
}
__device__ __forceinline__ void mbar_arrive(uint32_t bar) {
  asm volatile("mbarrier.arrive.shared::cta.b64 _, [%0];" ::"r"(bar) : "memory");
}
__device__ __forceinline__ bool mbar_try_wait(uint32_t bar, uint32_t parity) {
  uint32_t ok;
  asm volatile(
      "{\n.reg .pred p;\nmbarrier.try_wait.parity.shared::cta.b64 p, [%1], %2;\nselp.b32 %0, 1, 0, p;\n}\n"
      : "=r"(ok)
      : "r"(bar), "r"(parity)
      : "memory");
  return ok != 0;
}
__device__ __forceinline__ bool mbar_test(uint32_t bar, uint32_t parity) {
  uint32_t ok;
  asm volatile(
      "{\n.reg .pred p;\nmbarrier.test_wait.parity.shared::cta.b64 p, [%1], %2;\nselp.b32 %0, 1, 0, p;\n}\n"
      : "=r"(ok)
      : "r"(bar), "r"(parity)
      : "memory");
  return ok != 0;
}
__device__ __forceinline__ void mbar_wait(uint32_t bar, uint32_t parity) {
#pragma unroll 1
  for (uint32_t it = 0; it < (1u << 18); ++it) {
    if (mbar_try_wait(bar, parity)) return;
  }
}
__device__ __forceinline__ void mbar_pace(uint32_t bar, uint32_t parity) {
#pragma unroll 1
  for (uint32_t it = 0; it < 24; ++it) {
    if (mbar_try_wait(bar, parity)) return;
  }
}
template <int NS>
__device__ __forceinline__ void mbar_wait_lazy(uint32_t bar, uint32_t parity) {
#pragma unroll 1
  for (uint32_t it = 0; it < (1u << 18); ++it) {
    if (mbar_try_wait(bar, parity)) return;
    __nanosleep(NS);
  }
}
__device__ __forceinline__ bool elect_one() {
  uint32_t ok;
  asm volatile("{\n.reg .pred p;\nelect.sync _|p, 0xffffffff;\nselp.b32 %0, 1, 0, p;\n}\n" : "=r"(ok));
  return ok != 0;
}
__device__ __forceinline__ void fence_barrier_init() { asm volatile("fence.mbarrier_init.release.cluster;" ::: "memory"); }
__device__ __forceinline__ void fence_proxy_async_smem() { asm volatile("fence.proxy.async.shared::cta;" ::: "memory"); }
__device__ __forceinline__ void fence_proxy_async_all() { asm volatile("" ::: "memory"); }

__device__ __forceinline__ void tma_load_2d(uint32_t dst, const CUtensorMap* map, uint32_t bar, int c0, int c1) {
  asm volatile(
      "cp.async.bulk.tensor.2d.shared::cluster.global.mbarrier::complete_tx::bytes [%0], [%1, {%3, %4}], [%2];" ::"r"(dst),
      "l"(map), "r"(bar), "r"(c0), "r"(c1)
      : "memory");
}
__device__ __forceinline__ void tma_load_3d(uint32_t dst, const CUtensorMap* map, uint32_t bar, int c0, int c1) {
  asm volatile(
      "cp.async.bulk.tensor.3d.shared::cluster.global.mbarrier::complete_tx::bytes [%0], [%1, {%3, %4, %5}], [%2];" ::"r"(dst),
      "l"(map), "r"(bar), "r"(c0), "r"(c1), "r"(0)
      : "memory");
}
__device__ __forceinline__ void tma_load_5d(uint32_t dst, const CUtensorMap* map, uint32_t bar, int c0, int c4) {
  asm volatile(
      "cp.async.bulk.tensor.5d.shared::cluster.global.mbarrier::complete_tx::bytes [%0], [%1, {%3, %5, %5, %5, %4}], [%2];" ::"r"(dst),
      "l"(map), "r"(bar), "r"(c0), "r"(c4), "r"(0)
      : "memory");
}
__device__ __forceinline__ void bulk_load(uint32_t dst, const void* src, uint32_t bytes, uint32_t bar) {
  asm volatile("cp.async.bulk.shared::cluster.global.mbarrier::complete_tx::bytes [%0], [%1], %2, [%3];" ::"r"(dst),
               "l"(src), "r"(bytes), "r"(bar)
               : "memory");
}
__device__ __forceinline__ void bulk_store(void* dst, uint32_t src, uint32_t bytes) {
  asm volatile("cp.async.bulk.global.shared::cta.bulk_group [%0], [%1], %2;" ::"l"(dst), "r"(src), "r"(bytes) : "memory");
}
__device__ __forceinline__ void tma_store_2d(const CUtensorMap* map, uint32_t src, int c0, int c1) {
  asm volatile("cp.async.bulk.tensor.2d.global.shared::cta.bulk_group [%0, {%2, %3}], [%1];" ::"l"(map), "r"(src),
               "r"(c0), "r"(c1)
               : "memory");
}
__device__ __forceinline__ void bulk_announce(unsigned* p) {
  asm volatile("cp.reduce.async.bulk.global.shared::cta.bulk_group.add.u32 [%0], [%1], 16;" ::"l"(p), "r"(SBASE + OFF_ONE) : "memory");
}
__device__ __forceinline__ void bulk_commit() { asm volatile("cp.async.bulk.commit_group;" ::: "memory"); }
__device__ __forceinline__ void bulk_wait_read0() { asm volatile("cp.async.bulk.wait_group.read 0;" ::: "memory"); }
__device__ __forceinline__ void bulk_wait0() { asm volatile("cp.async.bulk.wait_group 0;" ::: "memory"); }
__device__ __forceinline__ void named_bar_sync(int id, int nthreads) {
  asm volatile("bar.sync %0, %1;" ::"r"(id), "r"(nthreads) : "memory");
}
__device__ __forceinline__ void named_bar_arrive(int id, int nthreads) {
  asm volatile("bar.arrive %0, %1;" ::"r"(id), "r"(nthreads) : "memory");
}

__device__ __forceinline__ bool named_bar_or(int id, int nthreads, bool v) {
  uint32_t r;
  asm volatile("{\n.reg .pred p, q;\nsetp.ne.b32 q, %3, 0;\nbar.red.or.pred p, %1, %2, q;\nselp.b32 %0, 1, 0, p;\n}\n"
               : "=r"(r) : "r"(id), "r"(nthreads), "r"((int)v) : "memory");
  return __any_sync(0xffffffffu, r != 0);
}

__device__ __forceinline__ void wgmma_fence() { asm volatile("wgmma.fence.sync.aligned;\n" ::: "memory"); }
__device__ __forceinline__ void wgmma_commit() { asm volatile("wgmma.commit_group.sync.aligned;\n" ::: "memory"); }
template <int N>
__device__ __forceinline__ void wgmma_wait() {
  asm volatile("wgmma.wait_group.sync.aligned %0;\n" ::"n"(N) : "memory");
}
template <int R>
__device__ __forceinline__ void setmaxnreg_inc() { asm volatile("setmaxnreg.inc.sync.aligned.u32 %0;\n" ::"n"(R)); }
template <int R>
__device__ __forceinline__ void setmaxnreg_dec() { asm volatile("setmaxnreg.dec.sync.aligned.u32 %0;\n" ::"n"(R)); }
template <int N>
__device__ __forceinline__ void reg_fence(float* r) {
#pragma unroll
  for (int i = 0; i < N; i++) asm volatile("" : "+f"(r[i])::"memory");
}

template <int N>
__device__ __forceinline__ void reg_define(float* r) {
#pragma unroll
  for (int i = 0; i < N; i++) r[i] = 0.f;
}

__device__ __forceinline__ uint64_t desc_lo(uint32_t lo) {
  uint64_t d;
  asm("mov.b64 %0, {%1, %2};" : "=l"(d) : "r"(lo), "r"(0x40000040u));
  return d;
}
__device__ __forceinline__ uint64_t make_desc(uint32_t addr, uint32_t lbo_bytes) {
  return desc_lo((addr >> 4) + ((lbo_bytes >> 4) << 16));
}

__device__ __forceinline__ void wgmma_n192_ss_ta0_tb1(float* d, uint64_t descA, uint64_t descB, int scaleD) {
  asm volatile("{\n.reg .pred p;\nsetp.ne.b32 p, %98, 0;\n"
    "wgmma.mma_async.sync.aligned.m64n192k16.f32.bf16.bf16 {%0, %1, %2, %3, %4, %5, %6, %7, %8, %9, %10, %11, %12, %13, %14, %15, %16, %17, %18, %19, %20, %21, %22, %23, %24, %25, %26, %27, %28, %29, %30, %31, %32, %33, %34, %35, %36, %37, %38, %39, %40, %41, %42, %43, %44, %45, %46, %47, %48, %49, %50, %51, %52, %53, %54, %55, %56, %57, %58, %59, %60, %61, %62, %63, %64, %65, %66, %67, %68, %69, %70, %71, %72, %73, %74, %75, %76, %77, %78, %79, %80, %81, %82, %83, %84, %85, %86, %87, %88, %89, %90, %91, %92, %93, %94, %95}, %96, %97, p, 1, 1, 0, 1;\n}\n"
    : "+f"(d[0]), "+f"(d[1]), "+f"(d[2]), "+f"(d[3]), "+f"(d[4]), "+f"(d[5]), "+f"(d[6]), "+f"(d[7]), "+f"(d[8]), "+f"(d[9]), "+f"(d[10]), "+f"(d[11]), "+f"(d[12]), "+f"(d[13]), "+f"(d[14]), "+f"(d[15]), "+f"(d[16]), "+f"(d[17]), "+f"(d[18]), "+f"(d[19]), "+f"(d[20]), "+f"(d[21]), "+f"(d[22]), "+f"(d[23]), "+f"(d[24]), "+f"(d[25]), "+f"(d[26]), "+f"(d[27]), "+f"(d[28]), "+f"(d[29]), "+f"(d[30]), "+f"(d[31]), "+f"(d[32]), "+f"(d[33]), "+f"(d[34]), "+f"(d[35]), "+f"(d[36]), "+f"(d[37]), "+f"(d[38]), "+f"(d[39]), "+f"(d[40]), "+f"(d[41]), "+f"(d[42]), "+f"(d[43]), "+f"(d[44]), "+f"(d[45]), "+f"(d[46]), "+f"(d[47]), "+f"(d[48]), "+f"(d[49]), "+f"(d[50]), "+f"(d[51]), "+f"(d[52]), "+f"(d[53]), "+f"(d[54]), "+f"(d[55]), "+f"(d[56]), "+f"(d[57]), "+f"(d[58]), "+f"(d[59]), "+f"(d[60]), "+f"(d[61]), "+f"(d[62]), "+f"(d[63]), "+f"(d[64]), "+f"(d[65]), "+f"(d[66]), "+f"(d[67]), "+f"(d[68]), "+f"(d[69]), "+f"(d[70]), "+f"(d[71]), "+f"(d[72]), "+f"(d[73]), "+f"(d[74]), "+f"(d[75]), "+f"(d[76]), "+f"(d[77]), "+f"(d[78]), "+f"(d[79]), "+f"(d[80]), "+f"(d[81]), "+f"(d[82]), "+f"(d[83]), "+f"(d[84]), "+f"(d[85]), "+f"(d[86]), "+f"(d[87]), "+f"(d[88]), "+f"(d[89]), "+f"(d[90]), "+f"(d[91]), "+f"(d[92]), "+f"(d[93]), "+f"(d[94]), "+f"(d[95])
    : "l"(descA), "l"(descB), "r"(scaleD));
}

__device__ __forceinline__ void wgmma_n128_ss_ta0_tb1(float* d, uint64_t descA, uint64_t descB, int scaleD) {
  asm volatile("{\n.reg .pred p;\nsetp.ne.b32 p, %66, 0;\n"
    "wgmma.mma_async.sync.aligned.m64n128k16.f32.bf16.bf16 {%0, %1, %2, %3, %4, %5, %6, %7, %8, %9, %10, %11, %12, %13, %14, %15, %16, %17, %18, %19, %20, %21, %22, %23, %24, %25, %26, %27, %28, %29, %30, %31, %32, %33, %34, %35, %36, %37, %38, %39, %40, %41, %42, %43, %44, %45, %46, %47, %48, %49, %50, %51, %52, %53, %54, %55, %56, %57, %58, %59, %60, %61, %62, %63}, %64, %65, p, 1, 1, 0, 1;\n}\n"
    : "+f"(d[0]), "+f"(d[1]), "+f"(d[2]), "+f"(d[3]), "+f"(d[4]), "+f"(d[5]), "+f"(d[6]), "+f"(d[7]), "+f"(d[8]), "+f"(d[9]), "+f"(d[10]), "+f"(d[11]), "+f"(d[12]), "+f"(d[13]), "+f"(d[14]), "+f"(d[15]), "+f"(d[16]), "+f"(d[17]), "+f"(d[18]), "+f"(d[19]), "+f"(d[20]), "+f"(d[21]), "+f"(d[22]), "+f"(d[23]), "+f"(d[24]), "+f"(d[25]), "+f"(d[26]), "+f"(d[27]), "+f"(d[28]), "+f"(d[29]), "+f"(d[30]), "+f"(d[31]), "+f"(d[32]), "+f"(d[33]), "+f"(d[34]), "+f"(d[35]), "+f"(d[36]), "+f"(d[37]), "+f"(d[38]), "+f"(d[39]), "+f"(d[40]), "+f"(d[41]), "+f"(d[42]), "+f"(d[43]), "+f"(d[44]), "+f"(d[45]), "+f"(d[46]), "+f"(d[47]), "+f"(d[48]), "+f"(d[49]), "+f"(d[50]), "+f"(d[51]), "+f"(d[52]), "+f"(d[53]), "+f"(d[54]), "+f"(d[55]), "+f"(d[56]), "+f"(d[57]), "+f"(d[58]), "+f"(d[59]), "+f"(d[60]), "+f"(d[61]), "+f"(d[62]), "+f"(d[63])
    : "l"(descA), "l"(descB), "r"(scaleD));
}

__device__ __forceinline__ void wgmma_n192_ssz_ta0_tb1(float* d, uint64_t descA, uint64_t descB) {
  asm volatile("{\n.reg .pred p;\nsetp.ne.b32 p, 0, 0;\n"
    "wgmma.mma_async.sync.aligned.m64n192k16.f32.bf16.bf16 {%0, %1, %2, %3, %4, %5, %6, %7, %8, %9, %10, %11, %12, %13, %14, %15, %16, %17, %18, %19, %20, %21, %22, %23, %24, %25, %26, %27, %28, %29, %30, %31, %32, %33, %34, %35, %36, %37, %38, %39, %40, %41, %42, %43, %44, %45, %46, %47, %48, %49, %50, %51, %52, %53, %54, %55, %56, %57, %58, %59, %60, %61, %62, %63, %64, %65, %66, %67, %68, %69, %70, %71, %72, %73, %74, %75, %76, %77, %78, %79, %80, %81, %82, %83, %84, %85, %86, %87, %88, %89, %90, %91, %92, %93, %94, %95}, %96, %97, p, 1, 1, 0, 1;\n}\n"
    : "=f"(d[0]), "=f"(d[1]), "=f"(d[2]), "=f"(d[3]), "=f"(d[4]), "=f"(d[5]), "=f"(d[6]), "=f"(d[7]), "=f"(d[8]), "=f"(d[9]), "=f"(d[10]), "=f"(d[11]), "=f"(d[12]), "=f"(d[13]), "=f"(d[14]), "=f"(d[15]), "=f"(d[16]), "=f"(d[17]), "=f"(d[18]), "=f"(d[19]), "=f"(d[20]), "=f"(d[21]), "=f"(d[22]), "=f"(d[23]), "=f"(d[24]), "=f"(d[25]), "=f"(d[26]), "=f"(d[27]), "=f"(d[28]), "=f"(d[29]), "=f"(d[30]), "=f"(d[31]), "=f"(d[32]), "=f"(d[33]), "=f"(d[34]), "=f"(d[35]), "=f"(d[36]), "=f"(d[37]), "=f"(d[38]), "=f"(d[39]), "=f"(d[40]), "=f"(d[41]), "=f"(d[42]), "=f"(d[43]), "=f"(d[44]), "=f"(d[45]), "=f"(d[46]), "=f"(d[47]), "=f"(d[48]), "=f"(d[49]), "=f"(d[50]), "=f"(d[51]), "=f"(d[52]), "=f"(d[53]), "=f"(d[54]), "=f"(d[55]), "=f"(d[56]), "=f"(d[57]), "=f"(d[58]), "=f"(d[59]), "=f"(d[60]), "=f"(d[61]), "=f"(d[62]), "=f"(d[63]), "=f"(d[64]), "=f"(d[65]), "=f"(d[66]), "=f"(d[67]), "=f"(d[68]), "=f"(d[69]), "=f"(d[70]), "=f"(d[71]), "=f"(d[72]), "=f"(d[73]), "=f"(d[74]), "=f"(d[75]), "=f"(d[76]), "=f"(d[77]), "=f"(d[78]), "=f"(d[79]), "=f"(d[80]), "=f"(d[81]), "=f"(d[82]), "=f"(d[83]), "=f"(d[84]), "=f"(d[85]), "=f"(d[86]), "=f"(d[87]), "=f"(d[88]), "=f"(d[89]), "=f"(d[90]), "=f"(d[91]), "=f"(d[92]), "=f"(d[93]), "=f"(d[94]), "=f"(d[95])
    : "l"(descA), "l"(descB));
}

__device__ __forceinline__ void wgmma_n192_rs_tb1(float* d, const uint32_t* a, uint64_t descB, int scaleD) {
  asm volatile("{\n.reg .pred p;\nsetp.ne.b32 p, %101, 0;\n"
    "wgmma.mma_async.sync.aligned.m64n192k16.f32.bf16.bf16 {%0, %1, %2, %3, %4, %5, %6, %7, %8, %9, %10, %11, %12, %13, %14, %15, %16, %17, %18, %19, %20, %21, %22, %23, %24, %25, %26, %27, %28, %29, %30, %31, %32, %33, %34, %35, %36, %37, %38, %39, %40, %41, %42, %43, %44, %45, %46, %47, %48, %49, %50, %51, %52, %53, %54, %55, %56, %57, %58, %59, %60, %61, %62, %63, %64, %65, %66, %67, %68, %69, %70, %71, %72, %73, %74, %75, %76, %77, %78, %79, %80, %81, %82, %83, %84, %85, %86, %87, %88, %89, %90, %91, %92, %93, %94, %95}, {%96, %97, %98, %99}, %100, p, 1, 1, 1;\n}\n"
    : "+f"(d[0]), "+f"(d[1]), "+f"(d[2]), "+f"(d[3]), "+f"(d[4]), "+f"(d[5]), "+f"(d[6]), "+f"(d[7]), "+f"(d[8]), "+f"(d[9]), "+f"(d[10]), "+f"(d[11]), "+f"(d[12]), "+f"(d[13]), "+f"(d[14]), "+f"(d[15]), "+f"(d[16]), "+f"(d[17]), "+f"(d[18]), "+f"(d[19]), "+f"(d[20]), "+f"(d[21]), "+f"(d[22]), "+f"(d[23]), "+f"(d[24]), "+f"(d[25]), "+f"(d[26]), "+f"(d[27]), "+f"(d[28]), "+f"(d[29]), "+f"(d[30]), "+f"(d[31]), "+f"(d[32]), "+f"(d[33]), "+f"(d[34]), "+f"(d[35]), "+f"(d[36]), "+f"(d[37]), "+f"(d[38]), "+f"(d[39]), "+f"(d[40]), "+f"(d[41]), "+f"(d[42]), "+f"(d[43]), "+f"(d[44]), "+f"(d[45]), "+f"(d[46]), "+f"(d[47]), "+f"(d[48]), "+f"(d[49]), "+f"(d[50]), "+f"(d[51]), "+f"(d[52]), "+f"(d[53]), "+f"(d[54]), "+f"(d[55]), "+f"(d[56]), "+f"(d[57]), "+f"(d[58]), "+f"(d[59]), "+f"(d[60]), "+f"(d[61]), "+f"(d[62]), "+f"(d[63]), "+f"(d[64]), "+f"(d[65]), "+f"(d[66]), "+f"(d[67]), "+f"(d[68]), "+f"(d[69]), "+f"(d[70]), "+f"(d[71]), "+f"(d[72]), "+f"(d[73]), "+f"(d[74]), "+f"(d[75]), "+f"(d[76]), "+f"(d[77]), "+f"(d[78]), "+f"(d[79]), "+f"(d[80]), "+f"(d[81]), "+f"(d[82]), "+f"(d[83]), "+f"(d[84]), "+f"(d[85]), "+f"(d[86]), "+f"(d[87]), "+f"(d[88]), "+f"(d[89]), "+f"(d[90]), "+f"(d[91]), "+f"(d[92]), "+f"(d[93]), "+f"(d[94]), "+f"(d[95])
    : "r"(a[0]), "r"(a[1]), "r"(a[2]), "r"(a[3]), "l"(descB), "r"(scaleD));
}

__device__ __forceinline__ void wgmma_n80_rs_tb0(float* d, const uint32_t* a, uint64_t descB, int scaleD) {
  asm volatile("{\n.reg .pred p;\nsetp.ne.b32 p, %45, 0;\n"
    "wgmma.mma_async.sync.aligned.m64n80k16.f32.bf16.bf16 {%0, %1, %2, %3, %4, %5, %6, %7, %8, %9, %10, %11, %12, %13, %14, %15, %16, %17, %18, %19, %20, %21, %22, %23, %24, %25, %26, %27, %28, %29, %30, %31, %32, %33, %34, %35, %36, %37, %38, %39}, {%40, %41, %42, %43}, %44, p, 1, 1, 0;\n}\n"
    : "+f"(d[0]), "+f"(d[1]), "+f"(d[2]), "+f"(d[3]), "+f"(d[4]), "+f"(d[5]), "+f"(d[6]), "+f"(d[7]), "+f"(d[8]), "+f"(d[9]), "+f"(d[10]), "+f"(d[11]), "+f"(d[12]), "+f"(d[13]), "+f"(d[14]), "+f"(d[15]), "+f"(d[16]), "+f"(d[17]), "+f"(d[18]), "+f"(d[19]), "+f"(d[20]), "+f"(d[21]), "+f"(d[22]), "+f"(d[23]), "+f"(d[24]), "+f"(d[25]), "+f"(d[26]), "+f"(d[27]), "+f"(d[28]), "+f"(d[29]), "+f"(d[30]), "+f"(d[31]), "+f"(d[32]), "+f"(d[33]), "+f"(d[34]), "+f"(d[35]), "+f"(d[36]), "+f"(d[37]), "+f"(d[38]), "+f"(d[39])
    : "r"(a[0]), "r"(a[1]), "r"(a[2]), "r"(a[3]), "l"(descB), "r"(scaleD));
}

__device__ __forceinline__ void wgmma_n80_rsz_tb0(float* d, const uint32_t* a, uint64_t descB) {
  asm volatile("{\n.reg .pred p;\nsetp.ne.b32 p, 0, 0;\n"
    "wgmma.mma_async.sync.aligned.m64n80k16.f32.bf16.bf16 {%0, %1, %2, %3, %4, %5, %6, %7, %8, %9, %10, %11, %12, %13, %14, %15, %16, %17, %18, %19, %20, %21, %22, %23, %24, %25, %26, %27, %28, %29, %30, %31, %32, %33, %34, %35, %36, %37, %38, %39}, {%40, %41, %42, %43}, %44, p, 1, 1, 0;\n}\n"
    : "=f"(d[0]), "=f"(d[1]), "=f"(d[2]), "=f"(d[3]), "=f"(d[4]), "=f"(d[5]), "=f"(d[6]), "=f"(d[7]), "=f"(d[8]), "=f"(d[9]), "=f"(d[10]), "=f"(d[11]), "=f"(d[12]), "=f"(d[13]), "=f"(d[14]), "=f"(d[15]), "=f"(d[16]), "=f"(d[17]), "=f"(d[18]), "=f"(d[19]), "=f"(d[20]), "=f"(d[21]), "=f"(d[22]), "=f"(d[23]), "=f"(d[24]), "=f"(d[25]), "=f"(d[26]), "=f"(d[27]), "=f"(d[28]), "=f"(d[29]), "=f"(d[30]), "=f"(d[31]), "=f"(d[32]), "=f"(d[33]), "=f"(d[34]), "=f"(d[35]), "=f"(d[36]), "=f"(d[37]), "=f"(d[38]), "=f"(d[39])
    : "r"(a[0]), "r"(a[1]), "r"(a[2]), "r"(a[3]), "l"(descB));
}

__device__ __forceinline__ void wgmma_n32_rs_tb1(float* d, const uint32_t* a, uint64_t descB, int scaleD) {
  asm volatile("{\n.reg .pred p;\nsetp.ne.b32 p, %21, 0;\n"
    "wgmma.mma_async.sync.aligned.m64n32k16.f32.bf16.bf16 {%0, %1, %2, %3, %4, %5, %6, %7, %8, %9, %10, %11, %12, %13, %14, %15}, {%16, %17, %18, %19}, %20, p, 1, 1, 1;\n}\n"
    : "+f"(d[0]), "+f"(d[1]), "+f"(d[2]), "+f"(d[3]), "+f"(d[4]), "+f"(d[5]), "+f"(d[6]), "+f"(d[7]), "+f"(d[8]), "+f"(d[9]), "+f"(d[10]), "+f"(d[11]), "+f"(d[12]), "+f"(d[13]), "+f"(d[14]), "+f"(d[15])
    : "r"(a[0]), "r"(a[1]), "r"(a[2]), "r"(a[3]), "l"(descB), "r"(scaleD));
}

__device__ __forceinline__ void wgmma_n32_rsz_tb1(float* d, const uint32_t* a, uint64_t descB) {
  asm volatile("{\n.reg .pred p;\nsetp.ne.b32 p, 0, 0;\n"
    "wgmma.mma_async.sync.aligned.m64n32k16.f32.bf16.bf16 {%0, %1, %2, %3, %4, %5, %6, %7, %8, %9, %10, %11, %12, %13, %14, %15}, {%16, %17, %18, %19}, %20, p, 1, 1, 1;\n}\n"
    : "=f"(d[0]), "=f"(d[1]), "=f"(d[2]), "=f"(d[3]), "=f"(d[4]), "=f"(d[5]), "=f"(d[6]), "=f"(d[7]), "=f"(d[8]), "=f"(d[9]), "=f"(d[10]), "=f"(d[11]), "=f"(d[12]), "=f"(d[13]), "=f"(d[14]), "=f"(d[15])
    : "r"(a[0]), "r"(a[1]), "r"(a[2]), "r"(a[3]), "l"(descB));
}

__device__ __forceinline__ void wgmma_n32_rs_tb0(float* d, const uint32_t* a, uint64_t descB, int scaleD) {
  asm volatile("{\n.reg .pred p;\nsetp.ne.b32 p, %21, 0;\n"
    "wgmma.mma_async.sync.aligned.m64n32k16.f32.bf16.bf16 {%0, %1, %2, %3, %4, %5, %6, %7, %8, %9, %10, %11, %12, %13, %14, %15}, {%16, %17, %18, %19}, %20, p, 1, 1, 0;\n}\n"
    : "+f"(d[0]), "+f"(d[1]), "+f"(d[2]), "+f"(d[3]), "+f"(d[4]), "+f"(d[5]), "+f"(d[6]), "+f"(d[7]), "+f"(d[8]), "+f"(d[9]), "+f"(d[10]), "+f"(d[11]), "+f"(d[12]), "+f"(d[13]), "+f"(d[14]), "+f"(d[15])
    : "r"(a[0]), "r"(a[1]), "r"(a[2]), "r"(a[3]), "l"(descB), "r"(scaleD));
}

__device__ __forceinline__ void wgmma_n32_rsz_tb0(float* d, const uint32_t* a, uint64_t descB) {
  asm volatile("{\n.reg .pred p;\nsetp.ne.b32 p, 0, 0;\n"
    "wgmma.mma_async.sync.aligned.m64n32k16.f32.bf16.bf16 {%0, %1, %2, %3, %4, %5, %6, %7, %8, %9, %10, %11, %12, %13, %14, %15}, {%16, %17, %18, %19}, %20, p, 1, 1, 0;\n}\n"
    : "=f"(d[0]), "=f"(d[1]), "=f"(d[2]), "=f"(d[3]), "=f"(d[4]), "=f"(d[5]), "=f"(d[6]), "=f"(d[7]), "=f"(d[8]), "=f"(d[9]), "=f"(d[10]), "=f"(d[11]), "=f"(d[12]), "=f"(d[13]), "=f"(d[14]), "=f"(d[15])
    : "r"(a[0]), "r"(a[1]), "r"(a[2]), "r"(a[3]), "l"(descB));
}

__device__ __forceinline__ uint32_t pack_bf16x2(float lo, float hi) {
  uint32_t r;
  asm("cvt.rn.bf16x2.f32 %0, %1, %2;" : "=r"(r) : "f"(hi), "f"(lo));
  return r;
}
__device__ __forceinline__ float bf_lo(uint32_t p) { return __uint_as_float(p << 16); }
__device__ __forceinline__ float bf_hi(uint32_t p) { return __uint_as_float(p & 0xffff0000u); }
__device__ __forceinline__ float bf16_round(float v) { return __bfloat162float(__float2bfloat16_rn(v)); }
__device__ __forceinline__ float ex2_approx(float x) {
  float r;
  asm("ex2.approx.ftz.f32 %0, %1;" : "=f"(r) : "f"(x));
  return r;
}
__device__ __forceinline__ float rcp_fast(float x) {
  float r;
  asm("rcp.approx.ftz.f32 %0, %1;" : "=f"(r) : "f"(x));
  return r;
}
__device__ __forceinline__ void ldmatrix_x4(uint32_t (&r)[4], uint32_t addr) {
  asm volatile("ldmatrix.sync.aligned.m8n8.x4.shared.b16 {%0,%1,%2,%3}, [%4];"
               : "=r"(r[0]), "=r"(r[1]), "=r"(r[2]), "=r"(r[3])
               : "r"(addr)
               : "memory");
}
__device__ __forceinline__ void stmatrix_x4(uint32_t addr, uint32_t r0, uint32_t r1, uint32_t r2, uint32_t r3) {
  asm volatile("stmatrix.sync.aligned.m8n8.x4.shared.b16 [%0], {%1,%2,%3,%4};" ::"r"(addr), "r"(r0), "r"(r1), "r"(r2),
               "r"(r3));
}
__device__ __forceinline__ uint32_t add_bf16x2(uint32_t a, uint32_t b) {
  uint32_t r;
  asm("add.rn.bf16x2 %0, %1, %2;" : "=r"(r) : "r"(a), "r"(b));
  return r;
}
__device__ __forceinline__ uint4 lds128(uint32_t addr) {
  uint4 v;
  asm volatile("ld.shared.v4.b32 {%0,%1,%2,%3}, [%4];" : "=r"(v.x), "=r"(v.y), "=r"(v.z), "=r"(v.w) : "r"(addr) : "memory");
  return v;
}
__device__ __forceinline__ uint32_t lds32(uint32_t addr) {
  uint32_t v;
  asm volatile("ld.shared.b32 %0, [%1];" : "=r"(v) : "r"(addr) : "memory");
  return v;
}
__device__ __forceinline__ void sts32(uint32_t addr, uint32_t v) {
  asm volatile("st.shared.b32 [%0], %1;" ::"r"(addr), "r"(v) : "memory");
}

__device__ __forceinline__ unsigned ld_relaxed_u32(const void* p) {
  unsigned v;
  asm volatile("ld.relaxed.gpu.global.u32 %0, [%1];" : "=r"(v) : "l"(p) : "memory");
  return v;
}
__device__ __forceinline__ unsigned launch_epoch() { return (*(volatile unsigned*)g_done) / NCTA + 1u; }
__device__ __forceinline__ void red_announce(unsigned* p) {
  asm volatile("red.relaxed.gpu.global.add.u32 [%0], %1;" ::"l"(p), "r"(1u) : "memory");
}
__device__ __forceinline__ uint32_t set_tag(uint32_t w, uint32_t m, uint32_t tag) { return (w & ~m) | (tag & m); }
__device__ __forceinline__ uint32_t o_tag(int L) { return (L + 1) & 1; }
__device__ __forceinline__ uint32_t x_tag(unsigned ep1, int L) { return (ep1 + L + 1) & 1; }

__device__ __forceinline__ void wait_count(const unsigned* f, unsigned target, int i, uint32_t& seen, int lane) {
  if ((seen >> i) & 1u) return;
#pragma unroll 1
  for (uint32_t it = 0; it < (1u << 17); ++it) {
    seen = __ballot_sync(0xffffffffu, (int)(ld_relaxed_u32(f + (lane & 15)) - target) >= 0);
    if ((seen >> i) & 1u) break;
  }
  fence_proxy_async_all();
}
__device__ __forceinline__ float4 ld_rec(const float4* p) {
  float4 v;
  asm volatile("ld.relaxed.gpu.global.v4.f32 {%0,%1,%2,%3}, [%4];" : "=f"(v.x), "=f"(v.y), "=f"(v.z), "=f"(v.w) : "l"(p) : "memory");
  return v;
}
__device__ __forceinline__ void st_rec(float4* p, float a, float b, float c, unsigned tag) {
  asm volatile("st.relaxed.gpu.global.v4.f32 [%0], {%1,%2,%3,%4};" ::"l"(p), "f"(a), "f"(b), "f"(c), "f"(__uint_as_float(tag)) : "memory");
}
template <int N>
__device__ __forceinline__ float4 sum_recs(const float4* p, int stride, unsigned tag) {
  float4 s;
#pragma unroll 1
  for (uint32_t it = 0; it < (1u << 17); ++it) {
    float4 v[N];
#pragma unroll
    for (int t = 0; t < N; t++) v[t] = ld_rec(p + t * stride);
    bool ok = true;
    s = make_float4(0.f, 0.f, 0.f, 0.f);
#pragma unroll
    for (int t = 0; t < N; t++) {
      ok &= __float_as_uint(v[t].w) == tag;
      s.x += v[t].x;
      s.y += v[t].y;
      s.z += v[t].z;
    }
    if (ok) break;
    __nanosleep(200);
  }
  return s;
}

__device__ __forceinline__ int fresh_tid() {
  int t;
  asm volatile("mov.u32 %0, %%tid.x;" : "=r"(t));
  return t;
}
#define PHASE_IDS                                  \
  const int tid_ = fresh_tid();                    \
  const int lane = tid_ & 31, wwarp = __shfl_sync(0xffffffffu, (tid_ >> 5) & 3, 0), tid = tid_ & 127; \
  const int g = lane >> 2, c = lane & 3;           \
  (void)tid; (void)g; (void)c; (void)wwarp;

#define PHASE_IDS_W                                \
  const int lane = fresh_tid() & 31, wwarp = warp & 3; \
  const int g = lane >> 2, c = lane & 3;

#define GTL(i) do { } while (0)
#define TGET(v) do { } while (0)
#define TPUT(c, i, v) do { } while (0)

constexpr float SM_C = 0.17677669529663687f * 1.4426950408889634f;

__device__ __forceinline__ void stmatrix_x4_if(bool ok, uint32_t addr, uint32_t r0, uint32_t r1, uint32_t r2, uint32_t r3) {
  asm volatile("{\n.reg .pred p;\nsetp.ne.b32 p, %5, 0;\n@p stmatrix.sync.aligned.m8n8.x4.shared.b16 [%0], {%1,%2,%3,%4};\n}\n" ::"r"(addr),
               "r"(r0), "r"(r1), "r"(r2), "r"(r3), "r"((int)ok));
}

__device__ __forceinline__ void attn_a_slow(const uint8_t* __restrict__ kvimg, int L, int gb, int hp, uint32_t bad,
                                            int row0, int lane) {
  constexpr uint32_t sq = SBASE + OFF_SLOT + 3 * 16384;
#pragma unroll 1
  for (int j = 0; j < 8; j++) {
    const uint8_t* tp = kvimg + (size_t)(gb * 16 + hp) * 32768 + (j * 32 + lane) * 128 + ((lane & 7) << 4);
#pragma unroll 1
    for (uint32_t it = 0; it < (1u << 17); ++it)
      if (((ld_relaxed_u32(tp) ^ lds32(SBASE + OFF_EPOCH)) & 1u) == 0u) break;
  }
  __syncwarp();
#pragma unroll 1
  for (int t = 0; t < 32; t++) {
    const int hh = t >> 4, row = row0 + (t & 7) + (t & 8) * 4;
    if (!((bad >> hh) & 1u)) continue;
    const int qpos = gb * 128 + row;
    const uint32_t qaddr = sq + row * 128;
    float mx = -INFINITY, sum = 0.f, acc = 0.f;
#pragma unroll 1
    for (int pass = 0; pass < 2; pass++) {
#pragma unroll 1
      for (int j = 0; j < 8; j++) {
        const int kp = qpos - (lane + 32 * j);
        const uint8_t* kr = kvimg + ((size_t)((kp >> 7) * 16 + hp) * 2 + ((kp >> 6) & 1)) * 16384 + (kp & 63) * 128;
        float d = -INFINITY;
        if (kp >= 0) {
          d = 0.f;
#pragma unroll 1
          for (int q = 0; q < 4; q++) {
            const uint4 kv = __ldcg(reinterpret_cast<const uint4*>(kr + (((hh * 4 + q) ^ (kp & 7)) << 4)));
            const uint4 qv = lds128(qaddr + (((hh * 4 + q) ^ (row & 7)) << 4));
            const uint32_t kw[4] = {kv.x, kv.y, kv.z, kv.w}, qw[4] = {qv.x, qv.y, qv.z, qv.w};
#pragma unroll
            for (int e = 0; e < 4; e++) d = fmaf(bf_lo(kw[e]), bf_lo(qw[e]), fmaf(bf_hi(kw[e]), bf_hi(qw[e]), d));
          }
        }
        if (pass == 0) {
          mx = fmaxf(mx, d);
        } else {
          const float ev = ex2_approx(d - mx);
          sum += ev;
          const float pv = bf16_round(ev);
#pragma unroll 1
          for (int kk = 0; kk < 32; kk++) {
            const float pk = __shfl_sync(0xffffffffu, pv, kk);
            const int k2 = qpos - (kk + 32 * j);
            if (k2 >= 0) {
              const uint8_t* vr = kvimg + ((size_t)((k2 >> 7) * 16 + hp) * 2 + ((k2 >> 6) & 1)) * 16384 + 8192 + (k2 & 63) * 128;
              const unsigned short vv =
                  __ldcg(reinterpret_cast<const unsigned short*>(vr + (((hh * 4 + (lane >> 3)) ^ (k2 & 7)) << 4) + (lane & 7) * 2));
              acc = fmaf(pk, __uint_as_float((uint32_t)vv << 16), acc);
            }
          }
        }
      }
      if (pass == 0) {
#pragma unroll
        for (int o = 16; o > 0; o >>= 1) mx = fmaxf(mx, __shfl_xor_sync(0xffffffffu, mx, o));
      }
    }
#pragma unroll
    for (int o = 16; o > 0; o >>= 1) sum += __shfl_xor_sync(0xffffffffu, sum, o);
    acc *= rcp_fast(sum);
    const float hi = __shfl_down_sync(0xffffffffu, acc, 1);
    __syncwarp();
    if ((lane & 1) == 0) sts32(qaddr + (((hh * 4 + (lane >> 3)) ^ (row & 7)) << 4) + (lane & 7) * 2,
                               set_tag(pack_bf16x2(acc, hi), hh == 0 && lane == 0, o_tag(L)));
    __syncwarp();
  }
}

template <int HH>
__device__ __forceinline__ void store_o(const float (&o)[16], const float (&inv)[2], uint32_t ra, uint32_t tag, bool ok) {
  const uint32_t m = HH == 0 && (fresh_tid() & 3) == 0;
#pragma unroll
  for (int jp = 0; jp < 2; jp++) {
    uint32_t w0 = pack_bf16x2(o[8 * jp] * inv[0], o[8 * jp + 1] * inv[0]);
    uint32_t w1 = pack_bf16x2(o[8 * jp + 2] * inv[1], o[8 * jp + 3] * inv[1]);
    if (HH == 0 && jp == 0) {
      w0 = set_tag(w0, m, tag);
      w1 = set_tag(w1, m, tag);
    }
    stmatrix_x4_if(ok, ra ^ ((HH * 4 + 2 * jp) << 4), w0, w1, pack_bf16x2(o[8 * jp + 4] * inv[0], o[8 * jp + 5] * inv[0]),
                   pack_bf16x2(o[8 * jp + 6] * inv[1], o[8 * jp + 7] * inv[1]));
  }
}
__device__ __forceinline__ int tile_row(bool B, int w, int r, int g) { return (B ? 16 * w + 8 * r : 8 * w + 32 * r) + g; }
__device__ __forceinline__ uint32_t q_row_addr(bool B, int R, int w, int lane) {
  return SBASE + OFF_SLOT + 3 * 16384 + R * 8192 + tile_row(B, w, (lane >> 3) & 1, lane & 7) * 128 + (((lane >> 4) ^ (lane & 7)) << 4);
}

struct AttnA {
  float s[2][16], o[2][16], l[2][2], sh[2][3];
  uint32_t p[2][4], t[2], me[4], ra, bad, zero;
};
#define ATS_(i) do { } while (0)
template <int V>
__device__ __forceinline__ void attn_sum(AttnA& a, int nv) {
  constexpr int hh = (V >> 1) & 1, kh = V & 1, i = V >> 2;
#pragma unroll
  for (int r = 0; r < 2; r++) {
    const uint32_t t1 = add_bf16x2(add_bf16x2(a.p[0][r], a.p[0][2 + r]), add_bf16x2(a.p[1][r], a.p[1][2 + r]));
    if (kh == 0) {
      a.t[r] = t1;
    } else {
      uint32_t tt = add_bf16x2(a.t[r], t1);
      if (i > 0) tt = i <= nv ? tt : 0u;
      const float v = bf_lo(tt) + bf_hi(tt);
      a.l[hh][r] = i == 0 ? v : a.l[hh][r] + v;
    }
  }
}
template <int HH>
__device__ __forceinline__ void attn_shfl(AttnA& a) {
#pragma unroll
  for (int r = 0; r < 2; r++)
#pragma unroll
    for (int j = 0; j < 3; j++) a.sh[r][j] = __shfl_xor_sync(0xffffffffu, a.l[HH][r], j + 1);
}
template <int HH>
__device__ __forceinline__ void attn_fin(AttnA& a) {
  bool bad = false;
  float inv[2];
#pragma unroll
  for (int r = 0; r < 2; r++) {
    const float v = (a.l[HH][r] + a.sh[r][0]) + (a.sh[r][1] + a.sh[r][2]);
    bad |= !(v <= 1.152921504606846976e18f && v >= 8.673617379884035e-19f);
    inv[r] = rcp_fast(v);
  }
  bad = __any_sync(0xffffffffu, bad);
  if (HH == 1) wgmma_wait<0>();
  reg_fence<16>(a.o[HH]);
  store_o<HH>(a.o[HH], inv, a.ra, o_tag(0), !bad);
  a.bad = (HH == 0 ? 0u : a.bad) | (bad ? 1u << HH : 0u);
}
__device__ __forceinline__ void attn_masks(AttnA& a, int wr) {
  const int lane = fresh_tid() & 31, d = (lane >> 2) - 2 * (lane & 3);
  const uint32_t tri = d >= 1 ? 0xffffffffu : (d == 0 ? 0xffffu : 0u);
#pragma unroll
  for (int t = 0; t < 4; t++) a.me[t] = wr > t ? 0xffffffffu : (wr == t ? tri : 0u);
}
template <int V, int K>
__device__ __forceinline__ uint32_t attn_exp(AttnA& a) {
  constexpr int i = V >> 2, kh = V & 1, r = K & 1;
  if ((i == 0 && kh > r) || (i == 4 && kh < r)) return 0u;
  const uint32_t w = pack_bf16x2(ex2_approx(a.s[V & 1][2 * K]), ex2_approx(a.s[V & 1][2 * K + 1]));
  if (i == 0 && kh == r) return w & a.me[K >> 1];
  if (i == 4 && kh == r) return w & ~a.me[K >> 1];
  return w;
}
template <int V>
__device__ __forceinline__ void attn_unit(AttnA& a, const uint32_t (&q)[2][2][4], uint64_t dcur, uint64_t dnext, int R, int wr, int nv,
                                          uint32_t hbar, uint32_t hpar, uint32_t rbar, bool rel) {
  constexpr int hh = (V >> 1) & 1, kh = V & 1, i = V >> 2;
  ATS_(V + 1);
  asm volatile("" : "+l"(dcur), "+l"(dnext));
  wgmma_wait<1>();
  reg_fence<16>(a.s[V & 1]);
  bool hok = true;
  if (V == 4) hbar = SBASE + OFF_BAR + 8u * (R ? B_LOC : B_HV);
  if (((V & 3) == 2 && V < 16) || V == 4) hok = mbar_test(hbar, hpar);
  const uint64_t d0 = ((V & 3) >= 2 ? dnext : dcur) + ((hh ^ 1) * 4 + kh * 256), d1 = ((V & 3) >= 2 ? dnext : dcur) + ((hh ^ 1) * 4 + kh * 256 + 2);
  const uint64_t d2 = dcur + (512 + hh * 4 + kh * 256), d3 = dcur + (640 + hh * 4 + kh * 256);
  if ((V & 3) == 1 && V > 4 && rel) mbar_arrive(rbar);
  if (V > 0) attn_sum<V - 1>(a, nv);
  if (V == 15) attn_masks(a, wr);
  if (V == 18) {
    attn_shfl<0>(a);
    a.ra = q_row_addr(false, R, wr, fresh_tid() & 31);
  }
  if (V == 19) attn_fin<0>(a);
  uint32_t p[2][4];
  p[0][0] = attn_exp<V, 0>(a);
  p[0][1] = attn_exp<V, 1>(a);
  p[0][2] = attn_exp<V, 2>(a);
  p[0][3] = attn_exp<V, 3>(a);
  p[1][0] = attn_exp<V, 4>(a);
  p[1][1] = attn_exp<V, 5>(a);
  p[1][2] = attn_exp<V, 6>(a);
  p[1][3] = attn_exp<V, 7>(a);
  if (V > 0) {
#pragma unroll
    for (int r = 0; r < 2; r++) p[1][r] ^= (kh ? a.t[r] : __float_as_uint(a.l[hh ^ 1][r])) & a.zero;
  }
#pragma unroll
  for (int k = 0; k < 8; k++) {
    asm volatile("" : "+r"(p[k >> 2][k & 3]));
    a.p[k >> 2][k & 3] = p[k >> 2][k & 3];
  }
  if (!hok) mbar_wait(hbar, hpar);
  wgmma_fence();
  if (V < 18) wgmma_n32_rsz_tb0(a.s[V & 1], q[hh ^ 1][0], d0);
  if (i == 0 && kh == 0) wgmma_n32_rsz_tb1(a.o[hh], a.p[0], d2);
  else wgmma_n32_rs_tb1(a.o[hh], a.p[0], d2, 1);
  if (V < 18) wgmma_n32_rs_tb0(a.s[V & 1], q[hh ^ 1][1], d1, 1);
  wgmma_n32_rs_tb1(a.o[hh], a.p[1], d3, 1);
  wgmma_commit();
}
template <int I>
__device__ __forceinline__ void attn_step(AttnA& a, const uint32_t (&q)[2][2][4], uint64_t dcur, uint64_t dnext, int R, int wr, int nv,
                                          uint32_t hbar, uint32_t hpar, uint32_t rbar, bool rel) {
  attn_unit<4 * I>(a, q, dcur, dnext, R, wr, nv, hbar, hpar, rbar, rel);
  attn_unit<4 * I + 1>(a, q, dcur, dnext, R, wr, nv, hbar, hpar, rbar, rel);
  attn_unit<4 * I + 2>(a, q, dcur, dnext, R, wr, nv, hbar, hpar, rbar, rel);
  attn_unit<4 * I + 3>(a, q, dcur, dnext, R, wr, nv, hbar, hpar, rbar, rel);
}

__device__ __forceinline__ void attention_a(const uint32_t (&q)[2][2][4], int R, int L, int gb, int hp, uint32_t par, int wr,
                                            uint32_t zero) {
  constexpr uint32_t bars = SBASE + OFF_BAR;
  constexpr uint32_t dslot = ((SBASE + OFF_SLOT) >> 4) + 0x10000u;
  auto next = [&](uint64_t d) { return desc_lo((uint32_t)d == dslot ? dslot + 2048 : (uint32_t)d - 1024) + zero; };
  uint64_t d0 = desc_lo(dslot + R * 1024) + zero, d1 = next(d0);
  AttnA a;
  ATS_(0);
  wgmma_fence();
#pragma unroll
  for (int v = 0; v < 2; v++) {
    wgmma_n32_rsz_tb0(a.s[v], q[0][0], d0 + v * 256);
    wgmma_n32_rs_tb0(a.s[v], q[0][1], d0 + (v * 256 + 2), 1);
    wgmma_commit();
  }
  a.zero = zero;
  const bool lane0 = (fresh_tid() & 31) == 0;
  attn_masks(a, wr);
  const int nv = 2 * gb + R;
  const uint32_t hb = bars + 8u * (B_HALO - R), rb = bars + 8u * (B_REL - R);
  attn_step<0>(a, q, d0, d1, R, wr, nv, hb, par, 0, false);
  d0 = next(d1);
  attn_step<1>(a, q, d1, d0, R, wr, nv, R ? bars + 8u * B_HV : hb + 8, par, rb + 8, lane0);
  d1 = next(d0);
  attn_step<2>(a, q, d0, d1, R, wr, nv, hb + 16, par, rb + 16, lane0);
  d0 = next(d1);
  attn_step<3>(a, q, d1, d0, R, wr, nv, hb + 24, par, rb + 24, lane0 && R);
  attn_step<4>(a, q, d0, d0, R, wr, nv, 0, 0, rb, false);
  ATS_(21);
  attn_sum<19>(a, nv);
  attn_shfl<1>(a);
  attn_fin<1>(a);
  ATS_(22);
  if (a.bad != 0u) attn_a_slow(g_kvA[L >> 1][0][0][0], L, gb, hp, a.bad, R * 64 + wr * 8, fresh_tid() & 31);
}

constexpr uint32_t KB_ROW0 = SBASE + OFF_SLOT + 2048, VB_ROW0 = SBASE + OFF_SLOT + 24576 + 2048;

__device__ __forceinline__ void attention_b(const uint32_t (&q)[2][2][4], int R, int gb, uint32_t par0, int wr) {
  constexpr uint32_t bars = SBASE + OFF_BAR;
  const uint32_t dk = ((KB_ROW0 - 2048) >> 4) + 0x10000u + R * 512, dv = dk + ((VB_ROW0 - KB_ROW0) >> 4);
  float s[2][40];
  mbar_wait(bars + 8u * (B_HALO - R), par0);
  wgmma_fence();
#pragma unroll
  for (int hh = 0; hh < 2; hh++) {
    wgmma_n80_rsz_tb0(s[hh], q[hh][0], desc_lo(dk + hh * 4));
    wgmma_n80_rs_tb0(s[hh], q[hh][1], desc_lo(dk + hh * 4 + 2), 1);
  }
  wgmma_commit();
  const int lane = fresh_tid() & 31, g = lane >> 2;
  const bool odd = g & 1, edge = R == 0 && gb == 0 && wr == 0;
  const int D = 2 * (lane & 3) + (g & 1) - g;
  const uint32_t ra = q_row_addr(true, R, wr, lane);
  wgmma_wait<0>();
  reg_fence<40>(s[0]);
  reg_fence<40>(s[1]);
  float z[2][2], y[2][2];
#define GATHER_(W)                                                                                          \
  _Pragma("unroll") for (int hh = 0; hh < 2; hh++) _Pragma("unroll") for (int r = 0; r < 2; r++) {          \
    const float* e = &s[hh][4 * (2 * W + r) + 2 * r];                                                       \
    z[hh][r] = odd ? e[5] : e[4];                                                                           \
    y[hh][r] = D >= 2 ? (odd ? e[1] : e[0]) : (odd ? e[9] : e[8]);                                          \
  }
  if (wr < 2) {
    if (wr == 0) { GATHER_(0) } else { GATHER_(1) }
  } else {
    if (wr == 2) { GATHER_(2) } else { GATHER_(3) }
  }
#undef GATHER_
  float o[2][16], inv[2][2];
  uint32_t p[2][5][4];
  const int sh = odd ? 16 : 0, kb = wr + (D >= 2 ? 0 : 1);
#pragma unroll
  for (int hh = 0; hh < 2; hh++) {
    if (edge) {
      z[hh][0] = -INFINITY;
      if (D >= 2) y[hh][0] = y[hh][1] = -INFINITY;
    }
    uint32_t ab[2][2];
#pragma unroll
    for (int r = 0; r < 2; r++) {
      float m = fmaxf(z[hh][r], y[hh][r]);
      m = fmaxf(m, __shfl_xor_sync(0xffffffffu, m, 1));
      m = fmaxf(m, __shfl_xor_sync(0xffffffffu, m, 2));
      const float e0 = ex2_approx(z[hh][r] - m), e1 = ex2_approx(y[hh][r] - m);
      inv[hh][r] = e0 + e1;
      ab[r][0] = pack_bf16x2(e0, 0.f) << sh;
      ab[r][1] = pack_bf16x2(e1, 0.f) << sh;
    }
#pragma unroll
    for (int k = 0; k < 5; k++) {
      p[hh][k][0] = k == kb ? ab[0][1] : 0u;
      p[hh][k][1] = k == wr + 1 ? ab[1][0] : 0u;
      p[hh][k][2] = k == wr ? ab[0][0] : 0u;
      p[hh][k][3] = k == kb ? ab[1][1] : 0u;
#pragma unroll
      for (int j = 0; j < 4; j++) asm volatile("" : "+r"(p[hh][k][j]));
    }
  }
  wgmma_fence();
#pragma unroll
  for (int hh = 0; hh < 2; hh++) {
    wgmma_n32_rsz_tb1(o[hh], p[hh][0], desc_lo(dv + hh * 4));
#pragma unroll
    for (int k = 1; k < 5; k++) wgmma_n32_rs_tb1(o[hh], p[hh][k], desc_lo(dv + hh * 4 + k * 128), 1);
  }
  wgmma_commit();
#pragma unroll
  for (int hh = 0; hh < 2; hh++)
#pragma unroll
    for (int r = 0; r < 2; r++) {
      inv[hh][r] += __shfl_xor_sync(0xffffffffu, inv[hh][r], 1);
      inv[hh][r] += __shfl_xor_sync(0xffffffffu, inv[hh][r], 2);
      inv[hh][r] = rcp_fast(inv[hh][r]);
    }
  wgmma_wait<0>();
  reg_fence<16>(o[0]);
  reg_fence<16>(o[1]);
  store_o<0>(o[0], inv[0], ra, o_tag(1), true);
  store_o<1>(o[1], inv[1], ra, o_tag(1), true);
}

#define KTQM 0
#define TRICKLE 300
#define WTURN 15
#define QREL 8
#define PRESLEEP 200
#define QTURN 2
#define HTS(i) do { } while (0)
struct Params {
  CUtensorMap x[5], xq[4], o, wqkv[2], wqkv3[2], wo3[2];
  const __nv_bfloat16* in_x;
  const __nv_bfloat16* wqkv_p[2];
  const __nv_bfloat16* wo_p[2];
  __nv_bfloat16* out;
  uint32_t zero;
};

__device__ __forceinline__ void colsum_part(const CUtensorMap* wmap, int ty, int qr, int hp) {
  constexpr uint32_t bars = SBASE + OFF_BAR, slots = SBASE + OFF_SLOT;
  PHASE_IDS
  const unsigned ep1 = launch_epoch();
  if (wwarp == 0 && elect_one()) {
    mbar_expect_tx(bars + 8u * B_CS, 6 * UNIT);
#pragma unroll 1
    for (int j = 0; j < 6; j++) {
      if (ty == 0) mbar_pace(bars + 8u * (B_QF + B_E + (j & 3)), j >> 2);
      else __nanosleep(400);
      tma_load_2d(slots + j * UNIT, wmap, bars + 8u * B_CS, (j >> 1) * 1024 + hp * 64, qr * 128 + (j & 1) * 64);
    }
  }
  mbar_wait(bars + 8u * B_CS, ty);
  const uint32_t src = slots + (tid >> 3) * 128 + (((tid & 7) ^ ((tid >> 3) & 7)) << 4);
#pragma unroll 1
  for (int p = 0; p < 3; p++) {
    float s[8];
#pragma unroll
    for (int e = 0; e < 8; e++) s[e] = 0.f;
#pragma unroll
    for (int j = 0; j < 8; j++) {
      const uint4 v = lds128(src + p * 2 * UNIT + j * 2048);
      const uint32_t x[4] = {v.x, v.y, v.z, v.w};
#pragma unroll
      for (int e = 0; e < 4; e++) {
        s[2 * e] += bf_lo(x[e]);
        s[2 * e + 1] += bf_hi(x[e]);
      }
    }
#pragma unroll
    for (int st = 0; st < 2; st++) {
      const bool up = (lane >> (st + 3)) & 1;
#pragma unroll
      for (int e = 0; e < (4 >> st); e++) {
        const float keep = up ? s[e + (4 >> st)] : s[e], give = up ? s[e] : s[e + (4 >> st)];
        s[e] = keep + __shfl_xor_sync(0xffffffffu, give, 8 << st);
      }
    }
    const uint32_t dst = slots + 6 * UNIT + ((wwarp * 3 + p) * 64 + (lane & 7) * 8 + ((lane >> 3) & 1) * 4 + (lane >> 4) * 2) * 4;
    sts32(dst, __float_as_uint(s[0]));
    sts32(dst + 4, __float_as_uint(s[1]));
  }
  named_bar_sync(6, 128);
  if (tid < 64) {
    float r[3] = {0.f, 0.f, 0.f};
#pragma unroll
    for (int e = 0; e < 12; e++) r[e % 3] += __uint_as_float(lds32(slots + 6 * UNIT + (e * 64 + tid) * 4));
    st_rec(&g_cs[ty][hp][qr][tid], r[0], r[1], r[2], ep1);
  }
  named_bar_sync(6, 128);
}

__device__ __forceinline__ void put_colsums(int ty, int col, const float4& s) {
  const float v[3] = {s.x, s.y, s.z};
#pragma unroll
  for (int p = 0; p < 3; p++) {
    const uint32_t a = SBASE + OFF_CS + (p * 8 + (col >> 3)) * 64 + ty * 32 + (col & 7) * 2;
    const float hi = bf16_round(v[p]);
    const uint32_t w = pack_bf16x2(hi, v[p] - hi);
    asm volatile("st.shared.b16 [%0], %1;" ::"r"(a), "h"((unsigned short)w) : "memory");
    asm volatile("st.shared.b16 [%0], %1;" ::"r"(a + 16), "h"((unsigned short)(w >> 16)) : "memory");
  }
}

__device__ __forceinline__ uint32_t ln_params(float s1, float s2) {
  const float mean = s1 * (1.0f / DM);
  const float var = fmaxf(fmaf(-mean, mean, s2 * (1.0f / DM)), 0.f);
  float sd;
  asm("sqrt.approx.f32 %0, %1;" : "=f"(sd) : "f"(bf16_round(bf16_round(var) + 1e-5f)));
  return pack_bf16x2(mean, sd);
}

struct RingProd {
  uint32_t rel = ((B_QF << 1) | 1) * 0x01010101u + 0x06040200u;
  int st = 0;
  __device__ __forceinline__ uint32_t next(uint32_t bar, uint32_t par, bool wait) {
    const uint32_t e = (rel >> (8 * st)) & 255u, a = SBASE + st * 5 * UNIT;
    if (wait) mbar_wait(SBASE + OFF_BAR + 8u * B_E + 8u * (e >> 1), e & 1u);
    rel ^= (e ^ ((bar << 1) | par)) << (8 * st);
    st = (st + 1) & 3;
    return a;
  }
};

#define SP1 15
#define SP2 14
#define SP3 12
#define SP4 12
#define SP5 15
#define SP6 14
#define SP7 16
__device__ __forceinline__ int q_split(int inst) {
  constexpr uint32_t T = 15u | ((SP1 - 1) << 4) | ((SP2 - 1) << 8) | ((SP3 - 1) << 12) | ((SP4 - 1) << 16) | ((SP5 - 1) << 20) |
                         ((SP6 - 1) << 24) | ((uint32_t)(SP7 - 1) << 28);
  return (int)((T >> (4 * inst)) & 15u) + 1;
}
__host__ __device__ constexpr uint32_t turn_par(int kind) {
  const int sp[8] = {16, SP1, SP2, SP3, SP4, SP5, SP6, SP7};
  int cnt[2] = {0, 0};
  uint32_t m = 0;
  for (int i = 0; i < 8; i++)
    for (int k = 0; k < 3; k++) {
      if (k == kind) m |= (uint32_t)(cnt[i & 1] & 1) << i;
      if (k == 0 ? (i == 1 || (i > 1 && sp[i - 1] < 16)) : (k == 2 || sp[i] < 16)) cnt[i & 1]++;
    }
  return m;
}
#define PREMASK 0xBDu
__device__ __forceinline__ bool w_pre(int inst) { return (PREMASK >> inst) & 1u; }
__global__ void __launch_bounds__(512, 1) fused_kernel(const __grid_constant__ Params P) {
  extern __shared__ __align__(1024) uint8_t smem_raw[];
  constexpr uint32_t base = SBASE, bars = base + OFF_BAR, slots = base + OFF_SLOT;
  if (smem_u32(smem_raw) != base) __trap();
  const int warp = __shfl_sync(0xffffffffu, threadIdx.x >> 5, 0), lane = threadIdx.x & 31;
  const int b = blockIdx.x;
#define QS 0
#define WS 1
  const int qr = ((b & ((8 << QS) - 1)) >> QS) ^ (((b >> (3 + QS)) & 1) * 7);
  const int hp = ((b >> (3 + QS)) << QS) + (b & ((1 << QS) - 1));
  const int rt = ((b & ((16 << WS) - 1)) >> WS) ^ (((b >> (4 + WS)) & 1) * 15);
  const int ct = ((b >> (4 + WS)) << WS) + (b & ((1 << WS) - 1));

  if (warp == 12) {
    if (elect_one()) {
#pragma unroll
      for (int s = 0; s < 4; s++) {
        mbar_init(bars + 8u * (B_QF + s), 2);
        mbar_init(bars + 8u * (B_QF + B_E + s), 4);
      }
      mbar_init(bars + 8u * B_GO, 1);
      fence_barrier_init();
    }
    __syncwarp();
    named_bar_arrive(0, 512);
  }
  if (threadIdx.x == 0) {
    for (int s = B_WF; s <= B_RF; s++) {
      mbar_init(bars + 8u * s, s == B_RF ? 1 : 2);
      mbar_init(bars + 8u * (s + B_E), 4);
    }
    for (int s = 0; s < 4; s++) sts32(base + OFF_ONE + 4 * s, s == 0);
    fence_proxy_async_smem();
    mbar_init(bars + 8u * B_PREP, 1);
    mbar_init(bars + 8u * (B_PREP + 1), 1);
    mbar_init(bars + 8u * B_HL, 1);
    mbar_init(bars + 8u * (B_HL + 1), 1);
    mbar_init(bars + 8u * B_HV, 1);
    for (int s = 0; s < 4; s++) mbar_init(bars + 8u * (B_HALO + s), 1);
    for (int s = 0; s < 3; s++) mbar_init(bars + 8u * (B_REL + s), s == 0 ? 4 : 8);
    mbar_init(bars + 8u * B_LOC, 4);
    mbar_init(bars + 8u * B_AFREE, 2);
    mbar_init(bars + 8u * B_TURN, 4);
    mbar_init(bars + 8u * (B_TURN + 1), 4);
    mbar_init(bars + 8u * B_CS, 1);
    mbar_init(bars + 8u * B_PRE, 1);
    mbar_init(bars + 8u * B_PRE2, 1);
    mbar_init(bars + 8u * B_RDONE, 4);
    mbar_init(bars + 8u * B_CSD, 4);
    mbar_init(bars + 8u * B_XRDY, 1);
    mbar_init(bars + 8u * (B_XRDY + 1), 1);
    fence_barrier_init();
  }
  if (warp != 12) named_bar_sync(0, 512);

  if (warp >= 12) {
    setmaxnreg_dec<32>();
    if (warp == 12) {
      if (elect_one()) {
#pragma unroll 1
        for (int s = 0; s < 16; s++) {
          const uint32_t fb = bars + 8u * (B_QF + (s & 3)), sa = base + (s & 3) * 5 * UNIT;
          if (s >= 4) mbar_wait(fb + 8u * B_E, ((s >> 2) & 1) ^ 1);
          mbar_expect_tx(fb, 5 * UNIT);
          mbar_arrive(fb);
          tma_load_5d(sa, &P.xq[0], fb, s * 64, qr * 2);
          tma_load_3d(sa + 2 * UNIT, &P.wqkv3[0], fb, hp * 64, s * 64);
        }
        mbar_arrive(bars + 8u * B_GO);
        RingProd rp;
#pragma unroll 1
        for (int sg = 4; sg < 34; sg++) {
          const int part = sg & 3, inst = (sg >> 2) - (part & 1);
          if (part == 3 || inst == 8) continue;
          const int ty = (inst >> 1) & 1;
          if (part != 1) {
            const int k0 = part ? q_split(inst) : 0, k1 = part ? 16 : q_split(inst);
#pragma unroll 1
            for (int kt = k0; kt < k1; kt++) {
              const uint32_t sa = rp.next(B_QF + (kt & 3), (kt >> 2) & 1, true), fb = bars + 8u * (B_QF + (kt & 3));
              mbar_expect_tx(fb, 3 * UNIT);
              tma_load_3d(sa + 2 * UNIT, &P.wqkv3[ty], fb, hp * 64, kt * 64);
            }
          } else {
            const bool pre = w_pre(inst);
            const int lag = pre ? 8 : 5;
            uint32_t sa = 0;
#pragma unroll 1
            for (int kt = 0; kt < 16; kt++) {
              const int i = kt & 3;
              const uint32_t fb = bars + 8u * (B_WF + (kt & 7));
              if (i == 1) sa += 2 * UNIT;
              else if (i != 3 || !pre) sa = rp.next(kt == 14 ? B_RF : B_WF + ((kt | 1) & 7), kt == 14 ? inst & 1 : kt >> 3, kt < lag) + ((0x21 >> (2 * i)) & 3) * UNIT;
              if (kt >= lag) mbar_wait(bars + 8u * (B_WF + B_E + ((kt - lag) & 7)), (kt - lag) >> 3);
              if (i == 3 && pre) {
                mbar_arrive(fb);
              } else {
                mbar_expect_tx(fb, 2 * UNIT);
                tma_load_3d(sa, &P.wo3[ty], fb, ct * 128, kt * 64);
              }
            }
          }
        }
      }
    } else if (warp == 13) {
      RingProd rp;
      unsigned ep1 = 0;
      mbar_wait(bars + 8u * B_GO, 0);
#pragma unroll 1
      for (int sg = 4; sg < 34; sg++) {
        const int part = sg & 3, inst = (sg >> 2) - (part & 1);
        if (part == 3 || inst == 8) continue;
        const int L = inst >> 1, ch = inst & 1;
        uint32_t seen = 0;
        if (part != 1) {
          const CUtensorMap* tx = &P.xq[L];
          const int k0 = part ? q_split(inst) : 0, k1 = part ? 16 : q_split(inst);
          if (L == 0 || mbar_test(bars + 8u * (B_XRDY + ch), (L & 1) ^ 1)) {
            seen = 0xFFFFFFFFu;
            fence_proxy_async_all();
          }
          if (sg == 4) ep1 = launch_epoch();
          const int m0 = ch * 16 + qr * 2;
#pragma unroll 1
          for (int kt = k0; kt < k1; kt++) {
            wait_count(g_fx[ch * 8 + qr], 6u * ep1 - 6u + 2u * L, kt, seen, lane);
            TGET(t38);
            const uint32_t sa = rp.next(B_QF + (kt & 3), (kt >> 2) & 1, true);
            TGET(t39);
            if (elect_one()) {
              const uint32_t fb = bars + 8u * (B_QF + (kt & 3));
              mbar_expect_tx(fb, 2 * UNIT);
              tma_load_5d(sa, tx, fb, kt * 64, m0);
            }
            if (L == 3 && kt == 0 && lane == 0) { TPUT(ch, 38, t38); TPUT(ch, 39, t39); }
          }
        } else {
          const int m0 = ch * 1024 + rt * 64;
          const bool pre = w_pre(inst);
          const int lag = pre ? 8 : 5;
          uint32_t sa = 0;
#pragma unroll 1
          for (int kt = 0; kt < 16; kt++) {
            const int i = kt & 3;
            const uint32_t fb = bars + 8u * (B_WF + (kt & 7));
            wait_count(g_fo[ch * 16 + rt], 4u * ep1 - 3u + L, kt, seen, lane);
            if (i < 2) sa = rp.next(kt == 13 ? B_RF : B_WF + (kt & 7) + i + 1, kt == 13 ? inst & 1 : kt >> 3, kt < lag);
            else sa += (2 * i - 3) * UNIT;
            if (kt >= lag) mbar_wait(bars + 8u * (B_WF + B_E + ((kt - lag) & 7)), (kt - lag) >> 3);
            if (elect_one()) {
              mbar_expect_tx(fb, UNIT);
              tma_load_2d(sa, &P.o, fb, kt * 64, m0);
            }
            if (i == 3 && !pre) rp.next(B_WF + (kt & 7), kt >> 3, false);
          }
        }
      }
    } else if (warp == 14) {
      const unsigned ep1 = launch_epoch();
      uint32_t hpar = 0;
#pragma unroll 1
      for (int inst = 0; inst < 8; inst++) {
        const int L = inst >> 1, ch = inst & 1, gb = ch * 8 + qr;
        const unsigned kv0 = 8u * ep1 - 8u + 2u * L + (L & 1);
        named_bar_sync(3, 160);
        HTS(44);
        if ((L & 1) == 0) {
          uint8_t* img = g_kvA[L >> 1][gb][hp][0];
          if (elect_one()) {
            bulk_store(img + 16384, slots + 16384, 8192);
            bulk_announce(g_fk[hp][gb]);
            bulk_store(img + 24576, slots + 24576, 8192);
            bulk_announce(g_fk[hp][gb]);
            bulk_commit();
          }
          bool pub = false;
          auto publish = [&]() {
            if (!pub && mbar_test(bars + 8u * B_LOC, inst & 1)) {
              pub = true;
              HTS(45);
              if (elect_one()) {
                bulk_store(img, slots, 16384);
                bulk_announce(g_fk[hp][gb]);
                bulk_commit();
              }
            }
          };
          auto load = [&](int p) {
            const uint8_t* src = gb > (p >= 3) ? img - (p >= 3 ? 32 : 16) * 32768 + ((0x02032u >> (4 * p)) & 3u) * 8192 : g_zero;
            fence_proxy_async_all();
            if (elect_one()) {
              const uint32_t bar = bars + 8u * B_HL + 8u * (p & 1), bytes = p < 2 ? 8192 : 16384;
              mbar_expect_tx(bar, bytes);
              bulk_load(slots + ((0x40254u >> (4 * p)) & 7u) * 8192, src, bytes, bar);
            }
          };
          const unsigned* cp = g_fk[hp][max(gb - 1 - (lane >= 3), 0)];
          const unsigned ct0 = kv0 + ((0x32321u >> (4 * (lane & 7))) & 3u);
          uint32_t fr = gb == 0 ? 31u : (gb == 1 ? 24u : 0u);
          int iss = 0;
#pragma unroll 1
          for (int p = -1; p < 5; p++) {
            unsigned v = ld_relaxed_u32(cp);
            if (p >= 0) {
#pragma unroll 1
              for (int tries = 0; tries < 4096; tries++) {
#pragma unroll 1
                for (uint32_t it = 0; it < (1u << 20) && !mbar_test(bars + 8u * B_HL + 8u * (p & 1), (hpar >> (p & 1)) & 1u); ++it) publish();
                hpar ^= 1u << (p & 1);
                const uint32_t dst = slots + lane * 128 + ((lane & 7) << 4) + ((0x40254u >> (4 * p)) & 7u) * 8192;
                uint32_t t = (lds32(dst) ^ ep1) | (lds32(dst + 4096) ^ ep1);
                if (p >= 2) t |= (lds32(dst + 8192) ^ ep1) | (lds32(dst + 12288) ^ ep1);
                if (gb <= (p >= 3) || !__any_sync(0xffffffffu, t & 1u)) break;
                fence_proxy_async_smem();
                load(p);
              }
              if (lane == 0) mbar_arrive(bars + 8u * (p == 1 ? B_HV : B_HALO + max(p - 1, 0)));
              HTS(52 + p);
            }
#pragma unroll 1
            for (uint32_t it = 0; it < (1u << 18) && iss < min(p + 3, 5); ++it) {
              if (!((fr >> iss) & 1u)) {
                if (it > 0) v = ld_relaxed_u32(cp);
                fr |= __ballot_sync(0xffffffffu, (int)(v - ct0) >= 0);
              }
              publish();
              if (((fr >> iss) & 1u) && (iss < 2 || (pub && mbar_test(bars + 8u * (B_REL - 2) + 8u * iss, ch)))) {
                if (iss >= 2 && elect_one()) {
                  if (iss == 2) asm volatile("cp.async.bulk.wait_group.read 1;" ::: "memory");
                  else bulk_wait_read0();
                }
                HTS(46 + iss);
                load(iss++);
              } else if (iss == p + 2 && p >= 0) {
                break;
              }
            }
          }
        } else {
          uint8_t* img = g_kvB[L >> 1][gb][hp];
          if (elect_one()) {
            bulk_store(img, KB_ROW0 + 112 * 128, 2048);
            bulk_store(img + 2048, VB_ROW0 + 112 * 128, 2048);
            bulk_announce(g_fk[hp][gb]);
            bulk_commit();
          }
          const uint8_t* src = gb >= 1 ? img - 16 * 4096 : g_zero;
#pragma unroll 1
          for (uint32_t it = 0; it < (1u << 17); ++it)
            if (gb == 0 || (int)(ld_relaxed_u32(g_fk[hp][gb - 1]) - kv0) > 0) break;
          HTS(46);
#pragma unroll 1
          for (uint32_t it = 0; it < 4096; ++it) {
            fence_proxy_async_all();
            if (elect_one()) {
              mbar_expect_tx(bars + 8u * B_HL, 4096);
              bulk_load(KB_ROW0 - 2048, src, 2048, bars + 8u * B_HL);
              bulk_load(VB_ROW0 - 2048, src + 2048, 2048, bars + 8u * B_HL);
              bulk_wait_read0();
            }
            mbar_wait(bars + 8u * B_HL, hpar & 1u);
            hpar ^= 1u;
            const uint32_t t = lds32((lane < 16 ? KB_ROW0 - 2048 : VB_ROW0 - 4096) + lane * 128 + ((lane & 7) << 4)) ^ ep1;
            if (gb == 0 || !__any_sync(0xffffffffu, t & 1u)) break;
            fence_proxy_async_smem();
          }
          if (lane == 0) mbar_arrive(bars + 8u * B_HALO);
          HTS(52);
        }
        if (elect_one()) {
          mbar_wait(bars + 8u * B_AFREE, inst & 1);
          mbar_expect_tx(bars + 8u * B_RF, 2 * UNIT);
          tma_load_2d(slots + 6 * UNIT, &P.x[L], bars + 8u * B_RF, ct * 128, ch * 1024 + rt * 64);
          tma_load_2d(slots + 7 * UNIT, &P.x[L], bars + 8u * B_RF, ct * 128 + 64, ch * 1024 + rt * 64);
          if (w_pre(inst)) {
            if (inst == 1) mbar_wait(bars + 8u * B_CSD, 0);
            mbar_expect_tx(bars + 8u * B_PRE, 6 * UNIT);
            mbar_expect_tx(bars + 8u * B_PRE2, 2 * UNIT);
#pragma unroll 1
            for (int j = 0; j < 4; j++) {
              __nanosleep(PRESLEEP);
              if (j == 3) mbar_wait(bars + 8u * B_RDONE, (inst & 1) ^ 1);
              tma_load_3d(slots + j * 2 * UNIT, &P.wo3[L & 1], bars + 8u * (j == 3 ? B_PRE2 : B_PRE), ct * 128, (4 * j + 3) * 64);
            }
          }
        }
        __syncwarp();
      }
    } else {
      const unsigned ep1 = launch_epoch();
      mbar_wait(bars + 8u * B_GO, 0);
#pragma unroll 1
      for (int i = 0; i < 20; i++) {
        const char* src = i < 4 ? reinterpret_cast<const char*>(P.wo_p[0]) + (size_t)b * 16384 + i * 4096
                                : (i < 16 ? reinterpret_cast<const char*>(P.wqkv_p[1]) + (size_t)b * 49152 + (i - 4) * 4096
                                          : reinterpret_cast<const char*>(P.wo_p[1]) + (size_t)b * 16384 + (i - 16) * 4096);
        asm volatile("prefetch.global.L2 [%0];" ::"l"(src + lane * 128));
        __nanosleep(TRICKLE);
      }
#pragma unroll 1
      for (int inst = 2; inst < 8; inst++) {
        const int L = inst >> 1, ch = inst & 1, gb = ch * 8 + qr;
        mbar_wait_lazy<200>(bars + 8u * (B_RF + B_E), inst & 1);
#pragma unroll 1
        for (int h = 0; h < 4; h++) {
          const float4* sp = &g_stats[L][0][gb * 128 + h * 32 + lane];
          const float4 s0 = sum_recs<4>(sp, S_LEN, ep1), s1 = sum_recs<4>(sp + 4 * S_LEN, S_LEN, ep1);
          sts32(base + OFF_RS + (ch * 128 + h * 32 + lane) * 4, ln_params(s0.x + s1.x, s0.y + s1.y));
        }
        if (lane == 0) mbar_arrive(bars + 8u * (B_XRDY + ch));
        if (inst == 2) {
          mbar_wait(bars + 8u * B_CSD, 0);
#pragma unroll 1
          for (int hf = 0; hf < 2; hf++) {
            const float4* cp = &g_cs[1][hp][0][hf * 32 + lane];
            const float4 s0 = sum_recs<4>(cp, 64, ep1), s1 = sum_recs<4>(cp + 4 * 64, 64, ep1);
            put_colsums(1, hf * 32 + lane, make_float4(s0.x + s1.x, s0.y + s1.y, s0.z + s1.z, 0.f));
          }
        }
        fence_proxy_async_smem();
        __syncwarp();
        if (lane == 0) mbar_arrive(bars + 8u * (B_PREP + ch));
      }
    }
  } else {
    const bool asst = warp >= 8;
    GTL(0);
    if (asst) {
      colsum_part(&P.wqkv[0], 0, qr, hp);
      if ((threadIdx.x & 127) < 4) mbar_arrive(bars + 8u * B_RDONE);
    } else if (warp >= 4) {
      PHASE_IDS
      {
        const unsigned ep1 = launch_epoch();
        const int row = b * 16 + (tid >> 3);
        const uint4* src = reinterpret_cast<const uint4*>(P.in_x + (size_t)row * DM) + (tid & 7);
        float s1 = 0.f, s2 = 0.f;
#pragma unroll 1
        for (int k = 0; k < 4; k++) {
          mbar_pace(bars + 8u * (B_QF + B_E + ((2 * k) & 3)), k >> 1);
          uint4 v[4];
#pragma unroll
          for (int j = 0; j < 4; j++) v[j] = __ldg(src + (k * 4 + j) * 8);
#pragma unroll
          for (int j = 0; j < 4; j++) {
            const uint32_t w[4] = {v[j].x, v[j].y, v[j].z, v[j].w};
#pragma unroll
            for (int e = 0; e < 4; e++) {
              const float x0 = bf_lo(w[e]), x1 = bf_hi(w[e]);
              s1 += x0 + x1;
              s2 = fmaf(x0, x0, fmaf(x1, x1, s2));
            }
          }
        }
#pragma unroll
        for (int o = 1; o < 8; o <<= 1) {
          s1 += __shfl_xor_sync(0xffffffffu, s1, o);
          s2 += __shfl_xor_sync(0xffffffffu, s2, o);
        }
        if ((tid & 7) == 0) st_rec(&g_stats[0][0][row], s1, s2, 0.f, ep1);
        if (tid == 0) sts32(base + OFF_EPOCH, ep1);
        if (tid < 64) {
          const float4 s0 = sum_recs<8>(&g_cs[0][hp][0][tid], 64, ep1);
          put_colsums(0, tid, s0);
        } else {
          put_colsums(1, tid - 64, make_float4(0.f, 0.f, 0.f, 0.f));
        }
#pragma unroll 1
        for (int cc = 0; cc < 2; cc++) {
          const float4 s0 = sum_recs<1>(&g_stats[0][0][(cc * 8 + qr) * 128 + tid], 0, ep1);
          sts32(base + OFF_RS + (cc * 128 + tid) * 4, ln_params(s0.x, s0.y));
        }
        fence_proxy_async_smem();
        named_bar_sync(2, 128);
        if (tid < 2) mbar_arrive(bars + 8u * (B_PREP + tid));
      }
    }
#pragma unroll 1
    for (int inst = asst ? 0 : warp >> 2; inst < 8; inst += asst ? 1 : 2) {
      const int L = inst >> 1, ch = inst & 1, gb = ch * 8 + qr;
      uint32_t q[2][2][4];
      if (asst) {
        setmaxnreg_dec<24>();
        named_bar_sync(4, 256);
        setmaxnreg_inc<128>();
        const uint32_t ra = q_row_addr(L & 1, 1, warp & 3, fresh_tid() & 31);
#pragma unroll
        for (int j = 0; j < 4; j++) ldmatrix_x4(q[j >> 1][j & 1], ra ^ (j << 5));
      } else {
      setmaxnreg_inc<224>();
      {
        float acc[2][96];
        const int ksp = q_split(inst);
        constexpr uint32_t STG = 5 * (UNIT >> 4), D0 = (base >> 4) + 0x10000u;
        constexpr uint32_t DB = ((UNIT >> 4) << 16) - 0x10000u + 2 * (UNIT >> 4);
        uint32_t sd = D0;
        uint32_t tand = 1u, tor = 0u, tw = 0u;
        const uint32_t toff = ((fresh_tid() & 127) << 7) + ((fresh_tid() & 7) << 4);
        bool lane0 = (toff & 0xf80u) == 0u;
        if (inst == 1 || (inst > 1 && q_split(inst - 1) < 16)) mbar_wait_lazy<100>(bars + 8u * (B_TURN + ch), (turn_par(0) >> inst) & 1u);
        if (L == 3) GTL(37);
        mbar_wait(bars + 8u * B_QF, 0);
        GTL(1 + L * 8);
        {
          const uint64_t da = desc_lo(sd) + P.zero;
          wgmma_fence();
          wgmma_n192_ssz_ta0_tb1(acc[1], da + (UNIT >> 4), da + DB);
          wgmma_commit();
          wgmma_n192_ssz_ta0_tb1(acc[0], da, da + DB);
          wgmma_commit();
        }
#pragma unroll 1
        for (int kt = 0; kt < 15; kt++) {
          const bool last = kt + 1 == ksp;
          const uint64_t da = desc_lo(sd) + P.zero;
          const uint32_t fn = bars + 8u * (B_QF + ((kt + 1) & 3)), pn = ((kt + 1) >> 2) & 1;
#pragma unroll
          for (int k16 = 0; k16 < 4; k16++) {
            if (k16 == 0 && kt == 0) continue;
            wgmma_fence();
            wgmma_n192_ss_ta0_tb1(acc[1], da + ((UNIT >> 4) + k16 * 2), da + (DB + k16 * 128), 1);
            wgmma_commit();
            wgmma_wait<1>();
            if (k16 == 0 && lane0 && kt != ksp) mbar_arrive(bars + 8u * (B_QF + B_E + ((kt - 1) & 3)));
            wgmma_fence();
            wgmma_n192_ss_ta0_tb1(acc[0], da + k16 * 2, da + (DB + k16 * 128), 1);
            wgmma_commit();
            if (k16 == 1) tw = lds32(((sd & 0xffffu) << 4) + toff);
            if (k16 == 2) {
              tand &= tw;
              tor |= tw;
            }
            bool ok = true;
            if (k16 == 2) ok = mbar_test(fn, pn) || last;
            if (k16 == QTURN && last && lane0) mbar_arrive(bars + 8u * (B_TURN + (ch ^ 1)));
            if (k16 < 3) wgmma_wait<1>();
            if (k16 == 2 && !ok) mbar_wait(fn, pn);
          }
          sd = sd == D0 + 3 * STG ? D0 : sd + STG;
          if (last) {
            wgmma_wait<0>();
            if (lane0) mbar_arrive(bars + 8u * (B_QF + B_E + (kt & 3)));
            mbar_wait_lazy<100>(bars + 8u * (B_TURN + ch), (turn_par(1) >> inst) & 1u);
            mbar_wait(fn, pn);
          }
        }
        PHASE_IDS_W
        lane0 = lane == 0;
        constexpr uint32_t DL = D0 + 3 * STG;
        wgmma_fence();
#pragma unroll
        for (int k16 = 0; k16 < 4; k16++) wgmma_n192_ss_ta0_tb1(acc[1], desc_lo(DL + (UNIT >> 4) + k16 * 2), desc_lo(DL + DB + k16 * 128), 1);
        wgmma_commit();
        tw = lds32(((DL & 0xffffu) << 4) + toff);
        mbar_wait(bars + 8u * (B_PREP + ch), L & 1);
        const uint32_t rsa = base + OFF_RS + (ch * 128 + tile_row(L & 1, wwarp, 0, g)) * 4, rsd = (L & 1) ? 32 : 128;
        uint32_t rs[2][2];
        const uint32_t ep1 = __shfl_sync(0xffffffffu, lds32(base + OFF_EPOCH), 0);
        constexpr uint64_t DCS = (uint64_t)((base + OFF_CS) >> 4) | (4ull << 32);
        auto ln_mma = [&](float (&d)[96], uint32_t (&r)[2], int h) {
          uint32_t a[4];
#pragma unroll
          for (int i = 0; i < 2; i++) {
            r[i] = lds32(rsa + h * 256 + i * rsd);
            a[i] = c == (L & 1) ? __byte_perm(r[i], 0u, 0x1010) ^ 0x80008000u : 0u;
            a[i + 2] = r[i] & P.zero;
          }
#pragma unroll
          for (int i = 0; i < 4; i++) asm volatile("" : "+r"(a[i]));
          wgmma_fence();
          wgmma_n192_rs_tb1(d, a, DCS, 1);
          wgmma_commit();
        };
        wgmma_wait<1>();
        if (lane0 && ksp != 15) mbar_arrive(bars + 8u * (B_QF + B_E + 2));
        ln_mma(acc[1], rs[1], 1);
#pragma unroll
        for (int k16 = 0; k16 < 4; k16++) wgmma_n192_ss_ta0_tb1(acc[0], desc_lo(DL + k16 * 2), desc_lo(DL + DB + k16 * 128), 1);
        wgmma_commit();
        tand &= tw;
        tor |= tw;
        const bool redo = named_bar_or(1 + ch, 128, L > 0 && (((x_tag(ep1, L) ? ~tand : tor) & 1u) != 0u));
        if (ksp < 16) mbar_wait(bars + 8u * (B_WF + B_E + 7), 1);
        const bool afree = mbar_test(bars + 8u * B_RDONE, inst & 1);
        float rinv[2];
#pragma unroll
        for (int r = 0; r < 2; r++) rinv[r] = rcp_fast(bf_hi(rs[1][r]));
        const uint32_t soff = tile_row(L & 1, wwarp, (lane >> 3) & 1, lane & 7) * 128 + (((lane >> 4) ^ (lane & 7)) << 4);
        const uint32_t kdst = ((L & 1) ? KB_ROW0 : slots) + soff, vdst = ((L & 1) ? VB_ROW0 : slots + 8192) + soff;
        const uint32_t hs = (L & 1) ? 8192 : 16384;
        wgmma_wait<1>();
        if (lane0) mbar_arrive(bars + 8u * (B_TURN + (ch ^ 1)));
        if (redo) {
          wgmma_wait<0>();
          constexpr uint32_t sa = (DL & 0xffffu) << 4;
          const uint32_t rb = bars + 8u * (B_REDO + ch);
          if (toff == 0) {
            mbar_init(rb, 1);
            fence_barrier_init();
          }
          uint32_t rpar = 0;
#pragma unroll 1
          for (int kt = 0, tries = 0; kt < 16;) {
            fence_proxy_async_smem();
            named_bar_sync(1 + ch, 128);
            if ((warp & 3) == 0 && elect_one()) {
              fence_proxy_async_all();
              mbar_expect_tx(rb, 5 * UNIT);
              tma_load_5d(sa, &P.xq[L], rb, kt * 64, gb * 2);
              tma_load_3d(sa + 2 * UNIT, &P.wqkv3[L & 1], rb, hp * 64, kt * 64);
            }
            mbar_wait(rb, rpar);
            rpar ^= 1u;
            if (named_bar_or(1 + ch, 128, (lds32(sa + toff) ^ x_tag(ep1, L)) & 1u) && ++tries < 4096) continue;
            wgmma_fence();
#pragma unroll
            for (int k16 = 0; k16 < 4; k16++) {
              const uint64_t db = make_desc(sa + 2 * UNIT + k16 * 2048, UNIT);
              wgmma_n192_ss_ta0_tb1(acc[1], make_desc(sa + UNIT + k16 * 32, 16), db, kt | k16);
              wgmma_n192_ss_ta0_tb1(acc[0], make_desc(sa + k16 * 32, 16), db, kt | k16);
            }
            wgmma_commit();
            wgmma_wait<0>();
            kt++;
          }
          ln_mma(acc[1], rs[1], 1);
          wgmma_wait<0>();
        }
        ln_mma(acc[0], rs[0], 0);
        reg_fence<96>(acc[1]);
        GTL(2 + L * 8);
        if (!afree) mbar_wait(bars + 8u * B_RDONE, inst & 1);
#pragma unroll
        for (int t = 0; t < 24; t++) {
          const int h = t < 12 ? 1 : 0, p = ((t % 12) / 4 + 1) % 3, jp = t & 3;
          if (t == QREL) {
            wgmma_wait<0>();
            reg_fence<96>(acc[0]);
            if (lane0) mbar_arrive(bars + 8u * (B_QF + B_E + 3));
          }
          if (t == 8 || t == 20) {
            rinv[0] *= SM_C;
            rinv[1] *= SM_C;
          }
          const float* a = &acc[h][4 * (p * 8 + 2 * jp)];
          uint32_t r0 = pack_bf16x2(a[0] * rinv[0], a[1] * rinv[0]);
          uint32_t r1 = pack_bf16x2(a[2] * rinv[1], a[3] * rinv[1]);
          if (p != 0 && jp == 0) {
            r0 = set_tag(r0, c == 0, ep1);
            r1 = set_tag(r1, c == 0, ep1);
          }
          const uint32_t r2 = pack_bf16x2(a[4] * rinv[0], a[5] * rinv[0]);
          const uint32_t r3 = pack_bf16x2(a[6] * rinv[1], a[7] * rinv[1]);
          const uint32_t dst = p == 0 ? slots + 3 * 16384 + soff + h * 8192 : (p == 1 ? kdst : vdst) + h * hs;
          stmatrix_x4(dst ^ (jp << 5), r0, r1, r2, r3);
          if (t >= 20) {
            q[jp >> 1][jp & 1][0] = r0;
            q[jp >> 1][jp & 1][1] = r1;
            q[jp >> 1][jp & 1][2] = r2;
            q[jp >> 1][jp & 1][3] = r3;
          }
          if (t == 7 || t == 19) {
            fence_proxy_async_smem();
            if (t == 7) {
              named_bar_arrive(3, 160);
            } else {
              __syncwarp();
              if (lane0) mbar_arrive(bars + 8u * B_LOC);
            }
          }
          if (t == 11) {
            setmaxnreg_dec<128>();
            named_bar_arrive(4, 256);
#pragma unroll
            for (int r = 0; r < 2; r++) rinv[r] = rcp_fast(bf_hi(rs[0][r]));
          }
        }
        mbar_wait(bars + 8u * B_LOC, inst & 1);
      }
      }
      GTL(3 + L * 8);
      if ((L & 1) == 0) attention_a(q, asst, L, gb, hp, ch, warp & 3, P.zero);
      else attention_b(q, asst, gb, inst & 1, warp & 3);
      GTL(4 + L * 8);
      fence_proxy_async_smem();
      named_bar_sync(asst ? 6 : 1 + ch, 128);
      if ((warp & 3) == 0) {
        if (elect_one()) {
          tma_store_2d(&P.o, slots + 3 * 16384 + asst * 8192, hp * 64, gb * 128 + asst * 64);
          bulk_commit();
          bulk_wait0();
          red_announce(&g_fo[gb * 2 + asst][hp]);
          mbar_arrive(bars + 8u * B_AFREE);
        }
        __syncwarp();
      }
      if (asst) {
        if (inst == 1) {
          mbar_wait(bars + 8u * B_RDONE, 0);
          colsum_part(&P.wqkv[1], 1, qr, hp);
          if ((fresh_tid() & 31) == 0) mbar_arrive(bars + 8u * B_CSD);
        }
        continue;
      }
      GTL(5 + L * 8);

      {
        float acc[64];
        const int sp = inst < 7 ? q_split(inst + 1) : 0;
        int st = sp & 3;
        const bool pre = w_pre(inst);
        uint32_t tbad = 0u;
        const uint32_t toff = ((fresh_tid() & 63) << 7) + ((fresh_tid() & 7) << 4);
        const bool lane0 = (toff & 0xf80u) == 0u;
        constexpr uint32_t U4 = UNIT >> 4, LA = 0x10000u, LB = U4 << 16;
        reg_define<64>(acc);
        reg_fence<64>(acc);
        uint32_t xv[8][4];
        {
          PHASE_IDS_W
          const uint32_t xr = slots + 6 * UNIT + (wwarp * 16 + (lane & 15)) * 128 + (((lane >> 4) ^ (lane & 7)) << 4);
          mbar_wait(bars + 8u * B_RF, inst & 1);
#pragma unroll
          for (int jp = 0; jp < 8; jp++) ldmatrix_x4(xv[jp], (xr ^ ((jp & 3) << 5)) + (jp >> 2) * UNIT);
          fence_proxy_async_smem();
          __syncwarp();
          if (lane0) mbar_arrive(bars + 8u * B_RDONE);
          if (L > 0) {
            uint32_t lsb;
            asm volatile("ld.shared.u8 %0, [%1];" : "=r"(lsb) : "r"(base + OFF_LSB + ch * 32 + wwarp * 8 + g) : "memory");
#pragma unroll
            for (int k = 0; k < 4; k++) xv[(k >> 1) * 4][k & 1] = set_tag(xv[(k >> 1) * 4][k & 1], c == 0, lsb >> k);
          }
        }
        uint64_t d0 = desc_lo((base >> 4) + st * 5 * U4) + P.zero;
        if (inst < 7 || SP7 == 16) mbar_wait_lazy<100>(bars + 8u * (B_TURN + ch), (turn_par(2) >> inst) & 1u);
        mbar_wait(bars + 8u * B_WF, 0);
        GTL(6 + L * 8);
        uint32_t s1 = 0;
#pragma unroll 1
        for (int m = 0; m < 4; m++) {
          const uint32_t s0 = base + st * 5 * UNIT, fb = bars + 8u * (B_WF + 4 * (m & 1));
          s1 = base + ((st + 1) & 3) * 5 * UNIT;
          const uint64_t d1 = desc_lo(s1 >> 4) + P.zero;
          const uint64_t d2 = desc_lo((pre ? slots + m * 2 * UNIT : base + ((st + 2) & 3) * 5 * UNIT) >> 4) + P.zero;
          st = (st + (pre ? 2 : 3)) & 3;
#pragma unroll
          for (int i = 0; i < 4; i++) {
            const uint64_t da = (i == 0 ? d0 : d1) + (LA + (i == 2 ? 1 : (i == 3 ? 4 : 0)) * U4);
            const uint64_t db = (i < 2 ? d0 : (i == 2 ? d1 : d2)) + (LB + (i == 0 ? 1 : (i == 1 ? 3 : (i == 2 ? 2 : 0))) * U4);
            if (i == 3 && (m == 0 || m == 3) && pre) mbar_wait(bars + 8u * (m ? B_PRE2 : B_PRE), __popc(PREMASK & ((1u << inst) - 1u)) & 1);
            if (i == (WTURN & 3) && m == 3 && lane0 && (sp < 16 || inst == 6)) mbar_arrive(bars + 8u * (B_TURN + (ch ^ 1)));
            wgmma_fence();
#pragma unroll
            for (int k16 = 0; k16 < 4; k16++) wgmma_n128_ss_ta0_tb1(acc, da + 2 * k16, db + 128 * k16, 1);
            wgmma_commit();
            if (i == 2) d0 = desc_lo((base >> 4) + st * 5 * U4) + P.zero;
            tbad |= lds32((i == 0 ? s0 : s1) + (i == 2 ? 1 : (i == 3 ? 4 : 0)) * UNIT + toff) ^ o_tag(L);
            const uint32_t fn = i < 3 ? fb + 8u * (i + 1) : fb ^ 96u;
            const uint32_t pn = i < 3 ? m >> 1 : m > 0;
            const bool ok = mbar_test(fn, pn) || (i == 3 && m == 3);
            wgmma_wait<1>();
            if (lane0 && (i > 0 || m > 0)) mbar_arrive((i > 0 ? fb + 8u * (i - 1) : (fb ^ 96u) + 24u) + 8u * B_E);
            if (!ok) mbar_wait(fn, pn);
          }
        }
        const uint32_t xb = s1;
        const bool redo = named_bar_or(1 + ch, 128, tbad & 1u);
        if (redo) {
          wgmma_wait<0>();
          const uint32_t sa = s1 + 4 * UNIT, sb = s1 + 2 * UNIT;
          const uint32_t rb = bars + 8u * (B_REDO + ch);
          if ((fresh_tid() & 127) == 0) {
            mbar_init(rb, 1);
            fence_barrier_init();
          }
          uint32_t rpar = 0;
#pragma unroll 1
          for (int kt = 0, tries = 0; kt < 16;) {
            fence_proxy_async_smem();
            named_bar_sync(1 + ch, 128);
            if ((warp & 3) == 0 && elect_one()) {
              fence_proxy_async_all();
              mbar_expect_tx(rb, 3 * UNIT);
              tma_load_2d(sa, &P.o, rb, kt * 64, ch * 1024 + rt * 64);
              tma_load_3d(sb, &P.wo3[L & 1], rb, ct * 128, kt * 64);
            }
            mbar_wait(rb, rpar);
            rpar ^= 1u;
            if (named_bar_or(1 + ch, 128, (lds32(sa + toff) ^ o_tag(L)) & 1u) && ++tries < 4096) continue;
            wgmma_fence();
#pragma unroll
            for (int k16 = 0; k16 < 4; k16++)
              wgmma_n128_ss_ta0_tb1(acc, make_desc(sa + k16 * 32, 16), make_desc(sb + k16 * 2048, UNIT), kt | k16);
            wgmma_commit();
            wgmma_wait<0>();
            kt++;
          }
        }
        PHASE_IDS_W
        const uint32_t xrow = xb + (wwarp * 16 + (lane & 15)) * 128 + (((lane >> 4) ^ (lane & 7)) << 4);
        const unsigned ep1 = __shfl_sync(0xffffffffu, lds32(base + OFF_EPOCH), 0);
        const uint32_t tm = c == 0, lsa = base + OFF_LSB + ch * 32 + wwarp * 8 + g;
        wgmma_wait<0>();
        reg_fence<64>(acc);
        if (lane0) mbar_arrive(bars + 8u * (B_WF + B_E + 7));
        GTL(7 + L * 8);
        const uint32_t tmx = L < 3 ? tm : 0u, xt = x_tag(ep1, L + 1);
        const int grow = ch * 1024 + rt * 64;
#pragma unroll
        for (int jp = 0; jp < 8; jp++) {
#pragma unroll
          for (int q = 0; q < 4; q++) xv[jp][q] = add_bf16x2(xv[jp][q], pack_bf16x2(acc[8 * jp + 2 * q], acc[8 * jp + 2 * q + 1]));
          const bool tg = (jp & 3) == 0;
          stmatrix_x4((xrow ^ ((jp & 3) << 5)) + (jp >> 2) * UNIT,
                      tg ? set_tag(xv[jp][0], tmx, xt) : xv[jp][0], tg ? set_tag(xv[jp][1], tmx, xt) : xv[jp][1], xv[jp][2], xv[jp][3]);
          if ((jp & 3) == 3) {
            fence_proxy_async_smem();
            if (wwarp == jp >> 2) {
              named_bar_sync(8 + 2 * ch + (jp >> 2), 128);
              if (elect_one()) {
                tma_store_2d(&P.x[L + 1], xb + (jp >> 2) * UNIT, ct * 128 + (jp >> 2) * 64, grow);
                bulk_commit();
              }
              __syncwarp();
            } else {
              named_bar_arrive(8 + 2 * ch + (jp >> 2), 128);
            }
            if (L == 2 && jp == 3) GTL(36);
          }
        }
        if (elect_one()) {
          bulk_wait0();
          if (L < 3 && wwarp < 2) red_announce(&g_fx[ch * 8 + (rt >> 1)][ct * 2 + wwarp]);
          mbar_arrive(bars + 8u * (B_RF + B_E));
        }
        __syncwarp();
        if (L < 3) {
          if (c == 0)
            asm volatile("st.shared.u8 [%0], %1;" ::"r"(lsa),
                         "r"((xv[0][0] & 1u) | ((xv[0][1] & 1u) << 1) | ((xv[4][0] & 1u) << 2) | ((xv[4][1] & 1u) << 3)) : "memory");
          float s1[2] = {0.f, 0.f}, s2[2] = {0.f, 0.f};
#pragma unroll
          for (int jp = 0; jp < 8; jp++)
#pragma unroll
            for (int q = 0; q < 4; q++) {
              const float x0 = bf_lo(xv[jp][q]), x1 = bf_hi(xv[jp][q]);
              s1[q & 1] += x0 + x1;
              s2[q & 1] = fmaf(x0, x0, fmaf(x1, x1, s2[q & 1]));
            }
#pragma unroll
          for (int r = 0; r < 2; r++) {
            s1[r] += __shfl_xor_sync(0xffffffffu, s1[r], 1);
            s2[r] += __shfl_xor_sync(0xffffffffu, s2[r], 1);
            s1[r] += __shfl_xor_sync(0xffffffffu, s1[r], 2);
            s2[r] += __shfl_xor_sync(0xffffffffu, s2[r], 2);
            if (c == 0) st_rec(&g_stats[L + 1][ct][grow + wwarp * 16 + g + 8 * r], s1[r], s2[r], 0.f, ep1);
          }
        }
        GTL(8 + L * 8);
      }
    }
    if (threadIdx.x == 128) atomicAdd(g_done, 1u);
  }
}

typedef CUresult (*PFN_tmEncode)(CUtensorMap*, CUtensorMapDataType, cuuint32_t, void*, const cuuint64_t*,
                                 const cuuint64_t*, const cuuint32_t*, const cuuint32_t*, CUtensorMapInterleave,
                                 CUtensorMapSwizzle, CUtensorMapL2promotion, CUtensorMapFloatOOBfill);

PFN_tmEncode get_encode_fn() {
  static PFN_tmEncode fn = nullptr;
  if (!fn) {
    cudaDriverEntryPointQueryResult qr;
    void* p = nullptr;
    cudaGetDriverEntryPoint("cuTensorMapEncodeTiled", &p, cudaEnableDefault, &qr);
    fn = (PFN_tmEncode)p;
  }
  return fn;
}

CUtensorMap make_map(const void* ptr, int rows, int cols) {
  CUtensorMap m;
  cuuint64_t gdim[2] = {(cuuint64_t)cols, (cuuint64_t)rows};
  cuuint64_t gstr[1] = {(cuuint64_t)cols * 2};
  cuuint32_t box[2] = {64, 64};
  cuuint32_t estr[2] = {1, 1};
  get_encode_fn()(&m, CU_TENSOR_MAP_DATA_TYPE_BFLOAT16, 2, const_cast<void*>(ptr), gdim, gstr, box, estr,
                  CU_TENSOR_MAP_INTERLEAVE_NONE, CU_TENSOR_MAP_SWIZZLE_128B, CU_TENSOR_MAP_L2_PROMOTION_L2_128B,
                  CU_TENSOR_MAP_FLOAT_OOB_FILL_NONE);
  return m;
}

CUtensorMap make_map3(const void* ptr, int rows, int cols, int n, int step) {
  CUtensorMap m;
  cuuint64_t gdim[3] = {(cuuint64_t)(cols - (n - 1) * step), (cuuint64_t)rows, (cuuint64_t)n};
  cuuint64_t gstr[2] = {(cuuint64_t)cols * 2, (cuuint64_t)step * 2};
  cuuint32_t box[3] = {64, 64, (cuuint32_t)n};
  cuuint32_t estr[3] = {1, 1, 1};
  get_encode_fn()(&m, CU_TENSOR_MAP_DATA_TYPE_BFLOAT16, 3, const_cast<void*>(ptr), gdim, gstr, box, estr,
                  CU_TENSOR_MAP_INTERLEAVE_NONE, CU_TENSOR_MAP_SWIZZLE_128B, CU_TENSOR_MAP_L2_PROMOTION_L2_128B,
                  CU_TENSOR_MAP_FLOAT_OOB_FILL_NONE);
  return m;
}

CUtensorMap make_map_q(const void* ptr, int sw, int sr) {
  CUtensorMap m;
  cuuint64_t gdim[5] = {DM, 8, 2, 4, S_LEN / 64};
  cuuint64_t gstr[4] = {DM * 2, (cuuint64_t)sr * DM * 2, (cuuint64_t)sw * DM * 2, 64 * DM * 2};
  cuuint32_t box[5] = {64, 8, 2, 4, 2};
  cuuint32_t estr[5] = {1, 1, 1, 1, 1};
  get_encode_fn()(&m, CU_TENSOR_MAP_DATA_TYPE_BFLOAT16, 5, const_cast<void*>(ptr), gdim, gstr, box, estr,
                  CU_TENSOR_MAP_INTERLEAVE_NONE, CU_TENSOR_MAP_SWIZZLE_128B, CU_TENSOR_MAP_L2_PROMOTION_L2_128B,
                  CU_TENSOR_MAP_FLOAT_OOB_FILL_NONE);
  return m;
}

}

extern "C" void kernel_launch(void* const* d_in, const int* in_sizes, int n_in, void* d_out, int out_size) {
  (void)in_sizes; (void)n_in; (void)out_size;
  void *p_o, *p_x;
  cudaGetSymbolAddress(&p_o, g_o);
  cudaGetSymbolAddress(&p_x, g_x);
  static bool attr_done = false;
  if (!attr_done) {
    cudaFuncSetAttribute(fused_kernel, cudaFuncAttributeMaxDynamicSharedMemorySize, SMEM_BYTES);
    attr_done = true;
  }
  Params P;
  P.in_x = (const __nv_bfloat16*)d_in[0];
  P.wqkv_p[0] = (const __nv_bfloat16*)d_in[1];
  P.wo_p[0] = (const __nv_bfloat16*)d_in[2];
  P.wqkv_p[1] = (const __nv_bfloat16*)d_in[4];
  P.wo_p[1] = (const __nv_bfloat16*)d_in[5];
  P.out = (__nv_bfloat16*)d_out;
  P.zero = 0;
  for (int L = 0; L < 5; L++) {
    const void* px = L == 0 ? (const void*)P.in_x : (L == 4 ? d_out : p_x);
    P.x[L] = make_map(px, S_LEN, DM);
    if (L < 4) P.xq[L] = (L & 1) ? make_map_q(px, 16, 8) : make_map_q(px, 8, 32);
  }
  P.o = make_map(p_o, S_LEN, DM);
  for (int t = 0; t < 2; t++) {
    P.wqkv[t] = make_map(P.wqkv_p[t], DM, NQKV);
    P.wqkv3[t] = make_map3(P.wqkv_p[t], DM, NQKV, 3, 1024);
    P.wo3[t] = make_map3(P.wo_p[t], DM, DM, 2, 64);
  }
  fused_kernel<<<NCTA, 512, SMEM_BYTES>>>(P);
}
```

```cpp
#include <cuda_runtime.h>
#include <cuda_bf16.h>
#include <cuda.h>
#include <stdint.h>

namespace {

constexpr int S_LEN = 2048;
constexpr int DM = 1024;
constexpr int NQKV = 3072;
constexpr int NCTA = 128;

__device__ __align__(1024) uint8_t g_kvA[2][16][16][2][16384];
__device__ __align__(1024) uint8_t g_kvB[2][16][16][4096];
__device__ __align__(1024) uint8_t g_zero[16384];
__device__ __align__(1024) __nv_bfloat16 g_o[S_LEN * DM];
__device__ __align__(1024) __nv_bfloat16 g_x[S_LEN * DM];
__device__ __align__(1024) float4 g_stats[4][8][S_LEN];
__device__ __align__(1024) float4 g_cs[2][16][8][64];
__device__ __align__(128) unsigned g_fx[16][32];
__device__ __align__(128) unsigned g_fo[32][32];
__device__ __align__(128) unsigned g_fk[16][16][4];
__device__ __align__(128) unsigned g_done[32];

constexpr uint32_t SBASE = 1024;
constexpr int UNIT = 8192;
constexpr int NUNITS = 20;
constexpr int OFF_SLOT = NUNITS * UNIT;
constexpr int OFF_BAR = OFF_SLOT + 4 * 16384;
constexpr int OFF_EPOCH = OFF_BAR + 424;
constexpr int OFF_LSB = OFF_BAR + 432;
constexpr int OFF_CS = OFF_BAR + 496;
constexpr int OFF_RS = OFF_CS + 1536;
constexpr int OFF_ONE = OFF_RS + 1024;
constexpr int SMEM_BYTES = OFF_ONE + 16;
constexpr int B_QF = 0, B_WF = 4, B_RF = 12, B_E = 13, B_PREP = 26, B_LOC = 28, B_HALO = 29, B_REL = 33, B_AFREE = 36,
              B_TURN = 37, B_XRDY = 39, B_CS = 41, B_CSD = 42, B_GO = 43, B_PRE = 44, B_HV = 45, B_REDO = 46,
              B_RDONE = 48, B_PRE2 = 49, B_HL = 50;
static_assert(SMEM_BYTES <= 232448, "shared memory");

__device__ __forceinline__ uint32_t smem_u32(const void* p) { return (uint32_t)__cvta_generic_to_shared(p); }

__device__ __forceinline__ void mbar_init(uint32_t bar, uint32_t cnt) {
  asm volatile("mbarrier.init.shared::cta.b64 [%0], %1;" ::"r"(bar), "r"(cnt));
}
__device__ __forceinline__ void mbar_expect_tx(uint32_t bar, uint32_t bytes) {
  asm volatile("mbarrier.arrive.expect_tx.shared::cta.b64 _, [%0], %1;" ::"r"(bar), "r"(bytes) : "memory");
}
__device__ __forceinline__ void mbar_arrive(uint32_t bar) {
  asm volatile("mbarrier.arrive.shared::cta.b64 _, [%0];" ::"r"(bar) : "memory");
}
__device__ __forceinline__ bool mbar_try_wait(uint32_t bar, uint32_t parity) {
  uint32_t ok;
  asm volatile(
      "{\n.reg .pred p;\nmbarrier.try_wait.parity.shared::cta.b64 p, [%1], %2;\nselp.b32 %0, 1, 0, p;\n}\n"
      : "=r"(ok)
      : "r"(bar), "r"(parity)
      : "memory");
  return ok != 0;
}
__device__ __forceinline__ bool mbar_test(uint32_t bar, uint32_t parity) {
  uint32_t ok;
  asm volatile(
      "{\n.reg .pred p;\nmbarrier.test_wait.parity.shared::cta.b64 p, [%1], %2;\nselp.b32 %0, 1, 0, p;\n}\n"
      : "=r"(ok)
      : "r"(bar), "r"(parity)
      : "memory");
  return ok != 0;
}
__device__ __forceinline__ void mbar_wait(uint32_t bar, uint32_t parity) {
#pragma unroll 1
  for (uint32_t it = 0; it < (1u << 18); ++it) {
    if (mbar_try_wait(bar, parity)) return;
  }
}
__device__ __forceinline__ void mbar_pace(uint32_t bar, uint32_t parity) {
#pragma unroll 1
  for (uint32_t it = 0; it < 24; ++it) {
    if (mbar_try_wait(bar, parity)) return;
  }
}
template <int NS>
__device__ __forceinline__ void mbar_wait_lazy(uint32_t bar, uint32_t parity) {
#pragma unroll 1
  for (uint32_t it = 0; it < (1u << 18); ++it) {
    if (mbar_try_wait(bar, parity)) return;
    __nanosleep(NS);
  }
}
__device__ __forceinline__ bool elect_one() {
  uint32_t ok;
  asm volatile("{\n.reg .pred p;\nelect.sync _|p, 0xffffffff;\nselp.b32 %0, 1, 0, p;\n}\n" : "=r"(ok));
  return ok != 0;
}
__device__ __forceinline__ void fence_barrier_init() { asm volatile("fence.mbarrier_init.release.cluster;" ::: "memory"); }
__device__ __forceinline__ void fence_proxy_async_smem() { asm volatile("fence.proxy.async.shared::cta;" ::: "memory"); }

__device__ __forceinline__ void tma_load_2d(uint32_t dst, const CUtensorMap* map, uint32_t bar, int c0, int c1) {
  asm volatile(
      "cp.async.bulk.tensor.2d.shared::cluster.global.mbarrier::complete_tx::bytes [%0], [%1, {%3, %4}], [%2];" ::"r"(dst),
      "l"(map), "r"(bar), "r"(c0), "r"(c1)
      : "memory");
}
__device__ __forceinline__ void tma_load_3d(uint32_t dst, const CUtensorMap* map, uint32_t bar, int c0, int c1) {
  asm volatile(
      "cp.async.bulk.tensor.3d.shared::cluster.global.mbarrier::complete_tx::bytes [%0], [%1, {%3, %4, %5}], [%2];" ::"r"(dst),
      "l"(map), "r"(bar), "r"(c0), "r"(c1), "r"(0)
      : "memory");
}
__device__ __forceinline__ void tma_load_5d(uint32_t dst, const CUtensorMap* map, uint32_t bar, int c0, int c4) {
  asm volatile(
      "cp.async.bulk.tensor.5d.shared::cluster.global.mbarrier::complete_tx::bytes [%0], [%1, {%3, %5, %5, %5, %4}], [%2];" ::"r"(dst),
      "l"(map), "r"(bar), "r"(c0), "r"(c4), "r"(0)
      : "memory");
}
__device__ __forceinline__ void bulk_load(uint32_t dst, const void* src, uint32_t bytes, uint32_t bar) {
  asm volatile("cp.async.bulk.shared::cluster.global.mbarrier::complete_tx::bytes [%0], [%1], %2, [%3];" ::"r"(dst),
               "l"(src), "r"(bytes), "r"(bar)
               : "memory");
}
__device__ __forceinline__ void bulk_store(void* dst, uint32_t src, uint32_t bytes) {
  asm volatile("cp.async.bulk.global.shared::cta.bulk_group [%0], [%1], %2;" ::"l"(dst), "r"(src), "r"(bytes) : "memory");
}
__device__ __forceinline__ void tma_store_2d(const CUtensorMap* map, uint32_t src, int c0, int c1) {
  asm volatile("cp.async.bulk.tensor.2d.global.shared::cta.bulk_group [%0, {%2, %3}], [%1];" ::"l"(map), "r"(src),
               "r"(c0), "r"(c1)
               : "memory");
}
__device__ __forceinline__ void bulk_announce(unsigned* p) {
  asm volatile("cp.reduce.async.bulk.global.shared::cta.bulk_group.add.u32 [%0], [%1], 16;" ::"l"(p), "r"(SBASE + OFF_ONE) : "memory");
}
__device__ __forceinline__ void bulk_commit() { asm volatile("cp.async.bulk.commit_group;" ::: "memory"); }
__device__ __forceinline__ void bulk_wait_read0() { asm volatile("cp.async.bulk.wait_group.read 0;" ::: "memory"); }
__device__ __forceinline__ void bulk_wait0() { asm volatile("cp.async.bulk.wait_group 0;" ::: "memory"); }
__device__ __forceinline__ void named_bar_sync(int id, int nthreads) {
  asm volatile("bar.sync %0, %1;" ::"r"(id), "r"(nthreads) : "memory");
}
__device__ __forceinline__ void named_bar_arrive(int id, int nthreads) {
  asm volatile("bar.arrive %0, %1;" ::"r"(id), "r"(nthreads) : "memory");
}

__device__ __forceinline__ bool named_bar_or(int id, int nthreads, bool v) {
  uint32_t r;
  asm volatile("{\n.reg .pred p, q;\nsetp.ne.b32 q, %3, 0;\nbar.red.or.pred p, %1, %2, q;\nselp.b32 %0, 1, 0, p;\n}\n"
               : "=r"(r) : "r"(id), "r"(nthreads), "r"((int)v) : "memory");
  return __any_sync(0xffffffffu, r != 0);
}

__device__ __forceinline__ void wgmma_fence() { asm volatile("wgmma.fence.sync.aligned;\n" ::: "memory"); }
__device__ __forceinline__ void wgmma_commit() { asm volatile("wgmma.commit_group.sync.aligned;\n" ::: "memory"); }
template <int N>
__device__ __forceinline__ void wgmma_wait() {
  asm volatile("wgmma.wait_group.sync.aligned %0;\n" ::"n"(N) : "memory");
}
template <int R>
__device__ __forceinline__ void setmaxnreg_inc() { asm volatile("setmaxnreg.inc.sync.aligned.u32 %0;\n" ::"n"(R)); }
template <int R>
__device__ __forceinline__ void setmaxnreg_dec() { asm volatile("setmaxnreg.dec.sync.aligned.u32 %0;\n" ::"n"(R)); }
template <int N>
__device__ __forceinline__ void reg_fence(float* r) {
#pragma unroll
  for (int i = 0; i < N; i++) asm volatile("" : "+f"(r[i])::"memory");
}

template <int N>
__device__ __forceinline__ void reg_define(float* r) {
#pragma unroll
  for (int i = 0; i < N; i++) r[i] = 0.f;
}

__device__ __forceinline__ uint64_t desc_lo(uint32_t lo) {
  uint64_t d;
  asm("mov.b64 %0, {%1, %2};" : "=l"(d) : "r"(lo), "r"(0x40000040u));
  return d;
}
__device__ __forceinline__ uint64_t make_desc(uint32_t addr, uint32_t lbo_bytes) {
  return desc_lo((addr >> 4) + ((lbo_bytes >> 4) << 16));
}

__device__ __forceinline__ void wgmma_n192_ss_ta0_tb1(float* d, uint64_t descA, uint64_t descB, int scaleD) {
  asm volatile("{\n.reg .pred p;\nsetp.ne.b32 p, %98, 0;\n"
    "wgmma.mma_async.sync.aligned.m64n192k16.f32.bf16.bf16 {%0, %1, %2, %3, %4, %5, %6, %7, %8, %9, %10, %11, %12, %13, %14, %15, %16, %17, %18, %19, %20, %21, %22, %23, %24, %25, %26, %27, %28, %29, %30, %31, %32, %33, %34, %35, %36, %37, %38, %39, %40, %41, %42, %43, %44, %45, %46, %47, %48, %49, %50, %51, %52, %53, %54, %55, %56, %57, %58, %59, %60, %61, %62, %63, %64, %65, %66, %67, %68, %69, %70, %71, %72, %73, %74, %75, %76, %77, %78, %79, %80, %81, %82, %83, %84, %85, %86, %87, %88, %89, %90, %91, %92, %93, %94, %95}, %96, %97, p, 1, 1, 0, 1;\n}\n"
    : "+f"(d[0]), "+f"(d[1]), "+f"(d[2]), "+f"(d[3]), "+f"(d[4]), "+f"(d[5]), "+f"(d[6]), "+f"(d[7]), "+f"(d[8]), "+f"(d[9]), "+f"(d[10]), "+f"(d[11]), "+f"(d[12]), "+f"(d[13]), "+f"(d[14]), "+f"(d[15]), "+f"(d[16]), "+f"(d[17]), "+f"(d[18]), "+f"(d[19]), "+f"(d[20]), "+f"(d[21]), "+f"(d[22]), "+f"(d[23]), "+f"(d[24]), "+f"(d[25]), "+f"(d[26]), "+f"(d[27]), "+f"(d[28]), "+f"(d[29]), "+f"(d[30]), "+f"(d[31]), "+f"(d[32]), "+f"(d[33]), "+f"(d[34]), "+f"(d[35]), "+f"(d[36]), "+f"(d[37]), "+f"(d[38]), "+f"(d[39]), "+f"(d[40]), "+f"(d[41]), "+f"(d[42]), "+f"(d[43]), "+f"(d[44]), "+f"(d[45]), "+f"(d[46]), "+f"(d[47]), "+f"(d[48]), "+f"(d[49]), "+f"(d[50]), "+f"(d[51]), "+f"(d[52]), "+f"(d[53]), "+f"(d[54]), "+f"(d[55]), "+f"(d[56]), "+f"(d[57]), "+f"(d[58]), "+f"(d[59]), "+f"(d[60]), "+f"(d[61]), "+f"(d[62]), "+f"(d[63]), "+f"(d[64]), "+f"(d[65]), "+f"(d[66]), "+f"(d[67]), "+f"(d[68]), "+f"(d[69]), "+f"(d[70]), "+f"(d[71]), "+f"(d[72]), "+f"(d[73]), "+f"(d[74]), "+f"(d[75]), "+f"(d[76]), "+f"(d[77]), "+f"(d[78]), "+f"(d[79]), "+f"(d[80]), "+f"(d[81]), "+f"(d[82]), "+f"(d[83]), "+f"(d[84]), "+f"(d[85]), "+f"(d[86]), "+f"(d[87]), "+f"(d[88]), "+f"(d[89]), "+f"(d[90]), "+f"(d[91]), "+f"(d[92]), "+f"(d[93]), "+f"(d[94]), "+f"(d[95])
    : "l"(descA), "l"(descB), "r"(scaleD));
}

__device__ __forceinline__ void wgmma_n128_ss_ta0_tb1(float* d, uint64_t descA, uint64_t descB, int scaleD) {
  asm volatile("{\n.reg .pred p;\nsetp.ne.b32 p, %66, 0;\n"
    "wgmma.mma_async.sync.aligned.m64n128k16.f32.bf16.bf16 {%0, %1, %2, %3, %4, %5, %6, %7, %8, %9, %10, %11, %12, %13, %14, %15, %16, %17, %18, %19, %20, %21, %22, %23, %24, %25, %26, %27, %28, %29, %30, %31, %32, %33, %34, %35, %36, %37, %38, %39, %40, %41, %42, %43, %44, %45, %46, %47, %48, %49, %50, %51, %52, %53, %54, %55, %56, %57, %58, %59, %60, %61, %62, %63}, %64, %65, p, 1, 1, 0, 1;\n}\n"
    : "+f"(d[0]), "+f"(d[1]), "+f"(d[2]), "+f"(d[3]), "+f"(d[4]), "+f"(d[5]), "+f"(d[6]), "+f"(d[7]), "+f"(d[8]), "+f"(d[9]), "+f"(d[10]), "+f"(d[11]), "+f"(d[12]), "+f"(d[13]), "+f"(d[14]), "+f"(d[15]), "+f"(d[16]), "+f"(d[17]), "+f"(d[18]), "+f"(d[19]), "+f"(d[20]), "+f"(d[21]), "+f"(d[22]), "+f"(d[23]), "+f"(d[24]), "+f"(d[25]), "+f"(d[26]), "+f"(d[27]), "+f"(d[28]), "+f"(d[29]), "+f"(d[30]), "+f"(d[31]), "+f"(d[32]), "+f"(d[33]), "+f"(d[34]), "+f"(d[35]), "+f"(d[36]), "+f"(d[37]), "+f"(d[38]), "+f"(d[39]), "+f"(d[40]), "+f"(d[41]), "+f"(d[42]), "+f"(d[43]), "+f"(d[44]), "+f"(d[45]), "+f"(d[46]), "+f"(d[47]), "+f"(d[48]), "+f"(d[49]), "+f"(d[50]), "+f"(d[51]), "+f"(d[52]), "+f"(d[53]), "+f"(d[54]), "+f"(d[55]), "+f"(d[56]), "+f"(d[57]), "+f"(d[58]), "+f"(d[59]), "+f"(d[60]), "+f"(d[61]), "+f"(d[62]), "+f"(d[63])
    : "l"(descA), "l"(descB), "r"(scaleD));
}

__device__ __forceinline__ void wgmma_n192_ssz_ta0_tb1(float* d, uint64_t descA, uint64_t descB) {
  asm volatile("{\n.reg .pred p;\nsetp.ne.b32 p, 0, 0;\n"
    "wgmma.mma_async.sync.aligned.m64n192k16.f32.bf16.bf16 {%0, %1, %2, %3, %4, %5, %6, %7, %8, %9, %10, %11, %12, %13, %14, %15, %16, %17, %18, %19, %20, %21, %22, %23, %24, %25, %26, %27, %28, %29, %30, %31, %32, %33, %34, %35, %36, %37, %38, %39, %40, %41, %42, %43, %44, %45, %46, %47, %48, %49, %50, %51, %52, %53, %54, %55, %56, %57, %58, %59, %60, %61, %62, %63, %64, %65, %66, %67, %68, %69, %70, %71, %72, %73, %74, %75, %76, %77, %78, %79, %80, %81, %82, %83, %84, %85, %86, %87, %88, %89, %90, %91, %92, %93, %94, %95}, %96, %97, p, 1, 1, 0, 1;\n}\n"
    : "=f"(d[0]), "=f"(d[1]), "=f"(d[2]), "=f"(d[3]), "=f"(d[4]), "=f"(d[5]), "=f"(d[6]), "=f"(d[7]), "=f"(d[8]), "=f"(d[9]), "=f"(d[10]), "=f"(d[11]), "=f"(d[12]), "=f"(d[13]), "=f"(d[14]), "=f"(d[15]), "=f"(d[16]), "=f"(d[17]), "=f"(d[18]), "=f"(d[19]), "=f"(d[20]), "=f"(d[21]), "=f"(d[22]), "=f"(d[23]), "=f"(d[24]), "=f"(d[25]), "=f"(d[26]), "=f"(d[27]), "=f"(d[28]), "=f"(d[29]), "=f"(d[30]), "=f"(d[31]), "=f"(d[32]), "=f"(d[33]), "=f"(d[34]), "=f"(d[35]), "=f"(d[36]), "=f"(d[37]), "=f"(d[38]), "=f"(d[39]), "=f"(d[40]), "=f"(d[41]), "=f"(d[42]), "=f"(d[43]), "=f"(d[44]), "=f"(d[45]), "=f"(d[46]), "=f"(d[47]), "=f"(d[48]), "=f"(d[49]), "=f"(d[50]), "=f"(d[51]), "=f"(d[52]), "=f"(d[53]), "=f"(d[54]), "=f"(d[55]), "=f"(d[56]), "=f"(d[57]), "=f"(d[58]), "=f"(d[59]), "=f"(d[60]), "=f"(d[61]), "=f"(d[62]), "=f"(d[63]), "=f"(d[64]), "=f"(d[65]), "=f"(d[66]), "=f"(d[67]), "=f"(d[68]), "=f"(d[69]), "=f"(d[70]), "=f"(d[71]), "=f"(d[72]), "=f"(d[73]), "=f"(d[74]), "=f"(d[75]), "=f"(d[76]), "=f"(d[77]), "=f"(d[78]), "=f"(d[79]), "=f"(d[80]), "=f"(d[81]), "=f"(d[82]), "=f"(d[83]), "=f"(d[84]), "=f"(d[85]), "=f"(d[86]), "=f"(d[87]), "=f"(d[88]), "=f"(d[89]), "=f"(d[90]), "=f"(d[91]), "=f"(d[92]), "=f"(d[93]), "=f"(d[94]), "=f"(d[95])
    : "l"(descA), "l"(descB));
}

__device__ __forceinline__ void wgmma_n192_rs_tb1(float* d, const uint32_t* a, uint64_t descB, int scaleD) {
  asm volatile("{\n.reg .pred p;\nsetp.ne.b32 p, %101, 0;\n"
    "wgmma.mma_async.sync.aligned.m64n192k16.f32.bf16.bf16 {%0, %1, %2, %3, %4, %5, %6, %7, %8, %9, %10, %11, %12, %13, %14, %15, %16, %17, %18, %19, %20, %21, %22, %23, %24, %25, %26, %27, %28, %29, %30, %31, %32, %33, %34, %35, %36, %37, %38, %39, %40, %41, %42, %43, %44, %45, %46, %47, %48, %49, %50, %51, %52, %53, %54, %55, %56, %57, %58, %59, %60, %61, %62, %63, %64, %65, %66, %67, %68, %69, %70, %71, %72, %73, %74, %75, %76, %77, %78, %79, %80, %81, %82, %83, %84, %85, %86, %87, %88, %89, %90, %91, %92, %93, %94, %95}, {%96, %97, %98, %99}, %100, p, 1, 1, 1;\n}\n"
    : "+f"(d[0]), "+f"(d[1]), "+f"(d[2]), "+f"(d[3]), "+f"(d[4]), "+f"(d[5]), "+f"(d[6]), "+f"(d[7]), "+f"(d[8]), "+f"(d[9]), "+f"(d[10]), "+f"(d[11]), "+f"(d[12]), "+f"(d[13]), "+f"(d[14]), "+f"(d[15]), "+f"(d[16]), "+f"(d[17]), "+f"(d[18]), "+f"(d[19]), "+f"(d[20]), "+f"(d[21]), "+f"(d[22]), "+f"(d[23]), "+f"(d[24]), "+f"(d[25]), "+f"(d[26]), "+f"(d[27]), "+f"(d[28]), "+f"(d[29]), "+f"(d[30]), "+f"(d[31]), "+f"(d[32]), "+f"(d[33]), "+f"(d[34]), "+f"(d[35]), "+f"(d[36]), "+f"(d[37]), "+f"(d[38]), "+f"(d[39]), "+f"(d[40]), "+f"(d[41]), "+f"(d[42]), "+f"(d[43]), "+f"(d[44]), "+f"(d[45]), "+f"(d[46]), "+f"(d[47]), "+f"(d[48]), "+f"(d[49]), "+f"(d[50]), "+f"(d[51]), "+f"(d[52]), "+f"(d[53]), "+f"(d[54]), "+f"(d[55]), "+f"(d[56]), "+f"(d[57]), "+f"(d[58]), "+f"(d[59]), "+f"(d[60]), "+f"(d[61]), "+f"(d[62]), "+f"(d[63]), "+f"(d[64]), "+f"(d[65]), "+f"(d[66]), "+f"(d[67]), "+f"(d[68]), "+f"(d[69]), "+f"(d[70]), "+f"(d[71]), "+f"(d[72]), "+f"(d[73]), "+f"(d[74]), "+f"(d[75]), "+f"(d[76]), "+f"(d[77]), "+f"(d[78]), "+f"(d[79]), "+f"(d[80]), "+f"(d[81]), "+f"(d[82]), "+f"(d[83]), "+f"(d[84]), "+f"(d[85]), "+f"(d[86]), "+f"(d[87]), "+f"(d[88]), "+f"(d[89]), "+f"(d[90]), "+f"(d[91]), "+f"(d[92]), "+f"(d[93]), "+f"(d[94]), "+f"(d[95])
    : "r"(a[0]), "r"(a[1]), "r"(a[2]), "r"(a[3]), "l"(descB), "r"(scaleD));
}

__device__ __forceinline__ void wgmma_n80_rs_tb0(float* d, const uint32_t* a, uint64_t descB, int scaleD) {
  asm volatile("{\n.reg .pred p;\nsetp.ne.b32 p, %45, 0;\n"
    "wgmma.mma_async.sync.aligned.m64n80k16.f32.bf16.bf16 {%0, %1, %2, %3, %4, %5, %6, %7, %8, %9, %10, %11, %12, %13, %14, %15, %16, %17, %18, %19, %20, %21, %22, %23, %24, %25, %26, %27, %28, %29, %30, %31, %32, %33, %34, %35, %36, %37, %38, %39}, {%40, %41, %42, %43}, %44, p, 1, 1, 0;\n}\n"
    : "+f"(d[0]), "+f"(d[1]), "+f"(d[2]), "+f"(d[3]), "+f"(d[4]), "+f"(d[5]), "+f"(d[6]), "+f"(d[7]), "+f"(d[8]), "+f"(d[9]), "+f"(d[10]), "+f"(d[11]), "+f"(d[12]), "+f"(d[13]), "+f"(d[14]), "+f"(d[15]), "+f"(d[16]), "+f"(d[17]), "+f"(d[18]), "+f"(d[19]), "+f"(d[20]), "+f"(d[21]), "+f"(d[22]), "+f"(d[23]), "+f"(d[24]), "+f"(d[25]), "+f"(d[26]), "+f"(d[27]), "+f"(d[28]), "+f"(d[29]), "+f"(d[30]), "+f"(d[31]), "+f"(d[32]), "+f"(d[33]), "+f"(d[34]), "+f"(d[35]), "+f"(d[36]), "+f"(d[37]), "+f"(d[38]), "+f"(d[39])
    : "r"(a[0]), "r"(a[1]), "r"(a[2]), "r"(a[3]), "l"(descB), "r"(scaleD));
}

__device__ __forceinline__ void wgmma_n80_rsz_tb0(float* d, const uint32_t* a, uint64_t descB) {
  asm volatile("{\n.reg .pred p;\nsetp.ne.b32 p, 0, 0;\n"
    "wgmma.mma_async.sync.aligned.m64n80k16.f32.bf16.bf16 {%0, %1, %2, %3, %4, %5, %6, %7, %8, %9, %10, %11, %12, %13, %14, %15, %16, %17, %18, %19, %20, %21, %22, %23, %24, %25, %26, %27, %28, %29, %30, %31, %32, %33, %34, %35, %36, %37, %38, %39}, {%40, %41, %42, %43}, %44, p, 1, 1, 0;\n}\n"
    : "=f"(d[0]), "=f"(d[1]), "=f"(d[2]), "=f"(d[3]), "=f"(d[4]), "=f"(d[5]), "=f"(d[6]), "=f"(d[7]), "=f"(d[8]), "=f"(d[9]), "=f"(d[10]), "=f"(d[11]), "=f"(d[12]), "=f"(d[13]), "=f"(d[14]), "=f"(d[15]), "=f"(d[16]), "=f"(d[17]), "=f"(d[18]), "=f"(d[19]), "=f"(d[20]), "=f"(d[21]), "=f"(d[22]), "=f"(d[23]), "=f"(d[24]), "=f"(d[25]), "=f"(d[26]), "=f"(d[27]), "=f"(d[28]), "=f"(d[29]), "=f"(d[30]), "=f"(d[31]), "=f"(d[32]), "=f"(d[33]), "=f"(d[34]), "=f"(d[35]), "=f"(d[36]), "=f"(d[37]), "=f"(d[38]), "=f"(d[39])
    : "r"(a[0]), "r"(a[1]), "r"(a[2]), "r"(a[3]), "l"(descB));
}

__device__ __forceinline__ void wgmma_n32_rs_tb1(float* d, const uint32_t* a, uint64_t descB, int scaleD) {
  asm volatile("{\n.reg .pred p;\nsetp.ne.b32 p, %21, 0;\n"
    "wgmma.mma_async.sync.aligned.m64n32k16.f32.bf16.bf16 {%0, %1, %2, %3, %4, %5, %6, %7, %8, %9, %10, %11, %12, %13, %14, %15}, {%16, %17, %18, %19}, %20, p, 1, 1, 1;\n}\n"
    : "+f"(d[0]), "+f"(d[1]), "+f"(d[2]), "+f"(d[3]), "+f"(d[4]), "+f"(d[5]), "+f"(d[6]), "+f"(d[7]), "+f"(d[8]), "+f"(d[9]), "+f"(d[10]), "+f"(d[11]), "+f"(d[12]), "+f"(d[13]), "+f"(d[14]), "+f"(d[15])
    : "r"(a[0]), "r"(a[1]), "r"(a[2]), "r"(a[3]), "l"(descB), "r"(scaleD));
}

__device__ __forceinline__ void wgmma_n32_rsz_tb1(float* d, const uint32_t* a, uint64_t descB) {
  asm volatile("{\n.reg .pred p;\nsetp.ne.b32 p, 0, 0;\n"
    "wgmma.mma_async.sync.aligned.m64n32k16.f32.bf16.bf16 {%0, %1, %2, %3, %4, %5, %6, %7, %8, %9, %10, %11, %12, %13, %14, %15}, {%16, %17, %18, %19}, %20, p, 1, 1, 1;\n}\n"
    : "=f"(d[0]), "=f"(d[1]), "=f"(d[2]), "=f"(d[3]), "=f"(d[4]), "=f"(d[5]), "=f"(d[6]), "=f"(d[7]), "=f"(d[8]), "=f"(d[9]), "=f"(d[10]), "=f"(d[11]), "=f"(d[12]), "=f"(d[13]), "=f"(d[14]), "=f"(d[15])
    : "r"(a[0]), "r"(a[1]), "r"(a[2]), "r"(a[3]), "l"(descB));
}

__device__ __forceinline__ void wgmma_n32_rs_tb0(float* d, const uint32_t* a, uint64_t descB, int scaleD) {
  asm volatile("{\n.reg .pred p;\nsetp.ne.b32 p, %21, 0;\n"
    "wgmma.mma_async.sync.aligned.m64n32k16.f32.bf16.bf16 {%0, %1, %2, %3, %4, %5, %6, %7, %8, %9, %10, %11, %12, %13, %14, %15}, {%16, %17, %18, %19}, %20, p, 1, 1, 0;\n}\n"
    : "+f"(d[0]), "+f"(d[1]), "+f"(d[2]), "+f"(d[3]), "+f"(d[4]), "+f"(d[5]), "+f"(d[6]), "+f"(d[7]), "+f"(d[8]), "+f"(d[9]), "+f"(d[10]), "+f"(d[11]), "+f"(d[12]), "+f"(d[13]), "+f"(d[14]), "+f"(d[15])
    : "r"(a[0]), "r"(a[1]), "r"(a[2]), "r"(a[3]), "l"(descB), "r"(scaleD));
}

__device__ __forceinline__ void wgmma_n32_rsz_tb0(float* d, const uint32_t* a, uint64_t descB) {
  asm volatile("{\n.reg .pred p;\nsetp.ne.b32 p, 0, 0;\n"
    "wgmma.mma_async.sync.aligned.m64n32k16.f32.bf16.bf16 {%0, %1, %2, %3, %4, %5, %6, %7, %8, %9, %10, %11, %12, %13, %14, %15}, {%16, %17, %18, %19}, %20, p, 1, 1, 0;\n}\n"
    : "=f"(d[0]), "=f"(d[1]), "=f"(d[2]), "=f"(d[3]), "=f"(d[4]), "=f"(d[5]), "=f"(d[6]), "=f"(d[7]), "=f"(d[8]), "=f"(d[9]), "=f"(d[10]), "=f"(d[11]), "=f"(d[12]), "=f"(d[13]), "=f"(d[14]), "=f"(d[15])
    : "r"(a[0]), "r"(a[1]), "r"(a[2]), "r"(a[3]), "l"(descB));
}

__device__ __forceinline__ uint32_t pack_bf16x2(float lo, float hi) {
  uint32_t r;
  asm("cvt.rn.bf16x2.f32 %0, %1, %2;" : "=r"(r) : "f"(hi), "f"(lo));
  return r;
}
__device__ __forceinline__ float bf_lo(uint32_t p) { return __uint_as_float(p << 16); }
__device__ __forceinline__ float bf_hi(uint32_t p) { return __uint_as_float(p & 0xffff0000u); }
__device__ __forceinline__ float bf16_round(float v) { return __bfloat162float(__float2bfloat16_rn(v)); }
__device__ __forceinline__ float ex2_approx(float x) {
  float r;
  asm("ex2.approx.ftz.f32 %0, %1;" : "=f"(r) : "f"(x));
  return r;
}
__device__ __forceinline__ float rcp_fast(float x) {
  float r;
  asm("rcp.approx.ftz.f32 %0, %1;" : "=f"(r) : "f"(x));
  return r;
}
__device__ __forceinline__ void ldmatrix_x4(uint32_t (&r)[4], uint32_t addr) {
  asm volatile("ldmatrix.sync.aligned.m8n8.x4.shared.b16 {%0,%1,%2,%3}, [%4];"
               : "=r"(r[0]), "=r"(r[1]), "=r"(r[2]), "=r"(r[3])
               : "r"(addr)
               : "memory");
}
__device__ __forceinline__ void stmatrix_x4(uint32_t addr, uint32_t r0, uint32_t r1, uint32_t r2, uint32_t r3) {
  asm volatile("stmatrix.sync.aligned.m8n8.x4.shared.b16 [%0], {%1,%2,%3,%4};" ::"r"(addr), "r"(r0), "r"(r1), "r"(r2),
               "r"(r3));
}
__device__ __forceinline__ uint32_t add_bf16x2(uint32_t a, uint32_t b) {
  uint32_t r;
  asm("add.rn.bf16x2 %0, %1, %2;" : "=r"(r) : "r"(a), "r"(b));
  return r;
}
__device__ __forceinline__ uint4 lds128(uint32_t addr) {
  uint4 v;
  asm volatile("ld.shared.v4.b32 {%0,%1,%2,%3}, [%4];" : "=r"(v.x), "=r"(v.y), "=r"(v.z), "=r"(v.w) : "r"(addr) : "memory");
  return v;
}
__device__ __forceinline__ uint32_t lds32(uint32_t addr) {
  uint32_t v;
  asm volatile("ld.shared.b32 %0, [%1];" : "=r"(v) : "r"(addr) : "memory");
  return v;
}
__device__ __forceinline__ void sts32(uint32_t addr, uint32_t v) {
  asm volatile("st.shared.b32 [%0], %1;" ::"r"(addr), "r"(v) : "memory");
}

__device__ __forceinline__ unsigned ld_relaxed_u32(const void* p) {
  unsigned v;
  asm volatile("ld.relaxed.gpu.global.u32 %0, [%1];" : "=r"(v) : "l"(p) : "memory");
  return v;
}
__device__ __forceinline__ unsigned launch_epoch() { return (*(volatile unsigned*)g_done) / NCTA + 1u; }
__device__ __forceinline__ void red_announce(unsigned* p) {
  asm volatile("red.relaxed.gpu.global.add.u32 [%0], %1;" ::"l"(p), "r"(1u) : "memory");
}
__device__ __forceinline__ uint32_t set_tag(uint32_t w, uint32_t m, uint32_t tag) { return (w & ~m) | (tag & m); }
__device__ __forceinline__ uint32_t o_tag(int L) { return (L + 1) & 1; }
__device__ __forceinline__ uint32_t x_tag(unsigned ep1, int L) { return (ep1 + L + 1) & 1; }

__device__ __forceinline__ void wait_count(const unsigned* f, unsigned target, int i, uint32_t& seen, int lane) {
  if ((seen >> i) & 1u) return;
#pragma unroll 1
  for (uint32_t it = 0; it < (1u << 17); ++it) {
    seen = __ballot_sync(0xffffffffu, (int)(ld_relaxed_u32(f + (lane & 15)) - target) >= 0);
    if ((seen >> i) & 1u) break;
  }
}
__device__ __forceinline__ float4 ld_rec(const float4* p) {
  float4 v;
  asm volatile("ld.relaxed.gpu.global.v4.f32 {%0,%1,%2,%3}, [%4];" : "=f"(v.x), "=f"(v.y), "=f"(v.z), "=f"(v.w) : "l"(p) : "memory");
  return v;
}
__device__ __forceinline__ void st_rec(float4* p, float a, float b, float c, unsigned tag) {
  asm volatile("st.relaxed.gpu.global.v4.f32 [%0], {%1,%2,%3,%4};" ::"l"(p), "f"(a), "f"(b), "f"(c), "f"(__uint_as_float(tag)) : "memory");
}
template <int N>
__device__ __forceinline__ float4 sum_recs(const float4* p, int stride, unsigned tag) {
  float4 s;
#pragma unroll 1
  for (uint32_t it = 0; it < (1u << 17); ++it) {
    float4 v[N];
#pragma unroll
    for (int t = 0; t < N; t++) v[t] = ld_rec(p + t * stride);
    bool ok = true;
    s = make_float4(0.f, 0.f, 0.f, 0.f);
#pragma unroll
    for (int t = 0; t < N; t++) {
      ok &= __float_as_uint(v[t].w) == tag;
      s.x += v[t].x;
      s.y += v[t].y;
      s.z += v[t].z;
    }
    if (ok) break;
    __nanosleep(200);
  }
  return s;
}

__device__ __forceinline__ int fresh_tid() {
  int t;
  asm volatile("mov.u32 %0, %%tid.x;" : "=r"(t));
  return t;
}
#define PHASE_IDS                                  \
  const int tid_ = fresh_tid();                    \
  const int lane = tid_ & 31, wwarp = __shfl_sync(0xffffffffu, (tid_ >> 5) & 3, 0), tid = tid_ & 127; \
  const int g = lane >> 2, c = lane & 3;           \
  (void)tid; (void)g; (void)c; (void)wwarp;

#define PHASE_IDS_W                                \
  const int lane = fresh_tid() & 31, wwarp = warp & 3; \
  const int g = lane >> 2, c = lane & 3;

#define GTL(i) do { } while (0)
#define TGET(v) do { } while (0)
#define TPUT(c, i, v) do { } while (0)

constexpr float SM_C = 0.17677669529663687f * 1.4426950408889634f;

__device__ __forceinline__ void stmatrix_x4_if(bool ok, uint32_t addr, uint32_t r0, uint32_t r1, uint32_t r2, uint32_t r3) {
  asm volatile("{\n.reg .pred p;\nsetp.ne.b32 p, %5, 0;\n@p stmatrix.sync.aligned.m8n8.x4.shared.b16 [%0], {%1,%2,%3,%4};\n}\n" ::"r"(addr),
               "r"(r0), "r"(r1), "r"(r2), "r"(r3), "r"((int)ok));
}

__device__ __forceinline__ void attn_a_slow(const uint8_t* __restrict__ kvimg, int L, int gb, int hp, uint32_t bad,
                                            int row0, int lane) {
  constexpr uint32_t sq = SBASE + OFF_SLOT + 3 * 16384;
#pragma unroll 1
  for (int j = 0; j < 8; j++) {
    const uint8_t* tp = kvimg + (size_t)(gb * 16 + hp) * 32768 + (j * 32 + lane) * 128 + ((lane & 7) << 4);
#pragma unroll 1
    for (uint32_t it = 0; it < (1u << 17); ++it)
      if (((ld_relaxed_u32(tp) ^ lds32(SBASE + OFF_EPOCH)) & 1u) == 0u) break;
  }
  __syncwarp();
#pragma unroll 1
  for (int t = 0; t < 32; t++) {
    const int hh = t >> 4, row = row0 + (t & 7) + (t & 8) * 4;
    if (!((bad >> hh) & 1u)) continue;
    const int qpos = gb * 128 + row;
    const uint32_t qaddr = sq + row * 128;
    float mx = -INFINITY, sum = 0.f, acc = 0.f;
#pragma unroll 1
    for (int pass = 0; pass < 2; pass++) {
#pragma unroll 1
      for (int j = 0; j < 8; j++) {
        const int kp = qpos - (lane + 32 * j);
        const uint8_t* kr = kvimg + ((size_t)((kp >> 7) * 16 + hp) * 2 + ((kp >> 6) & 1)) * 16384 + (kp & 63) * 128;
        float d = -INFINITY;
        if (kp >= 0) {
          d = 0.f;
#pragma unroll 1
          for (int q = 0; q < 4; q++) {
            const uint4 kv = __ldcg(reinterpret_cast<const uint4*>(kr + (((hh * 4 + q) ^ (kp & 7)) << 4)));
            const uint4 qv = lds128(qaddr + (((hh * 4 + q) ^ (row & 7)) << 4));
            const uint32_t kw[4] = {kv.x, kv.y, kv.z, kv.w}, qw[4] = {qv.x, qv.y, qv.z, qv.w};
#pragma unroll
            for (int e = 0; e < 4; e++) d = fmaf(bf_lo(kw[e]), bf_lo(qw[e]), fmaf(bf_hi(kw[e]), bf_hi(qw[e]), d));
          }
        }
        if (pass == 0) {
          mx = fmaxf(mx, d);
        } else {
          const float ev = ex2_approx(d - mx);
          sum += ev;
          const float pv = bf16_round(ev);
#pragma unroll 1
          for (int kk = 0; kk < 32; kk++) {
            const float pk = __shfl_sync(0xffffffffu, pv, kk);
            const int k2 = qpos - (kk + 32 * j);
            if (k2 >= 0) {
              const uint8_t* vr = kvimg + ((size_t)((k2 >> 7) * 16 + hp) * 2 + ((k2 >> 6) & 1)) * 16384 + 8192 + (k2 & 63) * 128;
              const unsigned short vv =
                  __ldcg(reinterpret_cast<const unsigned short*>(vr + (((hh * 4 + (lane >> 3)) ^ (k2 & 7)) << 4) + (lane & 7) * 2));
              acc = fmaf(pk, __uint_as_float((uint32_t)vv << 16), acc);
            }
          }
        }
      }
      if (pass == 0) {
#pragma unroll
        for (int o = 16; o > 0; o >>= 1) mx = fmaxf(mx, __shfl_xor_sync(0xffffffffu, mx, o));
      }
    }
#pragma unroll
    for (int o = 16; o > 0; o >>= 1) sum += __shfl_xor_sync(0xffffffffu, sum, o);
    acc *= rcp_fast(sum);
    const float hi = __shfl_down_sync(0xffffffffu, acc, 1);
    __syncwarp();
    if ((lane & 1) == 0) sts32(qaddr + (((hh * 4 + (lane >> 3)) ^ (row & 7)) << 4) + (lane & 7) * 2,
                               set_tag(pack_bf16x2(acc, hi), hh == 0 && lane == 0, o_tag(L)));
    __syncwarp();
  }
}

template <int HH>
__device__ __forceinline__ void store_o(const float (&o)[16], const float (&inv)[2], uint32_t ra, uint32_t tag, bool ok) {
  const uint32_t m = HH == 0 && (fresh_tid() & 3) == 0;
#pragma unroll
  for (int jp = 0; jp < 2; jp++) {
    uint32_t w0 = pack_bf16x2(o[8 * jp] * inv[0], o[8 * jp + 1] * inv[0]);
    uint32_t w1 = pack_bf16x2(o[8 * jp + 2] * inv[1], o[8 * jp + 3] * inv[1]);
    if (HH == 0 && jp == 0) {
      w0 = set_tag(w0, m, tag);
      w1 = set_tag(w1, m, tag);
    }
    stmatrix_x4_if(ok, ra ^ ((HH * 4 + 2 * jp) << 4), w0, w1, pack_bf16x2(o[8 * jp + 4] * inv[0], o[8 * jp + 5] * inv[0]),
                   pack_bf16x2(o[8 * jp + 6] * inv[1], o[8 * jp + 7] * inv[1]));
  }
}
__device__ __forceinline__ int tile_row(bool B, int w, int r, int g) { return (B ? 16 * w + 8 * r : 8 * w + 32 * r) + g; }
__device__ __forceinline__ uint32_t q_row_addr(bool B, int R, int w, int lane) {
  return SBASE + OFF_SLOT + 3 * 16384 + R * 8192 + tile_row(B, w, (lane >> 3) & 1, lane & 7) * 128 + (((lane >> 4) ^ (lane & 7)) << 4);
}

struct AttnA {
  float s[2][16], o[2][16], l[2][2], sh[2][3];
  uint32_t p[2][4], t[2], me[4], ra, bad, zero;
};
#define ATS_(i) do { } while (0)
template <int V>
__device__ __forceinline__ void attn_sum(AttnA& a, int nv) {
  constexpr int hh = (V >> 1) & 1, kh = V & 1, i = V >> 2;
#pragma unroll
  for (int r = 0; r < 2; r++) {
    const uint32_t t1 = add_bf16x2(add_bf16x2(a.p[0][r], a.p[0][2 + r]), add_bf16x2(a.p[1][r], a.p[1][2 + r]));
    if (kh == 0) {
      a.t[r] = t1;
    } else {
      uint32_t tt = add_bf16x2(a.t[r], t1);
      if (i > 0) tt = i <= nv ? tt : 0u;
      const float v = bf_lo(tt) + bf_hi(tt);
      a.l[hh][r] = i == 0 ? v : a.l[hh][r] + v;
    }
  }
}
template <int HH>
__device__ __forceinline__ void attn_shfl(AttnA& a) {
#pragma unroll
  for (int r = 0; r < 2; r++)
#pragma unroll
    for (int j = 0; j < 3; j++) a.sh[r][j] = __shfl_xor_sync(0xffffffffu, a.l[HH][r], j + 1);
}
template <int HH>
__device__ __forceinline__ void attn_fin(AttnA& a) {
  bool bad = false;
  float inv[2];
#pragma unroll
  for (int r = 0; r < 2; r++) {
    const float v = (a.l[HH][r] + a.sh[r][0]) + (a.sh[r][1] + a.sh[r][2]);
    bad |= !(v <= 1.152921504606846976e18f && v >= 8.673617379884035e-19f);
    inv[r] = rcp_fast(v);
  }
  bad = __any_sync(0xffffffffu, bad);
  if (HH == 1) wgmma_wait<0>();
  reg_fence<16>(a.o[HH]);
  store_o<HH>(a.o[HH], inv, a.ra, o_tag(0), !bad);
  a.bad = (HH == 0 ? 0u : a.bad) | (bad ? 1u << HH : 0u);
}
__device__ __forceinline__ void attn_masks(AttnA& a, int wr) {
  const int lane = fresh_tid() & 31, d = (lane >> 2) - 2 * (lane & 3);
  const uint32_t tri = d >= 1 ? 0xffffffffu : (d == 0 ? 0xffffu : 0u);
#pragma unroll
  for (int t = 0; t < 4; t++) a.me[t] = wr > t ? 0xffffffffu : (wr == t ? tri : 0u);
}
template <int V, int K>
__device__ __forceinline__ uint32_t attn_exp(AttnA& a) {
  constexpr int i = V >> 2, kh = V & 1, r = K & 1;
  if ((i == 0 && kh > r) || (i == 4 && kh < r)) return 0u;
  const uint32_t w = pack_bf16x2(ex2_approx(a.s[V & 1][2 * K]), ex2_approx(a.s[V & 1][2 * K + 1]));
  if (i == 0 && kh == r) return w & a.me[K >> 1];
  if (i == 4 && kh == r) return w & ~a.me[K >> 1];
  return w;
}
template <int V>
__device__ __forceinline__ void attn_unit(AttnA& a, const uint32_t (&q)[2][2][4], uint64_t dcur, uint64_t dnext, int R, int wr, int nv,
                                          uint32_t hbar, uint32_t hpar, uint32_t rbar, bool rel) {
  constexpr int hh = (V >> 1) & 1, kh = V & 1, i = V >> 2;
  ATS_(V + 1);
  asm volatile("" : "+l"(dcur), "+l"(dnext));
  wgmma_wait<1>();
  reg_fence<16>(a.s[V & 1]);
  bool hok = true;
  if (V == 4) hbar = SBASE + OFF_BAR + 8u * (R ? B_LOC : B_HV);
  if (((V & 3) == 2 && V < 16) || V == 4) hok = mbar_test(hbar, hpar);
  const uint64_t d0 = ((V & 3) >= 2 ? dnext : dcur) + ((hh ^ 1) * 4 + kh * 256), d1 = ((V & 3) >= 2 ? dnext : dcur) + ((hh ^ 1) * 4 + kh * 256 + 2);
  const uint64_t d2 = dcur + (512 + hh * 4 + kh * 256), d3 = dcur + (640 + hh * 4 + kh * 256);
  if ((V & 3) == 1 && V > 4 && rel) mbar_arrive(rbar);
  if (V > 0) attn_sum<V - 1>(a, nv);
  if (V == 15) attn_masks(a, wr);
  if (V == 18) {
    attn_shfl<0>(a);
    a.ra = q_row_addr(false, R, wr, fresh_tid() & 31);
  }
  if (V == 19) attn_fin<0>(a);
  uint32_t p[2][4];
  p[0][0] = attn_exp<V, 0>(a);
  p[0][1] = attn_exp<V, 1>(a);
  p[0][2] = attn_exp<V, 2>(a);
  p[0][3] = attn_exp<V, 3>(a);
  p[1][0] = attn_exp<V, 4>(a);
  p[1][1] = attn_exp<V, 5>(a);
  p[1][2] = attn_exp<V, 6>(a);
  p[1][3] = attn_exp<V, 7>(a);
  if (V > 0) {
#pragma unroll
    for (int r = 0; r < 2; r++) p[1][r] ^= (kh ? a.t[r] : __float_as_uint(a.l[hh ^ 1][r])) & a.zero;
  }
#pragma unroll
  for (int k = 0; k < 8; k++) {
    asm volatile("" : "+r"(p[k >> 2][k & 3]));
    a.p[k >> 2][k & 3] = p[k >> 2][k & 3];
  }
  if (!hok) mbar_wait(hbar, hpar);
  wgmma_fence();
  if (V < 18) wgmma_n32_rsz_tb0(a.s[V & 1], q[hh ^ 1][0], d0);
  if (i == 0 && kh == 0) wgmma_n32_rsz_tb1(a.o[hh], a.p[0], d2);
  else wgmma_n32_rs_tb1(a.o[hh], a.p[0], d2, 1);
  if (V < 18) wgmma_n32_rs_tb0(a.s[V & 1], q[hh ^ 1][1], d1, 1);
  wgmma_n32_rs_tb1(a.o[hh], a.p[1], d3, 1);
  wgmma_commit();
}
template <int I>
__device__ __forceinline__ void attn_step(AttnA& a, const uint32_t (&q)[2][2][4], uint64_t dcur, uint64_t dnext, int R, int wr, int nv,
                                          uint32_t hbar, uint32_t hpar, uint32_t rbar, bool rel) {
  attn_unit<4 * I>(a, q, dcur, dnext, R, wr, nv, hbar, hpar, rbar, rel);
  attn_unit<4 * I + 1>(a, q, dcur, dnext, R, wr, nv, hbar, hpar, rbar, rel);
  attn_unit<4 * I + 2>(a, q, dcur, dnext, R, wr, nv, hbar, hpar, rbar, rel);
  attn_unit<4 * I + 3>(a, q, dcur, dnext, R, wr, nv, hbar, hpar, rbar, rel);
}

__device__ __forceinline__ void attention_a(const uint32_t (&q)[2][2][4], int R, int L, int gb, int hp, uint32_t par, int wr,
                                            uint32_t zero) {
  constexpr uint32_t bars = SBASE + OFF_BAR;
  constexpr uint32_t dslot = ((SBASE + OFF_SLOT) >> 4) + 0x10000u;
  auto next = [&](uint64_t d) { return desc_lo((uint32_t)d == dslot ? dslot + 2048 : (uint32_t)d - 1024) + zero; };
  uint64_t d0 = desc_lo(dslot + R * 1024) + zero, d1 = next(d0);
  AttnA a;
  ATS_(0);
  wgmma_fence();
#pragma unroll
  for (int v = 0; v < 2; v++) {
    wgmma_n32_rsz_tb0(a.s[v], q[0][0], d0 + v * 256);
    wgmma_n32_rs_tb0(a.s[v], q[0][1], d0 + (v * 256 + 2), 1);
    wgmma_commit();
  }
  a.zero = zero;
  const bool lane0 = (fresh_tid() & 31) == 0;
  attn_masks(a, wr);
  const int nv = 2 * gb + R;
  const uint32_t hb = bars + 8u * (B_HALO - R), rb = bars + 8u * (B_REL - R);
  attn_step<0>(a, q, d0, d1, R, wr, nv, hb, par, 0, false);
  d0 = next(d1);
  attn_step<1>(a, q, d1, d0, R, wr, nv, R ? bars + 8u * B_HV : hb + 8, par, rb + 8, lane0);
  d1 = next(d0);
  attn_step<2>(a, q, d0, d1, R, wr, nv, hb + 16, par, rb + 16, lane0);
  d0 = next(d1);
  attn_step<3>(a, q, d1, d0, R, wr, nv, hb + 24, par, rb + 24, lane0 && R);
  attn_step<4>(a, q, d0, d0, R, wr, nv, 0, 0, rb, false);
  ATS_(21);
  attn_sum<19>(a, nv);
  attn_shfl<1>(a);
  attn_fin<1>(a);
  ATS_(22);
  if (a.bad != 0u) attn_a_slow(g_kvA[L >> 1][0][0][0], L, gb, hp, a.bad, R * 64 + wr * 8, fresh_tid() & 31);
}

constexpr uint32_t KB_ROW0 = SBASE + OFF_SLOT + 2048, VB_ROW0 = SBASE + OFF_SLOT + 24576 + 2048;

__device__ __forceinline__ void attention_b(const uint32_t (&q)[2][2][4], int R, int gb, uint32_t par0, int wr) {
  constexpr uint32_t bars = SBASE + OFF_BAR;
  const uint32_t dk = ((KB_ROW0 - 2048) >> 4) + 0x10000u + R * 512, dv = dk + ((VB_ROW0 - KB_ROW0) >> 4);
  float s[2][40];
  mbar_wait(bars + 8u * (B_HALO - R), par0);
  wgmma_fence();
#pragma unroll
  for (int hh = 0; hh < 2; hh++) {
    wgmma_n80_rsz_tb0(s[hh], q[hh][0], desc_lo(dk + hh * 4));
    wgmma_n80_rs_tb0(s[hh], q[hh][1], desc_lo(dk + hh * 4 + 2), 1);
  }
  wgmma_commit();
  const int lane = fresh_tid() & 31, g = lane >> 2;
  const bool odd = g & 1, edge = R == 0 && gb == 0 && wr == 0;
  const int D = 2 * (lane & 3) + (g & 1) - g;
  const uint32_t ra = q_row_addr(true, R, wr, lane);
  wgmma_wait<0>();
  reg_fence<40>(s[0]);
  reg_fence<40>(s[1]);
  float z[2][2], y[2][2];
#define GATHER_(W)                                                                                          \
  _Pragma("unroll") for (int hh = 0; hh < 2; hh++) _Pragma("unroll") for (int r = 0; r < 2; r++) {          \
    const float* e = &s[hh][4 * (2 * W + r) + 2 * r];                                                       \
    z[hh][r] = odd ? e[5] : e[4];                                                                           \
    y[hh][r] = D >= 2 ? (odd ? e[1] : e[0]) : (odd ? e[9] : e[8]);                                          \
  }
  if (wr < 2) {
    if (wr == 0) { GATHER_(0) } else { GATHER_(1) }
  } else {
    if (wr == 2) { GATHER_(2) } else { GATHER_(3) }
  }
#undef GATHER_
  float o[2][16], inv[2][2];
  uint32_t p[2][5][4];
  const int sh = odd ? 16 : 0, kb = wr + (D >= 2 ? 0 : 1);
#pragma unroll
  for (int hh = 0; hh < 2; hh++) {
    if (edge) {
      z[hh][0] = -INFINITY;
      if (D >= 2) y[hh][0] = y[hh][1] = -INFINITY;
    }
    uint32_t ab[2][2];
#pragma unroll
    for (int r = 0; r < 2; r++) {
      float m = fmaxf(z[hh][r], y[hh][r]);
      m = fmaxf(m, __shfl_xor_sync(0xffffffffu, m, 1));
      m = fmaxf(m, __shfl_xor_sync(0xffffffffu, m, 2));
      const float e0 = ex2_approx(z[hh][r] - m), e1 = ex2_approx(y[hh][r] - m);
      inv[hh][r] = e0 + e1;
      ab[r][0] = pack_bf16x2(e0, 0.f) << sh;
      ab[r][1] = pack_bf16x2(e1, 0.f) << sh;
    }
#pragma unroll
    for (int k = 0; k < 5; k++) {
      p[hh][k][0] = k == kb ? ab[0][1] : 0u;
      p[hh][k][1] = k == wr + 1 ? ab[1][0] : 0u;
      p[hh][k][2] = k == wr ? ab[0][0] : 0u;
      p[hh][k][3] = k == kb ? ab[1][1] : 0u;
#pragma unroll
      for (int j = 0; j < 4; j++) asm volatile("" : "+r"(p[hh][k][j]));
    }
  }
  wgmma_fence();
#pragma unroll
  for (int hh = 0; hh < 2; hh++) {
    wgmma_n32_rsz_tb1(o[hh], p[hh][0], desc_lo(dv + hh * 4));
#pragma unroll
    for (int k = 1; k < 5; k++) wgmma_n32_rs_tb1(o[hh], p[hh][k], desc_lo(dv + hh * 4 + k * 128), 1);
  }
  wgmma_commit();
#pragma unroll
  for (int hh = 0; hh < 2; hh++)
#pragma unroll
    for (int r = 0; r < 2; r++) {
      inv[hh][r] += __shfl_xor_sync(0xffffffffu, inv[hh][r], 1);
      inv[hh][r] += __shfl_xor_sync(0xffffffffu, inv[hh][r], 2);
      inv[hh][r] = rcp_fast(inv[hh][r]);
    }
  wgmma_wait<0>();
  reg_fence<16>(o[0]);
  reg_fence<16>(o[1]);
  store_o<0>(o[0], inv[0], ra, o_tag(1), true);
  store_o<1>(o[1], inv[1], ra, o_tag(1), true);
}

#define KTQM 0
#define TRICKLE 300
#define WTURN 15
#define QREL 8
#define PRESLEEP 200
#define QTURN 2
#define HTS(i) do { } while (0)
struct Params {
  CUtensorMap x[5], xq[4], o, wqkv[2], wqkv3[2], wo3[2];
  const __nv_bfloat16* in_x;
  const __nv_bfloat16* wqkv_p[2];
  const __nv_bfloat16* wo_p[2];
  __nv_bfloat16* out;
  uint32_t zero;
};

__device__ __forceinline__ void colsum_part(const CUtensorMap* wmap, int ty, int qr, int hp) {
  constexpr uint32_t bars = SBASE + OFF_BAR, slots = SBASE + OFF_SLOT;
  PHASE_IDS
  const unsigned ep1 = launch_epoch();
  if (wwarp == 0 && elect_one()) {
    mbar_expect_tx(bars + 8u * B_CS, 6 * UNIT);
#pragma unroll 1
    for (int j = 0; j < 6; j++) {
      if (ty == 0) mbar_pace(bars + 8u * (B_QF + B_E + (j & 3)), j >> 2);
      else __nanosleep(400);
      tma_load_2d(slots + j * UNIT, wmap, bars + 8u * B_CS, (j >> 1) * 1024 + hp * 64, qr * 128 + (j & 1) * 64);
    }
  }
  mbar_wait(bars + 8u * B_CS, ty);
  const uint32_t src = slots + (tid >> 3) * 128 + (((tid & 7) ^ ((tid >> 3) & 7)) << 4);
#pragma unroll 1
  for (int p = 0; p < 3; p++) {
    float s[8];
#pragma unroll
    for (int e = 0; e < 8; e++) s[e] = 0.f;
#pragma unroll
    for (int j = 0; j < 8; j++) {
      const uint4 v = lds128(src + p * 2 * UNIT + j * 2048);
      const uint32_t x[4] = {v.x, v.y, v.z, v.w};
#pragma unroll
      for (int e = 0; e < 4; e++) {
        s[2 * e] += bf_lo(x[e]);
        s[2 * e + 1] += bf_hi(x[e]);
      }
    }
#pragma unroll
    for (int st = 0; st < 2; st++) {
      const bool up = (lane >> (st + 3)) & 1;
#pragma unroll
      for (int e = 0; e < (4 >> st); e++) {
        const float keep = up ? s[e + (4 >> st)] : s[e], give = up ? s[e] : s[e + (4 >> st)];
        s[e] = keep + __shfl_xor_sync(0xffffffffu, give, 8 << st);
      }
    }
    const uint32_t dst = slots + 6 * UNIT + ((wwarp * 3 + p) * 64 + (lane & 7) * 8 + ((lane >> 3) & 1) * 4 + (lane >> 4) * 2) * 4;
    sts32(dst, __float_as_uint(s[0]));
    sts32(dst + 4, __float_as_uint(s[1]));
  }
  named_bar_sync(6, 128);
  if (tid < 64) {
    float r[3] = {0.f, 0.f, 0.f};
#pragma unroll
    for (int e = 0; e < 12; e++) r[e % 3] += __uint_as_float(lds32(slots + 6 * UNIT + (e * 64 + tid) * 4));
    st_rec(&g_cs[ty][hp][qr][tid], r[0], r[1], r[2], ep1);
  }
  named_bar_sync(6, 128);
}

__device__ __forceinline__ void put_colsums(int ty, int col, const float4& s) {
  const float v[3] = {s.x, s.y, s.z};
#pragma unroll
  for (int p = 0; p < 3; p++) {
    const uint32_t a = SBASE + OFF_CS + (p * 8 + (col >> 3)) * 64 + ty * 32 + (col & 7) * 2;
    const float hi = bf16_round(v[p]);
    const uint32_t w = pack_bf16x2(hi, v[p] - hi);
    asm volatile("st.shared.b16 [%0], %1;" ::"r"(a), "h"((unsigned short)w) : "memory");
    asm volatile("st.shared.b16 [%0], %1;" ::"r"(a + 16), "h"((unsigned short)(w >> 16)) : "memory");
  }
}

__device__ __forceinline__ uint32_t ln_params(float s1, float s2) {
  const float mean = s1 * (1.0f / DM);
  const float var = fmaxf(fmaf(-mean, mean, s2 * (1.0f / DM)), 0.f);
  float sd;
  asm("sqrt.approx.f32 %0, %1;" : "=f"(sd) : "f"(bf16_round(bf16_round(var) + 1e-5f)));
  return pack_bf16x2(mean, sd);
}

struct RingProd {
  uint32_t rel = ((B_QF << 1) | 1) * 0x01010101u + 0x06040200u;
  int st = 0;
  __device__ __forceinline__ uint32_t next(uint32_t bar, uint32_t par, bool wait) {
    const uint32_t e = (rel >> (8 * st)) & 255u, a = SBASE + st * 5 * UNIT;
    if (wait) mbar_wait(SBASE + OFF_BAR + 8u * B_E + 8u * (e >> 1), e & 1u);
    rel ^= (e ^ ((bar << 1) | par)) << (8 * st);
    st = (st + 1) & 3;
    return a;
  }
};

#define SP1 15
#define SP2 14
#define SP3 12
#define SP4 12
#define SP5 15
#define SP6 14
#define SP7 16
__device__ __forceinline__ int q_split(int inst) {
  constexpr uint32_t T = 15u | ((SP1 - 1) << 4) | ((SP2 - 1) << 8) | ((SP3 - 1) << 12) | ((SP4 - 1) << 16) | ((SP5 - 1) << 20) |
                         ((SP6 - 1) << 24) | ((uint32_t)(SP7 - 1) << 28);
  return (int)((T >> (4 * inst)) & 15u) + 1;
}
__host__ __device__ constexpr uint32_t turn_par(int kind) {
  const int sp[8] = {16, SP1, SP2, SP3, SP4, SP5, SP6, SP7};
  int cnt[2] = {0, 0};
  uint32_t m = 0;
  for (int i = 0; i < 8; i++)
    for (int k = 0; k < 3; k++) {
      if (k == kind) m |= (uint32_t)(cnt[i & 1] & 1) << i;
      if (k == 0 ? (i == 1 || (i > 1 && sp[i - 1] < 16)) : (k == 2 || sp[i] < 16)) cnt[i & 1]++;
    }
  return m;
}
#define PREMASK 0xBDu
__device__ __forceinline__ bool w_pre(int inst) { return (PREMASK >> inst) & 1u; }
__global__ void __launch_bounds__(512, 1) fused_kernel(const __grid_constant__ Params P) {
  extern __shared__ __align__(1024) uint8_t smem_raw[];
  constexpr uint32_t base = SBASE, bars = base + OFF_BAR, slots = base + OFF_SLOT;
  if (smem_u32(smem_raw) != base) __trap();
  const int warp = __shfl_sync(0xffffffffu, threadIdx.x >> 5, 0), lane = threadIdx.x & 31;
  const int b = blockIdx.x;
#define QS 0
#define WS 1
  const int qr = ((b & ((8 << QS) - 1)) >> QS) ^ (((b >> (3 + QS)) & 1) * 7);
  const int hp = ((b >> (3 + QS)) << QS) + (b & ((1 << QS) - 1));
  const int rt = ((b & ((16 << WS) - 1)) >> WS) ^ (((b >> (4 + WS)) & 1) * 15);
  const int ct = ((b >> (4 + WS)) << WS) + (b & ((1 << WS) - 1));

  if (warp == 12) {
    if (elect_one()) {
#pragma unroll
      for (int s = 0; s < 4; s++) {
        mbar_init(bars + 8u * (B_QF + s), 2);
        mbar_init(bars + 8u * (B_QF + B_E + s), 4);
      }
      mbar_init(bars + 8u * B_GO, 1);
      fence_barrier_init();
    }
    __syncwarp();
    named_bar_arrive(0, 512);
  }
  if (threadIdx.x == 0) {
    for (int s = B_WF; s <= B_RF; s++) {
      mbar_init(bars + 8u * s, s == B_RF ? 1 : 2);
      mbar_init(bars + 8u * (s + B_E), 4);
    }
    for (int s = 0; s < 4; s++) sts32(base + OFF_ONE + 4 * s, s == 0);
    fence_proxy_async_smem();
    mbar_init(bars + 8u * B_PREP, 1);
    mbar_init(bars + 8u * (B_PREP + 1), 1);
    mbar_init(bars + 8u * B_HL, 1);
    mbar_init(bars + 8u * (B_HL + 1), 1);
    mbar_init(bars + 8u * B_HV, 1);
    for (int s = 0; s < 4; s++) mbar_init(bars + 8u * (B_HALO + s), 1);
    for (int s = 0; s < 3; s++) mbar_init(bars + 8u * (B_REL + s), s == 0 ? 4 : 8);
    mbar_init(bars + 8u * B_LOC, 4);
    mbar_init(bars + 8u * B_AFREE, 2);
    mbar_init(bars + 8u * B_TURN, 4);
    mbar_init(bars + 8u * (B_TURN + 1), 4);
    mbar_init(bars + 8u * B_CS, 1);
    mbar_init(bars + 8u * B_PRE, 1);
    mbar_init(bars + 8u * B_PRE2, 1);
    mbar_init(bars + 8u * B_RDONE, 4);
    mbar_init(bars + 8u * B_CSD, 4);
    mbar_init(bars + 8u * B_XRDY, 1);
    mbar_init(bars + 8u * (B_XRDY + 1), 1);
    fence_barrier_init();
  }
  if (warp != 12) named_bar_sync(0, 512);

  if (warp >= 12) {
    setmaxnreg_dec<32>();
    if (warp == 12) {
      if (elect_one()) {
#pragma unroll 1
        for (int s = 0; s < 16; s++) {
          const uint32_t fb = bars + 8u * (B_QF + (s & 3)), sa = base + (s & 3) * 5 * UNIT;
          if (s >= 4) mbar_wait(fb + 8u * B_E, ((s >> 2) & 1) ^ 1);
          mbar_expect_tx(fb, 5 * UNIT);
          mbar_arrive(fb);
          tma_load_5d(sa, &P.xq[0], fb, s * 64, qr * 2);
          tma_load_3d(sa + 2 * UNIT, &P.wqkv3[0], fb, hp * 64, s * 64);
        }
        mbar_arrive(bars + 8u * B_GO);
        RingProd rp;
#pragma unroll 1
        for (int sg = 4; sg < 34; sg++) {
          const int part = sg & 3, inst = (sg >> 2) - (part & 1);
          if (part == 3 || inst == 8) continue;
          const int ty = (inst >> 1) & 1;
          if (part != 1) {
            const int k0 = part ? q_split(inst) : 0, k1 = part ? 16 : q_split(inst);
#pragma unroll 1
            for (int kt = k0; kt < k1; kt++) {
              const uint32_t sa = rp.next(B_QF + (kt & 3), (kt >> 2) & 1, true), fb = bars + 8u * (B_QF + (kt & 3));
              mbar_expect_tx(fb, 3 * UNIT);
              tma_load_3d(sa + 2 * UNIT, &P.wqkv3[ty], fb, hp * 64, kt * 64);
            }
          } else {
            const bool pre = w_pre(inst);
            const int lag = pre ? 8 : 5;
            uint32_t sa = 0;
#pragma unroll 1
            for (int kt = 0; kt < 16; kt++) {
              const int i = kt & 3;
              const uint32_t fb = bars + 8u * (B_WF + (kt & 7));
              if (i == 1) sa += 2 * UNIT;
              else if (i != 3 || !pre) sa = rp.next(kt == 14 ? B_RF : B_WF + ((kt | 1) & 7), kt == 14 ? inst & 1 : kt >> 3, kt < lag) + ((0x21 >> (2 * i)) & 3) * UNIT;
              if (kt >= lag) mbar_wait(bars + 8u * (B_WF + B_E + ((kt - lag) & 7)), (kt - lag) >> 3);
              if (i == 3 && pre) {
                mbar_arrive(fb);
              } else {
                mbar_expect_tx(fb, 2 * UNIT);
                tma_load_3d(sa, &P.wo3[ty], fb, ct * 128, kt * 64);
              }
            }
          }
        }
      }
    } else if (warp == 13) {
      RingProd rp;
      unsigned ep1 = 0;
      mbar_wait(bars + 8u * B_GO, 0);
#pragma unroll 1
      for (int sg = 4; sg < 34; sg++) {
        const int part = sg & 3, inst = (sg >> 2) - (part & 1);
        if (part == 3 || inst == 8) continue;
        const int L = inst >> 1, ch = inst & 1;
        uint32_t seen = 0;
        if (part != 1) {
          const CUtensorMap* tx = &P.xq[L];
          const int k0 = part ? q_split(inst) : 0, k1 = part ? 16 : q_split(inst);
          if (L == 0 || mbar_test(bars + 8u * (B_XRDY + ch), (L & 1) ^ 1)) {
            seen = 0xFFFFFFFFu;
          }
          if (sg == 4) ep1 = launch_epoch();
          const int m0 = ch * 16 + qr * 2;
#pragma unroll 1
          for (int kt = k0; kt < k1; kt++) {
            wait_count(g_fx[ch * 8 + qr], 6u * ep1 - 6u + 2u * L, kt, seen, lane);
            TGET(t38);
            const uint32_t sa = rp.next(B_QF + (kt & 3), (kt >> 2) & 1, true);
            TGET(t39);
            if (elect_one()) {
              const uint32_t fb = bars + 8u * (B_QF + (kt & 3));
              mbar_expect_tx(fb, 2 * UNIT);
              tma_load_5d(sa, tx, fb, kt * 64, m0);
            }
            if (L == 3 && kt == 0 && lane == 0) { TPUT(ch, 38, t38); TPUT(ch, 39, t39); }
          }
        } else {
          const int m0 = ch * 1024 + rt * 64;
          const bool pre = w_pre(inst);
          const int lag = pre ? 8 : 5;
          uint32_t sa = 0;
#pragma unroll 1
          for (int kt = 0; kt < 16; kt++) {
            const int i = kt & 3;
            const uint32_t fb = bars + 8u * (B_WF + (kt & 7));
            wait_count(g_fo[ch * 16 + rt], 4u * ep1 - 3u + L, kt, seen, lane);
            if (i < 2) sa = rp.next(kt == 13 ? B_RF : B_WF + (kt & 7) + i + 1, kt == 13 ? inst & 1 : kt >> 3, kt < lag);
            else sa += (2 * i - 3) * UNIT;
            if (kt >= lag) mbar_wait(bars + 8u * (B_WF + B_E + ((kt - lag) & 7)), (kt - lag) >> 3);
            if (elect_one()) {
              mbar_expect_tx(fb, UNIT);
              tma_load_2d(sa, &P.o, fb, kt * 64, m0);
            }
            if (i == 3 && !pre) rp.next(B_WF + (kt & 7), kt >> 3, false);
          }
        }
      }
    } else if (warp == 14) {
      const unsigned ep1 = launch_epoch();
      uint32_t hpar = 0;
#pragma unroll 1
      for (int inst = 0; inst < 8; inst++) {
        const int L = inst >> 1, ch = inst & 1, gb = ch * 8 + qr;
        const unsigned kv0 = 8u * ep1 - 8u + 2u * L + (L & 1);
        if ((L & 1) == 0) {
          uint8_t* img = g_kvA[L >> 1][gb][hp][0];
          const uint8_t* s1 = gb > 0 ? img - 16 * 32768 : g_zero;
          const uint8_t* s2 = gb > 1 ? img - 32 * 32768 : g_zero;
          const uint32_t h1 = gb > 0 ? 16384 : 0, h2 = gb > 1 ? 16384 : 0;
          const unsigned* cp = g_fk[hp][max(gb - 1 - (lane >= 3), 0)];
          const unsigned ct0 = kv0 + ((0x32321u >> (4 * (lane & 7))) & 3u);
          uint32_t fr = gb == 0 ? 31u : (gb == 1 ? 24u : 0u);
          const uint32_t toff = slots + lane * 128 + ((lane & 7) << 4);
          auto seen = [&](uint32_t m) {
#pragma unroll 1
            for (uint32_t it = 0; it < (1u << 17) && !(fr & m); ++it)
              fr |= __ballot_sync(0xffffffffu, (int)(ld_relaxed_u32(cp) - ct0) >= 0);
          };
          auto load = [&](uint32_t off, const uint8_t* src, uint32_t bytes, int bi) {
            if (elect_one()) {
              mbar_expect_tx(bars + 8u * (B_HL + bi), bytes);
              bulk_load(slots + off, src, bytes, bars + 8u * (B_HL + bi));
            }
          };
          auto check = [&](uint32_t off, const uint8_t* src, uint32_t bytes, int bi, bool real, int done) {
#pragma unroll 1
            for (int tries = 0; tries < 4096; tries++) {
              mbar_wait(bars + 8u * (B_HL + bi), (hpar >> bi) & 1u);
              hpar ^= 1u << bi;
              uint32_t t = (lds32(toff + off) ^ ep1) | (lds32(toff + off + 4096) ^ ep1);
              if (bytes > 8192) t |= (lds32(toff + off + 8192) ^ ep1) | (lds32(toff + off + 12288) ^ ep1);
              if (!__any_sync(0xffffffffu, real && (t & 1u))) break;
              fence_proxy_async_smem();
              load(off, src, bytes, bi);
            }
            if (lane == 0) mbar_arrive(bars + 8u * done);
          };
          named_bar_sync(3, 160);
          HTS(44);
          if (elect_one()) {
            bulk_store(img + 16384, slots + 16384, 8192);
            bulk_announce(g_fk[hp][gb]);
            bulk_store(img + 24576, slots + 24576, 8192);
            bulk_announce(g_fk[hp][gb]);
            bulk_commit();
          }
          seen(1);
          HTS(46);
          load(32768, s1 + h1, 8192, 0);
          seen(2);
          HTS(47);
          load(40960, s1 + h1 + 8192, 8192, 1);
          mbar_wait(bars + 8u * B_LOC, inst & 1);
          HTS(45);
          if (elect_one()) {
            bulk_store(img, slots, 16384);
            bulk_announce(g_fk[hp][gb]);
            bulk_commit();
            asm volatile("cp.async.bulk.wait_group.read 1;" ::: "memory");
          }
          check(32768, s1 + h1, 8192, 0, gb > 0, B_HALO);
          HTS(52);
          check(40960, s1 + h1 + 8192, 8192, 1, gb > 0, B_HV);
          HTS(53);
#pragma unroll 1
          for (int n = 1; n < 4; n++) {
            const uint8_t* src = n == 1 ? s1 : (n == 2 ? s2 + h2 : s2);
            const uint32_t off = n == 3 ? 32768 : 32768 - n * 16384;
            seen(2u << n);
            if (n == 2 && elect_one()) bulk_wait_read0();
            mbar_wait(bars + 8u * (B_REL - 1) + 8u * n, ch);
            HTS(47 + n);
            load(off, src, 16384, 0);
            check(off, src, 16384, 0, gb > (n >> 1), B_HALO + n);
            HTS(53 + n);
          }
        } else {
          uint8_t* img = g_kvB[L >> 1][gb][hp];
          named_bar_sync(3, 160);
          HTS(44);
          if (elect_one()) {
            bulk_store(img, KB_ROW0 + 112 * 128, 2048);
            bulk_store(img + 2048, VB_ROW0 + 112 * 128, 2048);
            bulk_announce(g_fk[hp][gb]);
            bulk_commit();
          }
          const uint8_t* src = gb >= 1 ? img - 16 * 4096 : g_zero;
#pragma unroll 1
          for (uint32_t it = 0; it < (1u << 17); ++it)
            if (gb == 0 || (int)(ld_relaxed_u32(g_fk[hp][gb - 1]) - kv0) > 0) break;
          HTS(46);
#pragma unroll 1
          for (uint32_t it = 0; it < 4096; ++it) {
            if (elect_one()) {
              mbar_expect_tx(bars + 8u * B_HL, 4096);
              bulk_load(KB_ROW0 - 2048, src, 2048, bars + 8u * B_HL);
              bulk_load(VB_ROW0 - 2048, src + 2048, 2048, bars + 8u * B_HL);
              bulk_wait_read0();
            }
            mbar_wait(bars + 8u * B_HL, hpar & 1u);
            hpar ^= 1u;
            const uint32_t t = lds32((lane < 16 ? KB_ROW0 - 2048 : VB_ROW0 - 4096) + lane * 128 + ((lane & 7) << 4)) ^ ep1;
            if (gb == 0 || !__any_sync(0xffffffffu, t & 1u)) break;
            fence_proxy_async_smem();
          }
          if (lane == 0) mbar_arrive(bars + 8u * B_HALO);
          HTS(52);
        }
        if (elect_one()) {
          mbar_wait(bars + 8u * B_AFREE, inst & 1);
          mbar_expect_tx(bars + 8u * B_RF, 2 * UNIT);
          tma_load_2d(slots + 6 * UNIT, &P.x[L], bars + 8u * B_RF, ct * 128, ch * 1024 + rt * 64);
          tma_load_2d(slots + 7 * UNIT, &P.x[L], bars + 8u * B_RF, ct * 128 + 64, ch * 1024 + rt * 64);
          if (w_pre(inst)) {
            if (inst == 1) mbar_wait(bars + 8u * B_CSD, 0);
            mbar_expect_tx(bars + 8u * B_PRE, 6 * UNIT);
            mbar_expect_tx(bars + 8u * B_PRE2, 2 * UNIT);
#pragma unroll 1
            for (int j = 0; j < 4; j++) {
              __nanosleep(PRESLEEP);
              if (j == 3) mbar_wait(bars + 8u * B_RDONE, (inst & 1) ^ 1);
              tma_load_3d(slots + j * 2 * UNIT, &P.wo3[L & 1], bars + 8u * (j == 3 ? B_PRE2 : B_PRE), ct * 128, (4 * j + 3) * 64);
            }
          }
        }
        __syncwarp();
      }
    } else {
      const unsigned ep1 = launch_epoch();
      mbar_wait(bars + 8u * B_GO, 0);
#pragma unroll 1
      for (int i = 0; i < 20; i++) {
        const char* src = i < 4 ? reinterpret_cast<const char*>(P.wo_p[0]) + (size_t)b * 16384 + i * 4096
                                : (i < 16 ? reinterpret_cast<const char*>(P.wqkv_p[1]) + (size_t)b * 49152 + (i - 4) * 4096
                                          : reinterpret_cast<const char*>(P.wo_p[1]) + (size_t)b * 16384 + (i - 16) * 4096);
        asm volatile("prefetch.global.L2 [%0];" ::"l"(src + lane * 128));
        __nanosleep(TRICKLE);
      }
#pragma unroll 1
      for (int inst = 2; inst < 8; inst++) {
        const int L = inst >> 1, ch = inst & 1, gb = ch * 8 + qr;
        mbar_wait_lazy<200>(bars + 8u * (B_RF + B_E), inst & 1);
#pragma unroll 1
        for (int h = 0; h < 4; h++) {
          const float4* sp = &g_stats[L][0][gb * 128 + h * 32 + lane];
          const float4 s0 = sum_recs<4>(sp, S_LEN, ep1), s1 = sum_recs<4>(sp + 4 * S_LEN, S_LEN, ep1);
          sts32(base + OFF_RS + (ch * 128 + h * 32 + lane) * 4, ln_params(s0.x + s1.x, s0.y + s1.y));
        }
        if (lane == 0) mbar_arrive(bars + 8u * (B_XRDY + ch));
        if (inst == 2) {
          mbar_wait(bars + 8u * B_CSD, 0);
#pragma unroll 1
          for (int hf = 0; hf < 2; hf++) {
            const float4* cp = &g_cs[1][hp][0][hf * 32 + lane];
            const float4 s0 = sum_recs<4>(cp, 64, ep1), s1 = sum_recs<4>(cp + 4 * 64, 64, ep1);
            put_colsums(1, hf * 32 + lane, make_float4(s0.x + s1.x, s0.y + s1.y, s0.z + s1.z, 0.f));
          }
        }
        fence_proxy_async_smem();
        __syncwarp();
        if (lane == 0) mbar_arrive(bars + 8u * (B_PREP + ch));
      }
    }
  } else {
    const bool asst = warp >= 8;
    GTL(0);
    if (asst) {
      colsum_part(&P.wqkv[0], 0, qr, hp);
      if ((threadIdx.x & 127) < 4) mbar_arrive(bars + 8u * B_RDONE);
    } else if (warp >= 4) {
      PHASE_IDS
      {
        const unsigned ep1 = launch_epoch();
        const int row = b * 16 + (tid >> 3);
        const uint4* src = reinterpret_cast<const uint4*>(P.in_x + (size_t)row * DM) + (tid & 7);
        float s1 = 0.f, s2 = 0.f;
#pragma unroll 1
        for (int k = 0; k < 4; k++) {
          mbar_pace(bars + 8u * (B_QF + B_E + ((2 * k) & 3)), k >> 1);
          uint4 v[4];
#pragma unroll
          for (int j = 0; j < 4; j++) v[j] = __ldg(src + (k * 4 + j) * 8);
#pragma unroll
          for (int j = 0; j < 4; j++) {
            const uint32_t w[4] = {v[j].x, v[j].y, v[j].z, v[j].w};
#pragma unroll
            for (int e = 0; e < 4; e++) {
              const float x0 = bf_lo(w[e]), x1 = bf_hi(w[e]);
              s1 += x0 + x1;
              s2 = fmaf(x0, x0, fmaf(x1, x1, s2));
            }
          }
        }
#pragma unroll
        for (int o = 1; o < 8; o <<= 1) {
          s1 += __shfl_xor_sync(0xffffffffu, s1, o);
          s2 += __shfl_xor_sync(0xffffffffu, s2, o);
        }
        if ((tid & 7) == 0) st_rec(&g_stats[0][0][row], s1, s2, 0.f, ep1);
        if (tid == 0) sts32(base + OFF_EPOCH, ep1);
        if (tid < 64) {
          const float4 s0 = sum_recs<8>(&g_cs[0][hp][0][tid], 64, ep1);
          put_colsums(0, tid, s0);
        } else {
          put_colsums(1, tid - 64, make_float4(0.f, 0.f, 0.f, 0.f));
        }
#pragma unroll 1
        for (int cc = 0; cc < 2; cc++) {
          const float4 s0 = sum_recs<1>(&g_stats[0][0][(cc * 8 + qr) * 128 + tid], 0, ep1);
          sts32(base + OFF_RS + (cc * 128 + tid) * 4, ln_params(s0.x, s0.y));
        }
        fence_proxy_async_smem();
        named_bar_sync(2, 128);
        if (tid < 2) mbar_arrive(bars + 8u * (B_PREP + tid));
      }
    }
#pragma unroll 1
    for (int inst = asst ? 0 : warp >> 2; inst < 8; inst += asst ? 1 : 2) {
      const int L = inst >> 1, ch = inst & 1, gb = ch * 8 + qr;
      uint32_t q[2][2][4];
      if (asst) {
        setmaxnreg_dec<24>();
        named_bar_sync(4, 256);
        setmaxnreg_inc<128>();
        const uint32_t ra = q_row_addr(L & 1, 1, warp & 3, fresh_tid() & 31);
#pragma unroll
        for (int j = 0; j < 4; j++) ldmatrix_x4(q[j >> 1][j & 1], ra ^ (j << 5));
      } else {
      setmaxnreg_inc<224>();
      {
        float acc[2][96];
        const int ksp = q_split(inst);
        constexpr uint32_t STG = 5 * (UNIT >> 4), D0 = (base >> 4) + 0x10000u;
        constexpr uint32_t DB = ((UNIT >> 4) << 16) - 0x10000u + 2 * (UNIT >> 4);
        uint32_t sd = D0;
        uint32_t tand = 1u, tor = 0u, tw = 0u;
        const uint32_t toff = ((fresh_tid() & 127) << 7) + ((fresh_tid() & 7) << 4);
        bool lane0 = (toff & 0xf80u) == 0u;
        if (inst == 1 || (inst > 1 && q_split(inst - 1) < 16)) mbar_wait_lazy<100>(bars + 8u * (B_TURN + ch), (turn_par(0) >> inst) & 1u);
        if (L == 3) GTL(37);
        mbar_wait(bars + 8u * B_QF, 0);
        GTL(1 + L * 8);
        {
          const uint64_t da = desc_lo(sd) + P.zero;
          wgmma_fence();
          wgmma_n192_ssz_ta0_tb1(acc[1], da + (UNIT >> 4), da + DB);
          wgmma_commit();
          wgmma_n192_ssz_ta0_tb1(acc[0], da, da + DB);
          wgmma_commit();
        }
#pragma unroll 1
        for (int kt = 0; kt < 15; kt++) {
          const bool last = kt + 1 == ksp;
          const uint64_t da = desc_lo(sd) + P.zero;
          const uint32_t fn = bars + 8u * (B_QF + ((kt + 1) & 3)), pn = ((kt + 1) >> 2) & 1;
#pragma unroll
          for (int k16 = 0; k16 < 4; k16++) {
            if (k16 == 0 && kt == 0) continue;
            wgmma_fence();
            wgmma_n192_ss_ta0_tb1(acc[1], da + ((UNIT >> 4) + k16 * 2), da + (DB + k16 * 128), 1);
            wgmma_commit();
            wgmma_wait<1>();
            if (k16 == 0 && lane0 && kt != ksp) mbar_arrive(bars + 8u * (B_QF + B_E + ((kt - 1) & 3)));
            wgmma_fence();
            wgmma_n192_ss_ta0_tb1(acc[0], da + k16 * 2, da + (DB + k16 * 128), 1);
            wgmma_commit();
            if (k16 == 1) tw = lds32(((sd & 0xffffu) << 4) + toff);
            if (k16 == 2) {
              tand &= tw;
              tor |= tw;
            }
            bool ok = true;
            if (k16 == 2) ok = mbar_test(fn, pn) || last;
            if (k16 == QTURN && last && lane0) mbar_arrive(bars + 8u * (B_TURN + (ch ^ 1)));
            if (k16 < 3) wgmma_wait<1>();
            if (k16 == 2 && !ok) mbar_wait(fn, pn);
          }
          sd = sd == D0 + 3 * STG ? D0 : sd + STG;
          if (last) {
            wgmma_wait<0>();
            if (lane0) mbar_arrive(bars + 8u * (B_QF + B_E + (kt & 3)));
            mbar_wait_lazy<100>(bars + 8u * (B_TURN + ch), (turn_par(1) >> inst) & 1u);
            mbar_wait(fn, pn);
          }
        }
        PHASE_IDS_W
        lane0 = lane == 0;
        constexpr uint32_t DL = D0 + 3 * STG;
        wgmma_fence();
#pragma unroll
        for (int k16 = 0; k16 < 4; k16++) wgmma_n192_ss_ta0_tb1(acc[1], desc_lo(DL + (UNIT >> 4) + k16 * 2), desc_lo(DL + DB + k16 * 128), 1);
        wgmma_commit();
        tw = lds32(((DL & 0xffffu) << 4) + toff);
        mbar_wait(bars + 8u * (B_PREP + ch), L & 1);
        const uint32_t rsa = base + OFF_RS + (ch * 128 + tile_row(L & 1, wwarp, 0, g)) * 4, rsd = (L & 1) ? 32 : 128;
        uint32_t rs[2][2];
        const uint32_t ep1 = __shfl_sync(0xffffffffu, lds32(base + OFF_EPOCH), 0);
        constexpr uint64_t DCS = (uint64_t)((base + OFF_CS) >> 4) | (4ull << 32);
        auto ln_mma = [&](float (&d)[96], uint32_t (&r)[2], int h) {
          uint32_t a[4];
#pragma unroll
          for (int i = 0; i < 2; i++) {
            r[i] = lds32(rsa + h * 256 + i * rsd);
            a[i] = c == (L & 1) ? __byte_perm(r[i], 0u, 0x1010) ^ 0x80008000u : 0u;
            a[i + 2] = r[i] & P.zero;
          }
#pragma unroll
          for (int i = 0; i < 4; i++) asm volatile("" : "+r"(a[i]));
          wgmma_fence();
          wgmma_n192_rs_tb1(d, a, DCS, 1);
          wgmma_commit();
        };
        wgmma_wait<1>();
        if (lane0 && ksp != 15) mbar_arrive(bars + 8u * (B_QF + B_E + 2));
        ln_mma(acc[1], rs[1], 1);
#pragma unroll
        for (int k16 = 0; k16 < 4; k16++) wgmma_n192_ss_ta0_tb1(acc[0], desc_lo(DL + k16 * 2), desc_lo(DL + DB + k16 * 128), 1);
        wgmma_commit();
        tand &= tw;
        tor |= tw;
        const bool redo = named_bar_or(1 + ch, 128, L > 0 && (((x_tag(ep1, L) ? ~tand : tor) & 1u) != 0u));
        if (ksp < 16) mbar_wait(bars + 8u * (B_WF + B_E + 7), 1);
        const bool afree = mbar_test(bars + 8u * B_RDONE, inst & 1);
        float rinv[2];
#pragma unroll
        for (int r = 0; r < 2; r++) rinv[r] = rcp_fast(bf_hi(rs[1][r]));
        const uint32_t soff = tile_row(L & 1, wwarp, (lane >> 3) & 1, lane & 7) * 128 + (((lane >> 4) ^ (lane & 7)) << 4);
        const uint32_t kdst = ((L & 1) ? KB_ROW0 : slots) + soff, vdst = ((L & 1) ? VB_ROW0 : slots + 8192) + soff;
        const uint32_t hs = (L & 1) ? 8192 : 16384;
        wgmma_wait<1>();
        if (lane0) mbar_arrive(bars + 8u * (B_TURN + (ch ^ 1)));
        if (redo) {
          wgmma_wait<0>();
          constexpr uint32_t sa = (DL & 0xffffu) << 4;
          const uint32_t rb = bars + 8u * (B_REDO + ch);
          if (toff == 0) {
            mbar_init(rb, 1);
            fence_barrier_init();
          }
          uint32_t rpar = 0;
#pragma unroll 1
          for (int kt = 0, tries = 0; kt < 16;) {
            fence_proxy_async_smem();
            named_bar_sync(1 + ch, 128);
            if ((warp & 3) == 0 && elect_one()) {
                mbar_expect_tx(rb, 5 * UNIT);
              tma_load_5d(sa, &P.xq[L], rb, kt * 64, gb * 2);
              tma_load_3d(sa + 2 * UNIT, &P.wqkv3[L & 1], rb, hp * 64, kt * 64);
            }
            mbar_wait(rb, rpar);
            rpar ^= 1u;
            if (named_bar_or(1 + ch, 128, (lds32(sa + toff) ^ x_tag(ep1, L)) & 1u) && ++tries < 4096) continue;
            wgmma_fence();
#pragma unroll
            for (int k16 = 0; k16 < 4; k16++) {
              const uint64_t db = make_desc(sa + 2 * UNIT + k16 * 2048, UNIT);
              wgmma_n192_ss_ta0_tb1(acc[1], make_desc(sa + UNIT + k16 * 32, 16), db, kt | k16);
              wgmma_n192_ss_ta0_tb1(acc[0], make_desc(sa + k16 * 32, 16), db, kt | k16);
            }
            wgmma_commit();
            wgmma_wait<0>();
            kt++;
          }
          ln_mma(acc[1], rs[1], 1);
          wgmma_wait<0>();
        }
        ln_mma(acc[0], rs[0], 0);
        reg_fence<96>(acc[1]);
        GTL(2 + L * 8);
        if (!afree) mbar_wait(bars + 8u * B_RDONE, inst & 1);
#pragma unroll
        for (int t = 0; t < 24; t++) {
          const int h = t < 12 ? 1 : 0, p = ((t % 12) / 4 + 1) % 3, jp = t & 3;
          if (t == QREL) {
            wgmma_wait<0>();
            reg_fence<96>(acc[0]);
            if (lane0) mbar_arrive(bars + 8u * (B_QF + B_E + 3));
          }
          if (t == 8 || t == 20) {
            rinv[0] *= SM_C;
            rinv[1] *= SM_C;
          }
          const float* a = &acc[h][4 * (p * 8 + 2 * jp)];
          uint32_t r0 = pack_bf16x2(a[0] * rinv[0], a[1] * rinv[0]);
          uint32_t r1 = pack_bf16x2(a[2] * rinv[1], a[3] * rinv[1]);
          if (p != 0 && jp == 0) {
            r0 = set_tag(r0, c == 0, ep1);
            r1 = set_tag(r1, c == 0, ep1);
          }
          const uint32_t r2 = pack_bf16x2(a[4] * rinv[0], a[5] * rinv[0]);
          const uint32_t r3 = pack_bf16x2(a[6] * rinv[1], a[7] * rinv[1]);
          const uint32_t dst = p == 0 ? slots + 3 * 16384 + soff + h * 8192 : (p == 1 ? kdst : vdst) + h * hs;
          stmatrix_x4(dst ^ (jp << 5), r0, r1, r2, r3);
          if (t >= 20) {
            q[jp >> 1][jp & 1][0] = r0;
            q[jp >> 1][jp & 1][1] = r1;
            q[jp >> 1][jp & 1][2] = r2;
            q[jp >> 1][jp & 1][3] = r3;
          }
          if (t == 7 || t == 19) {
            fence_proxy_async_smem();
            if (t == 7) {
              named_bar_arrive(3, 160);
            } else {
              __syncwarp();
              if (lane0) mbar_arrive(bars + 8u * B_LOC);
            }
          }
          if (t == 11) {
            setmaxnreg_dec<128>();
            named_bar_arrive(4, 256);
#pragma unroll
            for (int r = 0; r < 2; r++) rinv[r] = rcp_fast(bf_hi(rs[0][r]));
          }
        }
        mbar_wait(bars + 8u * B_LOC, inst & 1);
      }
      }
      GTL(3 + L * 8);
      if ((L & 1) == 0) attention_a(q, asst, L, gb, hp, ch, warp & 3, P.zero);
      else attention_b(q, asst, gb, inst & 1, warp & 3);
      GTL(4 + L * 8);
      fence_proxy_async_smem();
      named_bar_sync(asst ? 6 : 1 + ch, 128);
      if ((warp & 3) == 0) {
        if (elect_one()) {
          tma_store_2d(&P.o, slots + 3 * 16384 + asst * 8192, hp * 64, gb * 128 + asst * 64);
          bulk_commit();
          bulk_wait0();
          red_announce(&g_fo[gb * 2 + asst][hp]);
          mbar_arrive(bars + 8u * B_AFREE);
        }
        __syncwarp();
      }
      if (asst) {
        if (inst == 1) {
          mbar_wait(bars + 8u * B_RDONE, 0);
          colsum_part(&P.wqkv[1], 1, qr, hp);
          if ((fresh_tid() & 31) == 0) mbar_arrive(bars + 8u * B_CSD);
        }
        continue;
      }
      GTL(5 + L * 8);

      {
        float acc[64];
        const int sp = inst < 7 ? q_split(inst + 1) : 0;
        int st = sp & 3;
        const bool pre = w_pre(inst);
        uint32_t tbad = 0u;
        const uint32_t toff = ((fresh_tid() & 63) << 7) + ((fresh_tid() & 7) << 4);
        const bool lane0 = (toff & 0xf80u) == 0u;
        constexpr uint32_t U4 = UNIT >> 4, LA = 0x10000u, LB = U4 << 16;
        reg_define<64>(acc);
        reg_fence<64>(acc);
        uint32_t xv[8][4];
        {
          PHASE_IDS_W
          const uint32_t xr = slots + 6 * UNIT + (wwarp * 16 + (lane & 15)) * 128 + (((lane >> 4) ^ (lane & 7)) << 4);
          mbar_wait(bars + 8u * B_RF, inst & 1);
#pragma unroll
          for (int jp = 0; jp < 8; jp++) ldmatrix_x4(xv[jp], (xr ^ ((jp & 3) << 5)) + (jp >> 2) * UNIT);
          fence_proxy_async_smem();
          __syncwarp();
          if (lane0) mbar_arrive(bars + 8u * B_RDONE);
          if (L > 0) {
            uint32_t lsb;
            asm volatile("ld.shared.u8 %0, [%1];" : "=r"(lsb) : "r"(base + OFF_LSB + ch * 32 + wwarp * 8 + g) : "memory");
#pragma unroll
            for (int k = 0; k < 4; k++) xv[(k >> 1) * 4][k & 1] = set_tag(xv[(k >> 1) * 4][k & 1], c == 0, lsb >> k);
          }
        }
        uint64_t d0 = desc_lo((base >> 4) + st * 5 * U4) + P.zero;
        if (inst < 7 || SP7 == 16) mbar_wait_lazy<100>(bars + 8u * (B_TURN + ch), (turn_par(2) >> inst) & 1u);
        mbar_wait(bars + 8u * B_WF, 0);
        GTL(6 + L * 8);
        uint32_t s1 = 0;
#pragma unroll 1
        for (int m = 0; m < 4; m++) {
          const uint32_t s0 = base + st * 5 * UNIT, fb = bars + 8u * (B_WF + 4 * (m & 1));
          s1 = base + ((st + 1) & 3) * 5 * UNIT;
          const uint64_t d1 = desc_lo(s1 >> 4) + P.zero;
          const uint64_t d2 = desc_lo((pre ? slots + m * 2 * UNIT : base + ((st + 2) & 3) * 5 * UNIT) >> 4) + P.zero;
          st = (st + (pre ? 2 : 3)) & 3;
#pragma unroll
          for (int i = 0; i < 4; i++) {
            const uint64_t da = (i == 0 ? d0 : d1) + (LA + (i == 2 ? 1 : (i == 3 ? 4 : 0)) * U4);
            const uint64_t db = (i < 2 ? d0 : (i == 2 ? d1 : d2)) + (LB + (i == 0 ? 1 : (i == 1 ? 3 : (i == 2 ? 2 : 0))) * U4);
            if (i == 3 && (m == 0 || m == 3) && pre) mbar_wait(bars + 8u * (m ? B_PRE2 : B_PRE), __popc(PREMASK & ((1u << inst) - 1u)) & 1);
            if (i == (WTURN & 3) && m == 3 && lane0 && (sp < 16 || inst == 6)) mbar_arrive(bars + 8u * (B_TURN + (ch ^ 1)));
            wgmma_fence();
#pragma unroll
            for (int k16 = 0; k16 < 4; k16++) wgmma_n128_ss_ta0_tb1(acc, da + 2 * k16, db + 128 * k16, 1);
            wgmma_commit();
            if (i == 2) d0 = desc_lo((base >> 4) + st * 5 * U4) + P.zero;
            tbad |= lds32((i == 0 ? s0 : s1) + (i == 2 ? 1 : (i == 3 ? 4 : 0)) * UNIT + toff) ^ o_tag(L);
            const uint32_t fn = i < 3 ? fb + 8u * (i + 1) : fb ^ 96u;
            const uint32_t pn = i < 3 ? m >> 1 : m > 0;
            const bool ok = mbar_test(fn, pn) || (i == 3 && m == 3);
            wgmma_wait<1>();
            if (lane0 && (i > 0 || m > 0)) mbar_arrive((i > 0 ? fb + 8u * (i - 1) : (fb ^ 96u) + 24u) + 8u * B_E);
            if (!ok) mbar_wait(fn, pn);
          }
        }
        const uint32_t xb = s1;
        const bool redo = named_bar_or(1 + ch, 128, tbad & 1u);
        if (redo) {
          wgmma_wait<0>();
          const uint32_t sa = s1 + 4 * UNIT, sb = s1 + 2 * UNIT;
          const uint32_t rb = bars + 8u * (B_REDO + ch);
          if ((fresh_tid() & 127) == 0) {
            mbar_init(rb, 1);
            fence_barrier_init();
          }
          uint32_t rpar = 0;
#pragma unroll 1
          for (int kt = 0, tries = 0; kt < 16;) {
            fence_proxy_async_smem();
            named_bar_sync(1 + ch, 128);
            if ((warp & 3) == 0 && elect_one()) {
                mbar_expect_tx(rb, 3 * UNIT);
              tma_load_2d(sa, &P.o, rb, kt * 64, ch * 1024 + rt * 64);
              tma_load_3d(sb, &P.wo3[L & 1], rb, ct * 128, kt * 64);
            }
            mbar_wait(rb, rpar);
            rpar ^= 1u;
            if (named_bar_or(1 + ch, 128, (lds32(sa + toff) ^ o_tag(L)) & 1u) && ++tries < 4096) continue;
            wgmma_fence();
#pragma unroll
            for (int k16 = 0; k16 < 4; k16++)
              wgmma_n128_ss_ta0_tb1(acc, make_desc(sa + k16 * 32, 16), make_desc(sb + k16 * 2048, UNIT), kt | k16);
            wgmma_commit();
            wgmma_wait<0>();
            kt++;
          }
        }
        PHASE_IDS_W
        const uint32_t xrow = xb + (wwarp * 16 + (lane & 15)) * 128 + (((lane >> 4) ^ (lane & 7)) << 4);
        const unsigned ep1 = __shfl_sync(0xffffffffu, lds32(base + OFF_EPOCH), 0);
        const uint32_t tm = c == 0, lsa = base + OFF_LSB + ch * 32 + wwarp * 8 + g;
        wgmma_wait<0>();
        reg_fence<64>(acc);
        if (lane0) mbar_arrive(bars + 8u * (B_WF + B_E + 7));
        GTL(7 + L * 8);
        const uint32_t tmx = L < 3 ? tm : 0u, xt = x_tag(ep1, L + 1);
        const int grow = ch * 1024 + rt * 64;
#pragma unroll
        for (int jp = 0; jp < 8; jp++) {
#pragma unroll
          for (int q = 0; q < 4; q++) xv[jp][q] = add_bf16x2(xv[jp][q], pack_bf16x2(acc[8 * jp + 2 * q], acc[8 * jp + 2 * q + 1]));
          const bool tg = (jp & 3) == 0;
          stmatrix_x4((xrow ^ ((jp & 3) << 5)) + (jp >> 2) * UNIT,
                      tg ? set_tag(xv[jp][0], tmx, xt) : xv[jp][0], tg ? set_tag(xv[jp][1], tmx, xt) : xv[jp][1], xv[jp][2], xv[jp][3]);
          if ((jp & 3) == 3) {
            fence_proxy_async_smem();
            if (wwarp == jp >> 2) {
              named_bar_sync(8 + 2 * ch + (jp >> 2), 128);
              if (elect_one()) {
                tma_store_2d(&P.x[L + 1], xb + (jp >> 2) * UNIT, ct * 128 + (jp >> 2) * 64, grow);
                bulk_commit();
              }
              __syncwarp();
            } else {
              named_bar_arrive(8 + 2 * ch + (jp >> 2), 128);
            }
            if (L == 2 && jp == 3) GTL(36);
          }
        }
        if (elect_one()) {
          bulk_wait0();
          if (L < 3 && wwarp < 2) red_announce(&g_fx[ch * 8 + (rt >> 1)][ct * 2 + wwarp]);
          mbar_arrive(bars + 8u * (B_RF + B_E));
        }
        __syncwarp();
        if (L < 3) {
          if (c == 0)
            asm volatile("st.shared.u8 [%0], %1;" ::"r"(lsa),
                         "r"((xv[0][0] & 1u) | ((xv[0][1] & 1u) << 1) | ((xv[4][0] & 1u) << 2) | ((xv[4][1] & 1u) << 3)) : "memory");
          float s1[2] = {0.f, 0.f}, s2[2] = {0.f, 0.f};
#pragma unroll
          for (int jp = 0; jp < 8; jp++)
#pragma unroll
            for (int q = 0; q < 4; q++) {
              const float x0 = bf_lo(xv[jp][q]), x1 = bf_hi(xv[jp][q]);
              s1[q & 1] += x0 + x1;
              s2[q & 1] = fmaf(x0, x0, fmaf(x1, x1, s2[q & 1]));
            }
#pragma unroll
          for (int r = 0; r < 2; r++) {
            s1[r] += __shfl_xor_sync(0xffffffffu, s1[r], 1);
            s2[r] += __shfl_xor_sync(0xffffffffu, s2[r], 1);
            s1[r] += __shfl_xor_sync(0xffffffffu, s1[r], 2);
            s2[r] += __shfl_xor_sync(0xffffffffu, s2[r], 2);
            if (c == 0) st_rec(&g_stats[L + 1][ct][grow + wwarp * 16 + g + 8 * r], s1[r], s2[r], 0.f, ep1);
          }
        }
        GTL(8 + L * 8);
      }
    }
    if (threadIdx.x == 128) atomicAdd(g_done, 1u);
  }
}

typedef CUresult (*PFN_tmEncode)(CUtensorMap*, CUtensorMapDataType, cuuint32_t, void*, const cuuint64_t*,
                                 const cuuint64_t*, const cuuint32_t*, const cuuint32_t*, CUtensorMapInterleave,
                                 CUtensorMapSwizzle, CUtensorMapL2promotion, CUtensorMapFloatOOBfill);

PFN_tmEncode get_encode_fn() {
  static PFN_tmEncode fn = nullptr;
  if (!fn) {
    cudaDriverEntryPointQueryResult qr;
    void* p = nullptr;
    cudaGetDriverEntryPoint("cuTensorMapEncodeTiled", &p, cudaEnableDefault, &qr);
    fn = (PFN_tmEncode)p;
  }
  return fn;
}

CUtensorMap make_map(const void* ptr, int rows, int cols) {
  CUtensorMap m;
  cuuint64_t gdim[2] = {(cuuint64_t)cols, (cuuint64_t)rows};
  cuuint64_t gstr[1] = {(cuuint64_t)cols * 2};
  cuuint32_t box[2] = {64, 64};
  cuuint32_t estr[2] = {1, 1};
  get_encode_fn()(&m, CU_TENSOR_MAP_DATA_TYPE_BFLOAT16, 2, const_cast<void*>(ptr), gdim, gstr, box, estr,
                  CU_TENSOR_MAP_INTERLEAVE_NONE, CU_TENSOR_MAP_SWIZZLE_128B, CU_TENSOR_MAP_L2_PROMOTION_L2_128B,
                  CU_TENSOR_MAP_FLOAT_OOB_FILL_NONE);
  return m;
}

CUtensorMap make_map3(const void* ptr, int rows, int cols, int n, int step) {
  CUtensorMap m;
  cuuint64_t gdim[3] = {(cuuint64_t)(cols - (n - 1) * step), (cuuint64_t)rows, (cuuint64_t)n};
  cuuint64_t gstr[2] = {(cuuint64_t)cols * 2, (cuuint64_t)step * 2};
  cuuint32_t box[3] = {64, 64, (cuuint32_t)n};
  cuuint32_t estr[3] = {1, 1, 1};
  get_encode_fn()(&m, CU_TENSOR_MAP_DATA_TYPE_BFLOAT16, 3, const_cast<void*>(ptr), gdim, gstr, box, estr,
                  CU_TENSOR_MAP_INTERLEAVE_NONE, CU_TENSOR_MAP_SWIZZLE_128B, CU_TENSOR_MAP_L2_PROMOTION_L2_128B,
                  CU_TENSOR_MAP_FLOAT_OOB_FILL_NONE);
  return m;
}

CUtensorMap make_map_q(const void* ptr, int sw, int sr) {
  CUtensorMap m;
  cuuint64_t gdim[5] = {DM, 8, 2, 4, S_LEN / 64};
  cuuint64_t gstr[4] = {DM * 2, (cuuint64_t)sr * DM * 2, (cuuint64_t)sw * DM * 2, 64 * DM * 2};
  cuuint32_t box[5] = {64, 8, 2, 4, 2};
  cuuint32_t estr[5] = {1, 1, 1, 1, 1};
  get_encode_fn()(&m, CU_TENSOR_MAP_DATA_TYPE_BFLOAT16, 5, const_cast<void*>(ptr), gdim, gstr, box, estr,
                  CU_TENSOR_MAP_INTERLEAVE_NONE, CU_TENSOR_MAP_SWIZZLE_128B, CU_TENSOR_MAP_L2_PROMOTION_L2_128B,
                  CU_TENSOR_MAP_FLOAT_OOB_FILL_NONE);
  return m;
}

}

extern "C" void kernel_launch(void* const* d_in, const int* in_sizes, int n_in, void* d_out, int out_size) {
  (void)in_sizes; (void)n_in; (void)out_size;
  void *p_o, *p_x;
  cudaGetSymbolAddress(&p_o, g_o);
  cudaGetSymbolAddress(&p_x, g_x);
  static bool attr_done = false;
  if (!attr_done) {
    cudaFuncSetAttribute(fused_kernel, cudaFuncAttributeMaxDynamicSharedMemorySize, SMEM_BYTES);
    attr_done = true;
  }
  Params P;
  P.in_x = (const __nv_bfloat16*)d_in[0];
  P.wqkv_p[0] = (const __nv_bfloat16*)d_in[1];
  P.wo_p[0] = (const __nv_bfloat16*)d_in[2];
  P.wqkv_p[1] = (const __nv_bfloat16*)d_in[4];
  P.wo_p[1] = (const __nv_bfloat16*)d_in[5];
  P.out = (__nv_bfloat16*)d_out;
  P.zero = 0;
  for (int L = 0; L < 5; L++) {
    const void* px = L == 0 ? (const void*)P.in_x : (L == 4 ? d_out : p_x);
    P.x[L] = make_map(px, S_LEN, DM);
    if (L < 4) P.xq[L] = (L & 1) ? make_map_q(px, 16, 8) : make_map_q(px, 8, 32);
  }
  P.o = make_map(p_o, S_LEN, DM);
  for (int t = 0; t < 2; t++) {
    P.wqkv[t] = make_map(P.wqkv_p[t], DM, NQKV);
    P.wqkv3[t] = make_map3(P.wqkv_p[t], DM, NQKV, 3, 1024);
    P.wo3[t] = make_map3(P.wo_p[t], DM, DM, 2, 64);
  }
  fused_kernel<<<NCTA, 512, SMEM_BYTES>>>(P);
}
```

```cpp
#include <cuda_runtime.h>
#include <cuda_bf16.h>
#include <cuda.h>
#include <stdint.h>

namespace {

constexpr int S_LEN = 2048;
constexpr int DM = 1024;
constexpr int NQKV = 3072;
constexpr int NCTA = 128;

__device__ __align__(1024) uint8_t g_kvA[2][16][16][2][16384];
__device__ __align__(1024) uint8_t g_kvB[2][16][16][4096];
__device__ __align__(1024) uint8_t g_zero[16384];
__device__ __align__(1024) __nv_bfloat16 g_o[S_LEN * DM];
__device__ __align__(1024) __nv_bfloat16 g_x[S_LEN * DM];
__device__ __align__(1024) float4 g_stats[4][8][S_LEN];
__device__ __align__(1024) float4 g_cs[2][16][8][64];
__device__ __align__(128) unsigned g_fx[16][16][4];
__device__ __align__(128) unsigned g_fo[32][16][4];
__device__ __align__(128) unsigned g_fk[16][16][4];
__device__ __align__(128) unsigned g_done[32];

constexpr uint32_t SBASE = 1024;
constexpr int UNIT = 8192;
constexpr int NUNITS = 20;
constexpr int OFF_SLOT = NUNITS * UNIT;
constexpr int OFF_BAR = OFF_SLOT + 4 * 16384;
constexpr int OFF_EPOCH = OFF_BAR + 424;
constexpr int OFF_LSB = OFF_BAR + 432;
constexpr int OFF_CS = OFF_BAR + 496;
constexpr int OFF_RS = OFF_CS + 1536;
constexpr int OFF_ONE = OFF_RS + 1024;
constexpr int SMEM_BYTES = OFF_ONE + 16;
constexpr int B_QF = 0, B_WF = 4, B_RF = 12, B_E = 13, B_PREP = 26, B_LOC = 28, B_HALO = 29, B_REL = 33, B_AFREE = 36,
              B_TURN = 37, B_XRDY = 39, B_CS = 41, B_CSD = 42, B_GO = 43, B_PRE = 44, B_HV = 45, B_REDO = 46,
              B_RDONE = 48, B_PRE2 = 49, B_HL = 50;
static_assert(SMEM_BYTES <= 232448, "shared memory");

__device__ __forceinline__ uint32_t smem_u32(const void* p) { return (uint32_t)__cvta_generic_to_shared(p); }

__device__ __forceinline__ void mbar_init(uint32_t bar, uint32_t cnt) {
  asm volatile("mbarrier.init.shared::cta.b64 [%0], %1;" ::"r"(bar), "r"(cnt));
}
__device__ __forceinline__ void mbar_expect_tx(uint32_t bar, uint32_t bytes) {
  asm volatile("mbarrier.arrive.expect_tx.shared::cta.b64 _, [%0], %1;" ::"r"(bar), "r"(bytes) : "memory");
}
__device__ __forceinline__ void mbar_arrive(uint32_t bar) {
  asm volatile("mbarrier.arrive.shared::cta.b64 _, [%0];" ::"r"(bar) : "memory");
}
__device__ __forceinline__ bool mbar_try_wait(uint32_t bar, uint32_t parity) {
  uint32_t ok;
  asm volatile(
      "{\n.reg .pred p;\nmbarrier.try_wait.parity.shared::cta.b64 p, [%1], %2;\nselp.b32 %0, 1, 0, p;\n}\n"
      : "=r"(ok)
      : "r"(bar), "r"(parity)
      : "memory");
  return ok != 0;
}
__device__ __forceinline__ bool mbar_test(uint32_t bar, uint32_t parity) {
  uint32_t ok;
  asm volatile(
      "{\n.reg .pred p;\nmbarrier.test_wait.parity.shared::cta.b64 p, [%1], %2;\nselp.b32 %0, 1, 0, p;\n}\n"
      : "=r"(ok)
      : "r"(bar), "r"(parity)
      : "memory");
  return ok != 0;
}
__device__ __forceinline__ void mbar_wait(uint32_t bar, uint32_t parity) {
#pragma unroll 1
  for (uint32_t it = 0; it < (1u << 18); ++it) {
    if (mbar_try_wait(bar, parity)) return;
  }
}
__device__ __forceinline__ void mbar_pace(uint32_t bar, uint32_t parity) {
#pragma unroll 1
  for (uint32_t it = 0; it < 24; ++it) {
    if (mbar_try_wait(bar, parity)) return;
  }
}
template <int NS>
__device__ __forceinline__ void mbar_wait_lazy(uint32_t bar, uint32_t parity) {
#pragma unroll 1
  for (uint32_t it = 0; it < (1u << 18); ++it) {
    if (mbar_try_wait(bar, parity)) return;
    __nanosleep(NS);
  }
}
__device__ __forceinline__ bool elect_one() {
  uint32_t ok;
  asm volatile("{\n.reg .pred p;\nelect.sync _|p, 0xffffffff;\nselp.b32 %0, 1, 0, p;\n}\n" : "=r"(ok));
  return ok != 0;
}
__device__ __forceinline__ void fence_barrier_init() { asm volatile("fence.mbarrier_init.release.cluster;" ::: "memory"); }
__device__ __forceinline__ void fence_proxy_async_smem() { asm volatile("fence.proxy.async.shared::cta;" ::: "memory"); }

__device__ __forceinline__ void tma_load_2d(uint32_t dst, const CUtensorMap* map, uint32_t bar, int c0, int c1) {
  asm volatile(
      "cp.async.bulk.tensor.2d.shared::cluster.global.mbarrier::complete_tx::bytes [%0], [%1, {%3, %4}], [%2];" ::"r"(dst),
      "l"(map), "r"(bar), "r"(c0), "r"(c1)
      : "memory");
}
__device__ __forceinline__ void tma_load_3d(uint32_t dst, const CUtensorMap* map, uint32_t bar, int c0, int c1) {
  asm volatile(
      "cp.async.bulk.tensor.3d.shared::cluster.global.mbarrier::complete_tx::bytes [%0], [%1, {%3, %4, %5}], [%2];" ::"r"(dst),
      "l"(map), "r"(bar), "r"(c0), "r"(c1), "r"(0)
      : "memory");
}
__device__ __forceinline__ void tma_load_5d(uint32_t dst, const CUtensorMap* map, uint32_t bar, int c0, int c4) {
  asm volatile(
      "cp.async.bulk.tensor.5d.shared::cluster.global.mbarrier::complete_tx::bytes [%0], [%1, {%3, %5, %5, %5, %4}], [%2];" ::"r"(dst),
      "l"(map), "r"(bar), "r"(c0), "r"(c4), "r"(0)
      : "memory");
}
__device__ __forceinline__ void bulk_load(uint32_t dst, const void* src, uint32_t bytes, uint32_t bar) {
  asm volatile("cp.async.bulk.shared::cluster.global.mbarrier::complete_tx::bytes [%0], [%1], %2, [%3];" ::"r"(dst),
               "l"(src), "r"(bytes), "r"(bar)
               : "memory");
}
__device__ __forceinline__ void bulk_store(void* dst, uint32_t src, uint32_t bytes) {
  asm volatile("cp.async.bulk.global.shared::cta.bulk_group [%0], [%1], %2;" ::"l"(dst), "r"(src), "r"(bytes) : "memory");
}
__device__ __forceinline__ void tma_store_2d(const CUtensorMap* map, uint32_t src, int c0, int c1) {
  asm volatile("cp.async.bulk.tensor.2d.global.shared::cta.bulk_group [%0, {%2, %3}], [%1];" ::"l"(map), "r"(src),
               "r"(c0), "r"(c1)
               : "memory");
}
__device__ __forceinline__ void bulk_announce(unsigned* p) {
  asm volatile("cp.reduce.async.bulk.global.shared::cta.bulk_group.add.u32 [%0], [%1], 16;" ::"l"(p), "r"(SBASE + OFF_ONE) : "memory");
}
__device__ __forceinline__ void bulk_commit() { asm volatile("cp.async.bulk.commit_group;" ::: "memory"); }
__device__ __forceinline__ void bulk_wait_read0() { asm volatile("cp.async.bulk.wait_group.read 0;" ::: "memory"); }
__device__ __forceinline__ void bulk_wait0() { asm volatile("cp.async.bulk.wait_group 0;" ::: "memory"); }
__device__ __forceinline__ void named_bar_sync(int id, int nthreads) {
  asm volatile("bar.sync %0, %1;" ::"r"(id), "r"(nthreads) : "memory");
}
__device__ __forceinline__ void named_bar_arrive(int id, int nthreads) {
  asm volatile("bar.arrive %0, %1;" ::"r"(id), "r"(nthreads) : "memory");
}

__device__ __forceinline__ bool named_bar_or(int id, int nthreads, bool v) {
  uint32_t r;
  asm volatile("{\n.reg .pred p, q;\nsetp.ne.b32 q, %3, 0;\nbar.red.or.pred p, %1, %2, q;\nselp.b32 %0, 1, 0, p;\n}\n"
               : "=r"(r) : "r"(id), "r"(nthreads), "r"((int)v) : "memory");
  return __any_sync(0xffffffffu, r != 0);
}

__device__ __forceinline__ void wgmma_fence() { asm volatile("wgmma.fence.sync.aligned;\n" ::: "memory"); }
__device__ __forceinline__ void wgmma_commit() { asm volatile("wgmma.commit_group.sync.aligned;\n" ::: "memory"); }
template <int N>
__device__ __forceinline__ void wgmma_wait() {
  asm volatile("wgmma.wait_group.sync.aligned %0;\n" ::"n"(N) : "memory");
}
template <int R>
__device__ __forceinline__ void setmaxnreg_inc() { asm volatile("setmaxnreg.inc.sync.aligned.u32 %0;\n" ::"n"(R)); }
template <int R>
__device__ __forceinline__ void setmaxnreg_dec() { asm volatile("setmaxnreg.dec.sync.aligned.u32 %0;\n" ::"n"(R)); }
template <int N>
__device__ __forceinline__ void reg_fence(float* r) {
#pragma unroll
  for (int i = 0; i < N; i++) asm volatile("" : "+f"(r[i])::"memory");
}

template <int N>
__device__ __forceinline__ void reg_define(float* r) {
#pragma unroll
  for (int i = 0; i < N; i++) r[i] = 0.f;
}

__device__ __forceinline__ uint64_t desc_lo(uint32_t lo) {
  uint64_t d;
  asm("mov.b64 %0, {%1, %2};" : "=l"(d) : "r"(lo), "r"(0x40000040u));
  return d;
}
__device__ __forceinline__ uint64_t make_desc(uint32_t addr, uint32_t lbo_bytes) {
  return desc_lo((addr >> 4) + ((lbo_bytes >> 4) << 16));
}

__device__ __forceinline__ void wgmma_n192_ss_ta0_tb1(float* d, uint64_t descA, uint64_t descB, int scaleD) {
  asm volatile("{\n.reg .pred p;\nsetp.ne.b32 p, %98, 0;\n"
    "wgmma.mma_async.sync.aligned.m64n192k16.f32.bf16.bf16 {%0, %1, %2, %3, %4, %5, %6, %7, %8, %9, %10, %11, %12, %13, %14, %15, %16, %17, %18, %19, %20, %21, %22, %23, %24, %25, %26, %27, %28, %29, %30, %31, %32, %33, %34, %35, %36, %37, %38, %39, %40, %41, %42, %43, %44, %45, %46, %47, %48, %49, %50, %51, %52, %53, %54, %55, %56, %57, %58, %59, %60, %61, %62, %63, %64, %65, %66, %67, %68, %69, %70, %71, %72, %73, %74, %75, %76, %77, %78, %79, %80, %81, %82, %83, %84, %85, %86, %87, %88, %89, %90, %91, %92, %93, %94, %95}, %96, %97, p, 1, 1, 0, 1;\n}\n"
    : "+f"(d[0]), "+f"(d[1]), "+f"(d[2]), "+f"(d[3]), "+f"(d[4]), "+f"(d[5]), "+f"(d[6]), "+f"(d[7]), "+f"(d[8]), "+f"(d[9]), "+f"(d[10]), "+f"(d[11]), "+f"(d[12]), "+f"(d[13]), "+f"(d[14]), "+f"(d[15]), "+f"(d[16]), "+f"(d[17]), "+f"(d[18]), "+f"(d[19]), "+f"(d[20]), "+f"(d[21]), "+f"(d[22]), "+f"(d[23]), "+f"(d[24]), "+f"(d[25]), "+f"(d[26]), "+f"(d[27]), "+f"(d[28]), "+f"(d[29]), "+f"(d[30]), "+f"(d[31]), "+f"(d[32]), "+f"(d[33]), "+f"(d[34]), "+f"(d[35]), "+f"(d[36]), "+f"(d[37]), "+f"(d[38]), "+f"(d[39]), "+f"(d[40]), "+f"(d[41]), "+f"(d[42]), "+f"(d[43]), "+f"(d[44]), "+f"(d[45]), "+f"(d[46]), "+f"(d[47]), "+f"(d[48]), "+f"(d[49]), "+f"(d[50]), "+f"(d[51]), "+f"(d[52]), "+f"(d[53]), "+f"(d[54]), "+f"(d[55]), "+f"(d[56]), "+f"(d[57]), "+f"(d[58]), "+f"(d[59]), "+f"(d[60]), "+f"(d[61]), "+f"(d[62]), "+f"(d[63]), "+f"(d[64]), "+f"(d[65]), "+f"(d[66]), "+f"(d[67]), "+f"(d[68]), "+f"(d[69]), "+f"(d[70]), "+f"(d[71]), "+f"(d[72]), "+f"(d[73]), "+f"(d[74]), "+f"(d[75]), "+f"(d[76]), "+f"(d[77]), "+f"(d[78]), "+f"(d[79]), "+f"(d[80]), "+f"(d[81]), "+f"(d[82]), "+f"(d[83]), "+f"(d[84]), "+f"(d[85]), "+f"(d[86]), "+f"(d[87]), "+f"(d[88]), "+f"(d[89]), "+f"(d[90]), "+f"(d[91]), "+f"(d[92]), "+f"(d[93]), "+f"(d[94]), "+f"(d[95])
    : "l"(descA), "l"(descB), "r"(scaleD));
}

__device__ __forceinline__ void wgmma_n128_ss_ta0_tb1(float* d, uint64_t descA, uint64_t descB, int scaleD) {
  asm volatile("{\n.reg .pred p;\nsetp.ne.b32 p, %66, 0;\n"
    "wgmma.mma_async.sync.aligned.m64n128k16.f32.bf16.bf16 {%0, %1, %2, %3, %4, %5, %6, %7, %8, %9, %10, %11, %12, %13, %14, %15, %16, %17, %18, %19, %20, %21, %22, %23, %24, %25, %26, %27, %28, %29, %30, %31, %32, %33, %34, %35, %36, %37, %38, %39, %40, %41, %42, %43, %44, %45, %46, %47, %48, %49, %50, %51, %52, %53, %54, %55, %56, %57, %58, %59, %60, %61, %62, %63}, %64, %65, p, 1, 1, 0, 1;\n}\n"
    : "+f"(d[0]), "+f"(d[1]), "+f"(d[2]), "+f"(d[3]), "+f"(d[4]), "+f"(d[5]), "+f"(d[6]), "+f"(d[7]), "+f"(d[8]), "+f"(d[9]), "+f"(d[10]), "+f"(d[11]), "+f"(d[12]), "+f"(d[13]), "+f"(d[14]), "+f"(d[15]), "+f"(d[16]), "+f"(d[17]), "+f"(d[18]), "+f"(d[19]), "+f"(d[20]), "+f"(d[21]), "+f"(d[22]), "+f"(d[23]), "+f"(d[24]), "+f"(d[25]), "+f"(d[26]), "+f"(d[27]), "+f"(d[28]), "+f"(d[29]), "+f"(d[30]), "+f"(d[31]), "+f"(d[32]), "+f"(d[33]), "+f"(d[34]), "+f"(d[35]), "+f"(d[36]), "+f"(d[37]), "+f"(d[38]), "+f"(d[39]), "+f"(d[40]), "+f"(d[41]), "+f"(d[42]), "+f"(d[43]), "+f"(d[44]), "+f"(d[45]), "+f"(d[46]), "+f"(d[47]), "+f"(d[48]), "+f"(d[49]), "+f"(d[50]), "+f"(d[51]), "+f"(d[52]), "+f"(d[53]), "+f"(d[54]), "+f"(d[55]), "+f"(d[56]), "+f"(d[57]), "+f"(d[58]), "+f"(d[59]), "+f"(d[60]), "+f"(d[61]), "+f"(d[62]), "+f"(d[63])
    : "l"(descA), "l"(descB), "r"(scaleD));
}

__device__ __forceinline__ void wgmma_n192_ssz_ta0_tb1(float* d, uint64_t descA, uint64_t descB) {
  asm volatile("{\n.reg .pred p;\nsetp.ne.b32 p, 0, 0;\n"
    "wgmma.mma_async.sync.aligned.m64n192k16.f32.bf16.bf16 {%0, %1, %2, %3, %4, %5, %6, %7, %8, %9, %10, %11, %12, %13, %14, %15, %16, %17, %18, %19, %20, %21, %22, %23, %24, %25, %26, %27, %28, %29, %30, %31, %32, %33, %34, %35, %36, %37, %38, %39, %40, %41, %42, %43, %44, %45, %46, %47, %48, %49, %50, %51, %52, %53, %54, %55, %56, %57, %58, %59, %60, %61, %62, %63, %64, %65, %66, %67, %68, %69, %70, %71, %72, %73, %74, %75, %76, %77, %78, %79, %80, %81, %82, %83, %84, %85, %86, %87, %88, %89, %90, %91, %92, %93, %94, %95}, %96, %97, p, 1, 1, 0, 1;\n}\n"
    : "=f"(d[0]), "=f"(d[1]), "=f"(d[2]), "=f"(d[3]), "=f"(d[4]), "=f"(d[5]), "=f"(d[6]), "=f"(d[7]), "=f"(d[8]), "=f"(d[9]), "=f"(d[10]), "=f"(d[11]), "=f"(d[12]), "=f"(d[13]), "=f"(d[14]), "=f"(d[15]), "=f"(d[16]), "=f"(d[17]), "=f"(d[18]), "=f"(d[19]), "=f"(d[20]), "=f"(d[21]), "=f"(d[22]), "=f"(d[23]), "=f"(d[24]), "=f"(d[25]), "=f"(d[26]), "=f"(d[27]), "=f"(d[28]), "=f"(d[29]), "=f"(d[30]), "=f"(d[31]), "=f"(d[32]), "=f"(d[33]), "=f"(d[34]), "=f"(d[35]), "=f"(d[36]), "=f"(d[37]), "=f"(d[38]), "=f"(d[39]), "=f"(d[40]), "=f"(d[41]), "=f"(d[42]), "=f"(d[43]), "=f"(d[44]), "=f"(d[45]), "=f"(d[46]), "=f"(d[47]), "=f"(d[48]), "=f"(d[49]), "=f"(d[50]), "=f"(d[51]), "=f"(d[52]), "=f"(d[53]), "=f"(d[54]), "=f"(d[55]), "=f"(d[56]), "=f"(d[57]), "=f"(d[58]), "=f"(d[59]), "=f"(d[60]), "=f"(d[61]), "=f"(d[62]), "=f"(d[63]), "=f"(d[64]), "=f"(d[65]), "=f"(d[66]), "=f"(d[67]), "=f"(d[68]), "=f"(d[69]), "=f"(d[70]), "=f"(d[71]), "=f"(d[72]), "=f"(d[73]), "=f"(d[74]), "=f"(d[75]), "=f"(d[76]), "=f"(d[77]), "=f"(d[78]), "=f"(d[79]), "=f"(d[80]), "=f"(d[81]), "=f"(d[82]), "=f"(d[83]), "=f"(d[84]), "=f"(d[85]), "=f"(d[86]), "=f"(d[87]), "=f"(d[88]), "=f"(d[89]), "=f"(d[90]), "=f"(d[91]), "=f"(d[92]), "=f"(d[93]), "=f"(d[94]), "=f"(d[95])
    : "l"(descA), "l"(descB));
}

__device__ __forceinline__ void wgmma_n8_ss_ta1_tb0(float* d, uint64_t descA, uint64_t descB, int scaleD) {
  asm volatile("{\n.reg .pred p;\nsetp.ne.b32 p, %6, 0;\n"
    "wgmma.mma_async.sync.aligned.m64n8k16.f32.bf16.bf16 {%0, %1, %2, %3}, %4, %5, p, 1, 1, 1, 0;\n}\n"
    : "+f"(d[0]), "+f"(d[1]), "+f"(d[2]), "+f"(d[3])
    : "l"(descA), "l"(descB), "r"(scaleD));
}

__device__ __forceinline__ void wgmma_n8_ssz_ta1_tb0(float* d, uint64_t descA, uint64_t descB) {
  asm volatile("{\n.reg .pred p;\nsetp.ne.b32 p, 0, 0;\n"
    "wgmma.mma_async.sync.aligned.m64n8k16.f32.bf16.bf16 {%0, %1, %2, %3}, %4, %5, p, 1, 1, 1, 0;\n}\n"
    : "=f"(d[0]), "=f"(d[1]), "=f"(d[2]), "=f"(d[3])
    : "l"(descA), "l"(descB));
}

__device__ __forceinline__ void wgmma_n192_rs_tb1(float* d, const uint32_t* a, uint64_t descB, int scaleD) {
  asm volatile("{\n.reg .pred p;\nsetp.ne.b32 p, %101, 0;\n"
    "wgmma.mma_async.sync.aligned.m64n192k16.f32.bf16.bf16 {%0, %1, %2, %3, %4, %5, %6, %7, %8, %9, %10, %11, %12, %13, %14, %15, %16, %17, %18, %19, %20, %21, %22, %23, %24, %25, %26, %27, %28, %29, %30, %31, %32, %33, %34, %35, %36, %37, %38, %39, %40, %41, %42, %43, %44, %45, %46, %47, %48, %49, %50, %51, %52, %53, %54, %55, %56, %57, %58, %59, %60, %61, %62, %63, %64, %65, %66, %67, %68, %69, %70, %71, %72, %73, %74, %75, %76, %77, %78, %79, %80, %81, %82, %83, %84, %85, %86, %87, %88, %89, %90, %91, %92, %93, %94, %95}, {%96, %97, %98, %99}, %100, p, 1, 1, 1;\n}\n"
    : "+f"(d[0]), "+f"(d[1]), "+f"(d[2]), "+f"(d[3]), "+f"(d[4]), "+f"(d[5]), "+f"(d[6]), "+f"(d[7]), "+f"(d[8]), "+f"(d[9]), "+f"(d[10]), "+f"(d[11]), "+f"(d[12]), "+f"(d[13]), "+f"(d[14]), "+f"(d[15]), "+f"(d[16]), "+f"(d[17]), "+f"(d[18]), "+f"(d[19]), "+f"(d[20]), "+f"(d[21]), "+f"(d[22]), "+f"(d[23]), "+f"(d[24]), "+f"(d[25]), "+f"(d[26]), "+f"(d[27]), "+f"(d[28]), "+f"(d[29]), "+f"(d[30]), "+f"(d[31]), "+f"(d[32]), "+f"(d[33]), "+f"(d[34]), "+f"(d[35]), "+f"(d[36]), "+f"(d[37]), "+f"(d[38]), "+f"(d[39]), "+f"(d[40]), "+f"(d[41]), "+f"(d[42]), "+f"(d[43]), "+f"(d[44]), "+f"(d[45]), "+f"(d[46]), "+f"(d[47]), "+f"(d[48]), "+f"(d[49]), "+f"(d[50]), "+f"(d[51]), "+f"(d[52]), "+f"(d[53]), "+f"(d[54]), "+f"(d[55]), "+f"(d[56]), "+f"(d[57]), "+f"(d[58]), "+f"(d[59]), "+f"(d[60]), "+f"(d[61]), "+f"(d[62]), "+f"(d[63]), "+f"(d[64]), "+f"(d[65]), "+f"(d[66]), "+f"(d[67]), "+f"(d[68]), "+f"(d[69]), "+f"(d[70]), "+f"(d[71]), "+f"(d[72]), "+f"(d[73]), "+f"(d[74]), "+f"(d[75]), "+f"(d[76]), "+f"(d[77]), "+f"(d[78]), "+f"(d[79]), "+f"(d[80]), "+f"(d[81]), "+f"(d[82]), "+f"(d[83]), "+f"(d[84]), "+f"(d[85]), "+f"(d[86]), "+f"(d[87]), "+f"(d[88]), "+f"(d[89]), "+f"(d[90]), "+f"(d[91]), "+f"(d[92]), "+f"(d[93]), "+f"(d[94]), "+f"(d[95])
    : "r"(a[0]), "r"(a[1]), "r"(a[2]), "r"(a[3]), "l"(descB), "r"(scaleD));
}

__device__ __forceinline__ void wgmma_n80_rs_tb0(float* d, const uint32_t* a, uint64_t descB, int scaleD) {
  asm volatile("{\n.reg .pred p;\nsetp.ne.b32 p, %45, 0;\n"
    "wgmma.mma_async.sync.aligned.m64n80k16.f32.bf16.bf16 {%0, %1, %2, %3, %4, %5, %6, %7, %8, %9, %10, %11, %12, %13, %14, %15, %16, %17, %18, %19, %20, %21, %22, %23, %24, %25, %26, %27, %28, %29, %30, %31, %32, %33, %34, %35, %36, %37, %38, %39}, {%40, %41, %42, %43}, %44, p, 1, 1, 0;\n}\n"
    : "+f"(d[0]), "+f"(d[1]), "+f"(d[2]), "+f"(d[3]), "+f"(d[4]), "+f"(d[5]), "+f"(d[6]), "+f"(d[7]), "+f"(d[8]), "+f"(d[9]), "+f"(d[10]), "+f"(d[11]), "+f"(d[12]), "+f"(d[13]), "+f"(d[14]), "+f"(d[15]), "+f"(d[16]), "+f"(d[17]), "+f"(d[18]), "+f"(d[19]), "+f"(d[20]), "+f"(d[21]), "+f"(d[22]), "+f"(d[23]), "+f"(d[24]), "+f"(d[25]), "+f"(d[26]), "+f"(d[27]), "+f"(d[28]), "+f"(d[29]), "+f"(d[30]), "+f"(d[31]), "+f"(d[32]), "+f"(d[33]), "+f"(d[34]), "+f"(d[35]), "+f"(d[36]), "+f"(d[37]), "+f"(d[38]), "+f"(d[39])
    : "r"(a[0]), "r"(a[1]), "r"(a[2]), "r"(a[3]), "l"(descB), "r"(scaleD));
}

__device__ __forceinline__ void wgmma_n80_rsz_tb0(float* d, const uint32_t* a, uint64_t descB) {
  asm volatile("{\n.reg .pred p;\nsetp.ne.b32 p, 0, 0;\n"
    "wgmma.mma_async.sync.aligned.m64n80k16.f32.bf16.bf16 {%0, %1, %2, %3, %4, %5, %6, %7, %8, %9, %10, %11, %12, %13, %14, %15, %16, %17, %18, %19, %20, %21, %22, %23, %24, %25, %26, %27, %28, %29, %30, %31, %32, %33, %34, %35, %36, %37, %38, %39}, {%40, %41, %42, %43}, %44, p, 1, 1, 0;\n}\n"
    : "=f"(d[0]), "=f"(d[1]), "=f"(d[2]), "=f"(d[3]), "=f"(d[4]), "=f"(d[5]), "=f"(d[6]), "=f"(d[7]), "=f"(d[8]), "=f"(d[9]), "=f"(d[10]), "=f"(d[11]), "=f"(d[12]), "=f"(d[13]), "=f"(d[14]), "=f"(d[15]), "=f"(d[16]), "=f"(d[17]), "=f"(d[18]), "=f"(d[19]), "=f"(d[20]), "=f"(d[21]), "=f"(d[22]), "=f"(d[23]), "=f"(d[24]), "=f"(d[25]), "=f"(d[26]), "=f"(d[27]), "=f"(d[28]), "=f"(d[29]), "=f"(d[30]), "=f"(d[31]), "=f"(d[32]), "=f"(d[33]), "=f"(d[34]), "=f"(d[35]), "=f"(d[36]), "=f"(d[37]), "=f"(d[38]), "=f"(d[39])
    : "r"(a[0]), "r"(a[1]), "r"(a[2]), "r"(a[3]), "l"(descB));
}

__device__ __forceinline__ void wgmma_n32_rs_tb1(float* d, const uint32_t* a, uint64_t descB, int scaleD) {
  asm volatile("{\n.reg .pred p;\nsetp.ne.b32 p, %21, 0;\n"
    "wgmma.mma_async.sync.aligned.m64n32k16.f32.bf16.bf16 {%0, %1, %2, %3, %4, %5, %6, %7, %8, %9, %10, %11, %12, %13, %14, %15}, {%16, %17, %18, %19}, %20, p, 1, 1, 1;\n}\n"
    : "+f"(d[0]), "+f"(d[1]), "+f"(d[2]), "+f"(d[3]), "+f"(d[4]), "+f"(d[5]), "+f"(d[6]), "+f"(d[7]), "+f"(d[8]), "+f"(d[9]), "+f"(d[10]), "+f"(d[11]), "+f"(d[12]), "+f"(d[13]), "+f"(d[14]), "+f"(d[15])
    : "r"(a[0]), "r"(a[1]), "r"(a[2]), "r"(a[3]), "l"(descB), "r"(scaleD));
}

__device__ __forceinline__ void wgmma_n32_rsz_tb1(float* d, const uint32_t* a, uint64_t descB) {
  asm volatile("{\n.reg .pred p;\nsetp.ne.b32 p, 0, 0;\n"
    "wgmma.mma_async.sync.aligned.m64n32k16.f32.bf16.bf16 {%0, %1, %2, %3, %4, %5, %6, %7, %8, %9, %10, %11, %12, %13, %14, %15}, {%16, %17, %18, %19}, %20, p, 1, 1, 1;\n}\n"
    : "=f"(d[0]), "=f"(d[1]), "=f"(d[2]), "=f"(d[3]), "=f"(d[4]), "=f"(d[5]), "=f"(d[6]), "=f"(d[7]), "=f"(d[8]), "=f"(d[9]), "=f"(d[10]), "=f"(d[11]), "=f"(d[12]), "=f"(d[13]), "=f"(d[14]), "=f"(d[15])
    : "r"(a[0]), "r"(a[1]), "r"(a[2]), "r"(a[3]), "l"(descB));
}

__device__ __forceinline__ void wgmma_n32_rs_tb0(float* d, const uint32_t* a, uint64_t descB, int scaleD) {
  asm volatile("{\n.reg .pred p;\nsetp.ne.b32 p, %21, 0;\n"
    "wgmma.mma_async.sync.aligned.m64n32k16.f32.bf16.bf16 {%0, %1, %2, %3, %4, %5, %6, %7, %8, %9, %10, %11, %12, %13, %14, %15}, {%16, %17, %18, %19}, %20, p, 1, 1, 0;\n}\n"
    : "+f"(d[0]), "+f"(d[1]), "+f"(d[2]), "+f"(d[3]), "+f"(d[4]), "+f"(d[5]), "+f"(d[6]), "+f"(d[7]), "+f"(d[8]), "+f"(d[9]), "+f"(d[10]), "+f"(d[11]), "+f"(d[12]), "+f"(d[13]), "+f"(d[14]), "+f"(d[15])
    : "r"(a[0]), "r"(a[1]), "r"(a[2]), "r"(a[3]), "l"(descB), "r"(scaleD));
}

__device__ __forceinline__ void wgmma_n32_rsz_tb0(float* d, const uint32_t* a, uint64_t descB) {
  asm volatile("{\n.reg .pred p;\nsetp.ne.b32 p, 0, 0;\n"
    "wgmma.mma_async.sync.aligned.m64n32k16.f32.bf16.bf16 {%0, %1, %2, %3, %4, %5, %6, %7, %8, %9, %10, %11, %12, %13, %14, %15}, {%16, %17, %18, %19}, %20, p, 1, 1, 0;\n}\n"
    : "=f"(d[0]), "=f"(d[1]), "=f"(d[2]), "=f"(d[3]), "=f"(d[4]), "=f"(d[5]), "=f"(d[6]), "=f"(d[7]), "=f"(d[8]), "=f"(d[9]), "=f"(d[10]), "=f"(d[11]), "=f"(d[12]), "=f"(d[13]), "=f"(d[14]), "=f"(d[15])
    : "r"(a[0]), "r"(a[1]), "r"(a[2]), "r"(a[3]), "l"(descB));
}

__device__ __forceinline__ uint32_t pack_bf16x2(float lo, float hi) {
  uint32_t r;
  asm("cvt.rn.bf16x2.f32 %0, %1, %2;" : "=r"(r) : "f"(hi), "f"(lo));
  return r;
}
__device__ __forceinline__ float bf_lo(uint32_t p) { return __uint_as_float(p << 16); }
__device__ __forceinline__ float bf_hi(uint32_t p) { return __uint_as_float(p & 0xffff0000u); }
__device__ __forceinline__ float bf16_round(float v) { return __bfloat162float(__float2bfloat16_rn(v)); }
__device__ __forceinline__ float ex2_approx(float x) {
  float r;
  asm("ex2.approx.ftz.f32 %0, %1;" : "=f"(r) : "f"(x));
  return r;
}
__device__ __forceinline__ float rcp_fast(float x) {
  float r;
  asm("rcp.approx.ftz.f32 %0, %1;" : "=f"(r) : "f"(x));
  return r;
}
__device__ __forceinline__ void ldmatrix_x4(uint32_t (&r)[4], uint32_t addr) {
  asm volatile("ldmatrix.sync.aligned.m8n8.x4.shared.b16 {%0,%1,%2,%3}, [%4];"
               : "=r"(r[0]), "=r"(r[1]), "=r"(r[2]), "=r"(r[3])
               : "r"(addr)
               : "memory");
}
__device__ __forceinline__ void stmatrix_x4(uint32_t addr, uint32_t r0, uint32_t r1, uint32_t r2, uint32_t r3) {
  asm volatile("stmatrix.sync.aligned.m8n8.x4.shared.b16 [%0], {%1,%2,%3,%4};" ::"r"(addr), "r"(r0), "r"(r1), "r"(r2),
               "r"(r3));
}
__device__ __forceinline__ uint32_t add_bf16x2(uint32_t a, uint32_t b) {
  uint32_t r;
  asm("add.rn.bf16x2 %0, %1, %2;" : "=r"(r) : "r"(a), "r"(b));
  return r;
}
__device__ __forceinline__ uint4 lds128(uint32_t addr) {
  uint4 v;
  asm volatile("ld.shared.v4.b32 {%0,%1,%2,%3}, [%4];" : "=r"(v.x), "=r"(v.y), "=r"(v.z), "=r"(v.w) : "r"(addr) : "memory");
  return v;
}
__device__ __forceinline__ uint32_t lds32(uint32_t addr) {
  uint32_t v;
  asm volatile("ld.shared.b32 %0, [%1];" : "=r"(v) : "r"(addr) : "memory");
  return v;
}
__device__ __forceinline__ void sts32(uint32_t addr, uint32_t v) {
  asm volatile("st.shared.b32 [%0], %1;" ::"r"(addr), "r"(v) : "memory");
}

__device__ __forceinline__ unsigned ld_relaxed_u32(const void* p) {
  unsigned v;
  asm volatile("ld.relaxed.gpu.global.u32 %0, [%1];" : "=r"(v) : "l"(p) : "memory");
  return v;
}
__device__ __forceinline__ unsigned launch_epoch() { return (*(volatile unsigned*)g_done) / NCTA + 1u; }
__device__ __forceinline__ uint32_t set_tag(uint32_t w, uint32_t m, uint32_t tag) { return (w & ~m) | (tag & m); }
__device__ __forceinline__ uint32_t o_tag(int L) { return (L + 1) & 1; }
__device__ __forceinline__ uint32_t x_tag(unsigned ep1, int L) { return (ep1 + L + 1) & 1; }

__device__ __forceinline__ void wait_count(const unsigned* f, unsigned target, int i, uint32_t& seen, int lane) {
  if ((seen >> i) & 1u) return;
#pragma unroll 1
  for (uint32_t it = 0; it < (1u << 17); ++it) {
    seen = __ballot_sync(0xffffffffu, (int)(ld_relaxed_u32(f + (lane & 15) * 4) - target) >= 0);
    if ((seen >> i) & 1u) break;
  }
}
__device__ __forceinline__ float4 ld_rec(const float4* p) {
  float4 v;
  asm volatile("ld.relaxed.gpu.global.v4.f32 {%0,%1,%2,%3}, [%4];" : "=f"(v.x), "=f"(v.y), "=f"(v.z), "=f"(v.w) : "l"(p) : "memory");
  return v;
}
__device__ __forceinline__ void st_rec(float4* p, float a, float b, float c, unsigned tag) {
  asm volatile("st.relaxed.gpu.global.v4.f32 [%0], {%1,%2,%3,%4};" ::"l"(p), "f"(a), "f"(b), "f"(c), "f"(__uint_as_float(tag)) : "memory");
}
template <int N>
__device__ __forceinline__ float4 sum_recs(const float4* p, int stride, unsigned tag) {
  float4 s;
#pragma unroll 1
  for (uint32_t it = 0; it < (1u << 17); ++it) {
    float4 v[N];
#pragma unroll
    for (int t = 0; t < N; t++) v[t] = ld_rec(p + t * stride);
    bool ok = true;
    s = make_float4(0.f, 0.f, 0.f, 0.f);
#pragma unroll
    for (int t = 0; t < N; t++) {
      ok &= __float_as_uint(v[t].w) == tag;
      s.x += v[t].x;
      s.y += v[t].y;
      s.z += v[t].z;
    }
    if (ok) break;
    __nanosleep(200);
  }
  return s;
}

__device__ __forceinline__ int fresh_tid() {
  int t;
  asm volatile("mov.u32 %0, %%tid.x;" : "=r"(t));
  return t;
}
#define PHASE_IDS                                  \
  const int tid_ = fresh_tid();                    \
  const int lane = tid_ & 31, wwarp = __shfl_sync(0xffffffffu, (tid_ >> 5) & 3, 0), tid = tid_ & 127; \
  const int g = lane >> 2, c = lane & 3;           \
  (void)tid; (void)g; (void)c; (void)wwarp;

#define PHASE_IDS_W                                \
  const int lane = fresh_tid() & 31, wwarp = warp & 3; \
  const int g = lane >> 2, c = lane & 3;

#define GTL(i) do { } while (0)
#define TGET(v) do { } while (0)
#define TPUT(c, i, v) do { } while (0)

constexpr float SM_C = 0.17677669529663687f * 1.4426950408889634f;

__device__ __forceinline__ void stmatrix_x4_if(bool ok, uint32_t addr, uint32_t r0, uint32_t r1, uint32_t r2, uint32_t r3) {
  asm volatile("{\n.reg .pred p;\nsetp.ne.b32 p, %5, 0;\n@p stmatrix.sync.aligned.m8n8.x4.shared.b16 [%0], {%1,%2,%3,%4};\n}\n" ::"r"(addr),
               "r"(r0), "r"(r1), "r"(r2), "r"(r3), "r"((int)ok));
}

__device__ __forceinline__ void attn_a_slow(const uint8_t* __restrict__ kvimg, int L, int gb, int hp, uint32_t bad,
                                            int row0, int lane) {
  constexpr uint32_t sq = SBASE + OFF_SLOT + 3 * 16384;
#pragma unroll 1
  for (int j = 0; j < 8; j++) {
    const uint8_t* tp = kvimg + (size_t)(gb * 16 + hp) * 32768 + (j * 32 + lane) * 128 + ((lane & 7) << 4);
#pragma unroll 1
    for (uint32_t it = 0; it < (1u << 17); ++it)
      if (((ld_relaxed_u32(tp) ^ lds32(SBASE + OFF_EPOCH)) & 1u) == 0u) break;
  }
  __syncwarp();
#pragma unroll 1
  for (int t = 0; t < 32; t++) {
    const int hh = t >> 4, row = row0 + (t & 7) + (t & 8) * 4;
    if (!((bad >> hh) & 1u)) continue;
    const int qpos = gb * 128 + row;
    const uint32_t qaddr = sq + row * 128;
    float mx = -INFINITY, sum = 0.f, acc = 0.f;
#pragma unroll 1
    for (int pass = 0; pass < 2; pass++) {
#pragma unroll 1
      for (int j = 0; j < 8; j++) {
        const int kp = qpos - (lane + 32 * j);
        const uint8_t* kr = kvimg + ((size_t)((kp >> 7) * 16 + hp) * 2 + ((kp >> 6) & 1)) * 16384 + (kp & 63) * 128;
        float d = -INFINITY;
        if (kp >= 0) {
          d = 0.f;
#pragma unroll 1
          for (int q = 0; q < 4; q++) {
            const uint4 kv = __ldcg(reinterpret_cast<const uint4*>(kr + (((hh * 4 + q) ^ (kp & 7)) << 4)));
            const uint4 qv = lds128(qaddr + (((hh * 4 + q) ^ (row & 7)) << 4));
            const uint32_t kw[4] = {kv.x, kv.y, kv.z, kv.w}, qw[4] = {qv.x, qv.y, qv.z, qv.w};
#pragma unroll
            for (int e = 0; e < 4; e++) d = fmaf(bf_lo(kw[e]), bf_lo(qw[e]), fmaf(bf_hi(kw[e]), bf_hi(qw[e]), d));
          }
        }
        if (pass == 0) {
          mx = fmaxf(mx, d);
        } else {
          const float ev = ex2_approx(d - mx);
          sum += ev;
          const float pv = bf16_round(ev);
#pragma unroll 1
          for (int kk = 0; kk < 32; kk++) {
            const float pk = __shfl_sync(0xffffffffu, pv, kk);
            const int k2 = qpos - (kk + 32 * j);
            if (k2 >= 0) {
              const uint8_t* vr = kvimg + ((size_t)((k2 >> 7) * 16 + hp) * 2 + ((k2 >> 6) & 1)) * 16384 + 8192 + (k2 & 63) * 128;
              const unsigned short vv =
                  __ldcg(reinterpret_cast<const unsigned short*>(vr + (((hh * 4 + (lane >> 3)) ^ (k2 & 7)) << 4) + (lane & 7) * 2));
              acc = fmaf(pk, __uint_as_float((uint32_t)vv << 16), acc);
            }
          }
        }
      }
      if (pass == 0) {
#pragma unroll
        for (int o = 16; o > 0; o >>= 1) mx = fmaxf(mx, __shfl_xor_sync(0xffffffffu, mx, o));
      }
    }
#pragma unroll
    for (int o = 16; o > 0; o >>= 1) sum += __shfl_xor_sync(0xffffffffu, sum, o);
    acc *= rcp_fast(sum);
    const float hi = __shfl_down_sync(0xffffffffu, acc, 1);
    __syncwarp();
    if ((lane & 1) == 0) sts32(qaddr + (((hh * 4 + (lane >> 3)) ^ (row & 7)) << 4) + (lane & 7) * 2,
                               set_tag(pack_bf16x2(acc, hi), hh == 0 && lane == 0, o_tag(L)));
    __syncwarp();
  }
}

template <int HH>
__device__ __forceinline__ void store_o(const float (&o)[16], const float (&inv)[2], uint32_t ra, uint32_t tag, bool ok) {
  const uint32_t m = HH == 0 && (fresh_tid() & 3) == 0;
#pragma unroll
  for (int jp = 0; jp < 2; jp++) {
    uint32_t w0 = pack_bf16x2(o[8 * jp] * inv[0], o[8 * jp + 1] * inv[0]);
    uint32_t w1 = pack_bf16x2(o[8 * jp + 2] * inv[1], o[8 * jp + 3] * inv[1]);
    if (HH == 0 && jp == 0) {
      w0 = set_tag(w0, m, tag);
      w1 = set_tag(w1, m, tag);
    }
    stmatrix_x4_if(ok, ra ^ ((HH * 4 + 2 * jp) << 4), w0, w1, pack_bf16x2(o[8 * jp + 4] * inv[0], o[8 * jp + 5] * inv[0]),
                   pack_bf16x2(o[8 * jp + 6] * inv[1], o[8 * jp + 7] * inv[1]));
  }
}
__device__ __forceinline__ int tile_row(bool B, int w, int r, int g) { return (B ? 16 * w + 8 * r : 8 * w + 32 * r) + g; }
__device__ __forceinline__ uint32_t q_row_addr(bool B, int R, int w, int lane) {
  return SBASE + OFF_SLOT + 3 * 16384 + R * 8192 + tile_row(B, w, (lane >> 3) & 1, lane & 7) * 128 + (((lane >> 4) ^ (lane & 7)) << 4);
}

struct AttnA {
  float s[2][16], o[2][16], l[2][2], sh[2][3];
  uint32_t p[2][4], t[2], me[4], ra, bad, zero;
};
#define ATS_(i) do { } while (0)
template <int V>
__device__ __forceinline__ void attn_sum(AttnA& a, int nv) {
  constexpr int hh = (V >> 1) & 1, kh = V & 1, i = V >> 2;
#pragma unroll
  for (int r = 0; r < 2; r++) {
    const uint32_t t1 = add_bf16x2(add_bf16x2(a.p[0][r], a.p[0][2 + r]), add_bf16x2(a.p[1][r], a.p[1][2 + r]));
    if (kh == 0) {
      a.t[r] = t1;
    } else {
      uint32_t tt = add_bf16x2(a.t[r], t1);
      if (i > 0) tt = i <= nv ? tt : 0u;
      const float v = bf_lo(tt) + bf_hi(tt);
      a.l[hh][r] = i == 0 ? v : a.l[hh][r] + v;
    }
  }
}
template <int HH>
__device__ __forceinline__ void attn_shfl(AttnA& a) {
#pragma unroll
  for (int r = 0; r < 2; r++)
#pragma unroll
    for (int j = 0; j < 3; j++) a.sh[r][j] = __shfl_xor_sync(0xffffffffu, a.l[HH][r], j + 1);
}
template <int HH>
__device__ __forceinline__ void attn_fin(AttnA& a) {
  bool bad = false;
  float inv[2];
#pragma unroll
  for (int r = 0; r < 2; r++) {
    const float v = (a.l[HH][r] + a.sh[r][0]) + (a.sh[r][1] + a.sh[r][2]);
    bad |= !(v <= 1.152921504606846976e18f && v >= 8.673617379884035e-19f);
    inv[r] = rcp_fast(v);
  }
  bad = __any_sync(0xffffffffu, bad);
  if (HH == 1) wgmma_wait<0>();
  reg_fence<16>(a.o[HH]);
  store_o<HH>(a.o[HH], inv, a.ra, o_tag(0), !bad);
  a.bad = (HH == 0 ? 0u : a.bad) | (bad ? 1u << HH : 0u);
}
__device__ __forceinline__ void attn_masks(AttnA& a, int wr) {
  const int lane = fresh_tid() & 31, d = (lane >> 2) - 2 * (lane & 3);
  const uint32_t tri = d >= 1 ? 0xffffffffu : (d == 0 ? 0xffffu : 0u);
#pragma unroll
  for (int t = 0; t < 4; t++) a.me[t] = wr > t ? 0xffffffffu : (wr == t ? tri : 0u);
}
template <int V, int K>
__device__ __forceinline__ uint32_t attn_exp(AttnA& a) {
  constexpr int i = V >> 2, kh = V & 1, r = K & 1;
  if ((i == 0 && kh > r) || (i == 4 && kh < r)) return 0u;
  const uint32_t w = pack_bf16x2(ex2_approx(a.s[V & 1][2 * K]), ex2_approx(a.s[V & 1][2 * K + 1]));
  if (i == 0 && kh == r) return w & a.me[K >> 1];
  if (i == 4 && kh == r) return w & ~a.me[K >> 1];
  return w;
}
template <int V>
__device__ __forceinline__ void attn_unit(AttnA& a, const uint32_t (&q)[2][2][4], uint64_t dcur, uint64_t dnext, int R, int wr, int nv,
                                          uint32_t hbar, uint32_t hpar, uint32_t rbar, bool rel) {
  constexpr int hh = (V >> 1) & 1, kh = V & 1, i = V >> 2;
  ATS_(V + 1);
  asm volatile("" : "+l"(dcur), "+l"(dnext));
  wgmma_wait<1>();
  reg_fence<16>(a.s[V & 1]);
  bool hok = true;
  if (V == 4) hbar = SBASE + OFF_BAR + 8u * (R ? B_LOC : B_HV);
  if (((V & 3) == 2 && V < 16) || V == 4) hok = mbar_test(hbar, hpar);
  const uint64_t d0 = ((V & 3) >= 2 ? dnext : dcur) + ((hh ^ 1) * 4 + kh * 256), d1 = ((V & 3) >= 2 ? dnext : dcur) + ((hh ^ 1) * 4 + kh * 256 + 2);
  const uint64_t d2 = dcur + (512 + hh * 4 + kh * 256), d3 = dcur + (640 + hh * 4 + kh * 256);
  if ((V & 3) == 1 && V > 4 && rel) mbar_arrive(rbar);
  if (V > 0) attn_sum<V - 1>(a, nv);
  if (V == 15) attn_masks(a, wr);
  if (V == 18) {
    attn_shfl<0>(a);
    a.ra = q_row_addr(false, R, wr, fresh_tid() & 31);
  }
  if (V == 19) attn_fin<0>(a);
  uint32_t p[2][4];
  p[0][0] = attn_exp<V, 0>(a);
  p[0][1] = attn_exp<V, 1>(a);
  p[0][2] = attn_exp<V, 2>(a);
  p[0][3] = attn_exp<V, 3>(a);
  p[1][0] = attn_exp<V, 4>(a);
  p[1][1] = attn_exp<V, 5>(a);
  p[1][2] = attn_exp<V, 6>(a);
  p[1][3] = attn_exp<V, 7>(a);
  if (V > 0) {
#pragma unroll
    for (int r = 0; r < 2; r++) p[1][r] ^= (kh ? a.t[r] : __float_as_uint(a.l[hh ^ 1][r])) & a.zero;
  }
#pragma unroll
  for (int k = 0; k < 8; k++) {
    asm volatile("" : "+r"(p[k >> 2][k & 3]));
    a.p[k >> 2][k & 3] = p[k >> 2][k & 3];
  }
  if (!hok) mbar_wait(hbar, hpar);
  wgmma_fence();
  if (V < 18) wgmma_n32_rsz_tb0(a.s[V & 1], q[hh ^ 1][0], d0);
  if (i == 0 && kh == 0) wgmma_n32_rsz_tb1(a.o[hh], a.p[0], d2);
  else wgmma_n32_rs_tb1(a.o[hh], a.p[0], d2, 1);
  if (V < 18) wgmma_n32_rs_tb0(a.s[V & 1], q[hh ^ 1][1], d1, 1);
  wgmma_n32_rs_tb1(a.o[hh], a.p[1], d3, 1);
  wgmma_commit();
}
template <int I>
__device__ __forceinline__ void attn_step(AttnA& a, const uint32_t (&q)[2][2][4], uint64_t dcur, uint64_t dnext, int R, int wr, int nv,
                                          uint32_t hbar, uint32_t hpar, uint32_t rbar, bool rel) {
  attn_unit<4 * I>(a, q, dcur, dnext, R, wr, nv, hbar, hpar, rbar, rel);
  attn_unit<4 * I + 1>(a, q, dcur, dnext, R, wr, nv, hbar, hpar, rbar, rel);
  attn_unit<4 * I + 2>(a, q, dcur, dnext, R, wr, nv, hbar, hpar, rbar, rel);
  attn_unit<4 * I + 3>(a, q, dcur, dnext, R, wr, nv, hbar, hpar, rbar, rel);
}

__device__ __forceinline__ void attention_a(const uint32_t (&q)[2][2][4], int R, int L, int gb, int hp, uint32_t par, int wr,
                                            uint32_t zero) {
  constexpr uint32_t bars = SBASE + OFF_BAR;
  constexpr uint32_t dslot = ((SBASE + OFF_SLOT) >> 4) + 0x10000u;
  auto next = [&](uint64_t d) { return desc_lo((uint32_t)d == dslot ? dslot + 2048 : (uint32_t)d - 1024) + zero; };
  uint64_t d0 = desc_lo(dslot + R * 1024) + zero, d1 = next(d0);
  AttnA a;
  ATS_(0);
  wgmma_fence();
#pragma unroll
  for (int v = 0; v < 2; v++) {
    wgmma_n32_rsz_tb0(a.s[v], q[0][0], d0 + v * 256);
    wgmma_n32_rs_tb0(a.s[v], q[0][1], d0 + (v * 256 + 2), 1);
    wgmma_commit();
  }
  a.zero = zero;
  const bool lane0 = (fresh_tid() & 31) == 0;
  attn_masks(a, wr);
  const int nv = 2 * gb + R;
  const uint32_t hb = bars + 8u * (B_HALO - R), rb = bars + 8u * (B_REL - R);
  attn_step<0>(a, q, d0, d1, R, wr, nv, hb, par, 0, false);
  d0 = next(d1);
  attn_step<1>(a, q, d1, d0, R, wr, nv, R ? bars + 8u * B_HV : hb + 8, par, rb + 8, lane0);
  d1 = next(d0);
  attn_step<2>(a, q, d0, d1, R, wr, nv, hb + 16, par, rb + 16, lane0);
  d0 = next(d1);
  attn_step<3>(a, q, d1, d0, R, wr, nv, hb + 24, par, rb + 24, lane0 && R);
  attn_step<4>(a, q, d0, d0, R, wr, nv, 0, 0, rb, false);
  ATS_(21);
  attn_sum<19>(a, nv);
  attn_shfl<1>(a);
  attn_fin<1>(a);
  ATS_(22);
  if (a.bad != 0u) attn_a_slow(g_kvA[L >> 1][0][0][0], L, gb, hp, a.bad, R * 64 + wr * 8, fresh_tid() & 31);
}

constexpr uint32_t KB_ROW0 = SBASE + OFF_SLOT + 2048, VB_ROW0 = SBASE + OFF_SLOT + 24576 + 2048;

__device__ __forceinline__ void attention_b(const uint32_t (&q)[2][2][4], int R, int gb, uint32_t par0, int wr) {
  constexpr uint32_t bars = SBASE + OFF_BAR;
  const uint32_t dk = ((KB_ROW0 - 2048) >> 4) + 0x10000u + R * 512, dv = dk + ((VB_ROW0 - KB_ROW0) >> 4);
  float s[2][40];
  mbar_wait(bars + 8u * (B_HALO - R), par0);
  wgmma_fence();
#pragma unroll
  for (int hh = 0; hh < 2; hh++) {
    wgmma_n80_rsz_tb0(s[hh], q[hh][0], desc_lo(dk + hh * 4));
    wgmma_n80_rs_tb0(s[hh], q[hh][1], desc_lo(dk + hh * 4 + 2), 1);
  }
  wgmma_commit();
  const int lane = fresh_tid() & 31, g = lane >> 2;
  const bool odd = g & 1, edge = R == 0 && gb == 0 && wr == 0;
  const int D = 2 * (lane & 3) + (g & 1) - g;
  const uint32_t ra = q_row_addr(true, R, wr, lane);
  wgmma_wait<0>();
  reg_fence<40>(s[0]);
  reg_fence<40>(s[1]);
  float z[2][2], y[2][2];
#define GATHER_(W)                                                                                          \
  _Pragma("unroll") for (int hh = 0; hh < 2; hh++) _Pragma("unroll") for (int r = 0; r < 2; r++) {          \
    const float* e = &s[hh][4 * (2 * W + r) + 2 * r];                                                       \
    z[hh][r] = odd ? e[5] : e[4];                                                                           \
    y[hh][r] = D >= 2 ? (odd ? e[1] : e[0]) : (odd ? e[9] : e[8]);                                          \
  }
  if (wr < 2) {
    if (wr == 0) { GATHER_(0) } else { GATHER_(1) }
  } else {
    if (wr == 2) { GATHER_(2) } else { GATHER_(3) }
  }
#undef GATHER_
  float o[2][16], inv[2][2];
  uint32_t p[2][5][4];
  const int sh = odd ? 16 : 0, kb = wr + (D >= 2 ? 0 : 1);
#pragma unroll
  for (int hh = 0; hh < 2; hh++) {
    if (edge) {
      z[hh][0] = -INFINITY;
      if (D >= 2) y[hh][0] = y[hh][1] = -INFINITY;
    }
    uint32_t ab[2][2];
#pragma unroll
    for (int r = 0; r < 2; r++) {
      float m = fmaxf(z[hh][r], y[hh][r]);
      m = fmaxf(m, __shfl_xor_sync(0xffffffffu, m, 1));
      m = fmaxf(m, __shfl_xor_sync(0xffffffffu, m, 2));
      const float e0 = ex2_approx(z[hh][r] - m), e1 = ex2_approx(y[hh][r] - m);
      inv[hh][r] = e0 + e1;
      ab[r][0] = pack_bf16x2(e0, 0.f) << sh;
      ab[r][1] = pack_bf16x2(e1, 0.f) << sh;
    }
#pragma unroll
    for (int k = 0; k < 5; k++) {
      p[hh][k][0] = k == kb ? ab[0][1] : 0u;
      p[hh][k][1] = k == wr + 1 ? ab[1][0] : 0u;
      p[hh][k][2] = k == wr ? ab[0][0] : 0u;
      p[hh][k][3] = k == kb ? ab[1][1] : 0u;
#pragma unroll
      for (int j = 0; j < 4; j++) asm volatile("" : "+r"(p[hh][k][j]));
    }
  }
  wgmma_fence();
#pragma unroll
  for (int hh = 0; hh < 2; hh++) {
    wgmma_n32_rsz_tb1(o[hh], p[hh][0], desc_lo(dv + hh * 4));
#pragma unroll
    for (int k = 1; k < 5; k++) wgmma_n32_rs_tb1(o[hh], p[hh][k], desc_lo(dv + hh * 4 + k * 128), 1);
  }
  wgmma_commit();
#pragma unroll
  for (int hh = 0; hh < 2; hh++)
#pragma unroll
    for (int r = 0; r < 2; r++) {
      inv[hh][r] += __shfl_xor_sync(0xffffffffu, inv[hh][r], 1);
      inv[hh][r] += __shfl_xor_sync(0xffffffffu, inv[hh][r], 2);
      inv[hh][r] = rcp_fast(inv[hh][r]);
    }
  wgmma_wait<0>();
  reg_fence<16>(o[0]);
  reg_fence<16>(o[1]);
  store_o<0>(o[0], inv[0], ra, o_tag(1), true);
  store_o<1>(o[1], inv[1], ra, o_tag(1), true);
}

#define KTQM 0
#define TRICKLE 300
#define WTURN 15
#define QREL 8
#define PRESLEEP 200
#define CSA 3
#define QTURN 2
#define HTS(i) do { } while (0)
struct Params {
  CUtensorMap x[5], xq[4], o, wqkv[2], wqkv3[2], wo3[2];
  const __nv_bfloat16* in_x;
  const __nv_bfloat16* wqkv_p[2];
  const __nv_bfloat16* wo_p[2];
  __nv_bfloat16* out;
  uint32_t zero;
};

__device__ __forceinline__ void colsum_part(const CUtensorMap* wmap, int ty, int qr, int hp) {
  constexpr uint32_t bars = SBASE + OFF_BAR, slots = SBASE + OFF_SLOT;
  PHASE_IDS
  const unsigned ep1 = launch_epoch();
  if (wwarp == 0 && elect_one()) {
    mbar_expect_tx(bars + 8u * B_CS, 6 * UNIT);
#pragma unroll 1
    for (int j = 0; j < 6; j++) {
      if (ty == 0) mbar_pace(bars + 8u * (B_QF + B_E + ((j * CSA / 6) & 3)), (j * CSA / 6) >> 2);
      else mbar_wait_lazy<100>(bars + 8u * (B_WF + B_E + ((2 * j + 3 - (j & 1)) & 7)), j >= 3);
      tma_load_2d(slots + j * UNIT, wmap, bars + 8u * B_CS, (j >> 1) * 1024 + hp * 64, qr * 128 + (j & 1) * 64);
    }
  }
  constexpr uint64_t ones = (SBASE + OFF_LSB + 32) >> 4;
  float s[3][4];
  mbar_wait_lazy<100>(bars + 8u * B_CS, ty);
  wgmma_fence();
#pragma unroll
  for (int p = 0; p < 3; p++) {
    wgmma_n8_ssz_ta1_tb0(s[p], make_desc(slots + p * 2 * UNIT, 16), ones);
#pragma unroll
    for (int k = 1; k < 8; k++) wgmma_n8_ss_ta1_tb0(s[p], make_desc(slots + p * 2 * UNIT + k * 2048, 16), ones, 1);
  }
  wgmma_commit();
  wgmma_wait<0>();
  reg_fence<12>(&s[0][0]);
  if (lane == 0) mbar_arrive(bars + 8u * (ty ? B_CSD : B_RDONE));
  if (c == 0) {
#pragma unroll
    for (int r = 0; r < 2; r++) st_rec(&g_cs[ty][hp][qr][wwarp * 16 + 8 * r + g], s[0][2 * r], s[1][2 * r], s[2][2 * r], ep1);
  }
}

__device__ __forceinline__ void put_colsums(int ty, int col, const float4& s) {
  const float v[3] = {s.x, s.y, s.z};
#pragma unroll
  for (int p = 0; p < 3; p++) {
    const uint32_t a = SBASE + OFF_CS + (p * 8 + (col >> 3)) * 64 + ty * 32 + (col & 7) * 2;
    const float hi = bf16_round(v[p]);
    const uint32_t w = pack_bf16x2(hi, v[p] - hi);
    asm volatile("st.shared.b16 [%0], %1;" ::"r"(a), "h"((unsigned short)w) : "memory");
    asm volatile("st.shared.b16 [%0], %1;" ::"r"(a + 16), "h"((unsigned short)(w >> 16)) : "memory");
  }
}

__device__ __forceinline__ uint32_t ln_params(float s1, float s2) {
  const float mean = s1 * (1.0f / DM);
  const float var = fmaxf(fmaf(-mean, mean, s2 * (1.0f / DM)), 0.f);
  float sd;
  asm("sqrt.approx.f32 %0, %1;" : "=f"(sd) : "f"(bf16_round(bf16_round(var) + 1e-5f)));
  return pack_bf16x2(mean, sd);
}

struct RingProd {
  uint32_t rel = ((B_QF << 1) | 1) * 0x01010101u + 0x06040200u;
  int st = 0;
  __device__ __forceinline__ uint32_t next(uint32_t bar, uint32_t par, bool wait) {
    const uint32_t e = (rel >> (8 * st)) & 255u, a = SBASE + st * 5 * UNIT;
    if (wait) mbar_wait(SBASE + OFF_BAR + 8u * B_E + 8u * (e >> 1), e & 1u);
    rel ^= (e ^ ((bar << 1) | par)) << (8 * st);
    st = (st + 1) & 3;
    return a;
  }
};

#define SP1 15
#define SP2 14
#define SP3 12
#define SP4 12
#define SP5 15
#define SP6 14
#define SP7 16
__device__ __forceinline__ int q_split(int inst) {
  constexpr uint32_t T = 15u | ((SP1 - 1) << 4) | ((SP2 - 1) << 8) | ((SP3 - 1) << 12) | ((SP4 - 1) << 16) | ((SP5 - 1) << 20) |
                         ((SP6 - 1) << 24) | ((uint32_t)(SP7 - 1) << 28);
  return (int)((T >> (4 * inst)) & 15u) + 1;
}
__host__ __device__ constexpr uint32_t turn_par(int kind) {
  const int sp[8] = {16, SP1, SP2, SP3, SP4, SP5, SP6, SP7};
  int cnt[2] = {0, 0};
  uint32_t m = 0;
  for (int i = 0; i < 8; i++)
    for (int k = 0; k < 3; k++) {
      if (k == kind) m |= (uint32_t)(cnt[i & 1] & 1) << i;
      if (k == 0 ? (i == 1 || (i > 1 && sp[i - 1] < 16)) : (k == 2 || sp[i] < 16)) cnt[i & 1]++;
    }
  return m;
}
#define PREMASK 0xBFu
__device__ __forceinline__ bool w_pre(int inst) { return (PREMASK >> inst) & 1u; }
__global__ void __launch_bounds__(512, 1) fused_kernel(const __grid_constant__ Params P) {
  extern __shared__ __align__(1024) uint8_t smem_raw[];
  constexpr uint32_t base = SBASE, bars = base + OFF_BAR, slots = base + OFF_SLOT;
  if (smem_u32(smem_raw) != base) __trap();
  const int warp = __shfl_sync(0xffffffffu, threadIdx.x >> 5, 0), lane = threadIdx.x & 31;
  const int b = blockIdx.x;
#define QS 0
#define WS 1
  const int qr = ((b & ((8 << QS) - 1)) >> QS) ^ (((b >> (3 + QS)) & 1) * 7);
  const int hp = ((b >> (3 + QS)) << QS) + (b & ((1 << QS) - 1));
  const int rt = ((b & ((16 << WS) - 1)) >> WS) ^ (((b >> (4 + WS)) & 1) * 15);
  const int ct = ((b >> (4 + WS)) << WS) + (b & ((1 << WS) - 1));

  if (warp == 12) {
    if (elect_one()) {
#pragma unroll
      for (int s = 0; s < 4; s++) {
        mbar_init(bars + 8u * (B_QF + s), 2);
        mbar_init(bars + 8u * (B_QF + B_E + s), 4);
      }
      mbar_init(bars + 8u * B_GO, 1);
      fence_barrier_init();
    }
    __syncwarp();
    named_bar_arrive(0, 512);
  }
  if (threadIdx.x == 0) {
    for (int s = B_WF; s <= B_RF; s++) {
      mbar_init(bars + 8u * s, s == B_RF ? 1 : 2);
      mbar_init(bars + 8u * (s + B_E), 4);
    }
    for (int s = 0; s < 4; s++) {
      sts32(base + OFF_ONE + 4 * s, s == 0);
      sts32(base + OFF_LSB + 32 + 4 * s, 0x3f803f80u);
    }
    fence_proxy_async_smem();
    mbar_init(bars + 8u * B_PREP, 1);
    mbar_init(bars + 8u * (B_PREP + 1), 1);
    mbar_init(bars + 8u * B_HL, 1);
    mbar_init(bars + 8u * (B_HL + 1), 1);
    mbar_init(bars + 8u * B_HV, 1);
    for (int s = 0; s < 4; s++) mbar_init(bars + 8u * (B_HALO + s), 1);
    for (int s = 0; s < 3; s++) mbar_init(bars + 8u * (B_REL + s), s == 0 ? 4 : 8);
    mbar_init(bars + 8u * B_LOC, 4);
    mbar_init(bars + 8u * B_AFREE, 2);
    mbar_init(bars + 8u * B_TURN, 4);
    mbar_init(bars + 8u * (B_TURN + 1), 4);
    mbar_init(bars + 8u * B_CS, 1);
    mbar_init(bars + 8u * B_PRE, 1);
    mbar_init(bars + 8u * B_PRE2, 1);
    mbar_init(bars + 8u * B_CSD, 4);
    mbar_init(bars + 8u * B_RDONE, 4);
    mbar_init(bars + 8u * B_XRDY, 1);
    mbar_init(bars + 8u * (B_XRDY + 1), 1);
    fence_barrier_init();
  }
  if (warp != 12) named_bar_sync(0, 512);

  if (warp >= 12) {
    setmaxnreg_dec<32>();
    if (warp == 12) {
      if (elect_one()) {
#pragma unroll 1
        for (int s = 0; s < 16; s++) {
          const uint32_t fb = bars + 8u * (B_QF + (s & 3)), sa = base + (s & 3) * 5 * UNIT;
          if (s >= 4) mbar_wait(fb + 8u * B_E, ((s >> 2) & 1) ^ 1);
          mbar_expect_tx(fb, 5 * UNIT);
          mbar_arrive(fb);
          tma_load_5d(sa + 3 * UNIT, &P.xq[0], fb, s * 64, qr * 2);
          tma_load_3d(sa, &P.wqkv3[0], fb, hp * 64, s * 64);
        }
        mbar_arrive(bars + 8u * B_GO);
        RingProd rp;
#pragma unroll 1
        for (int sg = 4; sg < 34; sg++) {
          const int part = sg & 3, inst = (sg >> 2) - (part & 1);
          if (part == 3 || inst == 8) continue;
          const int ty = (inst >> 1) & 1;
          if (part != 1) {
            const int k0 = part ? q_split(inst) : 0, k1 = part ? 16 : q_split(inst);
#pragma unroll 1
            for (int kt = k0; kt < k1; kt++) {
              const uint32_t sa = rp.next(B_QF + (kt & 3), (kt >> 2) & 1, true), fb = bars + 8u * (B_QF + (kt & 3));
              mbar_expect_tx(fb, 3 * UNIT);
              tma_load_3d(sa, &P.wqkv3[ty], fb, hp * 64, kt * 64);
            }
          } else {
            const bool pre = w_pre(inst);
            const int lag = pre ? 8 : 5;
            uint32_t sa = 0;
#pragma unroll 1
            for (int kt = 0; kt < 16; kt++) {
              const int i = kt & 3;
              const uint32_t fb = bars + 8u * (B_WF + (kt & 7));
              if (i == 1) sa += 2 * UNIT;
              else if (i != 3 || !pre) sa = rp.next(kt == 14 ? B_RF : B_WF + ((kt | 1) & 7), kt == 14 ? inst & 1 : kt >> 3, kt < lag) + ((0x21 >> (2 * i)) & 3) * UNIT;
              if (kt >= lag) mbar_wait(bars + 8u * (B_WF + B_E + ((kt - lag) & 7)), (kt - lag) >> 3);
              if (i == 3 && pre) {
                mbar_arrive(fb);
              } else {
                mbar_expect_tx(fb, 2 * UNIT);
                tma_load_3d(sa, &P.wo3[ty], fb, ct * 128, kt * 64);
              }
            }
          }
        }
      }
    } else if (warp == 13) {
      RingProd rp;
      unsigned ep1 = 0;
      mbar_wait(bars + 8u * B_GO, 0);
#pragma unroll 1
      for (int sg = 4; sg < 34; sg++) {
        const int part = sg & 3, inst = (sg >> 2) - (part & 1);
        if (part == 3 || inst == 8) continue;
        const int L = inst >> 1, ch = inst & 1;
        uint32_t seen = 0;
        if (part != 1) {
          const CUtensorMap* tx = &P.xq[L];
          const int k0 = part ? q_split(inst) : 0, k1 = part ? 16 : q_split(inst);
          if (L == 0 || mbar_test(bars + 8u * (B_XRDY + ch), (L & 1) ^ 1)) {
            seen = 0xFFFFFFFFu;
          }
          if (sg == 4) ep1 = launch_epoch();
          const int m0 = ch * 16 + qr * 2;
#pragma unroll 1
          for (int kt = k0; kt < k1; kt++) {
            wait_count(g_fx[ch * 8 + qr][0], 6u * ep1 - 6u + 2u * L, kt, seen, lane);
            TGET(t38);
            const uint32_t sa = rp.next(B_QF + (kt & 3), (kt >> 2) & 1, true);
            TGET(t39);
            if (elect_one()) {
              const uint32_t fb = bars + 8u * (B_QF + (kt & 3));
              mbar_expect_tx(fb, 2 * UNIT);
              tma_load_5d(sa + 3 * UNIT, tx, fb, kt * 64, m0);
            }
            if (L == 3 && kt == 0 && lane == 0) { TPUT(ch, 38, t38); TPUT(ch, 39, t39); }
          }
        } else {
          const int m0 = ch * 1024 + rt * 64;
          const bool pre = w_pre(inst);
          const int lag = pre ? 8 : 5;
          uint32_t sa = 0;
#pragma unroll 1
          for (int kt = 0; kt < 16; kt++) {
            const int i = kt & 3;
            const uint32_t fb = bars + 8u * (B_WF + (kt & 7));
            wait_count(g_fo[ch * 16 + rt][0], 4u * ep1 - 3u + L, kt, seen, lane);
            const bool stg = kt == 13 && inst == 6 && SP7 == 16;
            if (i < 2) sa = rp.next(stg ? B_RF : B_WF + (kt & 7) + i + 1, stg ? inst & 1 : kt >> 3, kt < lag);
            else sa += (2 * i - 3) * UNIT;
            if (kt >= lag) mbar_wait(bars + 8u * (B_WF + B_E + ((kt - lag) & 7)), (kt - lag) >> 3);
            if (elect_one()) {
              mbar_expect_tx(fb, UNIT);
              tma_load_2d(sa, &P.o, fb, kt * 64, m0);
            }
            if (i == 3 && !pre) rp.next(B_WF + (kt & 7), kt >> 3, false);
          }
        }
      }
    } else if (warp == 14) {
      const unsigned ep1 = launch_epoch();
      uint32_t hpar = 0;
#pragma unroll 1
      for (int inst = 0; inst < 8; inst++) {
        const int L = inst >> 1, ch = inst & 1, gb = ch * 8 + qr;
        const unsigned kv0 = 8u * ep1 - 8u + 2u * L + (L & 1);
        if ((L & 1) == 0) {
          uint8_t* img = g_kvA[L >> 1][gb][hp][0];
          const uint8_t* s1 = gb > 0 ? img - 16 * 32768 : g_zero;
          const uint8_t* s2 = gb > 1 ? img - 32 * 32768 : g_zero;
          const uint32_t h1 = gb > 0 ? 16384 : 0, h2 = gb > 1 ? 16384 : 0;
          const unsigned* cp = g_fk[hp][max(gb - 1 - (lane >= 3), 0)];
          const unsigned ct0 = kv0 + ((0x32321u >> (4 * (lane & 7))) & 3u);
          uint32_t fr = gb == 0 ? 31u : (gb == 1 ? 24u : 0u);
          const uint32_t toff = slots + lane * 128 + ((lane & 7) << 4);
          auto seen = [&](uint32_t m) {
#pragma unroll 1
            for (uint32_t it = 0; it < (1u << 17) && !(fr & m); ++it)
              fr |= __ballot_sync(0xffffffffu, (int)(ld_relaxed_u32(cp) - ct0) >= 0);
          };
          auto load = [&](uint32_t off, const uint8_t* src, uint32_t bytes, int bi) {
            if (elect_one()) {
              mbar_expect_tx(bars + 8u * (B_HL + bi), bytes);
              bulk_load(slots + off, src, bytes, bars + 8u * (B_HL + bi));
            }
          };
          auto check = [&](uint32_t off, const uint8_t* src, uint32_t bytes, int bi, bool real, int done) {
#pragma unroll 1
            for (int tries = 0; tries < 4096; tries++) {
              mbar_wait(bars + 8u * (B_HL + bi), (hpar >> bi) & 1u);
              hpar ^= 1u << bi;
              uint32_t t = (lds32(toff + off) ^ ep1) | (lds32(toff + off + 4096) ^ ep1);
              if (bytes > 8192) t |= (lds32(toff + off + 8192) ^ ep1) | (lds32(toff + off + 12288) ^ ep1);
              if (!__any_sync(0xffffffffu, real && (t & 1u))) break;
              fence_proxy_async_smem();
              load(off, src, bytes, bi);
            }
            if (lane == 0) mbar_arrive(bars + 8u * done);
          };
          named_bar_sync(3, 160);
          HTS(44);
          if (elect_one()) {
            bulk_store(img + 16384, slots + 16384, 8192);
            bulk_announce(g_fk[hp][gb]);
            bulk_store(img + 24576, slots + 24576, 8192);
            bulk_announce(g_fk[hp][gb]);
            bulk_commit();
          }
          seen(1);
          HTS(46);
          load(32768, s1 + h1, 8192, 0);
          seen(2);
          HTS(47);
          load(40960, s1 + h1 + 8192, 8192, 1);
          mbar_wait(bars + 8u * B_LOC, inst & 1);
          HTS(45);
          if (elect_one()) {
            bulk_store(img, slots, 16384);
            bulk_announce(g_fk[hp][gb]);
            bulk_commit();
            asm volatile("cp.async.bulk.wait_group.read 1;" ::: "memory");
          }
          check(32768, s1 + h1, 8192, 0, gb > 0, B_HALO);
          HTS(52);
          check(40960, s1 + h1 + 8192, 8192, 1, gb > 0, B_HV);
          HTS(53);
#pragma unroll 1
          for (int n = 1; n < 4; n++) {
            const uint8_t* src = n == 1 ? s1 : (n == 2 ? s2 + h2 : s2);
            const uint32_t off = n == 3 ? 32768 : 32768 - n * 16384;
            seen(2u << n);
            if (n == 2 && elect_one()) bulk_wait_read0();
            mbar_wait(bars + 8u * (B_REL - 1) + 8u * n, ch);
            HTS(47 + n);
            load(off, src, 16384, 0);
            check(off, src, 16384, 0, gb > (n >> 1), B_HALO + n);
            HTS(53 + n);
          }
        } else {
          uint8_t* img = g_kvB[L >> 1][gb][hp];
          named_bar_sync(3, 160);
          HTS(44);
          if (elect_one()) {
            bulk_store(img, KB_ROW0 + 112 * 128, 2048);
            bulk_store(img + 2048, VB_ROW0 + 112 * 128, 2048);
            bulk_announce(g_fk[hp][gb]);
            bulk_commit();
          }
          const uint8_t* src = gb >= 1 ? img - 16 * 4096 : g_zero;
#pragma unroll 1
          for (uint32_t it = 0; it < (1u << 17); ++it)
            if (gb == 0 || (int)(ld_relaxed_u32(g_fk[hp][gb - 1]) - kv0) > 0) break;
          HTS(46);
#pragma unroll 1
          for (uint32_t it = 0; it < 4096; ++it) {
            if (elect_one()) {
              mbar_expect_tx(bars + 8u * B_HL, 4096);
              bulk_load(KB_ROW0 - 2048, src, 2048, bars + 8u * B_HL);
              bulk_load(VB_ROW0 - 2048, src + 2048, 2048, bars + 8u * B_HL);
              bulk_wait_read0();
            }
            mbar_wait(bars + 8u * B_HL, hpar & 1u);
            hpar ^= 1u;
            const uint32_t t = lds32((lane < 16 ? KB_ROW0 - 2048 : VB_ROW0 - 4096) + lane * 128 + ((lane & 7) << 4)) ^ ep1;
            if (gb == 0 || !__any_sync(0xffffffffu, t & 1u)) break;
            fence_proxy_async_smem();
          }
          if (lane == 0) mbar_arrive(bars + 8u * B_HALO);
          HTS(52);
        }
        if (elect_one()) {
          mbar_wait(bars + 8u * B_AFREE, inst & 1);
          mbar_expect_tx(bars + 8u * B_RF, 2 * UNIT);
          tma_load_2d(slots + 6 * UNIT, &P.x[L], bars + 8u * B_RF, ct * 128, ch * 1024 + rt * 64);
          tma_load_2d(slots + 7 * UNIT, &P.x[L], bars + 8u * B_RF, ct * 128 + 64, ch * 1024 + rt * 64);
          if (w_pre(inst)) {
            mbar_expect_tx(bars + 8u * B_PRE, 6 * UNIT);
            mbar_expect_tx(bars + 8u * B_PRE2, 2 * UNIT);
#pragma unroll 1
            for (int j = 0; j < 4; j++) {
              __nanosleep(PRESLEEP);
              if (j == 3) mbar_wait(bars + 8u * B_RDONE, (inst & 1) ^ 1);
              tma_load_3d(slots + j * 2 * UNIT, &P.wo3[L & 1], bars + 8u * (j == 3 ? B_PRE2 : B_PRE), ct * 128, (4 * j + 3) * 64);
            }
          }
        }
        __syncwarp();
      }
    } else {
      const unsigned ep1 = launch_epoch();
      mbar_wait(bars + 8u * B_GO, 0);
#pragma unroll 1
      for (int i = 0; i < 20; i++) {
        const char* src = i < 4 ? reinterpret_cast<const char*>(P.wo_p[0]) + (size_t)b * 16384 + i * 4096
                                : (i < 16 ? reinterpret_cast<const char*>(P.wqkv_p[1]) + (size_t)b * 49152 + (i - 4) * 4096
                                          : reinterpret_cast<const char*>(P.wo_p[1]) + (size_t)b * 16384 + (i - 16) * 4096);
        asm volatile("prefetch.global.L2 [%0];" ::"l"(src + lane * 128));
        __nanosleep(TRICKLE);
      }
#pragma unroll 1
      for (int inst = 2; inst < 8; inst++) {
        const int L = inst >> 1, ch = inst & 1, gb = ch * 8 + qr;
        mbar_wait_lazy<200>(bars + 8u * (B_RF + B_E), inst & 1);
#pragma unroll 1
        for (int h = 0; h < 4; h++) {
          const float4* sp = &g_stats[L][0][gb * 128 + h * 32 + lane];
          const float4 s0 = sum_recs<4>(sp, S_LEN, ep1), s1 = sum_recs<4>(sp + 4 * S_LEN, S_LEN, ep1);
          sts32(base + OFF_RS + (ch * 128 + h * 32 + lane) * 4, ln_params(s0.x + s1.x, s0.y + s1.y));
        }
        if (lane == 0) mbar_arrive(bars + 8u * (B_XRDY + ch));
        if (inst == 2) {
#pragma unroll 1
          for (int hf = 0; hf < 2; hf++) {
            const float4* cp = &g_cs[1][hp][0][hf * 32 + lane];
            const float4 s0 = sum_recs<4>(cp, 64, ep1), s1 = sum_recs<4>(cp + 4 * 64, 64, ep1);
            put_colsums(1, hf * 32 + lane, make_float4(s0.x + s1.x, s0.y + s1.y, s0.z + s1.z, 0.f));
          }
        }
        fence_proxy_async_smem();
        __syncwarp();
        if (lane == 0) mbar_arrive(bars + 8u * (B_PREP + ch));
      }
    }
  } else {
    const bool asst = warp >= 8;
    GTL(0);
    if (warp >= 4 && !asst) {
      PHASE_IDS
      {
        const unsigned ep1 = launch_epoch();
        const int row = b * 16 + (tid >> 3);
        const uint4* src = reinterpret_cast<const uint4*>(P.in_x + (size_t)row * DM) + (tid & 7);
        float s1 = 0.f, s2 = 0.f;
#pragma unroll 1
        for (int k = 0; k < 4; k++) {
          mbar_pace(bars + 8u * (B_QF + B_E + ((2 * k) & 3)), k >> 1);
          uint4 v[4];
#pragma unroll
          for (int j = 0; j < 4; j++) v[j] = __ldg(src + (k * 4 + j) * 8);
#pragma unroll
          for (int j = 0; j < 4; j++) {
            const uint32_t w[4] = {v[j].x, v[j].y, v[j].z, v[j].w};
#pragma unroll
            for (int e = 0; e < 4; e++) {
              const float x0 = bf_lo(w[e]), x1 = bf_hi(w[e]);
              s1 += x0 + x1;
              s2 = fmaf(x0, x0, fmaf(x1, x1, s2));
            }
          }
        }
#pragma unroll
        for (int o = 1; o < 8; o <<= 1) {
          s1 += __shfl_xor_sync(0xffffffffu, s1, o);
          s2 += __shfl_xor_sync(0xffffffffu, s2, o);
        }
        if ((tid & 7) == 0) st_rec(&g_stats[0][0][row], s1, s2, 0.f, ep1);
        if (tid == 0) sts32(base + OFF_EPOCH, ep1);
        if (tid < 64) {
          const float4 s0 = sum_recs<8>(&g_cs[0][hp][0][tid], 64, ep1);
          put_colsums(0, tid, s0);
        } else {
          put_colsums(1, tid - 64, make_float4(0.f, 0.f, 0.f, 0.f));
        }
#pragma unroll 1
        for (int cc = 0; cc < 2; cc++) {
          const float4 s0 = sum_recs<1>(&g_stats[0][0][(cc * 8 + qr) * 128 + tid], 0, ep1);
          sts32(base + OFF_RS + (cc * 128 + tid) * 4, ln_params(s0.x, s0.y));
        }
        fence_proxy_async_smem();
        named_bar_sync(2, 128);
        if (tid < 2) mbar_arrive(bars + 8u * (B_PREP + tid));
      }
    }
#pragma unroll 1
    for (int inst = asst ? 0 : warp >> 2; inst < 8; inst += asst ? 1 : 2) {
      const int L = inst >> 1, ch = inst & 1, gb = ch * 8 + qr;
      uint32_t q[2][2][4];
      if (asst) {
        if (inst < 2) colsum_part(&P.wqkv[inst], inst, qr, hp);
        setmaxnreg_dec<24>();
        named_bar_sync(4, 256);
        setmaxnreg_inc<128>();
        const uint32_t ra = q_row_addr(L & 1, 1, warp & 3, fresh_tid() & 31);
#pragma unroll
        for (int j = 0; j < 4; j++) ldmatrix_x4(q[j >> 1][j & 1], ra ^ (j << 5));
      } else {
      setmaxnreg_inc<224>();
      {
        float acc[2][96];
        const int ksp = q_split(inst);
        constexpr uint32_t STG = 5 * (UNIT >> 4), D0 = ((base + 3 * UNIT) >> 4) + 0x10000u;
        constexpr uint32_t DB = ((UNIT >> 4) << 16) - 0x10000u - 3 * (UNIT >> 4);
        uint32_t sd = D0;
        uint32_t tand = 1u, tor = 0u, tw = 0u;
        const uint32_t toff = ((fresh_tid() & 127) << 7) + ((fresh_tid() & 7) << 4);
        bool lane0 = (toff & 0xf80u) == 0u;
        if (inst == 1 || (inst > 1 && q_split(inst - 1) < 16)) mbar_wait_lazy<100>(bars + 8u * (B_TURN + ch), (turn_par(0) >> inst) & 1u);
        if (L == 3) GTL(37);
        mbar_wait(bars + 8u * B_QF, 0);
        GTL(1 + L * 8);
        {
          const uint64_t da = desc_lo(sd) + P.zero;
          wgmma_fence();
          wgmma_n192_ssz_ta0_tb1(acc[1], da + (UNIT >> 4), da + DB);
          wgmma_commit();
          wgmma_n192_ssz_ta0_tb1(acc[0], da, da + DB);
          wgmma_commit();
        }
#pragma unroll 1
        for (int kt = 0; kt < 15; kt++) {
          const bool last = kt + 1 == ksp;
          const uint64_t da = desc_lo(sd) + P.zero;
          const uint32_t fn = bars + 8u * (B_QF + ((kt + 1) & 3)), pn = ((kt + 1) >> 2) & 1;
#pragma unroll
          for (int k16 = 0; k16 < 4; k16++) {
            if (k16 == 0 && kt == 0) continue;
            wgmma_fence();
            wgmma_n192_ss_ta0_tb1(acc[1], da + ((UNIT >> 4) + k16 * 2), da + (DB + k16 * 128), 1);
            wgmma_commit();
            wgmma_wait<1>();
            if (k16 == 0 && lane0 && kt != ksp) mbar_arrive(bars + 8u * (B_QF + B_E + ((kt - 1) & 3)));
            wgmma_fence();
            wgmma_n192_ss_ta0_tb1(acc[0], da + k16 * 2, da + (DB + k16 * 128), 1);
            wgmma_commit();
            if (k16 == 1) tw = lds32(((sd & 0xffffu) << 4) + toff);
            if (k16 == 2) {
              tand &= tw;
              tor |= tw;
            }
            bool ok = true;
            if (k16 == 2) ok = mbar_test(fn, pn) || last;
            if (k16 == QTURN && last && lane0) mbar_arrive(bars + 8u * (B_TURN + (ch ^ 1)));
            if (k16 < 3) wgmma_wait<1>();
            if (k16 == 2 && !ok) mbar_wait(fn, pn);
          }
          sd = sd == D0 + 3 * STG ? D0 : sd + STG;
          if (last) {
            wgmma_wait<0>();
            if (lane0) mbar_arrive(bars + 8u * (B_QF + B_E + (kt & 3)));
            mbar_wait_lazy<100>(bars + 8u * (B_TURN + ch), (turn_par(1) >> inst) & 1u);
            mbar_wait(fn, pn);
          }
        }
        PHASE_IDS_W
        lane0 = lane == 0;
        constexpr uint32_t DL = D0 + 3 * STG;
        wgmma_fence();
#pragma unroll
        for (int k16 = 0; k16 < 4; k16++) wgmma_n192_ss_ta0_tb1(acc[1], desc_lo(DL + (UNIT >> 4) + k16 * 2), desc_lo(DL + DB + k16 * 128), 1);
        wgmma_commit();
        tw = lds32(((DL & 0xffffu) << 4) + toff);
        mbar_wait(bars + 8u * (B_PREP + ch), L & 1);
        const uint32_t rsa = base + OFF_RS + (ch * 128 + tile_row(L & 1, wwarp, 0, g)) * 4, rsd = (L & 1) ? 32 : 128;
        uint32_t rs[2][2];
        const uint32_t ep1 = __shfl_sync(0xffffffffu, lds32(base + OFF_EPOCH), 0);
        constexpr uint64_t DCS = (uint64_t)((base + OFF_CS) >> 4) | (4ull << 32);
        auto ln_mma = [&](float (&d)[96], uint32_t (&r)[2], int h) {
          uint32_t a[4];
#pragma unroll
          for (int i = 0; i < 2; i++) {
            r[i] = lds32(rsa + h * 256 + i * rsd);
            a[i] = c == (L & 1) ? __byte_perm(r[i], 0u, 0x1010) ^ 0x80008000u : 0u;
            a[i + 2] = r[i] & P.zero;
          }
#pragma unroll
          for (int i = 0; i < 4; i++) asm volatile("" : "+r"(a[i]));
          wgmma_fence();
          wgmma_n192_rs_tb1(d, a, DCS, 1);
          wgmma_commit();
        };
        wgmma_wait<1>();
        if (lane0 && ksp != 15) mbar_arrive(bars + 8u * (B_QF + B_E + 2));
        ln_mma(acc[1], rs[1], 1);
#pragma unroll
        for (int k16 = 0; k16 < 4; k16++) wgmma_n192_ss_ta0_tb1(acc[0], desc_lo(DL + k16 * 2), desc_lo(DL + DB + k16 * 128), 1);
        wgmma_commit();
        tand &= tw;
        tor |= tw;
        const bool redo = named_bar_or(1 + ch, 128, L > 0 && (((x_tag(ep1, L) ? ~tand : tor) & 1u) != 0u));
        if (ksp < 16) mbar_wait(bars + 8u * (B_WF + B_E + 7), 1);
        static_assert(SP1 < 16 && (PREMASK & 1u), "column sums of B");
        const bool afree = mbar_test(bars + 8u * (inst == 1 ? B_CSD : B_RDONE), inst == 1 ? 0 : inst & 1);
        float rinv[2];
#pragma unroll
        for (int r = 0; r < 2; r++) rinv[r] = rcp_fast(bf_hi(rs[1][r]));
        const uint32_t soff = tile_row(L & 1, wwarp, (lane >> 3) & 1, lane & 7) * 128 + (((lane >> 4) ^ (lane & 7)) << 4);
        const uint32_t kdst = ((L & 1) ? KB_ROW0 : slots) + soff, vdst = ((L & 1) ? VB_ROW0 : slots + 8192) + soff;
        const uint32_t hs = (L & 1) ? 8192 : 16384;
        wgmma_wait<1>();
        if (lane0) mbar_arrive(bars + 8u * (B_TURN + (ch ^ 1)));
        if (redo) {
          wgmma_wait<0>();
          constexpr uint32_t sa = (DL & 0xffffu) << 4;
          const uint32_t rb = bars + 8u * (B_REDO + ch);
          if (toff == 0) {
            mbar_init(rb, 1);
            fence_barrier_init();
          }
          uint32_t rpar = 0;
#pragma unroll 1
          for (int kt = 0, tries = 0; kt < 16;) {
            fence_proxy_async_smem();
            named_bar_sync(1 + ch, 128);
            if ((warp & 3) == 0 && elect_one()) {
                mbar_expect_tx(rb, 5 * UNIT);
              tma_load_5d(sa, &P.xq[L], rb, kt * 64, gb * 2);
              tma_load_3d(sa - 3 * UNIT, &P.wqkv3[L & 1], rb, hp * 64, kt * 64);
            }
            mbar_wait(rb, rpar);
            rpar ^= 1u;
            if (named_bar_or(1 + ch, 128, (lds32(sa + toff) ^ x_tag(ep1, L)) & 1u) && ++tries < 4096) continue;
            wgmma_fence();
#pragma unroll
            for (int k16 = 0; k16 < 4; k16++) {
              const uint64_t db = make_desc(sa - 3 * UNIT + k16 * 2048, UNIT);
              wgmma_n192_ss_ta0_tb1(acc[1], make_desc(sa + UNIT + k16 * 32, 16), db, kt | k16);
              wgmma_n192_ss_ta0_tb1(acc[0], make_desc(sa + k16 * 32, 16), db, kt | k16);
            }
            wgmma_commit();
            wgmma_wait<0>();
            kt++;
          }
          ln_mma(acc[1], rs[1], 1);
          wgmma_wait<0>();
        }
        ln_mma(acc[0], rs[0], 0);
        reg_fence<96>(acc[1]);
        GTL(2 + L * 8);
        if (!afree) mbar_wait(bars + 8u * (inst == 1 ? B_CSD : B_RDONE), inst == 1 ? 0 : inst & 1);
#pragma unroll
        for (int t = 0; t < 24; t++) {
          const int h = t < 12 ? 1 : 0, p = ((t % 12) / 4 + 1) % 3, jp = t & 3;
          if (t == QREL) {
            wgmma_wait<0>();
            reg_fence<96>(acc[0]);
            if (lane0) mbar_arrive(bars + 8u * (B_QF + B_E + 3));
          }
          if (t == 8 || t == 20) {
            rinv[0] *= SM_C;
            rinv[1] *= SM_C;
          }
          const float* a = &acc[h][4 * (p * 8 + 2 * jp)];
          uint32_t r0 = pack_bf16x2(a[0] * rinv[0], a[1] * rinv[0]);
          uint32_t r1 = pack_bf16x2(a[2] * rinv[1], a[3] * rinv[1]);
          if (p != 0 && jp == 0) {
            r0 = set_tag(r0, c == 0, ep1);
            r1 = set_tag(r1, c == 0, ep1);
          }
          const uint32_t r2 = pack_bf16x2(a[4] * rinv[0], a[5] * rinv[0]);
          const uint32_t r3 = pack_bf16x2(a[6] * rinv[1], a[7] * rinv[1]);
          const uint32_t dst = p == 0 ? slots + 3 * 16384 + soff + h * 8192 : (p == 1 ? kdst : vdst) + h * hs;
          stmatrix_x4(dst ^ (jp << 5), r0, r1, r2, r3);
          if (t >= 20) {
            q[jp >> 1][jp & 1][0] = r0;
            q[jp >> 1][jp & 1][1] = r1;
            q[jp >> 1][jp & 1][2] = r2;
            q[jp >> 1][jp & 1][3] = r3;
          }
          if (t == 7 || t == 19) {
            fence_proxy_async_smem();
            if (t == 7) {
              named_bar_arrive(3, 160);
            } else {
              __syncwarp();
              if (lane0) mbar_arrive(bars + 8u * B_LOC);
            }
          }
          if (t == 11) {
            setmaxnreg_dec<128>();
            named_bar_arrive(4, 256);
#pragma unroll
            for (int r = 0; r < 2; r++) rinv[r] = rcp_fast(bf_hi(rs[0][r]));
          }
        }
        mbar_wait(bars + 8u * B_LOC, inst & 1);
      }
      }
      GTL(3 + L * 8);
      if ((L & 1) == 0) attention_a(q, asst, L, gb, hp, ch, warp & 3, P.zero);
      else attention_b(q, asst, gb, inst & 1, warp & 3);
      GTL(4 + L * 8);
      fence_proxy_async_smem();
      named_bar_sync(asst ? 6 : 1 + ch, 128);
      if ((warp & 3) == 0) {
        if (elect_one()) {
          tma_store_2d(&P.o, slots + 3 * 16384 + asst * 8192, hp * 64, gb * 128 + asst * 64);
          bulk_announce(g_fo[gb * 2 + asst][hp]);
          bulk_commit();
          bulk_wait_read0();
          mbar_arrive(bars + 8u * B_AFREE);
        }
        __syncwarp();
      }
      if (asst) continue;
      GTL(5 + L * 8);

      {
        float acc[64];
        const int sp = inst < 7 ? q_split(inst + 1) : 0;
        int st = sp & 3;
        const bool pre = w_pre(inst);
        uint32_t tbad = 0u;
        const uint32_t toff = ((fresh_tid() & 63) << 7) + ((fresh_tid() & 7) << 4);
        const bool lane0 = (toff & 0xf80u) == 0u;
        constexpr uint32_t U4 = UNIT >> 4, LA = 0x10000u, LB = U4 << 16;
        reg_define<64>(acc);
        reg_fence<64>(acc);
        uint32_t xv[8][4];
        {
          PHASE_IDS_W
          const uint32_t xr = slots + 6 * UNIT + (wwarp * 16 + (lane & 15)) * 128 + (((lane >> 4) ^ (lane & 7)) << 4);
          mbar_wait(bars + 8u * B_RF, inst & 1);
#pragma unroll
          for (int jp = 0; jp < 8; jp++) ldmatrix_x4(xv[jp], (xr ^ ((jp & 3) << 5)) + (jp >> 2) * UNIT);
          fence_proxy_async_smem();
          __syncwarp();
          if (lane0) mbar_arrive(bars + 8u * B_RDONE);
          if (L > 0) {
            uint32_t lsb;
            asm volatile("ld.shared.u8 %0, [%1];" : "=r"(lsb) : "r"(base + OFF_LSB + ch * 32 + wwarp * 8 + g) : "memory");
#pragma unroll
            for (int k = 0; k < 4; k++) xv[(k >> 1) * 4][k & 1] = set_tag(xv[(k >> 1) * 4][k & 1], c == 0, lsb >> k);
          }
        }
        uint64_t d0 = desc_lo((base >> 4) + st * 5 * U4) + P.zero;
        if (inst < 7 || SP7 == 16) mbar_wait_lazy<100>(bars + 8u * (B_TURN + ch), (turn_par(2) >> inst) & 1u);
        mbar_wait(bars + 8u * B_WF, 0);
        GTL(6 + L * 8);
        uint32_t s1 = 0;
#pragma unroll 1
        for (int m = 0; m < 4; m++) {
          const uint32_t s0 = base + st * 5 * UNIT, fb = bars + 8u * (B_WF + 4 * (m & 1));
          s1 = base + ((st + 1) & 3) * 5 * UNIT;
          const uint64_t d1 = desc_lo(s1 >> 4) + P.zero;
          const uint64_t d2 = desc_lo((pre ? slots + m * 2 * UNIT : base + ((st + 2) & 3) * 5 * UNIT) >> 4) + P.zero;
          st = (st + (pre ? 2 : 3)) & 3;
#pragma unroll
          for (int i = 0; i < 4; i++) {
            const uint64_t da = (i == 0 ? d0 : d1) + (LA + (i == 2 ? 1 : (i == 3 ? 4 : 0)) * U4);
            const uint64_t db = (i < 2 ? d0 : (i == 2 ? d1 : d2)) + (LB + (i == 0 ? 1 : (i == 1 ? 3 : (i == 2 ? 2 : 0))) * U4);
            if (i == 3 && (m == 0 || m == 3) && pre) mbar_wait(bars + 8u * (m ? B_PRE2 : B_PRE), __popc(PREMASK & ((1u << inst) - 1u)) & 1);
            if (i == (WTURN & 3) && m == 3 && lane0 && (sp < 16 || inst == 6)) mbar_arrive(bars + 8u * (B_TURN + (ch ^ 1)));
            wgmma_fence();
#pragma unroll
            for (int k16 = 0; k16 < 4; k16++) wgmma_n128_ss_ta0_tb1(acc, da + 2 * k16, db + 128 * k16, 1);
            wgmma_commit();
            if (i == 2) d0 = desc_lo((base >> 4) + st * 5 * U4) + P.zero;
            tbad |= lds32((i == 0 ? s0 : s1) + (i == 2 ? 1 : (i == 3 ? 4 : 0)) * UNIT + toff) ^ o_tag(L);
            const uint32_t fn = i < 3 ? fb + 8u * (i + 1) : fb ^ 96u;
            const uint32_t pn = i < 3 ? m >> 1 : m > 0;
            const bool ok = mbar_test(fn, pn) || (i == 3 && m == 3);
            wgmma_wait<1>();
            if (lane0 && (i > 0 || m > 0)) mbar_arrive((i > 0 ? fb + 8u * (i - 1) : (fb ^ 96u) + 24u) + 8u * B_E);
            if (!ok) mbar_wait(fn, pn);
          }
        }
        const uint32_t xb = s1;
        const bool redo = named_bar_or(1 + ch, 128, tbad & 1u);
        if (redo) {
          wgmma_wait<0>();
          const uint32_t sa = s1 + 4 * UNIT, sb = s1 + 2 * UNIT;
          const uint32_t rb = bars + 8u * (B_REDO + ch);
          if ((fresh_tid() & 127) == 0) {
            mbar_init(rb, 1);
            fence_barrier_init();
          }
          uint32_t rpar = 0;
#pragma unroll 1
          for (int kt = 0, tries = 0; kt < 16;) {
            fence_proxy_async_smem();
            named_bar_sync(1 + ch, 128);
            if ((warp & 3) == 0 && elect_one()) {
                mbar_expect_tx(rb, 3 * UNIT);
              tma_load_2d(sa, &P.o, rb, kt * 64, ch * 1024 + rt * 64);
              tma_load_3d(sb, &P.wo3[L & 1], rb, ct * 128, kt * 64);
            }
            mbar_wait(rb, rpar);
            rpar ^= 1u;
            if (named_bar_or(1 + ch, 128, (lds32(sa + toff) ^ o_tag(L)) & 1u) && ++tries < 4096) continue;
            wgmma_fence();
#pragma unroll
            for (int k16 = 0; k16 < 4; k16++)
              wgmma_n128_ss_ta0_tb1(acc, make_desc(sa + k16 * 32, 16), make_desc(sb + k16 * 2048, UNIT), kt | k16);
            wgmma_commit();
            wgmma_wait<0>();
            kt++;
          }
        }
        PHASE_IDS_W
        const uint32_t xrow = xb + (wwarp * 16 + (lane & 15)) * 128 + (((lane >> 4) ^ (lane & 7)) << 4);
        const unsigned ep1 = __shfl_sync(0xffffffffu, lds32(base + OFF_EPOCH), 0);
        const uint32_t tm = c == 0, lsa = base + OFF_LSB + ch * 32 + wwarp * 8 + g;
        wgmma_wait<0>();
        reg_fence<64>(acc);
        if (lane0) mbar_arrive(bars + 8u * (B_WF + B_E + 7));
        GTL(7 + L * 8);
        const uint32_t tmx = L < 3 ? tm : 0u, xt = x_tag(ep1, L + 1);
        const int grow = ch * 1024 + rt * 64;
#pragma unroll
        for (int jp = 0; jp < 8; jp++) {
#pragma unroll
          for (int q = 0; q < 4; q++) xv[jp][q] = add_bf16x2(xv[jp][q], pack_bf16x2(acc[8 * jp + 2 * q], acc[8 * jp + 2 * q + 1]));
          const bool tg = (jp & 3) == 0;
          stmatrix_x4((xrow ^ ((jp & 3) << 5)) + (jp >> 2) * UNIT,
                      tg ? set_tag(xv[jp][0], tmx, xt) : xv[jp][0], tg ? set_tag(xv[jp][1], tmx, xt) : xv[jp][1], xv[jp][2], xv[jp][3]);
          if ((jp & 3) == 3) {
            fence_proxy_async_smem();
            if (wwarp == jp >> 2) {
              named_bar_sync(8 + 2 * ch + (jp >> 2), 128);
              if (elect_one()) {
                tma_store_2d(&P.x[L + 1], xb + (jp >> 2) * UNIT, ct * 128 + (jp >> 2) * 64, grow);
                if (L < 3) bulk_announce(g_fx[ch * 8 + (rt >> 1)][ct * 2 + (jp >> 2)]);
                bulk_commit();
              }
              __syncwarp();
            } else {
              named_bar_arrive(8 + 2 * ch + (jp >> 2), 128);
            }
            if (L == 2 && jp == 3) GTL(36);
          }
        }
        if (elect_one()) {
          bulk_wait_read0();
          mbar_arrive(bars + 8u * (B_RF + B_E));
        }
        __syncwarp();
        if (L < 3) {
          if (c == 0)
            asm volatile("st.shared.u8 [%0], %1;" ::"r"(lsa),
                         "r"((xv[0][0] & 1u) | ((xv[0][1] & 1u) << 1) | ((xv[4][0] & 1u) << 2) | ((xv[4][1] & 1u) << 3)) : "memory");
          float s1[2] = {0.f, 0.f}, s2[2] = {0.f, 0.f};
#pragma unroll
          for (int jp = 0; jp < 8; jp++)
#pragma unroll
            for (int q = 0; q < 4; q++) {
              const float x0 = bf_lo(xv[jp][q]), x1 = bf_hi(xv[jp][q]);
              s1[q & 1] += x0 + x1;
              s2[q & 1] = fmaf(x0, x0, fmaf(x1, x1, s2[q & 1]));
            }
#pragma unroll
          for (int r = 0; r < 2; r++) {
            s1[r] += __shfl_xor_sync(0xffffffffu, s1[r], 1);
            s2[r] += __shfl_xor_sync(0xffffffffu, s2[r], 1);
            s1[r] += __shfl_xor_sync(0xffffffffu, s1[r], 2);
            s2[r] += __shfl_xor_sync(0xffffffffu, s2[r], 2);
            if (c == 0) st_rec(&g_stats[L + 1][ct][grow + wwarp * 16 + g + 8 * r], s1[r], s2[r], 0.f, ep1);
          }
        }
        GTL(8 + L * 8);
      }
    }
    if (threadIdx.x == 128) atomicAdd(g_done, 1u);
  }
}

typedef CUresult (*PFN_tmEncode)(CUtensorMap*, CUtensorMapDataType, cuuint32_t, void*, const cuuint64_t*,
                                 const cuuint64_t*, const cuuint32_t*, const cuuint32_t*, CUtensorMapInterleave,
                                 CUtensorMapSwizzle, CUtensorMapL2promotion, CUtensorMapFloatOOBfill);

PFN_tmEncode get_encode_fn() {
  static PFN_tmEncode fn = nullptr;
  if (!fn) {
    cudaDriverEntryPointQueryResult qr;
    void* p = nullptr;
    cudaGetDriverEntryPoint("cuTensorMapEncodeTiled", &p, cudaEnableDefault, &qr);
    fn = (PFN_tmEncode)p;
  }
  return fn;
}

CUtensorMap make_map(const void* ptr, int rows, int cols) {
  CUtensorMap m;
  cuuint64_t gdim[2] = {(cuuint64_t)cols, (cuuint64_t)rows};
  cuuint64_t gstr[1] = {(cuuint64_t)cols * 2};
  cuuint32_t box[2] = {64, 64};
  cuuint32_t estr[2] = {1, 1};
  get_encode_fn()(&m, CU_TENSOR_MAP_DATA_TYPE_BFLOAT16, 2, const_cast<void*>(ptr), gdim, gstr, box, estr,
                  CU_TENSOR_MAP_INTERLEAVE_NONE, CU_TENSOR_MAP_SWIZZLE_128B, CU_TENSOR_MAP_L2_PROMOTION_L2_128B,
                  CU_TENSOR_MAP_FLOAT_OOB_FILL_NONE);
  return m;
}

CUtensorMap make_map3(const void* ptr, int rows, int cols, int n, int step) {
  CUtensorMap m;
  cuuint64_t gdim[3] = {(cuuint64_t)(cols - (n - 1) * step), (cuuint64_t)rows, (cuuint64_t)n};
  cuuint64_t gstr[2] = {(cuuint64_t)cols * 2, (cuuint64_t)step * 2};
  cuuint32_t box[3] = {64, 64, (cuuint32_t)n};
  cuuint32_t estr[3] = {1, 1, 1};
  get_encode_fn()(&m, CU_TENSOR_MAP_DATA_TYPE_BFLOAT16, 3, const_cast<void*>(ptr), gdim, gstr, box, estr,
                  CU_TENSOR_MAP_INTERLEAVE_NONE, CU_TENSOR_MAP_SWIZZLE_128B, CU_TENSOR_MAP_L2_PROMOTION_L2_128B,
                  CU_TENSOR_MAP_FLOAT_OOB_FILL_NONE);
  return m;
}

CUtensorMap make_map_q(const void* ptr, int sw, int sr) {
  CUtensorMap m;
  cuuint64_t gdim[5] = {DM, 8, 2, 4, S_LEN / 64};
  cuuint64_t gstr[4] = {DM * 2, (cuuint64_t)sr * DM * 2, (cuuint64_t)sw * DM * 2, 64 * DM * 2};
  cuuint32_t box[5] = {64, 8, 2, 4, 2};
  cuuint32_t estr[5] = {1, 1, 1, 1, 1};
  get_encode_fn()(&m, CU_TENSOR_MAP_DATA_TYPE_BFLOAT16, 5, const_cast<void*>(ptr), gdim, gstr, box, estr,
                  CU_TENSOR_MAP_INTERLEAVE_NONE, CU_TENSOR_MAP_SWIZZLE_128B, CU_TENSOR_MAP_L2_PROMOTION_L2_128B,
                  CU_TENSOR_MAP_FLOAT_OOB_FILL_NONE);
  return m;
}

}

extern "C" void kernel_launch(void* const* d_in, const int* in_sizes, int n_in, void* d_out, int out_size) {
  (void)in_sizes; (void)n_in; (void)out_size;
  void *p_o, *p_x;
  cudaGetSymbolAddress(&p_o, g_o);
  cudaGetSymbolAddress(&p_x, g_x);
  static bool attr_done = false;
  if (!attr_done) {
    cudaFuncSetAttribute(fused_kernel, cudaFuncAttributeMaxDynamicSharedMemorySize, SMEM_BYTES);
    attr_done = true;
  }
  Params P;
  P.in_x = (const __nv_bfloat16*)d_in[0];
  P.wqkv_p[0] = (const __nv_bfloat16*)d_in[1];
  P.wo_p[0] = (const __nv_bfloat16*)d_in[2];
  P.wqkv_p[1] = (const __nv_bfloat16*)d_in[4];
  P.wo_p[1] = (const __nv_bfloat16*)d_in[5];
  P.out = (__nv_bfloat16*)d_out;
  P.zero = 0;
  for (int L = 0; L < 5; L++) {
    const void* px = L == 0 ? (const void*)P.in_x : (L == 4 ? d_out : p_x);
    P.x[L] = make_map(px, S_LEN, DM);
    if (L < 4) P.xq[L] = (L & 1) ? make_map_q(px, 16, 8) : make_map_q(px, 8, 32);
  }
  P.o = make_map(p_o, S_LEN, DM);
  for (int t = 0; t < 2; t++) {
    P.wqkv[t] = make_map(P.wqkv_p[t], DM, NQKV);
    P.wqkv3[t] = make_map3(P.wqkv_p[t], DM, NQKV, 3, 1024);
    P.wo3[t] = make_map3(P.wo_p[t], DM, DM, 2, 64);
  }
  fused_kernel<<<NCTA, 512, SMEM_BYTES>>>(P);
}
```

```cpp
#include <cuda_runtime.h>
#include <cuda_bf16.h>
#include <cuda.h>
#include <stdint.h>

namespace {

constexpr int S_LEN = 2048;
constexpr int DM = 1024;
constexpr int NQKV = 3072;
constexpr int NCTA = 128;

__device__ __align__(1024) uint8_t g_kvA[2][16][16][2][16384];
__device__ __align__(1024) uint8_t g_kvB[2][16][16][4096];
__device__ __align__(1024) uint8_t g_zero[16384];
__device__ __align__(1024) __nv_bfloat16 g_o[S_LEN * DM];
__device__ __align__(1024) __nv_bfloat16 g_x[S_LEN * DM];
__device__ __align__(1024) float4 g_stats[4][8][S_LEN];
__device__ __align__(1024) float4 g_cs[2][16][8][64];
__device__ __align__(128) unsigned g_fx[16][16][4];
__device__ __align__(128) unsigned g_fo[32][16][4];
__device__ __align__(128) unsigned g_fk[16][16][4];
__device__ __align__(128) unsigned g_done[32];

constexpr uint32_t SBASE = 1024;
constexpr int UNIT = 8192;
constexpr int NUNITS = 20;
constexpr int OFF_SLOT = NUNITS * UNIT;
constexpr int OFF_BAR = OFF_SLOT + 4 * 16384;
constexpr int OFF_EPOCH = OFF_BAR + 424;
constexpr int OFF_LSB = OFF_BAR + 432;
constexpr int OFF_CS = OFF_BAR + 496;
constexpr int OFF_RS = OFF_CS + 1536;
constexpr int OFF_ONE = OFF_RS + 1024;
constexpr int SMEM_BYTES = OFF_ONE + 16;
constexpr int B_QF = 0, B_WF = 4, B_RF = 12, B_E = 13, B_PREP = 26, B_LOC = 28, B_HALO = 29, B_REL = 33, B_AFREE = 36,
              B_TURN = 37, B_XRDY = 39, B_CS = 41, B_CSD = 42, B_GO = 43, B_PRE = 44, B_HV = 45, B_REDO = 46,
              B_RDONE = 48, B_PRE2 = 49, B_HL = 50;
static_assert(SMEM_BYTES <= 232448, "shared memory");

__device__ __forceinline__ uint32_t smem_u32(const void* p) { return (uint32_t)__cvta_generic_to_shared(p); }

__device__ __forceinline__ void mbar_init(uint32_t bar, uint32_t cnt) {
  asm volatile("mbarrier.init.shared::cta.b64 [%0], %1;" ::"r"(bar), "r"(cnt));
}
__device__ __forceinline__ void mbar_expect_tx(uint32_t bar, uint32_t bytes) {
  asm volatile("mbarrier.arrive.expect_tx.shared::cta.b64 _, [%0], %1;" ::"r"(bar), "r"(bytes) : "memory");
}
__device__ __forceinline__ void mbar_arrive(uint32_t bar) {
  asm volatile("mbarrier.arrive.shared::cta.b64 _, [%0];" ::"r"(bar) : "memory");
}
__device__ __forceinline__ bool mbar_try_wait(uint32_t bar, uint32_t parity) {
  uint32_t ok;
  asm volatile(
      "{\n.reg .pred p;\nmbarrier.try_wait.parity.shared::cta.b64 p, [%1], %2;\nselp.b32 %0, 1, 0, p;\n}\n"
      : "=r"(ok)
      : "r"(bar), "r"(parity)
      : "memory");
  return ok != 0;
}
__device__ __forceinline__ bool mbar_test(uint32_t bar, uint32_t parity) {
  uint32_t ok;
  asm volatile(
      "{\n.reg .pred p;\nmbarrier.test_wait.parity.shared::cta.b64 p, [%1], %2;\nselp.b32 %0, 1, 0, p;\n}\n"
      : "=r"(ok)
      : "r"(bar), "r"(parity)
      : "memory");
  return ok != 0;
}
__device__ __forceinline__ void mbar_wait(uint32_t bar, uint32_t parity) {
#pragma unroll 1
  for (uint32_t it = 0; it < (1u << 18); ++it) {
    if (mbar_try_wait(bar, parity)) return;
  }
}
__device__ __forceinline__ void mbar_pace(uint32_t bar, uint32_t parity) {
#pragma unroll 1
  for (uint32_t it = 0; it < 24; ++it) {
    if (mbar_try_wait(bar, parity)) return;
  }
}
template <int NS>
__device__ __forceinline__ void mbar_wait_lazy(uint32_t bar, uint32_t parity) {
#pragma unroll 1
  for (uint32_t it = 0; it < (1u << 18); ++it) {
    if (mbar_try_wait(bar, parity)) return;
    __nanosleep(NS);
  }
}
__device__ __forceinline__ bool elect_one() {
  uint32_t ok;
  asm volatile("{\n.reg .pred p;\nelect.sync _|p, 0xffffffff;\nselp.b32 %0, 1, 0, p;\n}\n" : "=r"(ok));
  return ok != 0;
}
__device__ __forceinline__ void fence_barrier_init() { asm volatile("fence.mbarrier_init.release.cluster;" ::: "memory"); }
__device__ __forceinline__ void fence_proxy_async_smem() { asm volatile("fence.proxy.async.shared::cta;" ::: "memory"); }

__device__ __forceinline__ void tma_load_2d(uint32_t dst, const CUtensorMap* map, uint32_t bar, int c0, int c1) {
  asm volatile(
      "cp.async.bulk.tensor.2d.shared::cluster.global.mbarrier::complete_tx::bytes [%0], [%1, {%3, %4}], [%2];" ::"r"(dst),
      "l"(map), "r"(bar), "r"(c0), "r"(c1)
      : "memory");
}
__device__ __forceinline__ void tma_load_3d(uint32_t dst, const CUtensorMap* map, uint32_t bar, int c0, int c1) {
  asm volatile(
      "cp.async.bulk.tensor.3d.shared::cluster.global.mbarrier::complete_tx::bytes [%0], [%1, {%3, %4, %5}], [%2];" ::"r"(dst),
      "l"(map), "r"(bar), "r"(c0), "r"(c1), "r"(0)
      : "memory");
}
__device__ __forceinline__ void tma_load_5d(uint32_t dst, const CUtensorMap* map, uint32_t bar, int c0, int c4) {
  asm volatile(
      "cp.async.bulk.tensor.5d.shared::cluster.global.mbarrier::complete_tx::bytes [%0], [%1, {%3, %5, %5, %5, %4}], [%2];" ::"r"(dst),
      "l"(map), "r"(bar), "r"(c0), "r"(c4), "r"(0)
      : "memory");
}
__device__ __forceinline__ void bulk_load(uint32_t dst, const void* src, uint32_t bytes, uint32_t bar) {
  asm volatile("cp.async.bulk.shared::cluster.global.mbarrier::complete_tx::bytes [%0], [%1], %2, [%3];" ::"r"(dst),
               "l"(src), "r"(bytes), "r"(bar)
               : "memory");
}
__device__ __forceinline__ void bulk_store(void* dst, uint32_t src, uint32_t bytes) {
  asm volatile("cp.async.bulk.global.shared::cta.bulk_group [%0], [%1], %2;" ::"l"(dst), "r"(src), "r"(bytes) : "memory");
}
__device__ __forceinline__ void tma_store_2d(const CUtensorMap* map, uint32_t src, int c0, int c1) {
  asm volatile("cp.async.bulk.tensor.2d.global.shared::cta.bulk_group [%0, {%2, %3}], [%1];" ::"l"(map), "r"(src),
               "r"(c0), "r"(c1)
               : "memory");
}
__device__ __forceinline__ void bulk_announce(unsigned* p) {
  asm volatile("cp.reduce.async.bulk.global.shared::cta.bulk_group.add.u32 [%0], [%1], 16;" ::"l"(p), "r"(SBASE + OFF_ONE) : "memory");
}
__device__ __forceinline__ void bulk_commit() { asm volatile("cp.async.bulk.commit_group;" ::: "memory"); }
__device__ __forceinline__ void bulk_wait_read0() { asm volatile("cp.async.bulk.wait_group.read 0;" ::: "memory"); }
__device__ __forceinline__ void bulk_wait0() { asm volatile("cp.async.bulk.wait_group 0;" ::: "memory"); }
__device__ __forceinline__ void named_bar_sync(int id, int nthreads) {
  asm volatile("bar.sync %0, %1;" ::"r"(id), "r"(nthreads) : "memory");
}
__device__ __forceinline__ void named_bar_arrive(int id, int nthreads) {
  asm volatile("bar.arrive %0, %1;" ::"r"(id), "r"(nthreads) : "memory");
}

__device__ __forceinline__ bool named_bar_or(int id, int nthreads, bool v) {
  uint32_t r;
  asm volatile("{\n.reg .pred p, q;\nsetp.ne.b32 q, %3, 0;\nbar.red.or.pred p, %1, %2, q;\nselp.b32 %0, 1, 0, p;\n}\n"
               : "=r"(r) : "r"(id), "r"(nthreads), "r"((int)v) : "memory");
  return __any_sync(0xffffffffu, r != 0);
}

__device__ __forceinline__ void wgmma_fence() { asm volatile("wgmma.fence.sync.aligned;\n" ::: "memory"); }
__device__ __forceinline__ void wgmma_commit() { asm volatile("wgmma.commit_group.sync.aligned;\n" ::: "memory"); }
template <int N>
__device__ __forceinline__ void wgmma_wait() {
  asm volatile("wgmma.wait_group.sync.aligned %0;\n" ::"n"(N) : "memory");
}
template <int R>
__device__ __forceinline__ void setmaxnreg_inc() { asm volatile("setmaxnreg.inc.sync.aligned.u32 %0;\n" ::"n"(R)); }
template <int R>
__device__ __forceinline__ void setmaxnreg_dec() { asm volatile("setmaxnreg.dec.sync.aligned.u32 %0;\n" ::"n"(R)); }
template <int N>
__device__ __forceinline__ void reg_fence(float* r) {
#pragma unroll
  for (int i = 0; i < N; i++) asm volatile("" : "+f"(r[i])::"memory");
}

template <int N>
__device__ __forceinline__ void reg_define(float* r) {
#pragma unroll
  for (int i = 0; i < N; i++) r[i] = 0.f;
}

__device__ __forceinline__ uint64_t desc_lo(uint32_t lo) {
  uint64_t d;
  asm("mov.b64 %0, {%1, %2};" : "=l"(d) : "r"(lo), "r"(0x40000040u));
  return d;
}
__device__ __forceinline__ uint64_t make_desc(uint32_t addr, uint32_t lbo_bytes) {
  return desc_lo((addr >> 4) + ((lbo_bytes >> 4) << 16));
}

__device__ __forceinline__ void wgmma_n192_ss_ta0_tb1(float* d, uint64_t descA, uint64_t descB, int scaleD) {
  asm volatile("{\n.reg .pred p;\nsetp.ne.b32 p, %98, 0;\n"
    "wgmma.mma_async.sync.aligned.m64n192k16.f32.bf16.bf16 {%0, %1, %2, %3, %4, %5, %6, %7, %8, %9, %10, %11, %12, %13, %14, %15, %16, %17, %18, %19, %20, %21, %22, %23, %24, %25, %26, %27, %28, %29, %30, %31, %32, %33, %34, %35, %36, %37, %38, %39, %40, %41, %42, %43, %44, %45, %46, %47, %48, %49, %50, %51, %52, %53, %54, %55, %56, %57, %58, %59, %60, %61, %62, %63, %64, %65, %66, %67, %68, %69, %70, %71, %72, %73, %74, %75, %76, %77, %78, %79, %80, %81, %82, %83, %84, %85, %86, %87, %88, %89, %90, %91, %92, %93, %94, %95}, %96, %97, p, 1, 1, 0, 1;\n}\n"
    : "+f"(d[0]), "+f"(d[1]), "+f"(d[2]), "+f"(d[3]), "+f"(d[4]), "+f"(d[5]), "+f"(d[6]), "+f"(d[7]), "+f"(d[8]), "+f"(d[9]), "+f"(d[10]), "+f"(d[11]), "+f"(d[12]), "+f"(d[13]), "+f"(d[14]), "+f"(d[15]), "+f"(d[16]), "+f"(d[17]), "+f"(d[18]), "+f"(d[19]), "+f"(d[20]), "+f"(d[21]), "+f"(d[22]), "+f"(d[23]), "+f"(d[24]), "+f"(d[25]), "+f"(d[26]), "+f"(d[27]), "+f"(d[28]), "+f"(d[29]), "+f"(d[30]), "+f"(d[31]), "+f"(d[32]), "+f"(d[33]), "+f"(d[34]), "+f"(d[35]), "+f"(d[36]), "+f"(d[37]), "+f"(d[38]), "+f"(d[39]), "+f"(d[40]), "+f"(d[41]), "+f"(d[42]), "+f"(d[43]), "+f"(d[44]), "+f"(d[45]), "+f"(d[46]), "+f"(d[47]), "+f"(d[48]), "+f"(d[49]), "+f"(d[50]), "+f"(d[51]), "+f"(d[52]), "+f"(d[53]), "+f"(d[54]), "+f"(d[55]), "+f"(d[56]), "+f"(d[57]), "+f"(d[58]), "+f"(d[59]), "+f"(d[60]), "+f"(d[61]), "+f"(d[62]), "+f"(d[63]), "+f"(d[64]), "+f"(d[65]), "+f"(d[66]), "+f"(d[67]), "+f"(d[68]), "+f"(d[69]), "+f"(d[70]), "+f"(d[71]), "+f"(d[72]), "+f"(d[73]), "+f"(d[74]), "+f"(d[75]), "+f"(d[76]), "+f"(d[77]), "+f"(d[78]), "+f"(d[79]), "+f"(d[80]), "+f"(d[81]), "+f"(d[82]), "+f"(d[83]), "+f"(d[84]), "+f"(d[85]), "+f"(d[86]), "+f"(d[87]), "+f"(d[88]), "+f"(d[89]), "+f"(d[90]), "+f"(d[91]), "+f"(d[92]), "+f"(d[93]), "+f"(d[94]), "+f"(d[95])
    : "l"(descA), "l"(descB), "r"(scaleD));
}

__device__ __forceinline__ void wgmma_n128_ss_ta0_tb1(float* d, uint64_t descA, uint64_t descB, int scaleD) {
  asm volatile("{\n.reg .pred p;\nsetp.ne.b32 p, %66, 0;\n"
    "wgmma.mma_async.sync.aligned.m64n128k16.f32.bf16.bf16 {%0, %1, %2, %3, %4, %5, %6, %7, %8, %9, %10, %11, %12, %13, %14, %15, %16, %17, %18, %19, %20, %21, %22, %23, %24, %25, %26, %27, %28, %29, %30, %31, %32, %33, %34, %35, %36, %37, %38, %39, %40, %41, %42, %43, %44, %45, %46, %47, %48, %49, %50, %51, %52, %53, %54, %55, %56, %57, %58, %59, %60, %61, %62, %63}, %64, %65, p, 1, 1, 0, 1;\n}\n"
    : "+f"(d[0]), "+f"(d[1]), "+f"(d[2]), "+f"(d[3]), "+f"(d[4]), "+f"(d[5]), "+f"(d[6]), "+f"(d[7]), "+f"(d[8]), "+f"(d[9]), "+f"(d[10]), "+f"(d[11]), "+f"(d[12]), "+f"(d[13]), "+f"(d[14]), "+f"(d[15]), "+f"(d[16]), "+f"(d[17]), "+f"(d[18]), "+f"(d[19]), "+f"(d[20]), "+f"(d[21]), "+f"(d[22]), "+f"(d[23]), "+f"(d[24]), "+f"(d[25]), "+f"(d[26]), "+f"(d[27]), "+f"(d[28]), "+f"(d[29]), "+f"(d[30]), "+f"(d[31]), "+f"(d[32]), "+f"(d[33]), "+f"(d[34]), "+f"(d[35]), "+f"(d[36]), "+f"(d[37]), "+f"(d[38]), "+f"(d[39]), "+f"(d[40]), "+f"(d[41]), "+f"(d[42]), "+f"(d[43]), "+f"(d[44]), "+f"(d[45]), "+f"(d[46]), "+f"(d[47]), "+f"(d[48]), "+f"(d[49]), "+f"(d[50]), "+f"(d[51]), "+f"(d[52]), "+f"(d[53]), "+f"(d[54]), "+f"(d[55]), "+f"(d[56]), "+f"(d[57]), "+f"(d[58]), "+f"(d[59]), "+f"(d[60]), "+f"(d[61]), "+f"(d[62]), "+f"(d[63])
    : "l"(descA), "l"(descB), "r"(scaleD));
}

__device__ __forceinline__ void wgmma_n192_ssz_ta0_tb1(float* d, uint64_t descA, uint64_t descB) {
  asm volatile("{\n.reg .pred p;\nsetp.ne.b32 p, 0, 0;\n"
    "wgmma.mma_async.sync.aligned.m64n192k16.f32.bf16.bf16 {%0, %1, %2, %3, %4, %5, %6, %7, %8, %9, %10, %11, %12, %13, %14, %15, %16, %17, %18, %19, %20, %21, %22, %23, %24, %25, %26, %27, %28, %29, %30, %31, %32, %33, %34, %35, %36, %37, %38, %39, %40, %41, %42, %43, %44, %45, %46, %47, %48, %49, %50, %51, %52, %53, %54, %55, %56, %57, %58, %59, %60, %61, %62, %63, %64, %65, %66, %67, %68, %69, %70, %71, %72, %73, %74, %75, %76, %77, %78, %79, %80, %81, %82, %83, %84, %85, %86, %87, %88, %89, %90, %91, %92, %93, %94, %95}, %96, %97, p, 1, 1, 0, 1;\n}\n"
    : "=f"(d[0]), "=f"(d[1]), "=f"(d[2]), "=f"(d[3]), "=f"(d[4]), "=f"(d[5]), "=f"(d[6]), "=f"(d[7]), "=f"(d[8]), "=f"(d[9]), "=f"(d[10]), "=f"(d[11]), "=f"(d[12]), "=f"(d[13]), "=f"(d[14]), "=f"(d[15]), "=f"(d[16]), "=f"(d[17]), "=f"(d[18]), "=f"(d[19]), "=f"(d[20]), "=f"(d[21]), "=f"(d[22]), "=f"(d[23]), "=f"(d[24]), "=f"(d[25]), "=f"(d[26]), "=f"(d[27]), "=f"(d[28]), "=f"(d[29]), "=f"(d[30]), "=f"(d[31]), "=f"(d[32]), "=f"(d[33]), "=f"(d[34]), "=f"(d[35]), "=f"(d[36]), "=f"(d[37]), "=f"(d[38]), "=f"(d[39]), "=f"(d[40]), "=f"(d[41]), "=f"(d[42]), "=f"(d[43]), "=f"(d[44]), "=f"(d[45]), "=f"(d[46]), "=f"(d[47]), "=f"(d[48]), "=f"(d[49]), "=f"(d[50]), "=f"(d[51]), "=f"(d[52]), "=f"(d[53]), "=f"(d[54]), "=f"(d[55]), "=f"(d[56]), "=f"(d[57]), "=f"(d[58]), "=f"(d[59]), "=f"(d[60]), "=f"(d[61]), "=f"(d[62]), "=f"(d[63]), "=f"(d[64]), "=f"(d[65]), "=f"(d[66]), "=f"(d[67]), "=f"(d[68]), "=f"(d[69]), "=f"(d[70]), "=f"(d[71]), "=f"(d[72]), "=f"(d[73]), "=f"(d[74]), "=f"(d[75]), "=f"(d[76]), "=f"(d[77]), "=f"(d[78]), "=f"(d[79]), "=f"(d[80]), "=f"(d[81]), "=f"(d[82]), "=f"(d[83]), "=f"(d[84]), "=f"(d[85]), "=f"(d[86]), "=f"(d[87]), "=f"(d[88]), "=f"(d[89]), "=f"(d[90]), "=f"(d[91]), "=f"(d[92]), "=f"(d[93]), "=f"(d[94]), "=f"(d[95])
    : "l"(descA), "l"(descB));
}

__device__ __forceinline__ void wgmma_n8_ss_ta1_tb0(float* d, uint64_t descA, uint64_t descB, int scaleD) {
  asm volatile("{\n.reg .pred p;\nsetp.ne.b32 p, %6, 0;\n"
    "wgmma.mma_async.sync.aligned.m64n8k16.f32.bf16.bf16 {%0, %1, %2, %3}, %4, %5, p, 1, 1, 1, 0;\n}\n"
    : "+f"(d[0]), "+f"(d[1]), "+f"(d[2]), "+f"(d[3])
    : "l"(descA), "l"(descB), "r"(scaleD));
}

__device__ __forceinline__ void wgmma_n8_ssz_ta1_tb0(float* d, uint64_t descA, uint64_t descB) {
  asm volatile("{\n.reg .pred p;\nsetp.ne.b32 p, 0, 0;\n"
    "wgmma.mma_async.sync.aligned.m64n8k16.f32.bf16.bf16 {%0, %1, %2, %3}, %4, %5, p, 1, 1, 1, 0;\n}\n"
    : "=f"(d[0]), "=f"(d[1]), "=f"(d[2]), "=f"(d[3])
    : "l"(descA), "l"(descB));
}

__device__ __forceinline__ void wgmma_n192_rs_tb1(float* d, const uint32_t* a, uint64_t descB, int scaleD) {
  asm volatile("{\n.reg .pred p;\nsetp.ne.b32 p, %101, 0;\n"
    "wgmma.mma_async.sync.aligned.m64n192k16.f32.bf16.bf16 {%0, %1, %2, %3, %4, %5, %6, %7, %8, %9, %10, %11, %12, %13, %14, %15, %16, %17, %18, %19, %20, %21, %22, %23, %24, %25, %26, %27, %28, %29, %30, %31, %32, %33, %34, %35, %36, %37, %38, %39, %40, %41, %42, %43, %44, %45, %46, %47, %48, %49, %50, %51, %52, %53, %54, %55, %56, %57, %58, %59, %60, %61, %62, %63, %64, %65, %66, %67, %68, %69, %70, %71, %72, %73, %74, %75, %76, %77, %78, %79, %80, %81, %82, %83, %84, %85, %86, %87, %88, %89, %90, %91, %92, %93, %94, %95}, {%96, %97, %98, %99}, %100, p, 1, 1, 1;\n}\n"
    : "+f"(d[0]), "+f"(d[1]), "+f"(d[2]), "+f"(d[3]), "+f"(d[4]), "+f"(d[5]), "+f"(d[6]), "+f"(d[7]), "+f"(d[8]), "+f"(d[9]), "+f"(d[10]), "+f"(d[11]), "+f"(d[12]), "+f"(d[13]), "+f"(d[14]), "+f"(d[15]), "+f"(d[16]), "+f"(d[17]), "+f"(d[18]), "+f"(d[19]), "+f"(d[20]), "+f"(d[21]), "+f"(d[22]), "+f"(d[23]), "+f"(d[24]), "+f"(d[25]), "+f"(d[26]), "+f"(d[27]), "+f"(d[28]), "+f"(d[29]), "+f"(d[30]), "+f"(d[31]), "+f"(d[32]), "+f"(d[33]), "+f"(d[34]), "+f"(d[35]), "+f"(d[36]), "+f"(d[37]), "+f"(d[38]), "+f"(d[39]), "+f"(d[40]), "+f"(d[41]), "+f"(d[42]), "+f"(d[43]), "+f"(d[44]), "+f"(d[45]), "+f"(d[46]), "+f"(d[47]), "+f"(d[48]), "+f"(d[49]), "+f"(d[50]), "+f"(d[51]), "+f"(d[52]), "+f"(d[53]), "+f"(d[54]), "+f"(d[55]), "+f"(d[56]), "+f"(d[57]), "+f"(d[58]), "+f"(d[59]), "+f"(d[60]), "+f"(d[61]), "+f"(d[62]), "+f"(d[63]), "+f"(d[64]), "+f"(d[65]), "+f"(d[66]), "+f"(d[67]), "+f"(d[68]), "+f"(d[69]), "+f"(d[70]), "+f"(d[71]), "+f"(d[72]), "+f"(d[73]), "+f"(d[74]), "+f"(d[75]), "+f"(d[76]), "+f"(d[77]), "+f"(d[78]), "+f"(d[79]), "+f"(d[80]), "+f"(d[81]), "+f"(d[82]), "+f"(d[83]), "+f"(d[84]), "+f"(d[85]), "+f"(d[86]), "+f"(d[87]), "+f"(d[88]), "+f"(d[89]), "+f"(d[90]), "+f"(d[91]), "+f"(d[92]), "+f"(d[93]), "+f"(d[94]), "+f"(d[95])
    : "r"(a[0]), "r"(a[1]), "r"(a[2]), "r"(a[3]), "l"(descB), "r"(scaleD));
}

__device__ __forceinline__ void wgmma_n80_rs_tb0(float* d, const uint32_t* a, uint64_t descB, int scaleD) {
  asm volatile("{\n.reg .pred p;\nsetp.ne.b32 p, %45, 0;\n"
    "wgmma.mma_async.sync.aligned.m64n80k16.f32.bf16.bf16 {%0, %1, %2, %3, %4, %5, %6, %7, %8, %9, %10, %11, %12, %13, %14, %15, %16, %17, %18, %19, %20, %21, %22, %23, %24, %25, %26, %27, %28, %29, %30, %31, %32, %33, %34, %35, %36, %37, %38, %39}, {%40, %41, %42, %43}, %44, p, 1, 1, 0;\n}\n"
    : "+f"(d[0]), "+f"(d[1]), "+f"(d[2]), "+f"(d[3]), "+f"(d[4]), "+f"(d[5]), "+f"(d[6]), "+f"(d[7]), "+f"(d[8]), "+f"(d[9]), "+f"(d[10]), "+f"(d[11]), "+f"(d[12]), "+f"(d[13]), "+f"(d[14]), "+f"(d[15]), "+f"(d[16]), "+f"(d[17]), "+f"(d[18]), "+f"(d[19]), "+f"(d[20]), "+f"(d[21]), "+f"(d[22]), "+f"(d[23]), "+f"(d[24]), "+f"(d[25]), "+f"(d[26]), "+f"(d[27]), "+f"(d[28]), "+f"(d[29]), "+f"(d[30]), "+f"(d[31]), "+f"(d[32]), "+f"(d[33]), "+f"(d[34]), "+f"(d[35]), "+f"(d[36]), "+f"(d[37]), "+f"(d[38]), "+f"(d[39])
    : "r"(a[0]), "r"(a[1]), "r"(a[2]), "r"(a[3]), "l"(descB), "r"(scaleD));
}

__device__ __forceinline__ void wgmma_n80_rsz_tb0(float* d, const uint32_t* a, uint64_t descB) {
  asm volatile("{\n.reg .pred p;\nsetp.ne.b32 p, 0, 0;\n"
    "wgmma.mma_async.sync.aligned.m64n80k16.f32.bf16.bf16 {%0, %1, %2, %3, %4, %5, %6, %7, %8, %9, %10, %11, %12, %13, %14, %15, %16, %17, %18, %19, %20, %21, %22, %23, %24, %25, %26, %27, %28, %29, %30, %31, %32, %33, %34, %35, %36, %37, %38, %39}, {%40, %41, %42, %43}, %44, p, 1, 1, 0;\n}\n"
    : "=f"(d[0]), "=f"(d[1]), "=f"(d[2]), "=f"(d[3]), "=f"(d[4]), "=f"(d[5]), "=f"(d[6]), "=f"(d[7]), "=f"(d[8]), "=f"(d[9]), "=f"(d[10]), "=f"(d[11]), "=f"(d[12]), "=f"(d[13]), "=f"(d[14]), "=f"(d[15]), "=f"(d[16]), "=f"(d[17]), "=f"(d[18]), "=f"(d[19]), "=f"(d[20]), "=f"(d[21]), "=f"(d[22]), "=f"(d[23]), "=f"(d[24]), "=f"(d[25]), "=f"(d[26]), "=f"(d[27]), "=f"(d[28]), "=f"(d[29]), "=f"(d[30]), "=f"(d[31]), "=f"(d[32]), "=f"(d[33]), "=f"(d[34]), "=f"(d[35]), "=f"(d[36]), "=f"(d[37]), "=f"(d[38]), "=f"(d[39])
    : "r"(a[0]), "r"(a[1]), "r"(a[2]), "r"(a[3]), "l"(descB));
}

__device__ __forceinline__ void wgmma_n32_rs_tb1(float* d, const uint32_t* a, uint64_t descB, int scaleD) {
  asm volatile("{\n.reg .pred p;\nsetp.ne.b32 p, %21, 0;\n"
    "wgmma.mma_async.sync.aligned.m64n32k16.f32.bf16.bf16 {%0, %1, %2, %3, %4, %5, %6, %7, %8, %9, %10, %11, %12, %13, %14, %15}, {%16, %17, %18, %19}, %20, p, 1, 1, 1;\n}\n"
    : "+f"(d[0]), "+f"(d[1]), "+f"(d[2]), "+f"(d[3]), "+f"(d[4]), "+f"(d[5]), "+f"(d[6]), "+f"(d[7]), "+f"(d[8]), "+f"(d[9]), "+f"(d[10]), "+f"(d[11]), "+f"(d[12]), "+f"(d[13]), "+f"(d[14]), "+f"(d[15])
    : "r"(a[0]), "r"(a[1]), "r"(a[2]), "r"(a[3]), "l"(descB), "r"(scaleD));
}

__device__ __forceinline__ void wgmma_n32_rsz_tb1(float* d, const uint32_t* a, uint64_t descB) {
  asm volatile("{\n.reg .pred p;\nsetp.ne.b32 p, 0, 0;\n"
    "wgmma.mma_async.sync.aligned.m64n32k16.f32.bf16.bf16 {%0, %1, %2, %3, %4, %5, %6, %7, %8, %9, %10, %11, %12, %13, %14, %15}, {%16, %17, %18, %19}, %20, p, 1, 1, 1;\n}\n"
    : "=f"(d[0]), "=f"(d[1]), "=f"(d[2]), "=f"(d[3]), "=f"(d[4]), "=f"(d[5]), "=f"(d[6]), "=f"(d[7]), "=f"(d[8]), "=f"(d[9]), "=f"(d[10]), "=f"(d[11]), "=f"(d[12]), "=f"(d[13]), "=f"(d[14]), "=f"(d[15])
    : "r"(a[0]), "r"(a[1]), "r"(a[2]), "r"(a[3]), "l"(descB));
}

__device__ __forceinline__ void wgmma_n32_rs_tb0(float* d, const uint32_t* a, uint64_t descB, int scaleD) {
  asm volatile("{\n.reg .pred p;\nsetp.ne.b32 p, %21, 0;\n"
    "wgmma.mma_async.sync.aligned.m64n32k16.f32.bf16.bf16 {%0, %1, %2, %3, %4, %5, %6, %7, %8, %9, %10, %11, %12, %13, %14, %15}, {%16, %17, %18, %19}, %20, p, 1, 1, 0;\n}\n"
    : "+f"(d[0]), "+f"(d[1]), "+f"(d[2]), "+f"(d[3]), "+f"(d[4]), "+f"(d[5]), "+f"(d[6]), "+f"(d[7]), "+f"(d[8]), "+f"(d[9]), "+f"(d[10]), "+f"(d[11]), "+f"(d[12]), "+f"(d[13]), "+f"(d[14]), "+f"(d[15])
    : "r"(a[0]), "r"(a[1]), "r"(a[2]), "r"(a[3]), "l"(descB), "r"(scaleD));
}

__device__ __forceinline__ void wgmma_n32_rsz_tb0(float* d, const uint32_t* a, uint64_t descB) {
  asm volatile("{\n.reg .pred p;\nsetp.ne.b32 p, 0, 0;\n"
    "wgmma.mma_async.sync.aligned.m64n32k16.f32.bf16.bf16 {%0, %1, %2, %3, %4, %5, %6, %7, %8, %9, %10, %11, %12, %13, %14, %15}, {%16, %17, %18, %19}, %20, p, 1, 1, 0;\n}\n"
    : "=f"(d[0]), "=f"(d[1]), "=f"(d[2]), "=f"(d[3]), "=f"(d[4]), "=f"(d[5]), "=f"(d[6]), "=f"(d[7]), "=f"(d[8]), "=f"(d[9]), "=f"(d[10]), "=f"(d[11]), "=f"(d[12]), "=f"(d[13]), "=f"(d[14]), "=f"(d[15])
    : "r"(a[0]), "r"(a[1]), "r"(a[2]), "r"(a[3]), "l"(descB));
}

__device__ __forceinline__ uint32_t pack_bf16x2(float lo, float hi) {
  uint32_t r;
  asm("cvt.rn.bf16x2.f32 %0, %1, %2;" : "=r"(r) : "f"(hi), "f"(lo));
  return r;
}
__device__ __forceinline__ float bf_lo(uint32_t p) { return __uint_as_float(p << 16); }
__device__ __forceinline__ float bf_hi(uint32_t p) { return __uint_as_float(p & 0xffff0000u); }
__device__ __forceinline__ float bf16_round(float v) { return __bfloat162float(__float2bfloat16_rn(v)); }
__device__ __forceinline__ float ex2_approx(float x) {
  float r;
  asm("ex2.approx.ftz.f32 %0, %1;" : "=f"(r) : "f"(x));
  return r;
}
__device__ __forceinline__ float rcp_fast(float x) {
  float r;
  asm("rcp.approx.ftz.f32 %0, %1;" : "=f"(r) : "f"(x));
  return r;
}
__device__ __forceinline__ void ldmatrix_x4(uint32_t (&r)[4], uint32_t addr) {
  asm volatile("ldmatrix.sync.aligned.m8n8.x4.shared.b16 {%0,%1,%2,%3}, [%4];"
               : "=r"(r[0]), "=r"(r[1]), "=r"(r[2]), "=r"(r[3])
               : "r"(addr)
               : "memory");
}
__device__ __forceinline__ void stmatrix_x4(uint32_t addr, uint32_t r0, uint32_t r1, uint32_t r2, uint32_t r3) {
  asm volatile("stmatrix.sync.aligned.m8n8.x4.shared.b16 [%0], {%1,%2,%3,%4};" ::"r"(addr), "r"(r0), "r"(r1), "r"(r2),
               "r"(r3));
}
__device__ __forceinline__ uint32_t add_bf16x2(uint32_t a, uint32_t b) {
  uint32_t r;
  asm("add.rn.bf16x2 %0, %1, %2;" : "=r"(r) : "r"(a), "r"(b));
  return r;
}
__device__ __forceinline__ uint4 lds128(uint32_t addr) {
  uint4 v;
  asm volatile("ld.shared.v4.b32 {%0,%1,%2,%3}, [%4];" : "=r"(v.x), "=r"(v.y), "=r"(v.z), "=r"(v.w) : "r"(addr) : "memory");
  return v;
}
__device__ __forceinline__ uint32_t lds32(uint32_t addr) {
  uint32_t v;
  asm volatile("ld.shared.b32 %0, [%1];" : "=r"(v) : "r"(addr) : "memory");
  return v;
}
__device__ __forceinline__ void sts32(uint32_t addr, uint32_t v) {
  asm volatile("st.shared.b32 [%0], %1;" ::"r"(addr), "r"(v) : "memory");
}

__device__ __forceinline__ unsigned ld_relaxed_u32(const void* p) {
  unsigned v;
  asm volatile("ld.relaxed.gpu.global.u32 %0, [%1];" : "=r"(v) : "l"(p) : "memory");
  return v;
}
__device__ __forceinline__ unsigned launch_epoch() { return (*(volatile unsigned*)g_done) / NCTA + 1u; }
__device__ __forceinline__ uint32_t set_tag(uint32_t w, uint32_t m, uint32_t tag) { return (w & ~m) | (tag & m); }
__device__ __forceinline__ uint32_t o_tag(int L) { return (L + 1) & 1; }
__device__ __forceinline__ uint32_t x_tag(unsigned ep1, int L) { return (ep1 + L + 1) & 1; }

__device__ __forceinline__ void wait_count(const unsigned* f, unsigned target, int i, uint32_t& seen, int lane) {
  if ((seen >> i) & 1u) return;
#pragma unroll 1
  for (uint32_t it = 0; it < (1u << 17); ++it) {
    seen = __ballot_sync(0xffffffffu, (int)(ld_relaxed_u32(f + (lane & 15) * 4) - target) >= 0);
    if ((seen >> i) & 1u) break;
  }
}
__device__ __forceinline__ float4 ld_rec(const float4* p) {
  float4 v;
  asm volatile("ld.relaxed.gpu.global.v4.f32 {%0,%1,%2,%3}, [%4];" : "=f"(v.x), "=f"(v.y), "=f"(v.z), "=f"(v.w) : "l"(p) : "memory");
  return v;
}
__device__ __forceinline__ void st_rec(float4* p, float a, float b, float c, unsigned tag) {
  asm volatile("st.relaxed.gpu.global.v4.f32 [%0], {%1,%2,%3,%4};" ::"l"(p), "f"(a), "f"(b), "f"(c), "f"(__uint_as_float(tag)) : "memory");
}
template <int N>
__device__ __forceinline__ float4 sum_recs(const float4* p, int stride, unsigned tag) {
  float4 s;
#pragma unroll 1
  for (uint32_t it = 0; it < (1u << 17); ++it) {
    float4 v[N];
#pragma unroll
    for (int t = 0; t < N; t++) v[t] = ld_rec(p + t * stride);
    bool ok = true;
    s = make_float4(0.f, 0.f, 0.f, 0.f);
#pragma unroll
    for (int t = 0; t < N; t++) {
      ok &= __float_as_uint(v[t].w) == tag;
      s.x += v[t].x;
      s.y += v[t].y;
      s.z += v[t].z;
    }
    if (ok) break;
    __nanosleep(200);
  }
  return s;
}

__device__ __forceinline__ int fresh_tid() {
  int t;
  asm volatile("mov.u32 %0, %%tid.x;" : "=r"(t));
  return t;
}
#define PHASE_IDS                                  \
  const int tid_ = fresh_tid();                    \
  const int lane = tid_ & 31, wwarp = __shfl_sync(0xffffffffu, (tid_ >> 5) & 3, 0), tid = tid_ & 127; \
  const int g = lane >> 2, c = lane & 3;           \
  (void)tid; (void)g; (void)c; (void)wwarp;

#define PHASE_IDS_W                                \
  const int lane = fresh_tid() & 31, wwarp = warp & 3; \
  const int g = lane >> 2, c = lane & 3;

#define GTL(i) do { } while (0)
#define TGET(v) do { } while (0)
#define TPUT(c, i, v) do { } while (0)

constexpr float SM_C = 0.17677669529663687f * 1.4426950408889634f;

__device__ __forceinline__ void stmatrix_x4_if(bool ok, uint32_t addr, uint32_t r0, uint32_t r1, uint32_t r2, uint32_t r3) {
  asm volatile("{\n.reg .pred p;\nsetp.ne.b32 p, %5, 0;\n@p stmatrix.sync.aligned.m8n8.x4.shared.b16 [%0], {%1,%2,%3,%4};\n}\n" ::"r"(addr),
               "r"(r0), "r"(r1), "r"(r2), "r"(r3), "r"((int)ok));
}

__device__ __forceinline__ void attn_a_slow(const uint8_t* __restrict__ kvimg, int L, int gb, int hp, uint32_t bad,
                                            int row0, int lane) {
  constexpr uint32_t sq = SBASE + OFF_SLOT + 3 * 16384;
#pragma unroll 1
  for (int j = 0; j < 8; j++) {
    const uint8_t* tp = kvimg + (size_t)(gb * 16 + hp) * 32768 + (j * 32 + lane) * 128 + ((lane & 7) << 4);
#pragma unroll 1
    for (uint32_t it = 0; it < (1u << 17); ++it)
      if (((ld_relaxed_u32(tp) ^ lds32(SBASE + OFF_EPOCH)) & 1u) == 0u) break;
  }
  __syncwarp();
#pragma unroll 1
  for (int t = 0; t < 32; t++) {
    const int hh = t >> 4, row = row0 + (t & 7) + (t & 8) * 4;
    if (!((bad >> hh) & 1u)) continue;
    const int qpos = gb * 128 + row;
    const uint32_t qaddr = sq + row * 128;
    float mx = -INFINITY, sum = 0.f, acc = 0.f;
#pragma unroll 1
    for (int pass = 0; pass < 2; pass++) {
#pragma unroll 1
      for (int j = 0; j < 8; j++) {
        const int kp = qpos - (lane + 32 * j);
        const uint8_t* kr = kvimg + ((size_t)((kp >> 7) * 16 + hp) * 2 + ((kp >> 6) & 1)) * 16384 + (kp & 63) * 128;
        float d = -INFINITY;
        if (kp >= 0) {
          d = 0.f;
#pragma unroll 1
          for (int q = 0; q < 4; q++) {
            const uint4 kv = __ldcg(reinterpret_cast<const uint4*>(kr + (((hh * 4 + q) ^ (kp & 7)) << 4)));
            const uint4 qv = lds128(qaddr + (((hh * 4 + q) ^ (row & 7)) << 4));
            const uint32_t kw[4] = {kv.x, kv.y, kv.z, kv.w}, qw[4] = {qv.x, qv.y, qv.z, qv.w};
#pragma unroll
            for (int e = 0; e < 4; e++) d = fmaf(bf_lo(kw[e]), bf_lo(qw[e]), fmaf(bf_hi(kw[e]), bf_hi(qw[e]), d));
          }
        }
        if (pass == 0) {
          mx = fmaxf(mx, d);
        } else {
          const float ev = ex2_approx(d - mx);
          sum += ev;
          const float pv = bf16_round(ev);
#pragma unroll 1
          for (int kk = 0; kk < 32; kk++) {
            const float pk = __shfl_sync(0xffffffffu, pv, kk);
            const int k2 = qpos - (kk + 32 * j);
            if (k2 >= 0) {
              const uint8_t* vr = kvimg + ((size_t)((k2 >> 7) * 16 + hp) * 2 + ((k2 >> 6) & 1)) * 16384 + 8192 + (k2 & 63) * 128;
              const unsigned short vv =
                  __ldcg(reinterpret_cast<const unsigned short*>(vr + (((hh * 4 + (lane >> 3)) ^ (k2 & 7)) << 4) + (lane & 7) * 2));
              acc = fmaf(pk, __uint_as_float((uint32_t)vv << 16), acc);
            }
          }
        }
      }
      if (pass == 0) {
#pragma unroll
        for (int o = 16; o > 0; o >>= 1) mx = fmaxf(mx, __shfl_xor_sync(0xffffffffu, mx, o));
      }
    }
#pragma unroll
    for (int o = 16; o > 0; o >>= 1) sum += __shfl_xor_sync(0xffffffffu, sum, o);
    acc *= rcp_fast(sum);
    const float hi = __shfl_down_sync(0xffffffffu, acc, 1);
    __syncwarp();
    if ((lane & 1) == 0) sts32(qaddr + (((hh * 4 + (lane >> 3)) ^ (row & 7)) << 4) + (lane & 7) * 2,
                               set_tag(pack_bf16x2(acc, hi), hh == 0 && lane == 0, o_tag(L)));
    __syncwarp();
  }
}

template <int HH>
__device__ __forceinline__ void store_o(const float (&o)[16], const float (&inv)[2], uint32_t ra, uint32_t tag, bool ok) {
  const uint32_t m = HH == 0 && (fresh_tid() & 3) == 0;
#pragma unroll
  for (int jp = 0; jp < 2; jp++) {
    uint32_t w0 = pack_bf16x2(o[8 * jp] * inv[0], o[8 * jp + 1] * inv[0]);
    uint32_t w1 = pack_bf16x2(o[8 * jp + 2] * inv[1], o[8 * jp + 3] * inv[1]);
    if (HH == 0 && jp == 0) {
      w0 = set_tag(w0, m, tag);
      w1 = set_tag(w1, m, tag);
    }
    stmatrix_x4_if(ok, ra ^ ((HH * 4 + 2 * jp) << 4), w0, w1, pack_bf16x2(o[8 * jp + 4] * inv[0], o[8 * jp + 5] * inv[0]),
                   pack_bf16x2(o[8 * jp + 6] * inv[1], o[8 * jp + 7] * inv[1]));
  }
}
__device__ __forceinline__ int tile_row(bool B, int w, int r, int g) { return (B ? 16 * w + 8 * r : 8 * w + 32 * r) + g; }
__device__ __forceinline__ uint32_t q_row_addr(bool B, int R, int w, int lane) {
  return SBASE + OFF_SLOT + 3 * 16384 + R * 8192 + tile_row(B, w, (lane >> 3) & 1, lane & 7) * 128 + (((lane >> 4) ^ (lane & 7)) << 4);
}

struct AttnA {
  float s[2][16], o[2][16], l[2][2], sh[2][3];
  uint32_t p[2][4], t[2], me[4], ra, bad, zero;
};
#define ATS_(i) do { } while (0)
template <int V>
__device__ __forceinline__ void attn_sum(AttnA& a, int nv) {
  constexpr int hh = (V >> 1) & 1, kh = V & 1, i = V >> 2;
#pragma unroll
  for (int r = 0; r < 2; r++) {
    const uint32_t t1 = add_bf16x2(add_bf16x2(a.p[0][r], a.p[0][2 + r]), add_bf16x2(a.p[1][r], a.p[1][2 + r]));
    if (kh == 0) {
      a.t[r] = t1;
    } else {
      uint32_t tt = add_bf16x2(a.t[r], t1);
      if (i > 0) tt = i <= nv ? tt : 0u;
      const float v = bf_lo(tt) + bf_hi(tt);
      a.l[hh][r] = i == 0 ? v : a.l[hh][r] + v;
    }
  }
}
template <int HH>
__device__ __forceinline__ void attn_shfl(AttnA& a) {
#pragma unroll
  for (int r = 0; r < 2; r++)
#pragma unroll
    for (int j = 0; j < 3; j++) a.sh[r][j] = __shfl_xor_sync(0xffffffffu, a.l[HH][r], j + 1);
}
template <int HH>
__device__ __forceinline__ void attn_fin(AttnA& a) {
  bool bad = false;
  float inv[2];
#pragma unroll
  for (int r = 0; r < 2; r++) {
    const float v = (a.l[HH][r] + a.sh[r][0]) + (a.sh[r][1] + a.sh[r][2]);
    bad |= !(v <= 1.152921504606846976e18f && v >= 8.673617379884035e-19f);
    inv[r] = rcp_fast(v);
  }
  bad = __any_sync(0xffffffffu, bad);
  if (HH == 1) wgmma_wait<0>();
  reg_fence<16>(a.o[HH]);
  store_o<HH>(a.o[HH], inv, a.ra, o_tag(0), !bad);
  a.bad = (HH == 0 ? 0u : a.bad) | (bad ? 1u << HH : 0u);
}
__device__ __forceinline__ void attn_masks(AttnA& a, int wr) {
  const int lane = fresh_tid() & 31, d = (lane >> 2) - 2 * (lane & 3);
  const uint32_t tri = d >= 1 ? 0xffffffffu : (d == 0 ? 0xffffu : 0u);
#pragma unroll
  for (int t = 0; t < 4; t++) a.me[t] = wr > t ? 0xffffffffu : (wr == t ? tri : 0u);
}
template <int V, int K>
__device__ __forceinline__ uint32_t attn_exp(AttnA& a) {
  constexpr int i = V >> 2, kh = V & 1, r = K & 1;
  if ((i == 0 && kh > r) || (i == 4 && kh < r)) return 0u;
  const uint32_t w = pack_bf16x2(ex2_approx(a.s[V & 1][2 * K]), ex2_approx(a.s[V & 1][2 * K + 1]));
  if (i == 0 && kh == r) return w & a.me[K >> 1];
  if (i == 4 && kh == r) return w & ~a.me[K >> 1];
  return w;
}
template <int V>
__device__ __forceinline__ void attn_unit(AttnA& a, const uint32_t (&q)[2][2][4], uint64_t dcur, uint64_t dnext, int R, int wr, int nv,
                                          uint32_t hbar, uint32_t hpar, uint32_t rbar, bool rel) {
  constexpr int hh = (V >> 1) & 1, kh = V & 1, i = V >> 2;
  ATS_(V + 1);
  asm volatile("" : "+l"(dcur), "+l"(dnext));
  wgmma_wait<1>();
  reg_fence<16>(a.s[V & 1]);
  bool hok = true;
  if (V == 4) hbar = SBASE + OFF_BAR + 8u * (R ? B_LOC : B_HV);
  if (((V & 3) == 2 && V < 16) || V == 4) hok = mbar_test(hbar, hpar);
  const uint64_t d0 = ((V & 3) >= 2 ? dnext : dcur) + ((hh ^ 1) * 4 + kh * 256), d1 = ((V & 3) >= 2 ? dnext : dcur) + ((hh ^ 1) * 4 + kh * 256 + 2);
  const uint64_t d2 = dcur + (512 + hh * 4 + kh * 256), d3 = dcur + (640 + hh * 4 + kh * 256);
  if ((V & 3) == 1 && V > 4 && rel) mbar_arrive(rbar);
  if (V > 0) attn_sum<V - 1>(a, nv);
  if (V == 15) attn_masks(a, wr);
  if (V == 18) {
    attn_shfl<0>(a);
    a.ra = q_row_addr(false, R, wr, fresh_tid() & 31);
  }
  if (V == 19) attn_fin<0>(a);
  uint32_t p[2][4];
  p[0][0] = attn_exp<V, 0>(a);
  p[0][1] = attn_exp<V, 1>(a);
  p[0][2] = attn_exp<V, 2>(a);
  p[0][3] = attn_exp<V, 3>(a);
  p[1][0] = attn_exp<V, 4>(a);
  p[1][1] = attn_exp<V, 5>(a);
  p[1][2] = attn_exp<V, 6>(a);
  p[1][3] = attn_exp<V, 7>(a);
  if (V > 0) {
#pragma unroll
    for (int r = 0; r < 2; r++) p[1][r] ^= (kh ? a.t[r] : __float_as_uint(a.l[hh ^ 1][r])) & a.zero;
  }
#pragma unroll
  for (int k = 0; k < 8; k++) {
    asm volatile("" : "+r"(p[k >> 2][k & 3]));
    a.p[k >> 2][k & 3] = p[k >> 2][k & 3];
  }
  if (!hok) mbar_wait(hbar, hpar);
  wgmma_fence();
  if (V < 18) wgmma_n32_rsz_tb0(a.s[V & 1], q[hh ^ 1][0], d0);
  if (i == 0 && kh == 0) wgmma_n32_rsz_tb1(a.o[hh], a.p[0], d2);
  else wgmma_n32_rs_tb1(a.o[hh], a.p[0], d2, 1);
  if (V < 18) wgmma_n32_rs_tb0(a.s[V & 1], q[hh ^ 1][1], d1, 1);
  wgmma_n32_rs_tb1(a.o[hh], a.p[1], d3, 1);
  wgmma_commit();
}
template <int I>
__device__ __forceinline__ void attn_step(AttnA& a, const uint32_t (&q)[2][2][4], uint64_t dcur, uint64_t dnext, int R, int wr, int nv,
                                          uint32_t hbar, uint32_t hpar, uint32_t rbar, bool rel) {
  attn_unit<4 * I>(a, q, dcur, dnext, R, wr, nv, hbar, hpar, rbar, rel);
  attn_unit<4 * I + 1>(a, q, dcur, dnext, R, wr, nv, hbar, hpar, rbar, rel);
  attn_unit<4 * I + 2>(a, q, dcur, dnext, R, wr, nv, hbar, hpar, rbar, rel);
  attn_unit<4 * I + 3>(a, q, dcur, dnext, R, wr, nv, hbar, hpar, rbar, rel);
}

__device__ __forceinline__ void attention_a(const uint32_t (&q)[2][2][4], int R, int L, int gb, int hp, uint32_t par, int wr,
                                            uint32_t zero) {
  constexpr uint32_t bars = SBASE + OFF_BAR;
  constexpr uint32_t dslot = ((SBASE + OFF_SLOT) >> 4) + 0x10000u;
  auto next = [&](uint64_t d) { return desc_lo((uint32_t)d == dslot ? dslot + 2048 : (uint32_t)d - 1024) + zero; };
  uint64_t d0 = desc_lo(dslot + R * 1024) + zero, d1 = next(d0);
  AttnA a;
  ATS_(0);
  wgmma_fence();
#pragma unroll
  for (int v = 0; v < 2; v++) {
    wgmma_n32_rsz_tb0(a.s[v], q[0][0], d0 + v * 256);
    wgmma_n32_rs_tb0(a.s[v], q[0][1], d0 + (v * 256 + 2), 1);
    wgmma_commit();
  }
  a.zero = zero;
  const bool lane0 = (fresh_tid() & 31) == 0;
  attn_masks(a, wr);
  const int nv = 2 * gb + R;
  const uint32_t hb = bars + 8u * (B_HALO - R), rb = bars + 8u * (B_REL - R);
  attn_step<0>(a, q, d0, d1, R, wr, nv, hb, par, 0, false);
  d0 = next(d1);
  attn_step<1>(a, q, d1, d0, R, wr, nv, R ? bars + 8u * B_HV : hb + 8, par, rb + 8, lane0);
  d1 = next(d0);
  attn_step<2>(a, q, d0, d1, R, wr, nv, hb + 16, par, rb + 16, lane0);
  d0 = next(d1);
  attn_step<3>(a, q, d1, d0, R, wr, nv, hb + 24, par, rb + 24, lane0 && R);
  attn_step<4>(a, q, d0, d0, R, wr, nv, 0, 0, rb, false);
  ATS_(21);
  attn_sum<19>(a, nv);
  attn_shfl<1>(a);
  attn_fin<1>(a);
  ATS_(22);
  if (a.bad != 0u) attn_a_slow(g_kvA[L >> 1][0][0][0], L, gb, hp, a.bad, R * 64 + wr * 8, fresh_tid() & 31);
}

constexpr uint32_t KB_ROW0 = SBASE + OFF_SLOT + 2048, VB_ROW0 = SBASE + OFF_SLOT + 24576 + 2048;

__device__ __forceinline__ void attention_b(const uint32_t (&q)[2][2][4], int R, int gb, uint32_t par0, int wr) {
  constexpr uint32_t bars = SBASE + OFF_BAR;
  const uint32_t dk = ((KB_ROW0 - 2048) >> 4) + 0x10000u + R * 512, dv = dk + ((VB_ROW0 - KB_ROW0) >> 4);
  float s[2][40];
  mbar_wait(bars + 8u * (B_HALO - R), par0);
  wgmma_fence();
#pragma unroll
  for (int hh = 0; hh < 2; hh++) {
    wgmma_n80_rsz_tb0(s[hh], q[hh][0], desc_lo(dk + hh * 4));
    wgmma_n80_rs_tb0(s[hh], q[hh][1], desc_lo(dk + hh * 4 + 2), 1);
  }
  wgmma_commit();
  const int lane = fresh_tid() & 31, g = lane >> 2;
  const bool odd = g & 1, edge = R == 0 && gb == 0 && wr == 0;
  const int D = 2 * (lane & 3) + (g & 1) - g;
  const uint32_t ra = q_row_addr(true, R, wr, lane);
  wgmma_wait<0>();
  reg_fence<40>(s[0]);
  reg_fence<40>(s[1]);
  float z[2][2], y[2][2];
#define GATHER_(W)                                                                                          \
  _Pragma("unroll") for (int hh = 0; hh < 2; hh++) _Pragma("unroll") for (int r = 0; r < 2; r++) {          \
    const float* e = &s[hh][4 * (2 * W + r) + 2 * r];                                                       \
    z[hh][r] = odd ? e[5] : e[4];                                                                           \
    y[hh][r] = D >= 2 ? (odd ? e[1] : e[0]) : (odd ? e[9] : e[8]);                                          \
  }
  if (wr < 2) {
    if (wr == 0) { GATHER_(0) } else { GATHER_(1) }
  } else {
    if (wr == 2) { GATHER_(2) } else { GATHER_(3) }
  }
#undef GATHER_
  float o[2][16], inv[2][2];
  uint32_t p[2][5][4];
  const int sh = odd ? 16 : 0, kb = wr + (D >= 2 ? 0 : 1);
#pragma unroll
  for (int hh = 0; hh < 2; hh++) {
    if (edge) {
      z[hh][0] = -INFINITY;
      if (D >= 2) y[hh][0] = y[hh][1] = -INFINITY;
    }
    uint32_t ab[2][2];
#pragma unroll
    for (int r = 0; r < 2; r++) {
      float m = fmaxf(z[hh][r], y[hh][r]);
      m = fmaxf(m, __shfl_xor_sync(0xffffffffu, m, 1));
      m = fmaxf(m, __shfl_xor_sync(0xffffffffu, m, 2));
      const float e0 = ex2_approx(z[hh][r] - m), e1 = ex2_approx(y[hh][r] - m);
      inv[hh][r] = e0 + e1;
      ab[r][0] = pack_bf16x2(e0, 0.f) << sh;
      ab[r][1] = pack_bf16x2(e1, 0.f) << sh;
    }
#pragma unroll
    for (int k = 0; k < 5; k++) {
      p[hh][k][0] = k == kb ? ab[0][1] : 0u;
      p[hh][k][1] = k == wr + 1 ? ab[1][0] : 0u;
      p[hh][k][2] = k == wr ? ab[0][0] : 0u;
      p[hh][k][3] = k == kb ? ab[1][1] : 0u;
#pragma unroll
      for (int j = 0; j < 4; j++) asm volatile("" : "+r"(p[hh][k][j]));
    }
  }
  wgmma_fence();
#pragma unroll
  for (int hh = 0; hh < 2; hh++) {
    wgmma_n32_rsz_tb1(o[hh], p[hh][0], desc_lo(dv + hh * 4));
#pragma unroll
    for (int k = 1; k < 5; k++) wgmma_n32_rs_tb1(o[hh], p[hh][k], desc_lo(dv + hh * 4 + k * 128), 1);
  }
  wgmma_commit();
#pragma unroll
  for (int hh = 0; hh < 2; hh++)
#pragma unroll
    for (int r = 0; r < 2; r++) {
      inv[hh][r] += __shfl_xor_sync(0xffffffffu, inv[hh][r], 1);
      inv[hh][r] += __shfl_xor_sync(0xffffffffu, inv[hh][r], 2);
      inv[hh][r] = rcp_fast(inv[hh][r]);
    }
  wgmma_wait<0>();
  reg_fence<16>(o[0]);
  reg_fence<16>(o[1]);
  store_o<0>(o[0], inv[0], ra, o_tag(1), true);
  store_o<1>(o[1], inv[1], ra, o_tag(1), true);
}

#define KTQM 0
#define TRICKLE 300
#define WTURN 15
#define QREL 8
#define PRESLEEP 200
#define CSA 3
#define TLAZY 100
#define QTURN 2
#define HTS(i) do { } while (0)
struct Params {
  CUtensorMap x[5], xq[4], o, wqkv[2], wqkv3[2], wo3[2];
  const __nv_bfloat16* in_x;
  const __nv_bfloat16* wqkv_p[2];
  const __nv_bfloat16* wo_p[2];
  __nv_bfloat16* out;
  uint32_t zero;
};

__device__ __forceinline__ void colsum_part(const CUtensorMap* wmap, int ty, int qr, int hp) {
  constexpr uint32_t bars = SBASE + OFF_BAR, slots = SBASE + OFF_SLOT;
  PHASE_IDS
  const unsigned ep1 = launch_epoch();
  if (wwarp == 0 && elect_one()) {
    mbar_expect_tx(bars + 8u * B_CS, 6 * UNIT);
#pragma unroll 1
    for (int j = 0; j < 6; j++) {
      if (ty == 0) mbar_pace(bars + 8u * (B_QF + B_E + ((j * CSA / 6) & 3)), (j * CSA / 6) >> 2);
      else mbar_wait_lazy<100>(bars + 8u * (B_WF + B_E + ((2 * j + 3 - (j & 1)) & 7)), j >= 3);
      tma_load_2d(slots + j * UNIT, wmap, bars + 8u * B_CS, (j >> 1) * 1024 + hp * 64, qr * 128 + (j & 1) * 64);
    }
  }
  constexpr uint64_t ones = (SBASE + OFF_LSB + 32) >> 4;
  float s[3][4];
  mbar_wait_lazy<100>(bars + 8u * B_CS, ty);
  wgmma_fence();
#pragma unroll
  for (int p = 0; p < 3; p++) {
    wgmma_n8_ssz_ta1_tb0(s[p], make_desc(slots + p * 2 * UNIT, 16), ones);
#pragma unroll
    for (int k = 1; k < 8; k++) wgmma_n8_ss_ta1_tb0(s[p], make_desc(slots + p * 2 * UNIT + k * 2048, 16), ones, 1);
  }
  wgmma_commit();
  wgmma_wait<0>();
  reg_fence<12>(&s[0][0]);
  if (lane == 0) mbar_arrive(bars + 8u * (ty ? B_CSD : B_RDONE));
  if (c == 0) {
#pragma unroll
    for (int r = 0; r < 2; r++) st_rec(&g_cs[ty][hp][qr][wwarp * 16 + 8 * r + g], s[0][2 * r], s[1][2 * r], s[2][2 * r], ep1);
  }
}

__device__ __forceinline__ void put_colsums(int ty, int col, const float4& s) {
  const float v[3] = {s.x, s.y, s.z};
#pragma unroll
  for (int p = 0; p < 3; p++) {
    const uint32_t a = SBASE + OFF_CS + (p * 8 + (col >> 3)) * 64 + ty * 32 + (col & 7) * 2;
    const float hi = bf16_round(v[p]);
    const uint32_t w = pack_bf16x2(hi, v[p] - hi);
    asm volatile("st.shared.b16 [%0], %1;" ::"r"(a), "h"((unsigned short)w) : "memory");
    asm volatile("st.shared.b16 [%0], %1;" ::"r"(a + 16), "h"((unsigned short)(w >> 16)) : "memory");
  }
}

__device__ __forceinline__ uint32_t ln_params(float s1, float s2) {
  const float mean = s1 * (1.0f / DM);
  const float var = fmaxf(fmaf(-mean, mean, s2 * (1.0f / DM)), 0.f);
  float sd;
  asm("sqrt.approx.f32 %0, %1;" : "=f"(sd) : "f"(bf16_round(bf16_round(var) + 1e-5f)));
  return pack_bf16x2(mean, sd);
}

struct RingProd {
  uint32_t rel = ((B_QF << 1) | 1) * 0x01010101u + 0x06040200u;
  int st = 0;
  __device__ __forceinline__ uint32_t next(uint32_t bar, uint32_t par, bool wait) {
    const uint32_t e = (rel >> (8 * st)) & 255u, a = SBASE + st * 5 * UNIT;
    if (wait) mbar_wait(SBASE + OFF_BAR + 8u * B_E + 8u * (e >> 1), e & 1u);
    rel ^= (e ^ ((bar << 1) | par)) << (8 * st);
    st = (st + 1) & 3;
    return a;
  }
};

#define SP1 15
#define SP2 14
#define SP3 12
#define SP4 12
#define SP5 15
#define SP6 14
#define SP7 16
__device__ __forceinline__ int q_split(int inst) {
  constexpr uint32_t T = 15u | ((SP1 - 1) << 4) | ((SP2 - 1) << 8) | ((SP3 - 1) << 12) | ((SP4 - 1) << 16) | ((SP5 - 1) << 20) |
                         ((SP6 - 1) << 24) | ((uint32_t)(SP7 - 1) << 28);
  return (int)((T >> (4 * inst)) & 15u) + 1;
}
__host__ __device__ constexpr uint32_t turn_par(int kind) {
  const int sp[8] = {16, SP1, SP2, SP3, SP4, SP5, SP6, SP7};
  int cnt[2] = {0, 0};
  uint32_t m = 0;
  for (int i = 0; i < 8; i++)
    for (int k = 0; k < 3; k++) {
      if (k == kind) m |= (uint32_t)(cnt[i & 1] & 1) << i;
      if (k == 0 ? (i == 1 || (i > 1 && sp[i - 1] < 16)) : (k == 2 || sp[i] < 16)) cnt[i & 1]++;
    }
  return m;
}
#define PREMASK 0xBFu
__device__ __forceinline__ bool w_pre(int inst) { return (PREMASK >> inst) & 1u; }
__global__ void __launch_bounds__(512, 1) fused_kernel(const __grid_constant__ Params P) {
  extern __shared__ __align__(1024) uint8_t smem_raw[];
  constexpr uint32_t base = SBASE, bars = base + OFF_BAR, slots = base + OFF_SLOT;
  if (smem_u32(smem_raw) != base) __trap();
  const int warp = __shfl_sync(0xffffffffu, threadIdx.x >> 5, 0), lane = threadIdx.x & 31;
  const int b = blockIdx.x;
#define QS 0
#define WS 1
  const int qr = ((b & ((8 << QS) - 1)) >> QS) ^ (((b >> (3 + QS)) & 1) * 7);
  const int hp = ((b >> (3 + QS)) << QS) + (b & ((1 << QS) - 1));
  const int rt = ((b & ((16 << WS) - 1)) >> WS) ^ (((b >> (4 + WS)) & 1) * 15);
  const int ct = ((b >> (4 + WS)) << WS) + (b & ((1 << WS) - 1));

  if (warp == 12) {
    if (elect_one()) {
#pragma unroll
      for (int s = 0; s < 4; s++) {
        mbar_init(bars + 8u * (B_QF + s), 2);
        mbar_init(bars + 8u * (B_QF + B_E + s), 4);
      }
      mbar_init(bars + 8u * B_GO, 1);
      fence_barrier_init();
    }
    __syncwarp();
    named_bar_arrive(0, 512);
  }
  if (threadIdx.x == 0) {
    for (int s = B_WF; s <= B_RF; s++) {
      mbar_init(bars + 8u * s, s == B_RF ? 1 : 2);
      mbar_init(bars + 8u * (s + B_E), 4);
    }
    for (int s = 0; s < 4; s++) {
      sts32(base + OFF_ONE + 4 * s, s == 0);
      sts32(base + OFF_LSB + 32 + 4 * s, 0x3f803f80u);
    }
    fence_proxy_async_smem();
    mbar_init(bars + 8u * B_PREP, 1);
    mbar_init(bars + 8u * (B_PREP + 1), 1);
    mbar_init(bars + 8u * B_HL, 1);
    mbar_init(bars + 8u * (B_HL + 1), 1);
    mbar_init(bars + 8u * B_HV, 1);
    for (int s = 0; s < 4; s++) mbar_init(bars + 8u * (B_HALO + s), 1);
    for (int s = 0; s < 3; s++) mbar_init(bars + 8u * (B_REL + s), s == 0 ? 4 : 8);
    mbar_init(bars + 8u * B_LOC, 4);
    mbar_init(bars + 8u * B_AFREE, 2);
    mbar_init(bars + 8u * B_TURN, 4);
    mbar_init(bars + 8u * (B_TURN + 1), 4);
    mbar_init(bars + 8u * B_CS, 1);
    mbar_init(bars + 8u * B_PRE, 1);
    mbar_init(bars + 8u * B_PRE2, 1);
    mbar_init(bars + 8u * B_CSD, 4);
    mbar_init(bars + 8u * B_RDONE, 4);
    mbar_init(bars + 8u * B_XRDY, 1);
    mbar_init(bars + 8u * (B_XRDY + 1), 1);
    fence_barrier_init();
  }
  if (warp != 12) named_bar_sync(0, 512);

  if (warp >= 12) {
    setmaxnreg_dec<32>();
    if (warp == 12) {
      if (elect_one()) {
#pragma unroll 1
        for (int s = 0; s < 16; s++) {
          const uint32_t fb = bars + 8u * (B_QF + (s & 3)), sa = base + (s & 3) * 5 * UNIT;
          if (s >= 4) mbar_wait(fb + 8u * B_E, ((s >> 2) & 1) ^ 1);
          mbar_expect_tx(fb, 5 * UNIT);
          mbar_arrive(fb);
          tma_load_5d(sa + 3 * UNIT, &P.xq[0], fb, s * 64, qr * 2);
          tma_load_3d(sa, &P.wqkv3[0], fb, hp * 64, s * 64);
        }
        mbar_arrive(bars + 8u * B_GO);
        RingProd rp;
#pragma unroll 1
        for (int sg = 4; sg < 34; sg++) {
          const int part = sg & 3, inst = (sg >> 2) - (part & 1);
          if (part == 3 || inst == 8) continue;
          const int ty = (inst >> 1) & 1;
          if (part != 1) {
            const int k0 = part ? q_split(inst) : 0, k1 = part ? 16 : q_split(inst);
#pragma unroll 1
            for (int kt = k0; kt < k1; kt++) {
              const uint32_t sa = rp.next(B_QF + (kt & 3), (kt >> 2) & 1, true), fb = bars + 8u * (B_QF + (kt & 3));
              mbar_expect_tx(fb, 3 * UNIT);
              tma_load_3d(sa, &P.wqkv3[ty], fb, hp * 64, kt * 64);
            }
          } else {
            const bool pre = w_pre(inst);
            const int lag = pre ? 8 : 5;
            uint32_t sa = 0;
#pragma unroll 1
            for (int kt = 0; kt < 16; kt++) {
              const int i = kt & 3;
              const uint32_t fb = bars + 8u * (B_WF + (kt & 7));
              if (i == 1) sa += 2 * UNIT;
              else if (i != 3 || !pre) sa = rp.next(kt == 14 ? B_RF : B_WF + ((kt | 1) & 7), kt == 14 ? inst & 1 : kt >> 3, kt < lag) + ((0x21 >> (2 * i)) & 3) * UNIT;
              if (kt >= lag) mbar_wait(bars + 8u * (B_WF + B_E + ((kt - lag) & 7)), (kt - lag) >> 3);
              if (i == 3 && pre) {
                mbar_arrive(fb);
              } else {
                mbar_expect_tx(fb, 2 * UNIT);
                tma_load_3d(sa, &P.wo3[ty], fb, ct * 128, kt * 64);
              }
            }
          }
        }
      }
    } else if (warp == 13) {
      RingProd rp;
      unsigned ep1 = 0;
      mbar_wait(bars + 8u * B_GO, 0);
#pragma unroll 1
      for (int sg = 4; sg < 34; sg++) {
        const int part = sg & 3, inst = (sg >> 2) - (part & 1);
        if (part == 3 || inst == 8) continue;
        const int L = inst >> 1, ch = inst & 1;
        uint32_t seen = 0;
        if (part != 1) {
          const CUtensorMap* tx = &P.xq[L];
          const int k0 = part ? q_split(inst) : 0, k1 = part ? 16 : q_split(inst);
          if (L == 0 || mbar_test(bars + 8u * (B_XRDY + ch), (L & 1) ^ 1)) {
            seen = 0xFFFFFFFFu;
          }
          if (sg == 4) ep1 = launch_epoch();
          const int m0 = ch * 16 + qr * 2;
#pragma unroll 1
          for (int kt = k0; kt < k1; kt++) {
            wait_count(g_fx[ch * 8 + qr][0], 6u * ep1 - 6u + 2u * L, kt, seen, lane);
            TGET(t38);
            const uint32_t sa = rp.next(B_QF + (kt & 3), (kt >> 2) & 1, true);
            TGET(t39);
            if (elect_one()) {
              const uint32_t fb = bars + 8u * (B_QF + (kt & 3));
              mbar_expect_tx(fb, 2 * UNIT);
              tma_load_5d(sa + 3 * UNIT, tx, fb, kt * 64, m0);
            }
            if (L == 3 && kt == 0 && lane == 0) { TPUT(ch, 38, t38); TPUT(ch, 39, t39); }
          }
        } else {
          const int m0 = ch * 1024 + rt * 64;
          const bool pre = w_pre(inst);
          const int lag = pre ? 8 : 5;
          uint32_t sa = 0;
#pragma unroll 1
          for (int kt = 0; kt < 16; kt++) {
            const int i = kt & 3;
            const uint32_t fb = bars + 8u * (B_WF + (kt & 7));
            wait_count(g_fo[ch * 16 + rt][0], 4u * ep1 - 3u + L, kt, seen, lane);
            const bool stg = kt == 13 && inst == 6 && SP7 == 16;
            if (i < 2) sa = rp.next(stg ? B_RF : B_WF + (kt & 7) + i + 1, stg ? inst & 1 : kt >> 3, kt < lag);
            else sa += (2 * i - 3) * UNIT;
            if (kt >= lag) mbar_wait(bars + 8u * (B_WF + B_E + ((kt - lag) & 7)), (kt - lag) >> 3);
            if (elect_one()) {
              mbar_expect_tx(fb, UNIT);
              tma_load_2d(sa, &P.o, fb, kt * 64, m0);
            }
            if (i == 3 && !pre) rp.next(B_WF + (kt & 7), kt >> 3, false);
          }
        }
      }
    } else if (warp == 14) {
      const unsigned ep1 = launch_epoch();
      uint32_t hpar = 0;
#pragma unroll 1
      for (int inst = 0; inst < 8; inst++) {
        const int L = inst >> 1, ch = inst & 1, gb = ch * 8 + qr;
        const unsigned kv0 = 8u * ep1 - 8u + 2u * L + (L & 1);
        if ((L & 1) == 0) {
          uint8_t* img = g_kvA[L >> 1][gb][hp][0];
          const uint8_t* s1 = gb > 0 ? img - 16 * 32768 : g_zero;
          const uint8_t* s2 = gb > 1 ? img - 32 * 32768 : g_zero;
          const uint32_t h1 = gb > 0 ? 16384 : 0, h2 = gb > 1 ? 16384 : 0;
          const unsigned* cp = g_fk[hp][max(gb - 1 - (lane >= 3), 0)];
          const unsigned ct0 = kv0 + ((0x32321u >> (4 * (lane & 7))) & 3u);
          uint32_t fr = gb == 0 ? 31u : (gb == 1 ? 24u : 0u);
          const uint32_t toff = slots + lane * 128 + ((lane & 7) << 4);
          auto seen = [&](uint32_t m) {
#pragma unroll 1
            for (uint32_t it = 0; it < (1u << 17) && !(fr & m); ++it)
              fr |= __ballot_sync(0xffffffffu, (int)(ld_relaxed_u32(cp) - ct0) >= 0);
          };
          auto load = [&](uint32_t off, const uint8_t* src, uint32_t bytes, int bi) {
            if (elect_one()) {
              mbar_expect_tx(bars + 8u * (B_HL + bi), bytes);
              bulk_load(slots + off, src, bytes, bars + 8u * (B_HL + bi));
            }
          };
          auto check = [&](uint32_t off, const uint8_t* src, uint32_t bytes, int bi, bool real, int done) {
#pragma unroll 1
            for (int tries = 0; tries < 4096; tries++) {
              mbar_wait(bars + 8u * (B_HL + bi), (hpar >> bi) & 1u);
              hpar ^= 1u << bi;
              uint32_t t = (lds32(toff + off) ^ ep1) | (lds32(toff + off + 4096) ^ ep1);
              if (bytes > 8192) t |= (lds32(toff + off + 8192) ^ ep1) | (lds32(toff + off + 12288) ^ ep1);
              if (!__any_sync(0xffffffffu, real && (t & 1u))) break;
              fence_proxy_async_smem();
              load(off, src, bytes, bi);
            }
            if (lane == 0) mbar_arrive(bars + 8u * done);
          };
          named_bar_sync(3, 160);
          HTS(44);
          if (elect_one()) {
            bulk_store(img + 16384, slots + 16384, 8192);
            bulk_announce(g_fk[hp][gb]);
            bulk_store(img + 24576, slots + 24576, 8192);
            bulk_announce(g_fk[hp][gb]);
            bulk_commit();
          }
          seen(1);
          HTS(46);
          load(32768, s1 + h1, 8192, 0);
          seen(2);
          HTS(47);
          load(40960, s1 + h1 + 8192, 8192, 1);
          mbar_wait(bars + 8u * B_LOC, inst & 1);
          HTS(45);
          if (elect_one()) {
            bulk_store(img, slots, 16384);
            bulk_announce(g_fk[hp][gb]);
            bulk_commit();
            asm volatile("cp.async.bulk.wait_group.read 1;" ::: "memory");
          }
          check(32768, s1 + h1, 8192, 0, gb > 0, B_HALO);
          HTS(52);
          check(40960, s1 + h1 + 8192, 8192, 1, gb > 0, B_HV);
          HTS(53);
#pragma unroll 1
          for (int n = 1; n < 4; n++) {
            const uint8_t* src = n == 1 ? s1 : (n == 2 ? s2 + h2 : s2);
            const uint32_t off = n == 3 ? 32768 : 32768 - n * 16384;
            seen(2u << n);
            if (n == 2 && elect_one()) bulk_wait_read0();
            mbar_wait(bars + 8u * (B_REL - 1) + 8u * n, ch);
            HTS(47 + n);
            load(off, src, 16384, 0);
            check(off, src, 16384, 0, gb > (n >> 1), B_HALO + n);
            HTS(53 + n);
          }
        } else {
          uint8_t* img = g_kvB[L >> 1][gb][hp];
          named_bar_sync(3, 160);
          HTS(44);
          if (elect_one()) {
            bulk_store(img, KB_ROW0 + 112 * 128, 2048);
            bulk_store(img + 2048, VB_ROW0 + 112 * 128, 2048);
            bulk_announce(g_fk[hp][gb]);
            bulk_commit();
          }
          const uint8_t* src = gb >= 1 ? img - 16 * 4096 : g_zero;
#pragma unroll 1
          for (uint32_t it = 0; it < (1u << 17); ++it)
            if (gb == 0 || (int)(ld_relaxed_u32(g_fk[hp][gb - 1]) - kv0) > 0) break;
          HTS(46);
#pragma unroll 1
          for (uint32_t it = 0; it < 4096; ++it) {
            if (elect_one()) {
              mbar_expect_tx(bars + 8u * B_HL, 4096);
              bulk_load(KB_ROW0 - 2048, src, 2048, bars + 8u * B_HL);
              bulk_load(VB_ROW0 - 2048, src + 2048, 2048, bars + 8u * B_HL);
              bulk_wait_read0();
            }
            mbar_wait(bars + 8u * B_HL, hpar & 1u);
            hpar ^= 1u;
            const uint32_t t = lds32((lane < 16 ? KB_ROW0 - 2048 : VB_ROW0 - 4096) + lane * 128 + ((lane & 7) << 4)) ^ ep1;
            if (gb == 0 || !__any_sync(0xffffffffu, t & 1u)) break;
            fence_proxy_async_smem();
          }
          if (lane == 0) mbar_arrive(bars + 8u * B_HALO);
          HTS(52);
        }
        if (elect_one()) {
          mbar_wait(bars + 8u * B_AFREE, inst & 1);
          mbar_expect_tx(bars + 8u * B_RF, 2 * UNIT);
          tma_load_2d(slots + 6 * UNIT, &P.x[L], bars + 8u * B_RF, ct * 128, ch * 1024 + rt * 64);
          tma_load_2d(slots + 7 * UNIT, &P.x[L], bars + 8u * B_RF, ct * 128 + 64, ch * 1024 + rt * 64);
          if (w_pre(inst)) {
            mbar_expect_tx(bars + 8u * B_PRE, 6 * UNIT);
            mbar_expect_tx(bars + 8u * B_PRE2, 2 * UNIT);
#pragma unroll 1
            for (int j = 0; j < 4; j++) {
              __nanosleep(PRESLEEP);
              if (j == 3) mbar_wait(bars + 8u * B_RDONE, (inst & 1) ^ 1);
              tma_load_3d(slots + j * 2 * UNIT, &P.wo3[L & 1], bars + 8u * (j == 3 ? B_PRE2 : B_PRE), ct * 128, (4 * j + 3) * 64);
            }
          }
        }
        __syncwarp();
      }
    } else {
      const unsigned ep1 = launch_epoch();
      mbar_wait(bars + 8u * B_GO, 0);
#pragma unroll 1
      for (int i = 0; i < 20; i++) {
        const char* src = i < 4 ? reinterpret_cast<const char*>(P.wo_p[0]) + (size_t)b * 16384 + i * 4096
                                : (i < 16 ? reinterpret_cast<const char*>(P.wqkv_p[1]) + (size_t)b * 49152 + (i - 4) * 4096
                                          : reinterpret_cast<const char*>(P.wo_p[1]) + (size_t)b * 16384 + (i - 16) * 4096);
        asm volatile("prefetch.global.L2 [%0];" ::"l"(src + lane * 128));
        __nanosleep(TRICKLE);
      }
#pragma unroll 1
      for (int inst = 2; inst < 8; inst++) {
        const int L = inst >> 1, ch = inst & 1, gb = ch * 8 + qr;
        mbar_wait_lazy<200>(bars + 8u * (B_RF + B_E), inst & 1);
#pragma unroll 1
        for (int h = 0; h < 4; h++) {
          const float4* sp = &g_stats[L][0][gb * 128 + h * 32 + lane];
          const float4 s0 = sum_recs<4>(sp, S_LEN, ep1), s1 = sum_recs<4>(sp + 4 * S_LEN, S_LEN, ep1);
          sts32(base + OFF_RS + (ch * 128 + h * 32 + lane) * 4, ln_params(s0.x + s1.x, s0.y + s1.y));
        }
        if (lane == 0) mbar_arrive(bars + 8u * (B_XRDY + ch));
        if (inst == 2) {
#pragma unroll 1
          for (int hf = 0; hf < 2; hf++) {
            const float4* cp = &g_cs[1][hp][0][hf * 32 + lane];
            const float4 s0 = sum_recs<4>(cp, 64, ep1), s1 = sum_recs<4>(cp + 4 * 64, 64, ep1);
            put_colsums(1, hf * 32 + lane, make_float4(s0.x + s1.x, s0.y + s1.y, s0.z + s1.z, 0.f));
          }
        }
        fence_proxy_async_smem();
        __syncwarp();
        if (lane == 0) mbar_arrive(bars + 8u * (B_PREP + ch));
      }
    }
  } else {
    const bool asst = warp >= 8;
    GTL(0);
    if (warp >= 4 && !asst) {
      PHASE_IDS
      {
        const unsigned ep1 = launch_epoch();
        const int row = b * 16 + (tid >> 3);
        const uint4* src = reinterpret_cast<const uint4*>(P.in_x + (size_t)row * DM) + (tid & 7);
        float s1 = 0.f, s2 = 0.f;
#pragma unroll 1
        for (int k = 0; k < 4; k++) {
          mbar_pace(bars + 8u * (B_QF + B_E + ((2 * k) & 3)), k >> 1);
          uint4 v[4];
#pragma unroll
          for (int j = 0; j < 4; j++) v[j] = __ldg(src + (k * 4 + j) * 8);
#pragma unroll
          for (int j = 0; j < 4; j++) {
            const uint32_t w[4] = {v[j].x, v[j].y, v[j].z, v[j].w};
#pragma unroll
            for (int e = 0; e < 4; e++) {
              const float x0 = bf_lo(w[e]), x1 = bf_hi(w[e]);
              s1 += x0 + x1;
              s2 = fmaf(x0, x0, fmaf(x1, x1, s2));
            }
          }
        }
#pragma unroll
        for (int o = 1; o < 8; o <<= 1) {
          s1 += __shfl_xor_sync(0xffffffffu, s1, o);
          s2 += __shfl_xor_sync(0xffffffffu, s2, o);
        }
        if ((tid & 7) == 0) st_rec(&g_stats[0][0][row], s1, s2, 0.f, ep1);
        if (tid == 0) sts32(base + OFF_EPOCH, ep1);
        if (tid < 64) {
          const float4 s0 = sum_recs<8>(&g_cs[0][hp][0][tid], 64, ep1);
          put_colsums(0, tid, s0);
        } else {
          put_colsums(1, tid - 64, make_float4(0.f, 0.f, 0.f, 0.f));
        }
#pragma unroll 1
        for (int cc = 0; cc < 2; cc++) {
          const float4 s0 = sum_recs<1>(&g_stats[0][0][(cc * 8 + qr) * 128 + tid], 0, ep1);
          sts32(base + OFF_RS + (cc * 128 + tid) * 4, ln_params(s0.x, s0.y));
        }
        fence_proxy_async_smem();
        named_bar_sync(2, 128);
        if (tid < 2) mbar_arrive(bars + 8u * (B_PREP + tid));
      }
    }
#pragma unroll 1
    for (int inst = asst ? 0 : warp >> 2; inst < 8; inst += asst ? 1 : 2) {
      const int L = inst >> 1, ch = inst & 1, gb = ch * 8 + qr;
      uint32_t q[2][2][4];
      if (asst) {
        if (inst < 2) colsum_part(&P.wqkv[inst], inst, qr, hp);
        setmaxnreg_dec<24>();
        named_bar_sync(4, 256);
        setmaxnreg_inc<128>();
        const uint32_t ra = q_row_addr(L & 1, 1, warp & 3, fresh_tid() & 31);
#pragma unroll
        for (int j = 0; j < 4; j++) ldmatrix_x4(q[j >> 1][j & 1], ra ^ (j << 5));
      } else {
      setmaxnreg_inc<224>();
      {
        float acc[2][96];
        const int ksp = q_split(inst);
        constexpr uint32_t STG = 5 * (UNIT >> 4), D0 = ((base + 3 * UNIT) >> 4) + 0x10000u;
        constexpr uint32_t DB = ((UNIT >> 4) << 16) - 0x10000u - 3 * (UNIT >> 4);
        uint32_t sd = D0;
        const uint32_t toff = ((fresh_tid() & 127) << 7) + ((fresh_tid() & 7) << 4);
        const bool lane0 = (toff & 0xf80u) == 0u;
        uint32_t tbad = 0u, tw, xt = x_tag(lds32(base + OFF_EPOCH), L);
        uint32_t rsa = base + OFF_RS + (ch * 128 + tile_row(L & 1, warp & 3, 0, (toff >> 9) & 7)) * 4;
        uint32_t rsb = rsa + ((L & 1) ? 32 : 128);
        uint32_t lnm = ((toff >> 7) & 3) == (L & 1) ? 0xffffffffu : 0u, tmk = L > 0;
        uint32_t soff = tile_row(L & 1, warp & 3, (toff >> 10) & 1, (toff >> 7) & 7) * 128 + ((toff ^ (toff >> 7)) & 0x10u) + (toff & 0x60u);
        uint32_t bprep = bars + 8u * (B_PREP + ch), bturn = bars + 8u * (B_TURN + (ch ^ 1));
        uint32_t bfree = bars + 8u * (inst == 1 ? B_CSD : B_RDONE), pfree = inst == 1 ? 0 : inst & 1, pprep = L & 1;
        asm volatile("" : "+r"(rsa), "+r"(rsb), "+r"(lnm), "+r"(soff), "+r"(xt), "+r"(tmk));
        asm volatile("" : "+r"(bprep), "+r"(bturn), "+r"(bfree), "+r"(pfree), "+r"(pprep));
        if (inst == 1 || (inst > 1 && q_split(inst - 1) < 16)) mbar_wait_lazy<TLAZY>(bars + 8u * (B_TURN + ch), (turn_par(0) >> inst) & 1u);
        if (L == 3) GTL(37);
        mbar_wait(bars + 8u * B_QF, 0);
        GTL(1 + L * 8);
        {
          const uint64_t da = desc_lo(sd) + P.zero;
          wgmma_fence();
          wgmma_n192_ssz_ta0_tb1(acc[1], da + (UNIT >> 4), da + DB);
          wgmma_commit();
          wgmma_n192_ssz_ta0_tb1(acc[0], da, da + DB);
          wgmma_commit();
        }
#pragma unroll 1
        for (int kt = 0; kt < 15; kt++) {
          const bool last = kt + 1 == ksp;
          const uint64_t da = desc_lo(sd) + P.zero;
          const uint32_t fn = bars + 8u * (B_QF + ((kt + 1) & 3)), pn = ((kt + 1) >> 2) & 1;
#pragma unroll
          for (int k16 = 0; k16 < 4; k16++) {
            if (k16 == 0 && kt == 0) continue;
            wgmma_fence();
            wgmma_n192_ss_ta0_tb1(acc[1], da + ((UNIT >> 4) + k16 * 2), da + (DB + k16 * 128), 1);
            wgmma_commit();
            wgmma_wait<1>();
            if (k16 == 0 && lane0 && kt != ksp) mbar_arrive(bars + 8u * (B_QF + B_E + ((kt - 1) & 3)));
            wgmma_fence();
            wgmma_n192_ss_ta0_tb1(acc[0], da + k16 * 2, da + (DB + k16 * 128), 1);
            wgmma_commit();
            if (k16 == 1) tw = lds32(((sd & 0xffffu) << 4) + toff);
            if (k16 == 2) tbad |= tw ^ xt;
            bool ok = true;
            if (k16 == 2) ok = mbar_test(fn, pn) || last;
            if (k16 == QTURN && last && lane0) mbar_arrive(bturn);
            if (k16 < 3) wgmma_wait<1>();
            if (k16 == 2 && !ok) mbar_wait(fn, pn);
          }
          sd = sd == D0 + 3 * STG ? D0 : sd + STG;
          if (last) {
            wgmma_wait<0>();
            if (lane0) mbar_arrive(bars + 8u * (B_QF + B_E + (kt & 3)));
            mbar_wait_lazy<TLAZY>(bars + 8u * (B_TURN + ch), (turn_par(1) >> inst) & 1u);
            mbar_wait(fn, pn);
          }
        }
        constexpr uint32_t DL = D0 + 3 * STG;
        wgmma_fence();
#pragma unroll
        for (int k16 = 0; k16 < 4; k16++) wgmma_n192_ss_ta0_tb1(acc[1], desc_lo(DL + (UNIT >> 4) + k16 * 2), desc_lo(DL + DB + k16 * 128), 1);
        wgmma_commit();
        tw = lds32(((DL & 0xffffu) << 4) + toff);
        mbar_wait(bprep, pprep);
        uint32_t rs[2][2];
        constexpr uint64_t DCS = (uint64_t)((base + OFF_CS) >> 4) | (4ull << 32);
        auto ln_mma = [&](float (&d)[96], uint32_t (&r)[2], int h) {
          uint32_t a[4];
#pragma unroll
          for (int i = 0; i < 2; i++) {
            if (h) r[i] = lds32((i ? rsb : rsa) + 256);
            a[i] = (__byte_perm(r[i], 0u, 0x1010) ^ 0x80008000u) & lnm;
            a[i + 2] = r[i] & P.zero;
          }
#pragma unroll
          for (int i = 0; i < 4; i++) asm volatile("" : "+r"(a[i]));
          wgmma_fence();
          wgmma_n192_rs_tb1(d, a, DCS, 1);
          wgmma_commit();
        };
        ln_mma(acc[1], rs[1], 1);
        wgmma_wait<2>();
        if (lane0 && ksp != 15) mbar_arrive(bars + 8u * (B_QF + B_E + 2));
        wgmma_fence();
#pragma unroll
        for (int k16 = 0; k16 < 4; k16++) wgmma_n192_ss_ta0_tb1(acc[0], desc_lo(DL + k16 * 2), desc_lo(DL + DB + k16 * 128), 1);
        wgmma_commit();
        if (lane0) mbar_arrive(bturn);
        const uint32_t ep1 = lds32(base + OFF_EPOCH);
        rs[0][0] = lds32(rsa);
        rs[0][1] = lds32(rsb);
        static_assert(SP1 < 16 && (PREMASK & 1u), "column sums of B");
        const bool afree = mbar_test(bfree, pfree) & (mbar_test(bars + 8u * (B_WF + B_E + 7), 1) | (ksp == 16));
        const bool redo = named_bar_or(1 + ch, 128, (tbad | (tw ^ xt)) & tmk);
        float rinv[2];
#pragma unroll
        for (int r = 0; r < 2; r++) {
          rinv[r] = rcp_fast(bf_hi(rs[1][r]));
          asm volatile("" : "+f"(rinv[r]));
        }
        const uint32_t kdst = ((L & 1) ? KB_ROW0 : slots) + soff, vdst = ((L & 1) ? VB_ROW0 : slots + 8192) + soff;
        const uint32_t hs = (L & 1) ? 8192 : 16384, c0 = (toff & 0x180u) == 0u;
        wgmma_wait<1>();
        if (redo) {
          wgmma_wait<0>();
          constexpr uint32_t sa = (DL & 0xffffu) << 4;
          const uint32_t rb = bars + 8u * (B_REDO + ch);
          if (toff == 0) {
            mbar_init(rb, 1);
            fence_barrier_init();
          }
          uint32_t rpar = 0;
#pragma unroll 1
          for (int kt = 0, tries = 0; kt < 16;) {
            fence_proxy_async_smem();
            named_bar_sync(1 + ch, 128);
            if ((warp & 3) == 0 && elect_one()) {
                mbar_expect_tx(rb, 5 * UNIT);
              tma_load_5d(sa, &P.xq[L], rb, kt * 64, gb * 2);
              tma_load_3d(sa - 3 * UNIT, &P.wqkv3[L & 1], rb, hp * 64, kt * 64);
            }
            mbar_wait(rb, rpar);
            rpar ^= 1u;
            if (named_bar_or(1 + ch, 128, (lds32(sa + toff) ^ xt) & 1u) && ++tries < 4096) continue;
            wgmma_fence();
#pragma unroll
            for (int k16 = 0; k16 < 4; k16++) {
              const uint64_t db = make_desc(sa - 3 * UNIT + k16 * 2048, UNIT);
              wgmma_n192_ss_ta0_tb1(acc[1], make_desc(sa + UNIT + k16 * 32, 16), db, kt | k16);
              wgmma_n192_ss_ta0_tb1(acc[0], make_desc(sa + k16 * 32, 16), db, kt | k16);
            }
            wgmma_commit();
            wgmma_wait<0>();
            kt++;
          }
          ln_mma(acc[1], rs[1], 1);
          wgmma_wait<0>();
        }
        ln_mma(acc[0], rs[0], 0);
        reg_fence<96>(acc[1]);
        GTL(2 + L * 8);
        if (!afree) {
          mbar_wait(bfree, pfree);
          if (ksp < 16) mbar_wait(bars + 8u * (B_WF + B_E + 7), 1);
        }
#pragma unroll
        for (int t = 0; t < 24; t++) {
          const int h = t < 12 ? 1 : 0, p = ((t % 12) / 4 + 1) % 3, jp = t & 3;
          if (t == QREL) {
            wgmma_wait<0>();
            reg_fence<96>(acc[0]);
            if (lane0) mbar_arrive(bars + 8u * (B_QF + B_E + 3));
          }
          if (t == 8 || t == 20) {
            rinv[0] *= SM_C;
            rinv[1] *= SM_C;
          }
          const float* a = &acc[h][4 * (p * 8 + 2 * jp)];
          uint32_t r0 = pack_bf16x2(a[0] * rinv[0], a[1] * rinv[0]);
          uint32_t r1 = pack_bf16x2(a[2] * rinv[1], a[3] * rinv[1]);
          if (p != 0 && jp == 0) {
            r0 = set_tag(r0, c0, ep1);
            r1 = set_tag(r1, c0, ep1);
          }
          const uint32_t r2 = pack_bf16x2(a[4] * rinv[0], a[5] * rinv[0]);
          const uint32_t r3 = pack_bf16x2(a[6] * rinv[1], a[7] * rinv[1]);
          const uint32_t dst = p == 0 ? slots + 3 * 16384 + soff + h * 8192 : (p == 1 ? kdst : vdst) + h * hs;
          stmatrix_x4(dst ^ (jp << 5), r0, r1, r2, r3);
          if (t >= 20) {
            q[jp >> 1][jp & 1][0] = r0;
            q[jp >> 1][jp & 1][1] = r1;
            q[jp >> 1][jp & 1][2] = r2;
            q[jp >> 1][jp & 1][3] = r3;
          }
          if (t == 7 || t == 19) {
            fence_proxy_async_smem();
            if (t == 7) {
              named_bar_arrive(3, 160);
            } else {
              __syncwarp();
              if (lane0) mbar_arrive(bars + 8u * B_LOC);
            }
          }
          if (t == 11) {
            setmaxnreg_dec<128>();
            named_bar_arrive(4, 256);
#pragma unroll
            for (int r = 0; r < 2; r++) rinv[r] = rcp_fast(bf_hi(rs[0][r]));
          }
        }
        mbar_wait(bars + 8u * B_LOC, inst & 1);
      }
      }
      GTL(3 + L * 8);
      if ((L & 1) == 0) attention_a(q, asst, L, gb, hp, ch, warp & 3, P.zero);
      else attention_b(q, asst, gb, inst & 1, warp & 3);
      GTL(4 + L * 8);
      fence_proxy_async_smem();
      named_bar_sync(asst ? 6 : 1 + ch, 128);
      if ((warp & 3) == 0) {
        if (elect_one()) {
          tma_store_2d(&P.o, slots + 3 * 16384 + asst * 8192, hp * 64, gb * 128 + asst * 64);
          bulk_announce(g_fo[gb * 2 + asst][hp]);
          bulk_commit();
          bulk_wait_read0();
          mbar_arrive(bars + 8u * B_AFREE);
        }
        __syncwarp();
      }
      if (asst) continue;
      GTL(5 + L * 8);

      {
        float acc[64];
        const int sp = inst < 7 ? q_split(inst + 1) : 0;
        int st = sp & 3;
        const bool pre = w_pre(inst);
        uint32_t tbad = 0u;
        const uint32_t toff = ((fresh_tid() & 63) << 7) + ((fresh_tid() & 7) << 4);
        const bool lane0 = (toff & 0xf80u) == 0u;
        constexpr uint32_t U4 = UNIT >> 4, LA = 0x10000u, LB = U4 << 16;
        reg_define<64>(acc);
        reg_fence<64>(acc);
        uint32_t xv[8][4];
        {
          PHASE_IDS_W
          const uint32_t xr = slots + 6 * UNIT + (wwarp * 16 + (lane & 15)) * 128 + (((lane >> 4) ^ (lane & 7)) << 4);
          mbar_wait(bars + 8u * B_RF, inst & 1);
#pragma unroll
          for (int jp = 0; jp < 8; jp++) ldmatrix_x4(xv[jp], (xr ^ ((jp & 3) << 5)) + (jp >> 2) * UNIT);
          fence_proxy_async_smem();
          __syncwarp();
          if (lane0) mbar_arrive(bars + 8u * B_RDONE);
          if (L > 0) {
            uint32_t lsb;
            asm volatile("ld.shared.u8 %0, [%1];" : "=r"(lsb) : "r"(base + OFF_LSB + ch * 32 + wwarp * 8 + g) : "memory");
#pragma unroll
            for (int k = 0; k < 4; k++) xv[(k >> 1) * 4][k & 1] = set_tag(xv[(k >> 1) * 4][k & 1], c == 0, lsb >> k);
          }
        }
        uint64_t d0 = desc_lo((base >> 4) + st * 5 * U4) + P.zero;
        if (inst < 7 || SP7 == 16) mbar_wait_lazy<TLAZY>(bars + 8u * (B_TURN + ch), (turn_par(2) >> inst) & 1u);
        mbar_wait(bars + 8u * B_WF, 0);
        GTL(6 + L * 8);
        uint32_t s1 = 0;
#pragma unroll 1
        for (int m = 0; m < 4; m++) {
          const uint32_t s0 = base + st * 5 * UNIT, fb = bars + 8u * (B_WF + 4 * (m & 1));
          s1 = base + ((st + 1) & 3) * 5 * UNIT;
          const uint64_t d1 = desc_lo(s1 >> 4) + P.zero;
          const uint64_t d2 = desc_lo((pre ? slots + m * 2 * UNIT : base + ((st + 2) & 3) * 5 * UNIT) >> 4) + P.zero;
          st = (st + (pre ? 2 : 3)) & 3;
#pragma unroll
          for (int i = 0; i < 4; i++) {
            const uint64_t da = (i == 0 ? d0 : d1) + (LA + (i == 2 ? 1 : (i == 3 ? 4 : 0)) * U4);
            const uint64_t db = (i < 2 ? d0 : (i == 2 ? d1 : d2)) + (LB + (i == 0 ? 1 : (i == 1 ? 3 : (i == 2 ? 2 : 0))) * U4);
            if (i == 3 && (m == 0 || m == 3) && pre) mbar_wait(bars + 8u * (m ? B_PRE2 : B_PRE), __popc(PREMASK & ((1u << inst) - 1u)) & 1);
            if (i == (WTURN & 3) && m == 3 && lane0 && (sp < 16 || inst == 6)) mbar_arrive(bars + 8u * (B_TURN + (ch ^ 1)));
            wgmma_fence();
#pragma unroll
            for (int k16 = 0; k16 < 4; k16++) wgmma_n128_ss_ta0_tb1(acc, da + 2 * k16, db + 128 * k16, 1);
            wgmma_commit();
            if (i == 2) d0 = desc_lo((base >> 4) + st * 5 * U4) + P.zero;
            tbad |= lds32((i == 0 ? s0 : s1) + (i == 2 ? 1 : (i == 3 ? 4 : 0)) * UNIT + toff) ^ o_tag(L);
            const uint32_t fn = i < 3 ? fb + 8u * (i + 1) : fb ^ 96u;
            const uint32_t pn = i < 3 ? m >> 1 : m > 0;
            const bool ok = mbar_test(fn, pn) || (i == 3 && m == 3);
            wgmma_wait<1>();
            if (lane0 && (i > 0 || m > 0)) mbar_arrive((i > 0 ? fb + 8u * (i - 1) : (fb ^ 96u) + 24u) + 8u * B_E);
            if (!ok) mbar_wait(fn, pn);
          }
        }
        const uint32_t xb = s1;
        const bool redo = named_bar_or(1 + ch, 128, tbad & 1u);
        if (redo) {
          wgmma_wait<0>();
          const uint32_t sa = s1 + 4 * UNIT, sb = s1 + 2 * UNIT;
          const uint32_t rb = bars + 8u * (B_REDO + ch);
          if ((fresh_tid() & 127) == 0) {
            mbar_init(rb, 1);
            fence_barrier_init();
          }
          uint32_t rpar = 0;
#pragma unroll 1
          for (int kt = 0, tries = 0; kt < 16;) {
            fence_proxy_async_smem();
            named_bar_sync(1 + ch, 128);
            if ((warp & 3) == 0 && elect_one()) {
                mbar_expect_tx(rb, 3 * UNIT);
              tma_load_2d(sa, &P.o, rb, kt * 64, ch * 1024 + rt * 64);
              tma_load_3d(sb, &P.wo3[L & 1], rb, ct * 128, kt * 64);
            }
            mbar_wait(rb, rpar);
            rpar ^= 1u;
            if (named_bar_or(1 + ch, 128, (lds32(sa + toff) ^ o_tag(L)) & 1u) && ++tries < 4096) continue;
            wgmma_fence();
#pragma unroll
            for (int k16 = 0; k16 < 4; k16++)
              wgmma_n128_ss_ta0_tb1(acc, make_desc(sa + k16 * 32, 16), make_desc(sb + k16 * 2048, UNIT), kt | k16);
            wgmma_commit();
            wgmma_wait<0>();
            kt++;
          }
        }
        PHASE_IDS_W
        const uint32_t xrow = xb + (wwarp * 16 + (lane & 15)) * 128 + (((lane >> 4) ^ (lane & 7)) << 4);
        const unsigned ep1 = __shfl_sync(0xffffffffu, lds32(base + OFF_EPOCH), 0);
        const uint32_t tm = c == 0, lsa = base + OFF_LSB + ch * 32 + wwarp * 8 + g;
        wgmma_wait<0>();
        reg_fence<64>(acc);
        if (lane0) mbar_arrive(bars + 8u * (B_WF + B_E + 7));
        GTL(7 + L * 8);
        const uint32_t tmx = L < 3 ? tm : 0u, xt = x_tag(ep1, L + 1);
        const int grow = ch * 1024 + rt * 64;
#pragma unroll
        for (int jp = 0; jp < 8; jp++) {
#pragma unroll
          for (int q = 0; q < 4; q++) xv[jp][q] = add_bf16x2(xv[jp][q], pack_bf16x2(acc[8 * jp + 2 * q], acc[8 * jp + 2 * q + 1]));
          const bool tg = (jp & 3) == 0;
          stmatrix_x4((xrow ^ ((jp & 3) << 5)) + (jp >> 2) * UNIT,
                      tg ? set_tag(xv[jp][0], tmx, xt) : xv[jp][0], tg ? set_tag(xv[jp][1], tmx, xt) : xv[jp][1], xv[jp][2], xv[jp][3]);
          if ((jp & 3) == 3) {
            fence_proxy_async_smem();
            if (wwarp == jp >> 2) {
              named_bar_sync(8 + 2 * ch + (jp >> 2), 128);
              if (elect_one()) {
                tma_store_2d(&P.x[L + 1], xb + (jp >> 2) * UNIT, ct * 128 + (jp >> 2) * 64, grow);
                if (L < 3) bulk_announce(g_fx[ch * 8 + (rt >> 1)][ct * 2 + (jp >> 2)]);
                bulk_commit();
              }
              __syncwarp();
            } else {
              named_bar_arrive(8 + 2 * ch + (jp >> 2), 128);
            }
            if (L == 2 && jp == 3) GTL(36);
          }
        }
        if (elect_one()) {
          bulk_wait_read0();
          mbar_arrive(bars + 8u * (B_RF + B_E));
        }
        __syncwarp();
        if (L < 3) {
          if (c == 0)
            asm volatile("st.shared.u8 [%0], %1;" ::"r"(lsa),
                         "r"((xv[0][0] & 1u) | ((xv[0][1] & 1u) << 1) | ((xv[4][0] & 1u) << 2) | ((xv[4][1] & 1u) << 3)) : "memory");
          float s1[2] = {0.f, 0.f}, s2[2] = {0.f, 0.f};
#pragma unroll
          for (int jp = 0; jp < 8; jp++)
#pragma unroll
            for (int q = 0; q < 4; q++) {
              const float x0 = bf_lo(xv[jp][q]), x1 = bf_hi(xv[jp][q]);
              s1[q & 1] += x0 + x1;
              s2[q & 1] = fmaf(x0, x0, fmaf(x1, x1, s2[q & 1]));
            }
#pragma unroll
          for (int r = 0; r < 2; r++) {
            s1[r] += __shfl_xor_sync(0xffffffffu, s1[r], 1);
            s2[r] += __shfl_xor_sync(0xffffffffu, s2[r], 1);
            s1[r] += __shfl_xor_sync(0xffffffffu, s1[r], 2);
            s2[r] += __shfl_xor_sync(0xffffffffu, s2[r], 2);
            if (c == 0) st_rec(&g_stats[L + 1][ct][grow + wwarp * 16 + g + 8 * r], s1[r], s2[r], 0.f, ep1);
          }
        }
        GTL(8 + L * 8);
      }
    }
    if (threadIdx.x == 128) atomicAdd(g_done, 1u);
  }
}

typedef CUresult (*PFN_tmEncode)(CUtensorMap*, CUtensorMapDataType, cuuint32_t, void*, const cuuint64_t*,
                                 const cuuint64_t*, const cuuint32_t*, const cuuint32_t*, CUtensorMapInterleave,
                                 CUtensorMapSwizzle, CUtensorMapL2promotion, CUtensorMapFloatOOBfill);

PFN_tmEncode get_encode_fn() {
  static PFN_tmEncode fn = nullptr;
  if (!fn) {
    cudaDriverEntryPointQueryResult qr;
    void* p = nullptr;
    cudaGetDriverEntryPoint("cuTensorMapEncodeTiled", &p, cudaEnableDefault, &qr);
    fn = (PFN_tmEncode)p;
  }
  return fn;
}

CUtensorMap make_map(const void* ptr, int rows, int cols) {
  CUtensorMap m;
  cuuint64_t gdim[2] = {(cuuint64_t)cols, (cuuint64_t)rows};
  cuuint64_t gstr[1] = {(cuuint64_t)cols * 2};
  cuuint32_t box[2] = {64, 64};
  cuuint32_t estr[2] = {1, 1};
  get_encode_fn()(&m, CU_TENSOR_MAP_DATA_TYPE_BFLOAT16, 2, const_cast<void*>(ptr), gdim, gstr, box, estr,
                  CU_TENSOR_MAP_INTERLEAVE_NONE, CU_TENSOR_MAP_SWIZZLE_128B, CU_TENSOR_MAP_L2_PROMOTION_L2_128B,
                  CU_TENSOR_MAP_FLOAT_OOB_FILL_NONE);
  return m;
}

CUtensorMap make_map3(const void* ptr, int rows, int cols, int n, int step) {
  CUtensorMap m;
  cuuint64_t gdim[3] = {(cuuint64_t)(cols - (n - 1) * step), (cuuint64_t)rows, (cuuint64_t)n};
  cuuint64_t gstr[2] = {(cuuint64_t)cols * 2, (cuuint64_t)step * 2};
  cuuint32_t box[3] = {64, 64, (cuuint32_t)n};
  cuuint32_t estr[3] = {1, 1, 1};
  get_encode_fn()(&m, CU_TENSOR_MAP_DATA_TYPE_BFLOAT16, 3, const_cast<void*>(ptr), gdim, gstr, box, estr,
                  CU_TENSOR_MAP_INTERLEAVE_NONE, CU_TENSOR_MAP_SWIZZLE_128B, CU_TENSOR_MAP_L2_PROMOTION_L2_128B,
                  CU_TENSOR_MAP_FLOAT_OOB_FILL_NONE);
  return m;
}

CUtensorMap make_map_q(const void* ptr, int sw, int sr) {
  CUtensorMap m;
  cuuint64_t gdim[5] = {DM, 8, 2, 4, S_LEN / 64};
  cuuint64_t gstr[4] = {DM * 2, (cuuint64_t)sr * DM * 2, (cuuint64_t)sw * DM * 2, 64 * DM * 2};
  cuuint32_t box[5] = {64, 8, 2, 4, 2};
  cuuint32_t estr[5] = {1, 1, 1, 1, 1};
  get_encode_fn()(&m, CU_TENSOR_MAP_DATA_TYPE_BFLOAT16, 5, const_cast<void*>(ptr), gdim, gstr, box, estr,
                  CU_TENSOR_MAP_INTERLEAVE_NONE, CU_TENSOR_MAP_SWIZZLE_128B, CU_TENSOR_MAP_L2_PROMOTION_L2_128B,
                  CU_TENSOR_MAP_FLOAT_OOB_FILL_NONE);
  return m;
}

}

extern "C" void kernel_launch(void* const* d_in, const int* in_sizes, int n_in, void* d_out, int out_size) {
  (void)in_sizes; (void)n_in; (void)out_size;
  void *p_o, *p_x;
  cudaGetSymbolAddress(&p_o, g_o);
  cudaGetSymbolAddress(&p_x, g_x);
  static bool attr_done = false;
  if (!attr_done) {
    cudaFuncSetAttribute(fused_kernel, cudaFuncAttributeMaxDynamicSharedMemorySize, SMEM_BYTES);
    attr_done = true;
  }
  Params P;
  P.in_x = (const __nv_bfloat16*)d_in[0];
  P.wqkv_p[0] = (const __nv_bfloat16*)d_in[1];
  P.wo_p[0] = (const __nv_bfloat16*)d_in[2];
  P.wqkv_p[1] = (const __nv_bfloat16*)d_in[4];
  P.wo_p[1] = (const __nv_bfloat16*)d_in[5];
  P.out = (__nv_bfloat16*)d_out;
  P.zero = 0;
  for (int L = 0; L < 5; L++) {
    const void* px = L == 0 ? (const void*)P.in_x : (L == 4 ? d_out : p_x);
    P.x[L] = make_map(px, S_LEN, DM);
    if (L < 4) P.xq[L] = (L & 1) ? make_map_q(px, 16, 8) : make_map_q(px, 8, 32);
  }
  P.o = make_map(p_o, S_LEN, DM);
  for (int t = 0; t < 2; t++) {
    P.wqkv[t] = make_map(P.wqkv_p[t], DM, NQKV);
    P.wqkv3[t] = make_map3(P.wqkv_p[t], DM, NQKV, 3, 1024);
    P.wo3[t] = make_map3(P.wo_p[t], DM, DM, 2, 64);
  }
  fused_kernel<<<NCTA, 512, SMEM_BYTES>>>(P);
}
```

```cpp
#include <cuda_runtime.h>
#include <cuda_bf16.h>
#include <cuda.h>
#include <stdint.h>

namespace {

constexpr int S_LEN = 2048;
constexpr int DM = 1024;
constexpr int NQKV = 3072;
constexpr int NCTA = 128;

__device__ __align__(1024) uint8_t g_kvA[2][16][16][2][16384];
__device__ __align__(1024) uint8_t g_kvB[2][16][16][4096];
__device__ __align__(1024) uint8_t g_zero[16384];
__device__ __align__(1024) __nv_bfloat16 g_o[S_LEN * DM];
__device__ __align__(1024) __nv_bfloat16 g_x[S_LEN * DM];
__device__ __align__(1024) float4 g_stats[4][8][S_LEN];
__device__ __align__(1024) float4 g_cs[2][16][8][64];
__device__ __align__(128) unsigned g_fx[16][16][4];
__device__ __align__(128) unsigned g_fo[32][16][4];
__device__ __align__(128) unsigned g_fk[16][16][4];
__device__ __align__(128) unsigned g_done[32];

constexpr uint32_t SBASE = 1024;
constexpr int UNIT = 8192;
constexpr int NUNITS = 20;
constexpr int OFF_SLOT = NUNITS * UNIT;
constexpr int OFF_BAR = OFF_SLOT + 4 * 16384;
constexpr int OFF_EPOCH = OFF_BAR + 424;
constexpr int OFF_LSB = OFF_BAR + 432;
constexpr int OFF_CS = OFF_BAR + 496;
constexpr int OFF_RS = OFF_CS + 1536;
constexpr int OFF_ONE = OFF_RS + 1024;
constexpr int SMEM_BYTES = OFF_ONE + 16;
constexpr int B_QF = 0, B_WF = 4, B_RF = 12, B_E = 13, B_PREP = 26, B_LOC = 28, B_HALO = 29, B_REL = 33, B_OS0 = 36,
              B_TURN = 37, B_XS = 39, B_CS = 41, B_CSD = 42, B_GO = 43, B_PRE = 44, B_HV = 45, B_REDO = 46,
              B_RDONE = 48, B_PRE2 = 49, B_HL = 50, B_KV = 52, B_OS1 = B_GO;
static_assert(SMEM_BYTES <= 232448, "shared memory");

__device__ __forceinline__ uint32_t smem_u32(const void* p) { return (uint32_t)__cvta_generic_to_shared(p); }

__device__ __forceinline__ void mbar_init(uint32_t bar, uint32_t cnt) {
  asm volatile("mbarrier.init.shared::cta.b64 [%0], %1;" ::"r"(bar), "r"(cnt));
}
__device__ __forceinline__ void mbar_expect_tx(uint32_t bar, uint32_t bytes) {
  asm volatile("mbarrier.arrive.expect_tx.shared::cta.b64 _, [%0], %1;" ::"r"(bar), "r"(bytes) : "memory");
}
__device__ __forceinline__ void mbar_arrive(uint32_t bar) {
  asm volatile("mbarrier.arrive.shared::cta.b64 _, [%0];" ::"r"(bar) : "memory");
}
__device__ __forceinline__ bool mbar_try_wait(uint32_t bar, uint32_t parity) {
  uint32_t ok;
  asm volatile(
      "{\n.reg .pred p;\nmbarrier.try_wait.parity.shared::cta.b64 p, [%1], %2;\nselp.b32 %0, 1, 0, p;\n}\n"
      : "=r"(ok)
      : "r"(bar), "r"(parity)
      : "memory");
  return ok != 0;
}
__device__ __forceinline__ bool mbar_test(uint32_t bar, uint32_t parity) {
  uint32_t ok;
  asm volatile(
      "{\n.reg .pred p;\nmbarrier.test_wait.parity.shared::cta.b64 p, [%1], %2;\nselp.b32 %0, 1, 0, p;\n}\n"
      : "=r"(ok)
      : "r"(bar), "r"(parity)
      : "memory");
  return ok != 0;
}
__device__ __forceinline__ void mbar_wait(uint32_t bar, uint32_t parity) {
#pragma unroll 1
  for (uint32_t it = 0; it < (1u << 18); ++it) {
    if (mbar_try_wait(bar, parity)) return;
  }
}
__device__ __forceinline__ void mbar_pace(uint32_t bar, uint32_t parity) {
#pragma unroll 1
  for (uint32_t it = 0; it < 24; ++it) {
    if (mbar_try_wait(bar, parity)) return;
  }
}
template <int NS>
__device__ __forceinline__ void mbar_wait_lazy(uint32_t bar, uint32_t parity) {
#pragma unroll 1
  for (uint32_t it = 0; it < (1u << 18); ++it) {
    if (mbar_try_wait(bar, parity)) return;
    __nanosleep(NS);
  }
}
__device__ __forceinline__ bool elect_one() {
  uint32_t ok;
  asm volatile("{\n.reg .pred p;\nelect.sync _|p, 0xffffffff;\nselp.b32 %0, 1, 0, p;\n}\n" : "=r"(ok));
  return ok != 0;
}
__device__ __forceinline__ void fence_barrier_init() { asm volatile("fence.mbarrier_init.release.cluster;" ::: "memory"); }
__device__ __forceinline__ void fence_proxy_async_smem() { asm volatile("fence.proxy.async.shared::cta;" ::: "memory"); }

__device__ __forceinline__ void signal_async(uint32_t bar, bool lane0) {
  fence_proxy_async_smem();
  __syncwarp();
  asm volatile("{\n.reg .pred p;\nsetp.ne.b32 p, %1, 0;\n@p mbarrier.arrive.shared::cta.b64 _, [%0];\n}\n" ::"r"(bar), "r"((int)lane0) : "memory");
}
template <class T>
__device__ __forceinline__ void pin64(T*& p) { asm volatile("" : "+l"(p)); }

__device__ __forceinline__ void tma_load_2d(uint32_t dst, const CUtensorMap* map, uint32_t bar, int c0, int c1) {
  asm volatile(
      "cp.async.bulk.tensor.2d.shared::cluster.global.mbarrier::complete_tx::bytes [%0], [%1, {%3, %4}], [%2];" ::"r"(dst),
      "l"(map), "r"(bar), "r"(c0), "r"(c1)
      : "memory");
}
__device__ __forceinline__ void tma_load_3d(uint32_t dst, const CUtensorMap* map, uint32_t bar, int c0, int c1) {
  asm volatile(
      "cp.async.bulk.tensor.3d.shared::cluster.global.mbarrier::complete_tx::bytes [%0], [%1, {%3, %4, %5}], [%2];" ::"r"(dst),
      "l"(map), "r"(bar), "r"(c0), "r"(c1), "r"(0)
      : "memory");
}
__device__ __forceinline__ void tma_load_5d(uint32_t dst, const CUtensorMap* map, uint32_t bar, int c0, int c4) {
  asm volatile(
      "cp.async.bulk.tensor.5d.shared::cluster.global.mbarrier::complete_tx::bytes [%0], [%1, {%3, %5, %5, %5, %4}], [%2];" ::"r"(dst),
      "l"(map), "r"(bar), "r"(c0), "r"(c4), "r"(0)
      : "memory");
}
__device__ __forceinline__ void bulk_load(uint32_t dst, const void* src, uint32_t bytes, uint32_t bar) {
  asm volatile("cp.async.bulk.shared::cluster.global.mbarrier::complete_tx::bytes [%0], [%1], %2, [%3];" ::"r"(dst),
               "l"(src), "r"(bytes), "r"(bar)
               : "memory");
}
__device__ __forceinline__ void bulk_store(void* dst, uint32_t src, uint32_t bytes) {
  asm volatile("cp.async.bulk.global.shared::cta.bulk_group [%0], [%1], %2;" ::"l"(dst), "r"(src), "r"(bytes) : "memory");
}
__device__ __forceinline__ void tma_store_2d(const CUtensorMap* map, uint32_t src, int c0, int c1) {
  asm volatile("cp.async.bulk.tensor.2d.global.shared::cta.bulk_group [%0, {%2, %3}], [%1];" ::"l"(map), "r"(src),
               "r"(c0), "r"(c1)
               : "memory");
}
__device__ __forceinline__ void bulk_announce(unsigned* p) {
  asm volatile("cp.reduce.async.bulk.global.shared::cta.bulk_group.add.u32 [%0], [%1], 16;" ::"l"(p), "r"(SBASE + OFF_ONE) : "memory");
}
__device__ __forceinline__ void bulk_commit() { asm volatile("cp.async.bulk.commit_group;" ::: "memory"); }
__device__ __forceinline__ void bulk_wait_read0() { asm volatile("cp.async.bulk.wait_group.read 0;" ::: "memory"); }
__device__ __forceinline__ void bulk_wait0() { asm volatile("cp.async.bulk.wait_group 0;" ::: "memory"); }
__device__ __forceinline__ void named_bar_sync(int id, int nthreads) {
  asm volatile("bar.sync %0, %1;" ::"r"(id), "r"(nthreads) : "memory");
}
__device__ __forceinline__ void named_bar_arrive(int id, int nthreads) {
  asm volatile("bar.arrive %0, %1;" ::"r"(id), "r"(nthreads) : "memory");
}

__device__ __forceinline__ bool named_bar_or(int id, int nthreads, bool v) {
  uint32_t r;
  asm volatile("{\n.reg .pred p, q;\nsetp.ne.b32 q, %3, 0;\nbar.red.or.pred p, %1, %2, q;\nselp.b32 %0, 1, 0, p;\n}\n"
               : "=r"(r) : "r"(id), "r"(nthreads), "r"((int)v) : "memory");
  return __any_sync(0xffffffffu, r != 0);
}

__device__ __forceinline__ void wgmma_fence() { asm volatile("wgmma.fence.sync.aligned;\n" ::: "memory"); }
__device__ __forceinline__ void wgmma_commit() { asm volatile("wgmma.commit_group.sync.aligned;\n" ::: "memory"); }
template <int N>
__device__ __forceinline__ void wgmma_wait() {
  asm volatile("wgmma.wait_group.sync.aligned %0;\n" ::"n"(N) : "memory");
}
template <int R>
__device__ __forceinline__ void setmaxnreg_inc() { asm volatile("setmaxnreg.inc.sync.aligned.u32 %0;\n" ::"n"(R)); }
template <int R>
__device__ __forceinline__ void setmaxnreg_dec() { asm volatile("setmaxnreg.dec.sync.aligned.u32 %0;\n" ::"n"(R)); }
template <int N>
__device__ __forceinline__ void reg_fence(float* r) {
#pragma unroll
  for (int i = 0; i < N; i++) asm volatile("" : "+f"(r[i])::"memory");
}

template <int N>
__device__ __forceinline__ void reg_define(float* r) {
#pragma unroll
  for (int i = 0; i < N; i++) r[i] = 0.f;
}

__device__ __forceinline__ uint64_t desc_lo(uint32_t lo) {
  uint64_t d;
  asm("mov.b64 %0, {%1, %2};" : "=l"(d) : "r"(lo), "r"(0x40000040u));
  return d;
}
__device__ __forceinline__ uint64_t make_desc(uint32_t addr, uint32_t lbo_bytes) {
  return desc_lo((addr >> 4) + ((lbo_bytes >> 4) << 16));
}

__device__ __forceinline__ void wgmma_n192_ss_ta0_tb1(float* d, uint64_t descA, uint64_t descB, int scaleD) {
  asm volatile("{\n.reg .pred p;\nsetp.ne.b32 p, %98, 0;\n"
    "wgmma.mma_async.sync.aligned.m64n192k16.f32.bf16.bf16 {%0, %1, %2, %3, %4, %5, %6, %7, %8, %9, %10, %11, %12, %13, %14, %15, %16, %17, %18, %19, %20, %21, %22, %23, %24, %25, %26, %27, %28, %29, %30, %31, %32, %33, %34, %35, %36, %37, %38, %39, %40, %41, %42, %43, %44, %45, %46, %47, %48, %49, %50, %51, %52, %53, %54, %55, %56, %57, %58, %59, %60, %61, %62, %63, %64, %65, %66, %67, %68, %69, %70, %71, %72, %73, %74, %75, %76, %77, %78, %79, %80, %81, %82, %83, %84, %85, %86, %87, %88, %89, %90, %91, %92, %93, %94, %95}, %96, %97, p, 1, 1, 0, 1;\n}\n"
    : "+f"(d[0]), "+f"(d[1]), "+f"(d[2]), "+f"(d[3]), "+f"(d[4]), "+f"(d[5]), "+f"(d[6]), "+f"(d[7]), "+f"(d[8]), "+f"(d[9]), "+f"(d[10]), "+f"(d[11]), "+f"(d[12]), "+f"(d[13]), "+f"(d[14]), "+f"(d[15]), "+f"(d[16]), "+f"(d[17]), "+f"(d[18]), "+f"(d[19]), "+f"(d[20]), "+f"(d[21]), "+f"(d[22]), "+f"(d[23]), "+f"(d[24]), "+f"(d[25]), "+f"(d[26]), "+f"(d[27]), "+f"(d[28]), "+f"(d[29]), "+f"(d[30]), "+f"(d[31]), "+f"(d[32]), "+f"(d[33]), "+f"(d[34]), "+f"(d[35]), "+f"(d[36]), "+f"(d[37]), "+f"(d[38]), "+f"(d[39]), "+f"(d[40]), "+f"(d[41]), "+f"(d[42]), "+f"(d[43]), "+f"(d[44]), "+f"(d[45]), "+f"(d[46]), "+f"(d[47]), "+f"(d[48]), "+f"(d[49]), "+f"(d[50]), "+f"(d[51]), "+f"(d[52]), "+f"(d[53]), "+f"(d[54]), "+f"(d[55]), "+f"(d[56]), "+f"(d[57]), "+f"(d[58]), "+f"(d[59]), "+f"(d[60]), "+f"(d[61]), "+f"(d[62]), "+f"(d[63]), "+f"(d[64]), "+f"(d[65]), "+f"(d[66]), "+f"(d[67]), "+f"(d[68]), "+f"(d[69]), "+f"(d[70]), "+f"(d[71]), "+f"(d[72]), "+f"(d[73]), "+f"(d[74]), "+f"(d[75]), "+f"(d[76]), "+f"(d[77]), "+f"(d[78]), "+f"(d[79]), "+f"(d[80]), "+f"(d[81]), "+f"(d[82]), "+f"(d[83]), "+f"(d[84]), "+f"(d[85]), "+f"(d[86]), "+f"(d[87]), "+f"(d[88]), "+f"(d[89]), "+f"(d[90]), "+f"(d[91]), "+f"(d[92]), "+f"(d[93]), "+f"(d[94]), "+f"(d[95])
    : "l"(descA), "l"(descB), "r"(scaleD));
}

__device__ __forceinline__ void wgmma_n128_ss_ta0_tb1(float* d, uint64_t descA, uint64_t descB, int scaleD) {
  asm volatile("{\n.reg .pred p;\nsetp.ne.b32 p, %66, 0;\n"
    "wgmma.mma_async.sync.aligned.m64n128k16.f32.bf16.bf16 {%0, %1, %2, %3, %4, %5, %6, %7, %8, %9, %10, %11, %12, %13, %14, %15, %16, %17, %18, %19, %20, %21, %22, %23, %24, %25, %26, %27, %28, %29, %30, %31, %32, %33, %34, %35, %36, %37, %38, %39, %40, %41, %42, %43, %44, %45, %46, %47, %48, %49, %50, %51, %52, %53, %54, %55, %56, %57, %58, %59, %60, %61, %62, %63}, %64, %65, p, 1, 1, 0, 1;\n}\n"
    : "+f"(d[0]), "+f"(d[1]), "+f"(d[2]), "+f"(d[3]), "+f"(d[4]), "+f"(d[5]), "+f"(d[6]), "+f"(d[7]), "+f"(d[8]), "+f"(d[9]), "+f"(d[10]), "+f"(d[11]), "+f"(d[12]), "+f"(d[13]), "+f"(d[14]), "+f"(d[15]), "+f"(d[16]), "+f"(d[17]), "+f"(d[18]), "+f"(d[19]), "+f"(d[20]), "+f"(d[21]), "+f"(d[22]), "+f"(d[23]), "+f"(d[24]), "+f"(d[25]), "+f"(d[26]), "+f"(d[27]), "+f"(d[28]), "+f"(d[29]), "+f"(d[30]), "+f"(d[31]), "+f"(d[32]), "+f"(d[33]), "+f"(d[34]), "+f"(d[35]), "+f"(d[36]), "+f"(d[37]), "+f"(d[38]), "+f"(d[39]), "+f"(d[40]), "+f"(d[41]), "+f"(d[42]), "+f"(d[43]), "+f"(d[44]), "+f"(d[45]), "+f"(d[46]), "+f"(d[47]), "+f"(d[48]), "+f"(d[49]), "+f"(d[50]), "+f"(d[51]), "+f"(d[52]), "+f"(d[53]), "+f"(d[54]), "+f"(d[55]), "+f"(d[56]), "+f"(d[57]), "+f"(d[58]), "+f"(d[59]), "+f"(d[60]), "+f"(d[61]), "+f"(d[62]), "+f"(d[63])
    : "l"(descA), "l"(descB), "r"(scaleD));
}

__device__ __forceinline__ void wgmma_n192_ssz_ta0_tb1(float* d, uint64_t descA, uint64_t descB) {
  asm volatile("{\n.reg .pred p;\nsetp.ne.b32 p, 0, 0;\n"
    "wgmma.mma_async.sync.aligned.m64n192k16.f32.bf16.bf16 {%0, %1, %2, %3, %4, %5, %6, %7, %8, %9, %10, %11, %12, %13, %14, %15, %16, %17, %18, %19, %20, %21, %22, %23, %24, %25, %26, %27, %28, %29, %30, %31, %32, %33, %34, %35, %36, %37, %38, %39, %40, %41, %42, %43, %44, %45, %46, %47, %48, %49, %50, %51, %52, %53, %54, %55, %56, %57, %58, %59, %60, %61, %62, %63, %64, %65, %66, %67, %68, %69, %70, %71, %72, %73, %74, %75, %76, %77, %78, %79, %80, %81, %82, %83, %84, %85, %86, %87, %88, %89, %90, %91, %92, %93, %94, %95}, %96, %97, p, 1, 1, 0, 1;\n}\n"
    : "=f"(d[0]), "=f"(d[1]), "=f"(d[2]), "=f"(d[3]), "=f"(d[4]), "=f"(d[5]), "=f"(d[6]), "=f"(d[7]), "=f"(d[8]), "=f"(d[9]), "=f"(d[10]), "=f"(d[11]), "=f"(d[12]), "=f"(d[13]), "=f"(d[14]), "=f"(d[15]), "=f"(d[16]), "=f"(d[17]), "=f"(d[18]), "=f"(d[19]), "=f"(d[20]), "=f"(d[21]), "=f"(d[22]), "=f"(d[23]), "=f"(d[24]), "=f"(d[25]), "=f"(d[26]), "=f"(d[27]), "=f"(d[28]), "=f"(d[29]), "=f"(d[30]), "=f"(d[31]), "=f"(d[32]), "=f"(d[33]), "=f"(d[34]), "=f"(d[35]), "=f"(d[36]), "=f"(d[37]), "=f"(d[38]), "=f"(d[39]), "=f"(d[40]), "=f"(d[41]), "=f"(d[42]), "=f"(d[43]), "=f"(d[44]), "=f"(d[45]), "=f"(d[46]), "=f"(d[47]), "=f"(d[48]), "=f"(d[49]), "=f"(d[50]), "=f"(d[51]), "=f"(d[52]), "=f"(d[53]), "=f"(d[54]), "=f"(d[55]), "=f"(d[56]), "=f"(d[57]), "=f"(d[58]), "=f"(d[59]), "=f"(d[60]), "=f"(d[61]), "=f"(d[62]), "=f"(d[63]), "=f"(d[64]), "=f"(d[65]), "=f"(d[66]), "=f"(d[67]), "=f"(d[68]), "=f"(d[69]), "=f"(d[70]), "=f"(d[71]), "=f"(d[72]), "=f"(d[73]), "=f"(d[74]), "=f"(d[75]), "=f"(d[76]), "=f"(d[77]), "=f"(d[78]), "=f"(d[79]), "=f"(d[80]), "=f"(d[81]), "=f"(d[82]), "=f"(d[83]), "=f"(d[84]), "=f"(d[85]), "=f"(d[86]), "=f"(d[87]), "=f"(d[88]), "=f"(d[89]), "=f"(d[90]), "=f"(d[91]), "=f"(d[92]), "=f"(d[93]), "=f"(d[94]), "=f"(d[95])
    : "l"(descA), "l"(descB));
}

__device__ __forceinline__ void wgmma_n8_ss_ta1_tb0(float* d, uint64_t descA, uint64_t descB, int scaleD) {
  asm volatile("{\n.reg .pred p;\nsetp.ne.b32 p, %6, 0;\n"
    "wgmma.mma_async.sync.aligned.m64n8k16.f32.bf16.bf16 {%0, %1, %2, %3}, %4, %5, p, 1, 1, 1, 0;\n}\n"
    : "+f"(d[0]), "+f"(d[1]), "+f"(d[2]), "+f"(d[3])
    : "l"(descA), "l"(descB), "r"(scaleD));
}

__device__ __forceinline__ void wgmma_n8_ssz_ta1_tb0(float* d, uint64_t descA, uint64_t descB) {
  asm volatile("{\n.reg .pred p;\nsetp.ne.b32 p, 0, 0;\n"
    "wgmma.mma_async.sync.aligned.m64n8k16.f32.bf16.bf16 {%0, %1, %2, %3}, %4, %5, p, 1, 1, 1, 0;\n}\n"
    : "=f"(d[0]), "=f"(d[1]), "=f"(d[2]), "=f"(d[3])
    : "l"(descA), "l"(descB));
}

__device__ __forceinline__ void wgmma_n192_rs_tb1(float* d, const uint32_t* a, uint64_t descB, int scaleD) {
  asm volatile("{\n.reg .pred p;\nsetp.ne.b32 p, %101, 0;\n"
    "wgmma.mma_async.sync.aligned.m64n192k16.f32.bf16.bf16 {%0, %1, %2, %3, %4, %5, %6, %7, %8, %9, %10, %11, %12, %13, %14, %15, %16, %17, %18, %19, %20, %21, %22, %23, %24, %25, %26, %27, %28, %29, %30, %31, %32, %33, %34, %35, %36, %37, %38, %39, %40, %41, %42, %43, %44, %45, %46, %47, %48, %49, %50, %51, %52, %53, %54, %55, %56, %57, %58, %59, %60, %61, %62, %63, %64, %65, %66, %67, %68, %69, %70, %71, %72, %73, %74, %75, %76, %77, %78, %79, %80, %81, %82, %83, %84, %85, %86, %87, %88, %89, %90, %91, %92, %93, %94, %95}, {%96, %97, %98, %99}, %100, p, 1, 1, 1;\n}\n"
    : "+f"(d[0]), "+f"(d[1]), "+f"(d[2]), "+f"(d[3]), "+f"(d[4]), "+f"(d[5]), "+f"(d[6]), "+f"(d[7]), "+f"(d[8]), "+f"(d[9]), "+f"(d[10]), "+f"(d[11]), "+f"(d[12]), "+f"(d[13]), "+f"(d[14]), "+f"(d[15]), "+f"(d[16]), "+f"(d[17]), "+f"(d[18]), "+f"(d[19]), "+f"(d[20]), "+f"(d[21]), "+f"(d[22]), "+f"(d[23]), "+f"(d[24]), "+f"(d[25]), "+f"(d[26]), "+f"(d[27]), "+f"(d[28]), "+f"(d[29]), "+f"(d[30]), "+f"(d[31]), "+f"(d[32]), "+f"(d[33]), "+f"(d[34]), "+f"(d[35]), "+f"(d[36]), "+f"(d[37]), "+f"(d[38]), "+f"(d[39]), "+f"(d[40]), "+f"(d[41]), "+f"(d[42]), "+f"(d[43]), "+f"(d[44]), "+f"(d[45]), "+f"(d[46]), "+f"(d[47]), "+f"(d[48]), "+f"(d[49]), "+f"(d[50]), "+f"(d[51]), "+f"(d[52]), "+f"(d[53]), "+f"(d[54]), "+f"(d[55]), "+f"(d[56]), "+f"(d[57]), "+f"(d[58]), "+f"(d[59]), "+f"(d[60]), "+f"(d[61]), "+f"(d[62]), "+f"(d[63]), "+f"(d[64]), "+f"(d[65]), "+f"(d[66]), "+f"(d[67]), "+f"(d[68]), "+f"(d[69]), "+f"(d[70]), "+f"(d[71]), "+f"(d[72]), "+f"(d[73]), "+f"(d[74]), "+f"(d[75]), "+f"(d[76]), "+f"(d[77]), "+f"(d[78]), "+f"(d[79]), "+f"(d[80]), "+f"(d[81]), "+f"(d[82]), "+f"(d[83]), "+f"(d[84]), "+f"(d[85]), "+f"(d[86]), "+f"(d[87]), "+f"(d[88]), "+f"(d[89]), "+f"(d[90]), "+f"(d[91]), "+f"(d[92]), "+f"(d[93]), "+f"(d[94]), "+f"(d[95])
    : "r"(a[0]), "r"(a[1]), "r"(a[2]), "r"(a[3]), "l"(descB), "r"(scaleD));
}

__device__ __forceinline__ void wgmma_n80_rs_tb0(float* d, const uint32_t* a, uint64_t descB, int scaleD) {
  asm volatile("{\n.reg .pred p;\nsetp.ne.b32 p, %45, 0;\n"
    "wgmma.mma_async.sync.aligned.m64n80k16.f32.bf16.bf16 {%0, %1, %2, %3, %4, %5, %6, %7, %8, %9, %10, %11, %12, %13, %14, %15, %16, %17, %18, %19, %20, %21, %22, %23, %24, %25, %26, %27, %28, %29, %30, %31, %32, %33, %34, %35, %36, %37, %38, %39}, {%40, %41, %42, %43}, %44, p, 1, 1, 0;\n}\n"
    : "+f"(d[0]), "+f"(d[1]), "+f"(d[2]), "+f"(d[3]), "+f"(d[4]), "+f"(d[5]), "+f"(d[6]), "+f"(d[7]), "+f"(d[8]), "+f"(d[9]), "+f"(d[10]), "+f"(d[11]), "+f"(d[12]), "+f"(d[13]), "+f"(d[14]), "+f"(d[15]), "+f"(d[16]), "+f"(d[17]), "+f"(d[18]), "+f"(d[19]), "+f"(d[20]), "+f"(d[21]), "+f"(d[22]), "+f"(d[23]), "+f"(d[24]), "+f"(d[25]), "+f"(d[26]), "+f"(d[27]), "+f"(d[28]), "+f"(d[29]), "+f"(d[30]), "+f"(d[31]), "+f"(d[32]), "+f"(d[33]), "+f"(d[34]), "+f"(d[35]), "+f"(d[36]), "+f"(d[37]), "+f"(d[38]), "+f"(d[39])
    : "r"(a[0]), "r"(a[1]), "r"(a[2]), "r"(a[3]), "l"(descB), "r"(scaleD));
}

__device__ __forceinline__ void wgmma_n80_rsz_tb0(float* d, const uint32_t* a, uint64_t descB) {
  asm volatile("{\n.reg .pred p;\nsetp.ne.b32 p, 0, 0;\n"
    "wgmma.mma_async.sync.aligned.m64n80k16.f32.bf16.bf16 {%0, %1, %2, %3, %4, %5, %6, %7, %8, %9, %10, %11, %12, %13, %14, %15, %16, %17, %18, %19, %20, %21, %22, %23, %24, %25, %26, %27, %28, %29, %30, %31, %32, %33, %34, %35, %36, %37, %38, %39}, {%40, %41, %42, %43}, %44, p, 1, 1, 0;\n}\n"
    : "=f"(d[0]), "=f"(d[1]), "=f"(d[2]), "=f"(d[3]), "=f"(d[4]), "=f"(d[5]), "=f"(d[6]), "=f"(d[7]), "=f"(d[8]), "=f"(d[9]), "=f"(d[10]), "=f"(d[11]), "=f"(d[12]), "=f"(d[13]), "=f"(d[14]), "=f"(d[15]), "=f"(d[16]), "=f"(d[17]), "=f"(d[18]), "=f"(d[19]), "=f"(d[20]), "=f"(d[21]), "=f"(d[22]), "=f"(d[23]), "=f"(d[24]), "=f"(d[25]), "=f"(d[26]), "=f"(d[27]), "=f"(d[28]), "=f"(d[29]), "=f"(d[30]), "=f"(d[31]), "=f"(d[32]), "=f"(d[33]), "=f"(d[34]), "=f"(d[35]), "=f"(d[36]), "=f"(d[37]), "=f"(d[38]), "=f"(d[39])
    : "r"(a[0]), "r"(a[1]), "r"(a[2]), "r"(a[3]), "l"(descB));
}

__device__ __forceinline__ void wgmma_n32_rs_tb1(float* d, const uint32_t* a, uint64_t descB, int scaleD) {
  asm volatile("{\n.reg .pred p;\nsetp.ne.b32 p, %21, 0;\n"
    "wgmma.mma_async.sync.aligned.m64n32k16.f32.bf16.bf16 {%0, %1, %2, %3, %4, %5, %6, %7, %8, %9, %10, %11, %12, %13, %14, %15}, {%16, %17, %18, %19}, %20, p, 1, 1, 1;\n}\n"
    : "+f"(d[0]), "+f"(d[1]), "+f"(d[2]), "+f"(d[3]), "+f"(d[4]), "+f"(d[5]), "+f"(d[6]), "+f"(d[7]), "+f"(d[8]), "+f"(d[9]), "+f"(d[10]), "+f"(d[11]), "+f"(d[12]), "+f"(d[13]), "+f"(d[14]), "+f"(d[15])
    : "r"(a[0]), "r"(a[1]), "r"(a[2]), "r"(a[3]), "l"(descB), "r"(scaleD));
}

__device__ __forceinline__ void wgmma_n32_rsz_tb1(float* d, const uint32_t* a, uint64_t descB) {
  asm volatile("{\n.reg .pred p;\nsetp.ne.b32 p, 0, 0;\n"
    "wgmma.mma_async.sync.aligned.m64n32k16.f32.bf16.bf16 {%0, %1, %2, %3, %4, %5, %6, %7, %8, %9, %10, %11, %12, %13, %14, %15}, {%16, %17, %18, %19}, %20, p, 1, 1, 1;\n}\n"
    : "=f"(d[0]), "=f"(d[1]), "=f"(d[2]), "=f"(d[3]), "=f"(d[4]), "=f"(d[5]), "=f"(d[6]), "=f"(d[7]), "=f"(d[8]), "=f"(d[9]), "=f"(d[10]), "=f"(d[11]), "=f"(d[12]), "=f"(d[13]), "=f"(d[14]), "=f"(d[15])
    : "r"(a[0]), "r"(a[1]), "r"(a[2]), "r"(a[3]), "l"(descB));
}

__device__ __forceinline__ void wgmma_n32_rs_tb0(float* d, const uint32_t* a, uint64_t descB, int scaleD) {
  asm volatile("{\n.reg .pred p;\nsetp.ne.b32 p, %21, 0;\n"
    "wgmma.mma_async.sync.aligned.m64n32k16.f32.bf16.bf16 {%0, %1, %2, %3, %4, %5, %6, %7, %8, %9, %10, %11, %12, %13, %14, %15}, {%16, %17, %18, %19}, %20, p, 1, 1, 0;\n}\n"
    : "+f"(d[0]), "+f"(d[1]), "+f"(d[2]), "+f"(d[3]), "+f"(d[4]), "+f"(d[5]), "+f"(d[6]), "+f"(d[7]), "+f"(d[8]), "+f"(d[9]), "+f"(d[10]), "+f"(d[11]), "+f"(d[12]), "+f"(d[13]), "+f"(d[14]), "+f"(d[15])
    : "r"(a[0]), "r"(a[1]), "r"(a[2]), "r"(a[3]), "l"(descB), "r"(scaleD));
}

__device__ __forceinline__ void wgmma_n32_rsz_tb0(float* d, const uint32_t* a, uint64_t descB) {
  asm volatile("{\n.reg .pred p;\nsetp.ne.b32 p, 0, 0;\n"
    "wgmma.mma_async.sync.aligned.m64n32k16.f32.bf16.bf16 {%0, %1, %2, %3, %4, %5, %6, %7, %8, %9, %10, %11, %12, %13, %14, %15}, {%16, %17, %18, %19}, %20, p, 1, 1, 0;\n}\n"
    : "=f"(d[0]), "=f"(d[1]), "=f"(d[2]), "=f"(d[3]), "=f"(d[4]), "=f"(d[5]), "=f"(d[6]), "=f"(d[7]), "=f"(d[8]), "=f"(d[9]), "=f"(d[10]), "=f"(d[11]), "=f"(d[12]), "=f"(d[13]), "=f"(d[14]), "=f"(d[15])
    : "r"(a[0]), "r"(a[1]), "r"(a[2]), "r"(a[3]), "l"(descB));
}

__device__ __forceinline__ uint32_t pack_bf16x2(float lo, float hi) {
  uint32_t r;
  asm("cvt.rn.bf16x2.f32 %0, %1, %2;" : "=r"(r) : "f"(hi), "f"(lo));
  return r;
}
__device__ __forceinline__ float bf_lo(uint32_t p) { return __uint_as_float(p << 16); }
__device__ __forceinline__ float bf_hi(uint32_t p) { return __uint_as_float(p & 0xffff0000u); }
__device__ __forceinline__ float bf16_round(float v) { return __bfloat162float(__float2bfloat16_rn(v)); }
__device__ __forceinline__ float ex2_approx(float x) {
  float r;
  asm("ex2.approx.ftz.f32 %0, %1;" : "=f"(r) : "f"(x));
  return r;
}
__device__ __forceinline__ float rcp_fast(float x) {
  float r;
  asm("rcp.approx.ftz.f32 %0, %1;" : "=f"(r) : "f"(x));
  return r;
}
__device__ __forceinline__ void ldmatrix_x4(uint32_t (&r)[4], uint32_t addr) {
  asm volatile("ldmatrix.sync.aligned.m8n8.x4.shared.b16 {%0,%1,%2,%3}, [%4];"
               : "=r"(r[0]), "=r"(r[1]), "=r"(r[2]), "=r"(r[3])
               : "r"(addr)
               : "memory");
}
__device__ __forceinline__ void stmatrix_x4(uint32_t addr, uint32_t r0, uint32_t r1, uint32_t r2, uint32_t r3) {
  asm volatile("stmatrix.sync.aligned.m8n8.x4.shared.b16 [%0], {%1,%2,%3,%4};" ::"r"(addr), "r"(r0), "r"(r1), "r"(r2),
               "r"(r3));
}
__device__ __forceinline__ uint32_t add_bf16x2(uint32_t a, uint32_t b) {
  uint32_t r;
  asm("add.rn.bf16x2 %0, %1, %2;" : "=r"(r) : "r"(a), "r"(b));
  return r;
}
__device__ __forceinline__ uint4 lds128(uint32_t addr) {
  uint4 v;
  asm volatile("ld.shared.v4.b32 {%0,%1,%2,%3}, [%4];" : "=r"(v.x), "=r"(v.y), "=r"(v.z), "=r"(v.w) : "r"(addr) : "memory");
  return v;
}
__device__ __forceinline__ uint32_t lds32(uint32_t addr) {
  uint32_t v;
  asm volatile("ld.shared.b32 %0, [%1];" : "=r"(v) : "r"(addr) : "memory");
  return v;
}
__device__ __forceinline__ void sts32(uint32_t addr, uint32_t v) {
  asm volatile("st.shared.b32 [%0], %1;" ::"r"(addr), "r"(v) : "memory");
}

__device__ __forceinline__ unsigned ld_relaxed_u32(const void* p) {
  unsigned v;
  asm volatile("ld.relaxed.gpu.global.u32 %0, [%1];" : "=r"(v) : "l"(p) : "memory");
  return v;
}
__device__ __forceinline__ unsigned launch_epoch() { return (*(volatile unsigned*)g_done) / NCTA + 1u; }
__device__ __forceinline__ uint32_t set_tag(uint32_t w, uint32_t m, uint32_t tag) { return (w & ~m) | (tag & m); }
__device__ __forceinline__ uint32_t o_tag(int L) { return (L + 1) & 1; }
__device__ __forceinline__ uint32_t x_tag(unsigned ep1, int L) { return (ep1 + L + 1) & 1; }

#define PIPEP 0
__device__ __forceinline__ void wait_count(const unsigned* f, unsigned target, int i, uint32_t& seen, int lane) {
  if ((seen >> i) & 1u) return;
  f += (lane & 15) * 4;
#pragma unroll 1
  for (uint32_t it = 0; it < (1u << 17); ++it) {
    seen = __ballot_sync(0xffffffffu, (int)(ld_relaxed_u32(f) - target) >= 0);
    if ((seen >> i) & 1u) break;
  }
}
__device__ __forceinline__ float4 ld_rec(const float4* p) {
  float4 v;
  asm volatile("ld.relaxed.gpu.global.v4.f32 {%0,%1,%2,%3}, [%4];" : "=f"(v.x), "=f"(v.y), "=f"(v.z), "=f"(v.w) : "l"(p) : "memory");
  return v;
}
__device__ __forceinline__ void st_rec(float4* p, float a, float b, float c, unsigned tag) {
  asm volatile("st.relaxed.gpu.global.v4.f32 [%0], {%1,%2,%3,%4};" ::"l"(p), "f"(a), "f"(b), "f"(c), "f"(__uint_as_float(tag)) : "memory");
}
template <int N>
__device__ __forceinline__ float4 sum_recs(const float4* p, int stride, unsigned tag) {
  float4 s;
#pragma unroll 1
  for (uint32_t it = 0; it < (1u << 17); ++it) {
    float4 v[N];
#pragma unroll
    for (int t = 0; t < N; t++) v[t] = ld_rec(p + t * stride);
    bool ok = true;
    s = make_float4(0.f, 0.f, 0.f, 0.f);
#pragma unroll
    for (int t = 0; t < N; t++) {
      ok &= __float_as_uint(v[t].w) == tag;
      s.x += v[t].x;
      s.y += v[t].y;
      s.z += v[t].z;
    }
    if (ok) break;
    __nanosleep(200);
  }
  return s;
}

__device__ __forceinline__ int fresh_tid() {
  int t;
  asm volatile("mov.u32 %0, %%tid.x;" : "=r"(t));
  return t;
}
#define PHASE_IDS                                  \
  const int tid_ = fresh_tid();                    \
  const int lane = tid_ & 31, wwarp = __shfl_sync(0xffffffffu, (tid_ >> 5) & 3, 0), tid = tid_ & 127; \
  const int g = lane >> 2, c = lane & 3;           \
  (void)tid; (void)g; (void)c; (void)wwarp;

#define PHASE_IDS_W                                \
  const int lane = fresh_tid() & 31, wwarp = warp & 3; \
  const int g = lane >> 2, c = lane & 3;

#define GTL(i) do { } while (0)
#define TGET(v) do { } while (0)
#define TPUT(c, i, v) do { } while (0)

constexpr float SM_C = 0.17677669529663687f * 1.4426950408889634f;

__device__ __forceinline__ void stmatrix_x4_if(bool ok, uint32_t addr, uint32_t r0, uint32_t r1, uint32_t r2, uint32_t r3) {
  asm volatile("{\n.reg .pred p;\nsetp.ne.b32 p, %5, 0;\n@p stmatrix.sync.aligned.m8n8.x4.shared.b16 [%0], {%1,%2,%3,%4};\n}\n" ::"r"(addr),
               "r"(r0), "r"(r1), "r"(r2), "r"(r3), "r"((int)ok));
}

__device__ __forceinline__ void attn_a_slow(const uint8_t* __restrict__ kvimg, int L, int gb, int hp, uint32_t bad,
                                            int row0, int lane) {
  constexpr uint32_t sq = SBASE + OFF_SLOT + 3 * 16384;
#pragma unroll 1
  for (int j = 0; j < 8; j++) {
    const uint8_t* tp = kvimg + (size_t)(gb * 16 + hp) * 32768 + (j * 32 + lane) * 128 + ((lane & 7) << 4);
#pragma unroll 1
    for (uint32_t it = 0; it < (1u << 17); ++it)
      if (((ld_relaxed_u32(tp) ^ lds32(SBASE + OFF_EPOCH)) & 1u) == 0u) break;
  }
  __syncwarp();
#pragma unroll 1
  for (int t = 0; t < 32; t++) {
    const int hh = t >> 4, row = row0 + (t & 7) + (t & 8) * 4;
    if (!((bad >> hh) & 1u)) continue;
    const int qpos = gb * 128 + row;
    const uint32_t qaddr = sq + row * 128;
    float mx = -INFINITY, sum = 0.f, acc = 0.f;
#pragma unroll 1
    for (int pass = 0; pass < 2; pass++) {
#pragma unroll 1
      for (int j = 0; j < 8; j++) {
        const int kp = qpos - (lane + 32 * j);
        const uint8_t* kr = kvimg + ((size_t)((kp >> 7) * 16 + hp) * 2 + ((kp >> 6) & 1)) * 16384 + (kp & 63) * 128;
        float d = -INFINITY;
        if (kp >= 0) {
          d = 0.f;
#pragma unroll 1
          for (int q = 0; q < 4; q++) {
            const uint4 kv = __ldcg(reinterpret_cast<const uint4*>(kr + (((hh * 4 + q) ^ (kp & 7)) << 4)));
            const uint4 qv = lds128(qaddr + (((hh * 4 + q) ^ (row & 7)) << 4));
            const uint32_t kw[4] = {kv.x, kv.y, kv.z, kv.w}, qw[4] = {qv.x, qv.y, qv.z, qv.w};
#pragma unroll
            for (int e = 0; e < 4; e++) d = fmaf(bf_lo(kw[e]), bf_lo(qw[e]), fmaf(bf_hi(kw[e]), bf_hi(qw[e]), d));
          }
        }
        if (pass == 0) {
          mx = fmaxf(mx, d);
        } else {
          const float ev = ex2_approx(d - mx);
          sum += ev;
          const float pv = bf16_round(ev);
#pragma unroll 1
          for (int kk = 0; kk < 32; kk++) {
            const float pk = __shfl_sync(0xffffffffu, pv, kk);
            const int k2 = qpos - (kk + 32 * j);
            if (k2 >= 0) {
              const uint8_t* vr = kvimg + ((size_t)((k2 >> 7) * 16 + hp) * 2 + ((k2 >> 6) & 1)) * 16384 + 8192 + (k2 & 63) * 128;
              const unsigned short vv =
                  __ldcg(reinterpret_cast<const unsigned short*>(vr + (((hh * 4 + (lane >> 3)) ^ (k2 & 7)) << 4) + (lane & 7) * 2));
              acc = fmaf(pk, __uint_as_float((uint32_t)vv << 16), acc);
            }
          }
        }
      }
      if (pass == 0) {
#pragma unroll
        for (int o = 16; o > 0; o >>= 1) mx = fmaxf(mx, __shfl_xor_sync(0xffffffffu, mx, o));
      }
    }
#pragma unroll
    for (int o = 16; o > 0; o >>= 1) sum += __shfl_xor_sync(0xffffffffu, sum, o);
    acc *= rcp_fast(sum);
    const float hi = __shfl_down_sync(0xffffffffu, acc, 1);
    __syncwarp();
    if ((lane & 1) == 0) sts32(qaddr + (((hh * 4 + (lane >> 3)) ^ (row & 7)) << 4) + (lane & 7) * 2,
                               set_tag(pack_bf16x2(acc, hi), hh == 0 && lane == 0, o_tag(L)));
    __syncwarp();
  }
}

template <int HH>
__device__ __forceinline__ void store_o(const float (&o)[16], const float (&inv)[2], uint32_t ra, uint32_t tag, bool ok) {
  const uint32_t m = HH == 0 && (fresh_tid() & 3) == 0;
#pragma unroll
  for (int jp = 0; jp < 2; jp++) {
    uint32_t w0 = pack_bf16x2(o[8 * jp] * inv[0], o[8 * jp + 1] * inv[0]);
    uint32_t w1 = pack_bf16x2(o[8 * jp + 2] * inv[1], o[8 * jp + 3] * inv[1]);
    if (HH == 0 && jp == 0) {
      w0 = set_tag(w0, m, tag);
      w1 = set_tag(w1, m, tag);
    }
    stmatrix_x4_if(ok, ra ^ ((HH * 4 + 2 * jp) << 4), w0, w1, pack_bf16x2(o[8 * jp + 4] * inv[0], o[8 * jp + 5] * inv[0]),
                   pack_bf16x2(o[8 * jp + 6] * inv[1], o[8 * jp + 7] * inv[1]));
  }
}
__device__ __forceinline__ int tile_row(bool B, int w, int r, int g) { return (B ? 16 * w + 8 * r : 8 * w + 32 * r) + g; }
__device__ __forceinline__ uint32_t q_row_addr(bool B, int R, int w, int lane) {
  return SBASE + OFF_SLOT + 3 * 16384 + R * 8192 + tile_row(B, w, (lane >> 3) & 1, lane & 7) * 128 + (((lane >> 4) ^ (lane & 7)) << 4);
}

struct AttnA {
  float s[2][16], o[2][16], l[2][2], sh[2][3];
  uint32_t p[2][4], t[2], me[4], ra, bad, zero;
};
#define ATS_(i) do { } while (0)
template <int V>
__device__ __forceinline__ void attn_sum(AttnA& a, int nv) {
  constexpr int hh = (V >> 1) & 1, kh = V & 1, i = V >> 2;
#pragma unroll
  for (int r = 0; r < 2; r++) {
    const uint32_t t1 = add_bf16x2(add_bf16x2(a.p[0][r], a.p[0][2 + r]), add_bf16x2(a.p[1][r], a.p[1][2 + r]));
    if (kh == 0) {
      a.t[r] = t1;
    } else {
      uint32_t tt = add_bf16x2(a.t[r], t1);
      if (i > 0) tt = i <= nv ? tt : 0u;
      const float v = bf_lo(tt) + bf_hi(tt);
      a.l[hh][r] = i == 0 ? v : a.l[hh][r] + v;
    }
  }
}
template <int HH>
__device__ __forceinline__ void attn_shfl(AttnA& a) {
#pragma unroll
  for (int r = 0; r < 2; r++)
#pragma unroll
    for (int j = 0; j < 3; j++) a.sh[r][j] = __shfl_xor_sync(0xffffffffu, a.l[HH][r], j + 1);
}
template <int HH>
__device__ __forceinline__ void attn_fin(AttnA& a) {
  bool bad = false;
  float inv[2];
#pragma unroll
  for (int r = 0; r < 2; r++) {
    const float v = (a.l[HH][r] + a.sh[r][0]) + (a.sh[r][1] + a.sh[r][2]);
    bad |= !(v <= 1.152921504606846976e18f && v >= 8.673617379884035e-19f);
    inv[r] = rcp_fast(v);
  }
  bad = __any_sync(0xffffffffu, bad);
  if (HH == 1) wgmma_wait<0>();
  reg_fence<16>(a.o[HH]);
  store_o<HH>(a.o[HH], inv, a.ra, o_tag(0), !bad);
  a.bad = (HH == 0 ? 0u : a.bad) | (bad ? 1u << HH : 0u);
}
__device__ __forceinline__ void attn_masks(AttnA& a, int wr) {
  const int lane = fresh_tid() & 31, d = (lane >> 2) - 2 * (lane & 3);
  const uint32_t tri = d >= 1 ? 0xffffffffu : (d == 0 ? 0xffffu : 0u);
#pragma unroll
  for (int t = 0; t < 4; t++) a.me[t] = wr > t ? 0xffffffffu : (wr == t ? tri : 0u);
}
template <int V, int K>
__device__ __forceinline__ uint32_t attn_exp(AttnA& a) {
  constexpr int i = V >> 2, kh = V & 1, r = K & 1;
  if ((i == 0 && kh > r) || (i == 4 && kh < r)) return 0u;
  const uint32_t w = pack_bf16x2(ex2_approx(a.s[V & 1][2 * K]), ex2_approx(a.s[V & 1][2 * K + 1]));
  if (i == 0 && kh == r) return w & a.me[K >> 1];
  if (i == 4 && kh == r) return w & ~a.me[K >> 1];
  return w;
}
template <int V>
__device__ __forceinline__ void attn_unit(AttnA& a, const uint32_t (&q)[2][2][4], uint64_t dcur, uint64_t dnext, int R, int wr, int nv,
                                          uint32_t hbar, uint32_t hpar, uint32_t rbar, bool rel) {
  constexpr int hh = (V >> 1) & 1, kh = V & 1, i = V >> 2;
  ATS_(V + 1);
  asm volatile("" : "+l"(dcur), "+l"(dnext));
  wgmma_wait<1>();
  reg_fence<16>(a.s[V & 1]);
  bool hok = true;
  if (V == 4) hbar = SBASE + OFF_BAR + 8u * (R ? B_LOC : B_HV);
  if (((V & 3) == 2 && V < 16) || V == 4) hok = mbar_test(hbar, hpar);
  const uint64_t d0 = ((V & 3) >= 2 ? dnext : dcur) + ((hh ^ 1) * 4 + kh * 256), d1 = ((V & 3) >= 2 ? dnext : dcur) + ((hh ^ 1) * 4 + kh * 256 + 2);
  const uint64_t d2 = dcur + (512 + hh * 4 + kh * 256), d3 = dcur + (640 + hh * 4 + kh * 256);
  if ((V & 3) == 1 && V > 4 && rel) mbar_arrive(rbar);
  if (V > 0) attn_sum<V - 1>(a, nv);
  if (V == 15) attn_masks(a, wr);
  if (V == 18) {
    attn_shfl<0>(a);
    a.ra = q_row_addr(false, R, wr, fresh_tid() & 31);
  }
  if (V == 19) attn_fin<0>(a);
  uint32_t p[2][4];
  p[0][0] = attn_exp<V, 0>(a);
  p[0][1] = attn_exp<V, 1>(a);
  p[0][2] = attn_exp<V, 2>(a);
  p[0][3] = attn_exp<V, 3>(a);
  p[1][0] = attn_exp<V, 4>(a);
  p[1][1] = attn_exp<V, 5>(a);
  p[1][2] = attn_exp<V, 6>(a);
  p[1][3] = attn_exp<V, 7>(a);
  if (V > 0) {
#pragma unroll
    for (int r = 0; r < 2; r++) p[1][r] ^= (kh ? a.t[r] : __float_as_uint(a.l[hh ^ 1][r])) & a.zero;
  }
#pragma unroll
  for (int k = 0; k < 8; k++) {
    asm volatile("" : "+r"(p[k >> 2][k & 3]));
    a.p[k >> 2][k & 3] = p[k >> 2][k & 3];
  }
  if (!hok) mbar_wait(hbar, hpar);
  wgmma_fence();
  if (V < 18) wgmma_n32_rsz_tb0(a.s[V & 1], q[hh ^ 1][0], d0);
  if (i == 0 && kh == 0) wgmma_n32_rsz_tb1(a.o[hh], a.p[0], d2);
  else wgmma_n32_rs_tb1(a.o[hh], a.p[0], d2, 1);
  if (V < 18) wgmma_n32_rs_tb0(a.s[V & 1], q[hh ^ 1][1], d1, 1);
  wgmma_n32_rs_tb1(a.o[hh], a.p[1], d3, 1);
  wgmma_commit();
}
template <int I>
__device__ __forceinline__ void attn_step(AttnA& a, const uint32_t (&q)[2][2][4], uint64_t dcur, uint64_t dnext, int R, int wr, int nv,
                                          uint32_t hbar, uint32_t hpar, uint32_t rbar, bool rel) {
  attn_unit<4 * I>(a, q, dcur, dnext, R, wr, nv, hbar, hpar, rbar, rel);
  attn_unit<4 * I + 1>(a, q, dcur, dnext, R, wr, nv, hbar, hpar, rbar, rel);
  attn_unit<4 * I + 2>(a, q, dcur, dnext, R, wr, nv, hbar, hpar, rbar, rel);
  attn_unit<4 * I + 3>(a, q, dcur, dnext, R, wr, nv, hbar, hpar, rbar, rel);
}

__device__ __forceinline__ void attention_a(const uint32_t (&q)[2][2][4], int R, int L, int gb, int hp, uint32_t par, int wr,
                                            uint32_t zero) {
  constexpr uint32_t bars = SBASE + OFF_BAR;
  constexpr uint32_t dslot = ((SBASE + OFF_SLOT) >> 4) + 0x10000u;
  auto next = [&](uint64_t d) { return desc_lo((uint32_t)d == dslot ? dslot + 2048 : (uint32_t)d - 1024) + zero; };
  uint64_t d0 = desc_lo(dslot + R * 1024) + zero, d1 = next(d0);
  AttnA a;
  ATS_(0);
  wgmma_fence();
#pragma unroll
  for (int v = 0; v < 2; v++) {
    wgmma_n32_rsz_tb0(a.s[v], q[0][0], d0 + v * 256);
    wgmma_n32_rs_tb0(a.s[v], q[0][1], d0 + (v * 256 + 2), 1);
    wgmma_commit();
  }
  a.zero = zero;
  const bool lane0 = (fresh_tid() & 31) == 0;
  attn_masks(a, wr);
  const int nv = 2 * gb + R;
  const uint32_t hb = bars + 8u * (B_HALO - R), rb = bars + 8u * (B_REL - R);
  attn_step<0>(a, q, d0, d1, R, wr, nv, hb, par, 0, false);
  d0 = next(d1);
  attn_step<1>(a, q, d1, d0, R, wr, nv, R ? bars + 8u * B_HV : hb + 8, par, rb + 8, lane0);
  d1 = next(d0);
  attn_step<2>(a, q, d0, d1, R, wr, nv, hb + 16, par, rb + 16, lane0);
  d0 = next(d1);
  attn_step<3>(a, q, d1, d0, R, wr, nv, hb + 24, par, rb + 24, lane0 && R);
  attn_step<4>(a, q, d0, d0, R, wr, nv, 0, 0, rb, false);
  ATS_(21);
  attn_sum<19>(a, nv);
  attn_shfl<1>(a);
  attn_fin<1>(a);
  ATS_(22);
  if (a.bad != 0u) {
    attn_a_slow(g_kvA[L >> 1][0][0][0], L, gb, hp, a.bad, R * 64 + wr * 8, fresh_tid() & 31);
    named_bar_sync(8 + R * 4 + wr, 32);
  }
}

constexpr uint32_t KB_ROW0 = SBASE + OFF_SLOT + 2048, VB_ROW0 = SBASE + OFF_SLOT + 24576 + 2048;

__device__ __forceinline__ void attention_b(const uint32_t (&q)[2][2][4], int R, int gb, uint32_t par0, int wr) {
  constexpr uint32_t bars = SBASE + OFF_BAR;
  const uint32_t dk = ((KB_ROW0 - 2048) >> 4) + 0x10000u + R * 512, dv = dk + ((VB_ROW0 - KB_ROW0) >> 4);
  float s[2][40];
  mbar_wait(bars + 8u * (B_HALO - R), par0);
  wgmma_fence();
#pragma unroll
  for (int hh = 0; hh < 2; hh++) {
    wgmma_n80_rsz_tb0(s[hh], q[hh][0], desc_lo(dk + hh * 4));
    wgmma_n80_rs_tb0(s[hh], q[hh][1], desc_lo(dk + hh * 4 + 2), 1);
  }
  wgmma_commit();
  const int lane = fresh_tid() & 31, g = lane >> 2;
  const bool odd = g & 1, edge = R == 0 && gb == 0 && wr == 0;
  const int D = 2 * (lane & 3) + (g & 1) - g;
  const uint32_t ra = q_row_addr(true, R, wr, lane);
  wgmma_wait<0>();
  reg_fence<40>(s[0]);
  reg_fence<40>(s[1]);
  float z[2][2], y[2][2];
#define GATHER_(W)                                                                                          \
  _Pragma("unroll") for (int hh = 0; hh < 2; hh++) _Pragma("unroll") for (int r = 0; r < 2; r++) {          \
    const float* e = &s[hh][4 * (2 * W + r) + 2 * r];                                                       \
    z[hh][r] = odd ? e[5] : e[4];                                                                           \
    y[hh][r] = D >= 2 ? (odd ? e[1] : e[0]) : (odd ? e[9] : e[8]);                                          \
  }
  if (wr < 2) {
    if (wr == 0) { GATHER_(0) } else { GATHER_(1) }
  } else {
    if (wr == 2) { GATHER_(2) } else { GATHER_(3) }
  }
#undef GATHER_
  float o[2][16], inv[2][2];
  uint32_t p[2][5][4];
  const int sh = odd ? 16 : 0, kb = wr + (D >= 2 ? 0 : 1);
#pragma unroll
  for (int hh = 0; hh < 2; hh++) {
    if (edge) {
      z[hh][0] = -INFINITY;
      if (D >= 2) y[hh][0] = y[hh][1] = -INFINITY;
    }
    uint32_t ab[2][2];
#pragma unroll
    for (int r = 0; r < 2; r++) {
      float m = fmaxf(z[hh][r], y[hh][r]);
      m = fmaxf(m, __shfl_xor_sync(0xffffffffu, m, 1));
      m = fmaxf(m, __shfl_xor_sync(0xffffffffu, m, 2));
      const float e0 = ex2_approx(z[hh][r] - m), e1 = ex2_approx(y[hh][r] - m);
      inv[hh][r] = e0 + e1;
      ab[r][0] = pack_bf16x2(e0, 0.f) << sh;
      ab[r][1] = pack_bf16x2(e1, 0.f) << sh;
    }
#pragma unroll
    for (int k = 0; k < 5; k++) {
      p[hh][k][0] = k == kb ? ab[0][1] : 0u;
      p[hh][k][1] = k == wr + 1 ? ab[1][0] : 0u;
      p[hh][k][2] = k == wr ? ab[0][0] : 0u;
      p[hh][k][3] = k == kb ? ab[1][1] : 0u;
#pragma unroll
      for (int j = 0; j < 4; j++) asm volatile("" : "+r"(p[hh][k][j]));
    }
  }
  wgmma_fence();
#pragma unroll
  for (int hh = 0; hh < 2; hh++) {
    wgmma_n32_rsz_tb1(o[hh], p[hh][0], desc_lo(dv + hh * 4));
#pragma unroll
    for (int k = 1; k < 5; k++) wgmma_n32_rs_tb1(o[hh], p[hh][k], desc_lo(dv + hh * 4 + k * 128), 1);
  }
  wgmma_commit();
#pragma unroll
  for (int hh = 0; hh < 2; hh++)
#pragma unroll
    for (int r = 0; r < 2; r++) {
      inv[hh][r] += __shfl_xor_sync(0xffffffffu, inv[hh][r], 1);
      inv[hh][r] += __shfl_xor_sync(0xffffffffu, inv[hh][r], 2);
      inv[hh][r] = rcp_fast(inv[hh][r]);
    }
  wgmma_wait<0>();
  reg_fence<16>(o[0]);
  reg_fence<16>(o[1]);
  store_o<0>(o[0], inv[0], ra, o_tag(1), true);
  store_o<1>(o[1], inv[1], ra, o_tag(1), true);
}

#define KTQM 0
#define TRICKLE 300
#define WTURN 15
#define QREL 8
#define PRESLEEP 200
#define CSA 3
#define TLAZY 100
#define QTURN 2
#define HTS(i) do { } while (0)
struct Params {
  CUtensorMap x[5], xq[4], o, wqkv[2], wqkv3[2], wo3[2];
  const __nv_bfloat16* in_x;
  const __nv_bfloat16* wqkv_p[2];
  const __nv_bfloat16* wo_p[2];
  __nv_bfloat16* out;
  uint32_t zero;
};

__device__ __forceinline__ void colsum_part(const CUtensorMap* wmap, int ty, int qr, int hp) {
  constexpr uint32_t bars = SBASE + OFF_BAR, slots = SBASE + OFF_SLOT;
  PHASE_IDS
  const unsigned ep1 = launch_epoch();
  if (wwarp == 0 && elect_one()) {
    mbar_expect_tx(bars + 8u * B_CS, 6 * UNIT);
#pragma unroll 1
    for (int j = 0; j < 6; j++) {
      if (ty == 0) mbar_pace(bars + 8u * (B_QF + B_E + ((j * CSA / 6) & 3)), (j * CSA / 6) >> 2);
      else mbar_wait_lazy<100>(bars + 8u * (B_WF + B_E + ((2 * j + 3 - (j & 1)) & 7)), j >= 3);
      tma_load_2d(slots + j * UNIT, wmap, bars + 8u * B_CS, (j >> 1) * 1024 + hp * 64, qr * 128 + (j & 1) * 64);
    }
  }
  constexpr uint64_t ones = (SBASE + OFF_LSB + 32) >> 4;
  float s[3][4];
  mbar_wait_lazy<100>(bars + 8u * B_CS, ty);
  wgmma_fence();
#pragma unroll
  for (int p = 0; p < 3; p++) {
    wgmma_n8_ssz_ta1_tb0(s[p], make_desc(slots + p * 2 * UNIT, 16), ones);
#pragma unroll
    for (int k = 1; k < 8; k++) wgmma_n8_ss_ta1_tb0(s[p], make_desc(slots + p * 2 * UNIT + k * 2048, 16), ones, 1);
  }
  wgmma_commit();
  wgmma_wait<0>();
  reg_fence<12>(&s[0][0]);
  if (lane == 0) mbar_arrive(bars + 8u * (ty ? B_CSD : B_RDONE));
  if (c == 0) {
#pragma unroll
    for (int r = 0; r < 2; r++) st_rec(&g_cs[ty][hp][qr][wwarp * 16 + 8 * r + g], s[0][2 * r], s[1][2 * r], s[2][2 * r], ep1);
  }
}

__device__ __forceinline__ void put_colsums(int ty, int col, const float4& s) {
  const float v[3] = {s.x, s.y, s.z};
#pragma unroll
  for (int p = 0; p < 3; p++) {
    const uint32_t a = SBASE + OFF_CS + (p * 8 + (col >> 3)) * 64 + ty * 32 + (col & 7) * 2;
    const float hi = bf16_round(v[p]);
    const uint32_t w = pack_bf16x2(hi, v[p] - hi);
    asm volatile("st.shared.b16 [%0], %1;" ::"r"(a), "h"((unsigned short)w) : "memory");
    asm volatile("st.shared.b16 [%0], %1;" ::"r"(a + 16), "h"((unsigned short)(w >> 16)) : "memory");
  }
}

__device__ __forceinline__ uint32_t ln_params(float s1, float s2) {
  const float mean = s1 * (1.0f / DM);
  const float var = fmaxf(fmaf(-mean, mean, s2 * (1.0f / DM)), 0.f);
  float sd;
  asm("sqrt.approx.f32 %0, %1;" : "=f"(sd) : "f"(bf16_round(bf16_round(var) + 1e-5f)));
  return pack_bf16x2(mean, sd);
}

struct RingProd {
  uint32_t rel = ((B_QF << 1) | 1) * 0x01010101u + 0x06040200u;
  int st = 0;
  __device__ __forceinline__ uint32_t next(uint32_t bar, uint32_t par, bool wait) {
    const uint32_t e = (rel >> (8 * st)) & 255u, a = SBASE + st * 5 * UNIT;
    if (wait) mbar_wait(SBASE + OFF_BAR + 8u * B_E + 8u * (e >> 1), e & 1u);
    rel ^= (e ^ ((bar << 1) | par)) << (8 * st);
    st = (st + 1) & 3;
    return a;
  }
};

#define SP1 15
#define SP2 14
#define SP3 12
#define SP4 12
#define SP5 15
#define SP6 14
#define SP7 16
__device__ __forceinline__ int q_split(int inst) {
  constexpr uint32_t T = 15u | ((SP1 - 1) << 4) | ((SP2 - 1) << 8) | ((SP3 - 1) << 12) | ((SP4 - 1) << 16) | ((SP5 - 1) << 20) |
                         ((SP6 - 1) << 24) | ((uint32_t)(SP7 - 1) << 28);
  return (int)((T >> (4 * inst)) & 15u) + 1;
}
__host__ __device__ constexpr uint32_t turn_par(int kind) {
  const int sp[8] = {16, SP1, SP2, SP3, SP4, SP5, SP6, SP7};
  int cnt[2] = {0, 0};
  uint32_t m = 0;
  for (int i = 0; i < 8; i++)
    for (int k = 0; k < 3; k++) {
      if (k == kind) m |= (uint32_t)(cnt[i & 1] & 1) << i;
      if (k == 0 ? (i == 1 || (i > 1 && sp[i - 1] < 16)) : (k == 2 || sp[i] < 16)) cnt[i & 1]++;
    }
  return m;
}
#define PREMASK 0xBFu
__device__ __forceinline__ bool w_pre(int inst) { return (PREMASK >> inst) & 1u; }
__global__ void __launch_bounds__(512, 1) fused_kernel(const __grid_constant__ Params P) {
  extern __shared__ __align__(1024) uint8_t smem_raw[];
  constexpr uint32_t base = SBASE, bars = base + OFF_BAR, slots = base + OFF_SLOT;
  if (smem_u32(smem_raw) != base) __trap();
  const int warp = __shfl_sync(0xffffffffu, threadIdx.x >> 5, 0), lane = threadIdx.x & 31;
  const int b = blockIdx.x;
#define QS 0
#define WS 1
  const int qr = ((b & ((8 << QS) - 1)) >> QS) ^ (((b >> (3 + QS)) & 1) * 7);
  const int hp = ((b >> (3 + QS)) << QS) + (b & ((1 << QS) - 1));
  const int rt = ((b & ((16 << WS) - 1)) >> WS) ^ (((b >> (4 + WS)) & 1) * 15);
  const int ct = ((b >> (4 + WS)) << WS) + (b & ((1 << WS) - 1));

  if (warp == 12) {
    if (elect_one()) {
#pragma unroll
      for (int s = 0; s < 4; s++) {
        mbar_init(bars + 8u * (B_QF + s), 2);
        mbar_init(bars + 8u * (B_QF + B_E + s), 4);
      }
      mbar_init(bars + 8u * B_GO, 4);
      fence_barrier_init();
    }
    __syncwarp();
    named_bar_arrive(0, 512);
  }
  if (threadIdx.x == 0) {
    for (int s = B_WF; s <= B_RF; s++) {
      mbar_init(bars + 8u * s, s == B_RF ? 1 : 2);
      mbar_init(bars + 8u * (s + B_E), s == B_RF ? 1 : 4);
    }
    for (int s = 0; s < 4; s++) {
      sts32(base + OFF_ONE + 4 * s, s == 0);
      sts32(base + OFF_LSB + 32 + 4 * s, 0x3f803f80u);
    }
    fence_proxy_async_smem();
    mbar_init(bars + 8u * B_PREP, 1);
    mbar_init(bars + 8u * (B_PREP + 1), 1);
    mbar_init(bars + 8u * B_HL, 1);
    mbar_init(bars + 8u * (B_HL + 1), 1);
    mbar_init(bars + 8u * B_HV, 1);
    for (int s = 0; s < 4; s++) mbar_init(bars + 8u * (B_HALO + s), 1);
    for (int s = 0; s < 3; s++) mbar_init(bars + 8u * (B_REL + s), s == 0 ? 4 : 8);
    mbar_init(bars + 8u * B_LOC, 4);
    mbar_init(bars + 8u * B_OS0, 4);
    mbar_init(bars + 8u * B_KV, 4);
    mbar_init(bars + 8u * B_TURN, 4);
    mbar_init(bars + 8u * (B_TURN + 1), 4);
    mbar_init(bars + 8u * B_CS, 1);
    mbar_init(bars + 8u * B_PRE, 1);
    mbar_init(bars + 8u * B_PRE2, 1);
    mbar_init(bars + 8u * B_CSD, 4);
    mbar_init(bars + 8u * B_RDONE, 4);
    mbar_init(bars + 8u * B_XS, 4);
    mbar_init(bars + 8u * (B_XS + 1), 4);
    fence_barrier_init();
  }
  if (warp != 12) named_bar_sync(0, 512);

  if (warp >= 12) {
    setmaxnreg_dec<32>();
    if (warp == 12) {
      if (elect_one()) {
#pragma unroll 1
        for (int s = 0; s < 16; s++) {
          const uint32_t fb = bars + 8u * (B_QF + (s & 3)), sa = base + (s & 3) * 5 * UNIT;
          if (s >= 4) mbar_wait(fb + 8u * B_E, ((s >> 2) & 1) ^ 1);
          mbar_expect_tx(fb, 5 * UNIT);
          mbar_arrive(fb);
          tma_load_5d(sa + 3 * UNIT, &P.xq[0], fb, s * 64, qr * 2);
          tma_load_3d(sa, &P.wqkv3[0], fb, hp * 64, s * 64);
        }
#pragma unroll
        for (int s = 0; s < 4; s++) mbar_arrive(bars + 8u * B_GO);
        RingProd rp;
#pragma unroll 1
        for (int sg = 4; sg < 34; sg++) {
          const int part = sg & 3, inst = (sg >> 2) - (part & 1);
          if (part == 3 || inst == 8) continue;
          const int ty = (inst >> 1) & 1;
          if (part != 1) {
            const int k0 = part ? q_split(inst) : 0, k1 = part ? 16 : q_split(inst);
#pragma unroll 1
            for (int kt = k0; kt < k1; kt++) {
              const uint32_t sa = rp.next(B_QF + (kt & 3), (kt >> 2) & 1, true), fb = bars + 8u * (B_QF + (kt & 3));
              mbar_expect_tx(fb, 3 * UNIT);
              tma_load_3d(sa, &P.wqkv3[ty], fb, hp * 64, kt * 64);
            }
          } else {
            const bool pre = w_pre(inst);
            const int lag = pre ? 8 : 5;
            uint32_t sa = 0;
#pragma unroll 1
            for (int kt = 0; kt < 16; kt++) {
              const int i = kt & 3;
              const uint32_t fb = bars + 8u * (B_WF + (kt & 7));
              if (i == 1) sa += 2 * UNIT;
              else if (i != 3 || !pre) sa = rp.next(kt == 14 ? B_RF : B_WF + ((kt | 1) & 7), kt == 14 ? inst & 1 : kt >> 3, kt < lag) + ((0x21 >> (2 * i)) & 3) * UNIT;
              if (kt >= lag) mbar_wait(bars + 8u * (B_WF + B_E + ((kt - lag) & 7)), (kt - lag) >> 3);
              if (i == 3 && pre) {
                mbar_arrive(fb);
              } else {
                mbar_expect_tx(fb, 2 * UNIT);
                tma_load_3d(sa, &P.wo3[ty], fb, ct * 128, kt * 64);
              }
            }
          }
        }
      }
    } else if (warp == 13) {
      RingProd rp;
      unsigned ep1 = 0;
      uint32_t seenx = 0;
      mbar_wait(bars + 8u * B_GO, 0);
#pragma unroll 1
      for (int sg = 4; sg < 34; sg++) {
        const int part = sg & 3, inst = (sg >> 2) - (part & 1);
        if (part == 3 || inst == 8) continue;
        const int L = inst >> 1, ch = inst & 1;
        uint32_t seen = 0;
        if (part != 1) {
          const CUtensorMap* tx = &P.xq[L];
          const int k0 = part ? q_split(inst) : 0, k1 = part ? 16 : q_split(inst);
          if (part == 0) seenx = L == 0 ? 0xffffffffu : 0u;
          if (sg == 4) ep1 = launch_epoch();
          const int m0 = ch * 16 + qr * 2;
#pragma unroll 1
          for (int kt = k0; kt < k1; kt++) {
            wait_count(g_fx[ch * 8 + qr][0], 6u * ep1 - 6u + 2u * L, kt, seenx, lane);
            TGET(t38);
            const uint32_t sa = rp.next(B_QF + (kt & 3), (kt >> 2) & 1, true);
            TGET(t39);
            if (elect_one()) {
              const uint32_t fb = bars + 8u * (B_QF + (kt & 3));
              mbar_expect_tx(fb, 2 * UNIT);
              tma_load_5d(sa + 3 * UNIT, tx, fb, kt * 64, m0);
            }
            if (L == 3 && kt == 0 && lane == 0) { TPUT(ch, 38, t38); TPUT(ch, 39, t39); }
          }
        } else {
          const int m0 = ch * 1024 + rt * 64;
          const bool pre = w_pre(inst);
          const int lag = pre ? 8 : 5;
          uint32_t sa = 0;
#pragma unroll 1
          for (int kt = 0; kt < 16; kt++) {
            const int i = kt & 3;
            const uint32_t fb = bars + 8u * (B_WF + (kt & 7));
            wait_count(g_fo[ch * 16 + rt][0], 4u * ep1 - 3u + L, kt, seen, lane);
            const bool stg = kt == 13 && inst == 6 && SP7 == 16;
            if (i < 2) sa = rp.next(stg ? B_RF : B_WF + (kt & 7) + i + 1, stg ? inst & 1 : kt >> 3, kt < lag);
            else sa += (2 * i - 3) * UNIT;
            if (kt >= lag) mbar_wait(bars + 8u * (B_WF + B_E + ((kt - lag) & 7)), (kt - lag) >> 3);
            if (elect_one()) {
              mbar_expect_tx(fb, UNIT);
              tma_load_2d(sa, &P.o, fb, kt * 64, m0);
            }
            if (i == 3 && !pre) rp.next(B_WF + (kt & 7), kt >> 3, false);
          }
        }
      }
    } else if (warp == 14) {
      const unsigned ep1 = launch_epoch();
      uint32_t hpar = 0;
#pragma unroll 1
      for (int inst = 0; inst < 8; inst++) {
        const int L = inst >> 1, ch = inst & 1, gb = ch * 8 + qr;
        const unsigned kv0 = 8u * ep1 - 8u + 2u * L + (L & 1);
        if ((L & 1) == 0) {
          uint8_t* img = g_kvA[L >> 1][gb][hp][0];
          const uint8_t* s1 = gb > 0 ? img - 16 * 32768 : g_zero;
          const uint8_t* s2 = gb > 1 ? img - 32 * 32768 : g_zero;
          const uint32_t h1 = gb > 0 ? 16384 : 0, h2 = gb > 1 ? 16384 : 0;
          const unsigned* cp = g_fk[hp][max(gb - 1 - (lane >= 3), 0)];
          const unsigned ct0 = kv0 + ((0x32321u >> (4 * (lane & 7))) & 3u);
          uint32_t fr = gb == 0 ? 31u : (gb == 1 ? 24u : 0u);
          const uint32_t toff = slots + lane * 128 + ((lane & 7) << 4);
          auto seen = [&](uint32_t m) {
#pragma unroll 1
            for (uint32_t it = 0; it < (1u << 17) && !(fr & m); ++it)
              fr |= __ballot_sync(0xffffffffu, (int)(ld_relaxed_u32(cp) - ct0) >= 0);
          };
          auto load = [&](uint32_t off, const uint8_t* src, uint32_t bytes, int bi) {
            if (elect_one()) {
              mbar_expect_tx(bars + 8u * (B_HL + bi), bytes);
              bulk_load(slots + off, src, bytes, bars + 8u * (B_HL + bi));
            }
          };
          auto check = [&](uint32_t off, const uint8_t* src, uint32_t bytes, int bi, bool real, int done) {
#pragma unroll 1
            for (int tries = 0; tries < 4096; tries++) {
              mbar_wait(bars + 8u * (B_HL + bi), (hpar >> bi) & 1u);
              hpar ^= 1u << bi;
              uint32_t t = (lds32(toff + off) ^ ep1) | (lds32(toff + off + 4096) ^ ep1);
              if (bytes > 8192) t |= (lds32(toff + off + 8192) ^ ep1) | (lds32(toff + off + 12288) ^ ep1);
              if (!__any_sync(0xffffffffu, real && (t & 1u))) break;
              fence_proxy_async_smem();
              load(off, src, bytes, bi);
            }
            if (lane == 0) mbar_arrive(bars + 8u * done);
          };
          uint8_t *pk = img + 16384, *pv = img + 24576;
          unsigned* f = g_fk[hp][gb];
          pin64(pk), pin64(pv), pin64(f);
          mbar_wait(bars + 8u * B_KV, inst & 1);
          if (elect_one()) {
            bulk_store(pk, slots + 16384, 8192);
            bulk_announce(f);
            bulk_store(pv, slots + 24576, 8192);
            bulk_announce(f);
            bulk_commit();
          }
          HTS(44);
          seen(1);
          HTS(46);
          load(32768, s1 + h1, 8192, 0);
          seen(2);
          HTS(47);
          load(40960, s1 + h1 + 8192, 8192, 1);
          mbar_wait(bars + 8u * B_LOC, inst & 1);
          HTS(45);
          if (elect_one()) {
            bulk_store(img, slots, 16384);
            bulk_announce(g_fk[hp][gb]);
            bulk_commit();
            asm volatile("cp.async.bulk.wait_group.read 1;" ::: "memory");
          }
          check(32768, s1 + h1, 8192, 0, gb > 0, B_HALO);
          HTS(52);
          check(40960, s1 + h1 + 8192, 8192, 1, gb > 0, B_HV);
          HTS(53);
#pragma unroll 1
          for (int n = 1; n < 4; n++) {
            const uint8_t* src = n == 1 ? s1 : (n == 2 ? s2 + h2 : s2);
            const uint32_t off = n == 3 ? 32768 : 32768 - n * 16384;
            seen(2u << n);
            if (n == 2 && elect_one()) bulk_wait_read0();
            mbar_wait(bars + 8u * (B_REL - 1) + 8u * n, ch);
            HTS(47 + n);
            load(off, src, 16384, 0);
            check(off, src, 16384, 0, gb > (n >> 1), B_HALO + n);
            HTS(53 + n);
          }
        } else {
          uint8_t* img = g_kvB[L >> 1][gb][hp];
          uint8_t *pk = img, *pv = img + 2048;
          unsigned* f = g_fk[hp][gb];
          pin64(pk), pin64(pv), pin64(f);
          mbar_wait(bars + 8u * B_KV, inst & 1);
          if (elect_one()) {
            bulk_store(pk, KB_ROW0 + 112 * 128, 2048);
            bulk_store(pv, VB_ROW0 + 112 * 128, 2048);
            bulk_announce(f);
            bulk_commit();
          }
          HTS(44);
          const uint8_t* src = gb >= 1 ? img - 16 * 4096 : g_zero;
#pragma unroll 1
          for (uint32_t it = 0; it < (1u << 17); ++it)
            if (gb == 0 || (int)(ld_relaxed_u32(g_fk[hp][gb - 1]) - kv0) > 0) break;
          HTS(46);
#pragma unroll 1
          for (uint32_t it = 0; it < 4096; ++it) {
            if (elect_one()) {
              mbar_expect_tx(bars + 8u * B_HL, 4096);
              bulk_load(KB_ROW0 - 2048, src, 2048, bars + 8u * B_HL);
              bulk_load(VB_ROW0 - 2048, src + 2048, 2048, bars + 8u * B_HL);
              bulk_wait_read0();
            }
            mbar_wait(bars + 8u * B_HL, hpar & 1u);
            hpar ^= 1u;
            const uint32_t t = lds32((lane < 16 ? KB_ROW0 - 2048 : VB_ROW0 - 4096) + lane * 128 + ((lane & 7) << 4)) ^ ep1;
            if (gb == 0 || !__any_sync(0xffffffffu, t & 1u)) break;
            fence_proxy_async_smem();
          }
          if (lane == 0) mbar_arrive(bars + 8u * B_HALO);
          HTS(52);
        }
        if (elect_one()) {
          const CUtensorMap* mo = &P.o;
          unsigned *f1 = g_fo[gb * 2 + 1][hp], *f0 = g_fo[gb * 2][hp];
          int c0 = hp * 64, r0 = gb * 128, r1 = r0 + 64;
          pin64(mo), pin64(f1), pin64(f0);
          asm volatile("" : "+r"(c0), "+r"(r0), "+r"(r1));
          mbar_wait(bars + 8u * B_OS1, (inst & 1) ^ 1);
          tma_store_2d(mo, slots + 7 * UNIT, c0, r1);
          bulk_announce(f1);
          bulk_commit();
          mbar_wait(bars + 8u * B_OS0, inst & 1);
          tma_store_2d(mo, slots + 6 * UNIT, c0, r0);
          bulk_announce(f0);
          bulk_commit();
          bulk_wait_read0();
          mbar_expect_tx(bars + 8u * B_RF, 2 * UNIT);
          tma_load_2d(slots + 6 * UNIT, &P.x[L], bars + 8u * B_RF, ct * 128, ch * 1024 + rt * 64);
          tma_load_2d(slots + 7 * UNIT, &P.x[L], bars + 8u * B_RF, ct * 128 + 64, ch * 1024 + rt * 64);
          if (w_pre(inst)) {
            mbar_expect_tx(bars + 8u * B_PRE, 6 * UNIT);
            mbar_expect_tx(bars + 8u * B_PRE2, 2 * UNIT);
#pragma unroll 1
            for (int j = 0; j < 4; j++) {
              __nanosleep(PRESLEEP);
              if (j == 3) mbar_wait(bars + 8u * B_RDONE, (inst & 1) ^ 1);
              tma_load_3d(slots + j * 2 * UNIT, &P.wo3[L & 1], bars + 8u * (j == 3 ? B_PRE2 : B_PRE), ct * 128, (4 * j + 3) * 64);
            }
          }
        }
        __syncwarp();
      }
    } else {
      const unsigned ep1 = launch_epoch();
      mbar_wait(bars + 8u * B_GO, 0);
#pragma unroll 1
      for (int i = 0; i < 20; i++) {
        const char* src = i < 4 ? reinterpret_cast<const char*>(P.wo_p[0]) + (size_t)b * 16384 + i * 4096
                                : (i < 16 ? reinterpret_cast<const char*>(P.wqkv_p[1]) + (size_t)b * 49152 + (i - 4) * 4096
                                          : reinterpret_cast<const char*>(P.wo_p[1]) + (size_t)b * 16384 + (i - 16) * 4096);
        asm volatile("prefetch.global.L2 [%0];" ::"l"(src + lane * 128));
        __nanosleep(TRICKLE);
      }
#pragma unroll 1
      for (int inst = 2; inst < 10; inst++) {
        const int L = inst >> 1, ch = inst & 1, gb = ch * 8 + qr;
        {
          uint32_t xb = base + (((inst < 9 ? q_split(inst - 1) : 0) + (w_pre(inst - 2) ? 3 : 2)) & 3) * 5 * UNIT;
          unsigned* f = g_fx[ch * 8 + (rt >> 1)][ct * 2];
          const CUtensorMap* mx = &P.x[L];
          int c0 = ct * 128, r0 = ch * 1024 + rt * 64;
          pin64(f), pin64(mx);
          asm volatile("" : "+r"(xb), "+r"(c0), "+r"(r0));
#pragma unroll
          for (int h = 0; h < 2; h++) {
            mbar_wait(bars + 8u * (B_XS + h), ch);
            if (elect_one()) {
              tma_store_2d(mx, xb + h * UNIT, c0 + h * 64, r0);
              if (L < 4) bulk_announce(f + 4 * h);
              bulk_commit();
              if (h == 1) {
                bulk_wait_read0();
                mbar_arrive(bars + 8u * (B_RF + B_E));
              }
            }
          }
          if (L == 4) continue;
        }
#pragma unroll 1
        for (int h = 0; h < 4; h++) {
          const float4* sp = &g_stats[L][0][gb * 128 + h * 32 + lane];
          const float4 s0 = sum_recs<4>(sp, S_LEN, ep1), s1 = sum_recs<4>(sp + 4 * S_LEN, S_LEN, ep1);
          sts32(base + OFF_RS + (ch * 128 + h * 32 + lane) * 4, ln_params(s0.x + s1.x, s0.y + s1.y));
        }
        if (inst == 2) {
#pragma unroll 1
          for (int hf = 0; hf < 2; hf++) {
            const float4* cp = &g_cs[1][hp][0][hf * 32 + lane];
            const float4 s0 = sum_recs<4>(cp, 64, ep1), s1 = sum_recs<4>(cp + 4 * 64, 64, ep1);
            put_colsums(1, hf * 32 + lane, make_float4(s0.x + s1.x, s0.y + s1.y, s0.z + s1.z, 0.f));
          }
        }
        fence_proxy_async_smem();
        __syncwarp();
        if (lane == 0) mbar_arrive(bars + 8u * (B_PREP + ch));
      }
    }
  } else {
    const bool asst = warp >= 8;
    GTL(0);
    if (warp >= 4 && !asst) {
      PHASE_IDS
      {
        const unsigned ep1 = launch_epoch();
        const int row = b * 16 + (tid >> 3);
        const uint4* src = reinterpret_cast<const uint4*>(P.in_x + (size_t)row * DM) + (tid & 7);
        float s1 = 0.f, s2 = 0.f;
#pragma unroll 1
        for (int k = 0; k < 4; k++) {
          mbar_pace(bars + 8u * (B_QF + B_E + ((2 * k) & 3)), k >> 1);
          uint4 v[4];
#pragma unroll
          for (int j = 0; j < 4; j++) v[j] = __ldg(src + (k * 4 + j) * 8);
#pragma unroll
          for (int j = 0; j < 4; j++) {
            const uint32_t w[4] = {v[j].x, v[j].y, v[j].z, v[j].w};
#pragma unroll
            for (int e = 0; e < 4; e++) {
              const float x0 = bf_lo(w[e]), x1 = bf_hi(w[e]);
              s1 += x0 + x1;
              s2 = fmaf(x0, x0, fmaf(x1, x1, s2));
            }
          }
        }
#pragma unroll
        for (int o = 1; o < 8; o <<= 1) {
          s1 += __shfl_xor_sync(0xffffffffu, s1, o);
          s2 += __shfl_xor_sync(0xffffffffu, s2, o);
        }
        if ((tid & 7) == 0) st_rec(&g_stats[0][0][row], s1, s2, 0.f, ep1);
        if (tid == 0) sts32(base + OFF_EPOCH, ep1);
        if (tid < 64) {
          const float4 s0 = sum_recs<8>(&g_cs[0][hp][0][tid], 64, ep1);
          put_colsums(0, tid, s0);
        } else {
          put_colsums(1, tid - 64, make_float4(0.f, 0.f, 0.f, 0.f));
        }
#pragma unroll 1
        for (int cc = 0; cc < 2; cc++) {
          const float4 s0 = sum_recs<1>(&g_stats[0][0][(cc * 8 + qr) * 128 + tid], 0, ep1);
          sts32(base + OFF_RS + (cc * 128 + tid) * 4, ln_params(s0.x, s0.y));
        }
        fence_proxy_async_smem();
        named_bar_sync(2, 128);
        if (tid < 2) mbar_arrive(bars + 8u * (B_PREP + tid));
      }
    }
#pragma unroll 1
    for (int inst = asst ? 0 : warp >> 2; inst < 8; inst += asst ? 1 : 2) {
      const int L = inst >> 1, ch = inst & 1, gb = ch * 8 + qr;
      uint32_t q[2][2][4];
      if (asst) {
        if (inst < 2) colsum_part(&P.wqkv[inst], inst, qr, hp);
        setmaxnreg_dec<24>();
        named_bar_sync(4, 256);
        setmaxnreg_inc<128>();
        const uint32_t ra = q_row_addr(L & 1, 1, warp & 3, fresh_tid() & 31);
#pragma unroll
        for (int j = 0; j < 4; j++) ldmatrix_x4(q[j >> 1][j & 1], ra ^ (j << 5));
      } else {
      setmaxnreg_inc<224>();
      {
        float acc[2][96];
        const int ksp = q_split(inst);
        constexpr uint32_t STG = 5 * (UNIT >> 4), D0 = ((base + 3 * UNIT) >> 4) + 0x10000u;
        constexpr uint32_t DB = ((UNIT >> 4) << 16) - 0x10000u - 3 * (UNIT >> 4);
        uint32_t sd = D0;
        const uint32_t toff = ((fresh_tid() & 127) << 7) + ((fresh_tid() & 7) << 4);
        const bool lane0 = (toff & 0xf80u) == 0u;
        uint32_t tbad = 0u, tw, xt = x_tag(lds32(base + OFF_EPOCH), L);
        uint32_t rsa = base + OFF_RS + (ch * 128 + tile_row(L & 1, warp & 3, 0, (toff >> 9) & 7)) * 4;
        uint32_t rsb = rsa + ((L & 1) ? 32 : 128);
        uint32_t lnm = ((toff >> 7) & 3) == (L & 1) ? 0xffffffffu : 0u, tmk = L > 0;
        uint32_t soff = tile_row(L & 1, warp & 3, (toff >> 10) & 1, (toff >> 7) & 7) * 128 + ((toff ^ (toff >> 7)) & 0x10u) + (toff & 0x60u);
        uint32_t bprep = bars + 8u * (B_PREP + ch), bturn = bars + 8u * (B_TURN + (ch ^ 1));
        uint32_t bfree = bars + 8u * (inst == 1 ? B_CSD : B_RDONE), pfree = inst == 1 ? 0 : inst & 1, pprep = L & 1;
        asm volatile("" : "+r"(rsa), "+r"(rsb), "+r"(lnm), "+r"(soff), "+r"(xt), "+r"(tmk));
        asm volatile("" : "+r"(bprep), "+r"(bturn), "+r"(bfree), "+r"(pfree), "+r"(pprep));
        if (inst == 1 || (inst > 1 && q_split(inst - 1) < 16)) mbar_wait_lazy<TLAZY>(bars + 8u * (B_TURN + ch), (turn_par(0) >> inst) & 1u);
        if (L == 3) GTL(37);
        mbar_wait(bars + 8u * B_QF, 0);
        GTL(1 + L * 8);
        {
          const uint64_t da = desc_lo(sd) + P.zero;
          wgmma_fence();
          wgmma_n192_ssz_ta0_tb1(acc[1], da + (UNIT >> 4), da + DB);
          wgmma_commit();
          wgmma_n192_ssz_ta0_tb1(acc[0], da, da + DB);
          wgmma_commit();
        }
#pragma unroll 1
        for (int kt = 0; kt < 15; kt++) {
          const bool last = kt + 1 == ksp;
          const uint64_t da = desc_lo(sd) + P.zero;
          const uint32_t fn = bars + 8u * (B_QF + ((kt + 1) & 3)), pn = ((kt + 1) >> 2) & 1;
#pragma unroll
          for (int k16 = 0; k16 < 4; k16++) {
            if (k16 == 0 && kt == 0) continue;
            wgmma_fence();
            wgmma_n192_ss_ta0_tb1(acc[1], da + ((UNIT >> 4) + k16 * 2), da + (DB + k16 * 128), 1);
            wgmma_commit();
            wgmma_wait<1>();
            if (k16 == 0 && lane0 && kt != ksp) mbar_arrive(bars + 8u * (B_QF + B_E + ((kt - 1) & 3)));
            wgmma_fence();
            wgmma_n192_ss_ta0_tb1(acc[0], da + k16 * 2, da + (DB + k16 * 128), 1);
            wgmma_commit();
            if (k16 == 1) tw = lds32(((sd & 0xffffu) << 4) + toff);
            if (k16 == 2) tbad |= tw ^ xt;
            bool ok = true;
            if (k16 == 2) ok = mbar_test(fn, pn) || last;
            if (k16 == QTURN && last && lane0) mbar_arrive(bturn);
            if (k16 < 3) wgmma_wait<1>();
            if (k16 == 2 && !ok) mbar_wait(fn, pn);
          }
          sd = sd == D0 + 3 * STG ? D0 : sd + STG;
          if (last) {
            wgmma_wait<0>();
            if (lane0) mbar_arrive(bars + 8u * (B_QF + B_E + (kt & 3)));
            mbar_wait_lazy<TLAZY>(bars + 8u * (B_TURN + ch), (turn_par(1) >> inst) & 1u);
            mbar_wait(fn, pn);
          }
        }
        constexpr uint32_t DL = D0 + 3 * STG;
        wgmma_fence();
#pragma unroll
        for (int k16 = 0; k16 < 4; k16++) wgmma_n192_ss_ta0_tb1(acc[1], desc_lo(DL + (UNIT >> 4) + k16 * 2), desc_lo(DL + DB + k16 * 128), 1);
        wgmma_commit();
        tw = lds32(((DL & 0xffffu) << 4) + toff);
        mbar_wait(bprep, pprep);
        uint32_t rs[2][2];
        constexpr uint64_t DCS = (uint64_t)((base + OFF_CS) >> 4) | (4ull << 32);
        auto ln_mma = [&](float (&d)[96], uint32_t (&r)[2], int h) {
          uint32_t a[4];
#pragma unroll
          for (int i = 0; i < 2; i++) {
            if (h) r[i] = lds32((i ? rsb : rsa) + 256);
            a[i] = (__byte_perm(r[i], 0u, 0x1010) ^ 0x80008000u) & lnm;
            a[i + 2] = r[i] & P.zero;
          }
#pragma unroll
          for (int i = 0; i < 4; i++) asm volatile("" : "+r"(a[i]));
          wgmma_fence();
          wgmma_n192_rs_tb1(d, a, DCS, 1);
          wgmma_commit();
        };
        ln_mma(acc[1], rs[1], 1);
        wgmma_wait<2>();
        if (lane0 && ksp != 15) mbar_arrive(bars + 8u * (B_QF + B_E + 2));
        wgmma_fence();
#pragma unroll
        for (int k16 = 0; k16 < 4; k16++) wgmma_n192_ss_ta0_tb1(acc[0], desc_lo(DL + k16 * 2), desc_lo(DL + DB + k16 * 128), 1);
        wgmma_commit();
        if (lane0) mbar_arrive(bturn);
        const uint32_t ep1 = lds32(base + OFF_EPOCH);
        rs[0][0] = lds32(rsa);
        rs[0][1] = lds32(rsb);
        static_assert(SP1 < 16 && (PREMASK & 1u), "column sums of B");
        const bool afree = mbar_test(bfree, pfree) & (mbar_test(bars + 8u * (B_WF + B_E + 7), 1) | (ksp == 16));
        const bool redo = named_bar_or(1 + ch, 128, (tbad | (tw ^ xt)) & tmk);
        float rinv[2];
#pragma unroll
        for (int r = 0; r < 2; r++) {
          rinv[r] = rcp_fast(bf_hi(rs[1][r]));
          asm volatile("" : "+f"(rinv[r]));
        }
        const uint32_t kdst = ((L & 1) ? KB_ROW0 : slots) + soff, vdst = ((L & 1) ? VB_ROW0 : slots + 8192) + soff;
        const uint32_t hs = (L & 1) ? 8192 : 16384, c0 = (toff & 0x180u) == 0u;
        wgmma_wait<1>();
        if (redo) {
          wgmma_wait<0>();
          constexpr uint32_t sa = (DL & 0xffffu) << 4;
          const uint32_t rb = bars + 8u * (B_REDO + ch);
          if (toff == 0) {
            mbar_init(rb, 1);
            fence_barrier_init();
          }
          uint32_t rpar = 0;
#pragma unroll 1
          for (int kt = 0, tries = 0; kt < 16;) {
            fence_proxy_async_smem();
            named_bar_sync(1 + ch, 128);
            if ((warp & 3) == 0 && elect_one()) {
                mbar_expect_tx(rb, 5 * UNIT);
              tma_load_5d(sa, &P.xq[L], rb, kt * 64, gb * 2);
              tma_load_3d(sa - 3 * UNIT, &P.wqkv3[L & 1], rb, hp * 64, kt * 64);
            }
            mbar_wait(rb, rpar);
            rpar ^= 1u;
            if (named_bar_or(1 + ch, 128, (lds32(sa + toff) ^ xt) & 1u) && ++tries < 4096) continue;
            wgmma_fence();
#pragma unroll
            for (int k16 = 0; k16 < 4; k16++) {
              const uint64_t db = make_desc(sa - 3 * UNIT + k16 * 2048, UNIT);
              wgmma_n192_ss_ta0_tb1(acc[1], make_desc(sa + UNIT + k16 * 32, 16), db, kt | k16);
              wgmma_n192_ss_ta0_tb1(acc[0], make_desc(sa + k16 * 32, 16), db, kt | k16);
            }
            wgmma_commit();
            wgmma_wait<0>();
            kt++;
          }
          ln_mma(acc[1], rs[1], 1);
          wgmma_wait<0>();
        }
        ln_mma(acc[0], rs[0], 0);
        reg_fence<96>(acc[1]);
        GTL(2 + L * 8);
        if (!afree) {
          mbar_wait(bfree, pfree);
          if (ksp < 16) mbar_wait(bars + 8u * (B_WF + B_E + 7), 1);
        }
#pragma unroll
        for (int t = 0; t < 24; t++) {
          const int h = t < 12 ? 1 : 0, p = ((t % 12) / 4 + 1) % 3, jp = t & 3;
          if (t == QREL) {
            wgmma_wait<0>();
            reg_fence<96>(acc[0]);
            if (lane0) mbar_arrive(bars + 8u * (B_QF + B_E + 3));
          }
          if (t == 8 || t == 20) {
            rinv[0] *= SM_C;
            rinv[1] *= SM_C;
          }
          const float* a = &acc[h][4 * (p * 8 + 2 * jp)];
          uint32_t r0 = pack_bf16x2(a[0] * rinv[0], a[1] * rinv[0]);
          uint32_t r1 = pack_bf16x2(a[2] * rinv[1], a[3] * rinv[1]);
          if (p != 0 && jp == 0) {
            r0 = set_tag(r0, c0, ep1);
            r1 = set_tag(r1, c0, ep1);
          }
          const uint32_t r2 = pack_bf16x2(a[4] * rinv[0], a[5] * rinv[0]);
          const uint32_t r3 = pack_bf16x2(a[6] * rinv[1], a[7] * rinv[1]);
          const uint32_t dst = p == 0 ? slots + 3 * 16384 + soff + h * 8192 : (p == 1 ? kdst : vdst) + h * hs;
          stmatrix_x4(dst ^ (jp << 5), r0, r1, r2, r3);
          if (t >= 20) {
            q[jp >> 1][jp & 1][0] = r0;
            q[jp >> 1][jp & 1][1] = r1;
            q[jp >> 1][jp & 1][2] = r2;
            q[jp >> 1][jp & 1][3] = r3;
          }
          if (t == 7 || t == 19) signal_async(bars + 8u * (t == 7 ? B_KV : B_LOC), lane0);
          if (t == 11) {
            setmaxnreg_dec<128>();
            named_bar_arrive(4, 256);
#pragma unroll
            for (int r = 0; r < 2; r++) rinv[r] = rcp_fast(bf_hi(rs[0][r]));
          }
        }
        mbar_wait(bars + 8u * B_LOC, inst & 1);
      }
      }
      GTL(3 + L * 8);
      if ((L & 1) == 0) attention_a(q, asst, L, gb, hp, ch, warp & 3, P.zero);
      else attention_b(q, asst, gb, inst & 1, warp & 3);
      GTL(4 + L * 8);
      signal_async(bars + 8u * (asst ? B_OS1 : B_OS0), (fresh_tid() & 31) == 0);
      if (asst) continue;
      GTL(5 + L * 8);

      {
        float acc[64];
        const int sp = inst < 7 ? q_split(inst + 1) : 0;
        int st = sp & 3;
        const bool pre = w_pre(inst);
        uint32_t tbad = 0u;
        const uint32_t toff = ((fresh_tid() & 63) << 7) + ((fresh_tid() & 7) << 4);
        const bool lane0 = (toff & 0xf80u) == 0u;
        constexpr uint32_t U4 = UNIT >> 4, LA = 0x10000u, LB = U4 << 16;
        reg_define<64>(acc);
        reg_fence<64>(acc);
        uint32_t xv[8][4];
        {
          PHASE_IDS_W
          const uint32_t xr = slots + 6 * UNIT + (wwarp * 16 + (lane & 15)) * 128 + (((lane >> 4) ^ (lane & 7)) << 4);
          mbar_wait(bars + 8u * B_RF, inst & 1);
#pragma unroll
          for (int jp = 0; jp < 8; jp++) ldmatrix_x4(xv[jp], (xr ^ ((jp & 3) << 5)) + (jp >> 2) * UNIT);
          signal_async(bars + 8u * B_RDONE, lane0);
          if (L > 0) {
            uint32_t lsb;
            asm volatile("ld.shared.u8 %0, [%1];" : "=r"(lsb) : "r"(base + OFF_LSB + ch * 32 + wwarp * 8 + g) : "memory");
#pragma unroll
            for (int k = 0; k < 4; k++) xv[(k >> 1) * 4][k & 1] = set_tag(xv[(k >> 1) * 4][k & 1], c == 0, lsb >> k);
          }
        }
        const unsigned ep1 = lds32(base + OFF_EPOCH);
        uint32_t tmx = L < 3 && (toff & 0x180u) == 0u, xt = x_tag(ep1, L + 1);
        uint32_t xrow = base + ((st + (pre ? 3 : 2)) & 3) * 5 * UNIT + (warp & 3) * 2048 + (toff & 0x7e0u) + ((toff ^ (toff >> 7)) & 0x10u);
        asm volatile("" : "+r"(tmx), "+r"(xt), "+r"(xrow));
        uint64_t d0 = desc_lo((base >> 4) + st * 5 * U4) + P.zero;
        if (inst < 7 || SP7 == 16) mbar_wait_lazy<TLAZY>(bars + 8u * (B_TURN + ch), (turn_par(2) >> inst) & 1u);
        mbar_wait(bars + 8u * B_WF, 0);
        GTL(6 + L * 8);
        uint32_t s1 = 0;
#pragma unroll 1
        for (int m = 0; m < 4; m++) {
          const uint32_t s0 = base + st * 5 * UNIT, fb = bars + 8u * (B_WF + 4 * (m & 1));
          s1 = base + ((st + 1) & 3) * 5 * UNIT;
          const uint64_t d1 = desc_lo(s1 >> 4) + P.zero;
          const uint64_t d2 = desc_lo((pre ? slots + m * 2 * UNIT : base + ((st + 2) & 3) * 5 * UNIT) >> 4) + P.zero;
          st = (st + (pre ? 2 : 3)) & 3;
#pragma unroll
          for (int i = 0; i < 4; i++) {
            const uint64_t da = (i == 0 ? d0 : d1) + (LA + (i == 2 ? 1 : (i == 3 ? 4 : 0)) * U4);
            const uint64_t db = (i < 2 ? d0 : (i == 2 ? d1 : d2)) + (LB + (i == 0 ? 1 : (i == 1 ? 3 : (i == 2 ? 2 : 0))) * U4);
            if (i == 3 && (m == 0 || m == 3) && pre) mbar_wait(bars + 8u * (m ? B_PRE2 : B_PRE), __popc(PREMASK & ((1u << inst) - 1u)) & 1);
            if (i == (WTURN & 3) && m == 3 && lane0 && (sp < 16 || inst == 6)) mbar_arrive(bars + 8u * (B_TURN + (ch ^ 1)));
            wgmma_fence();
#pragma unroll
            for (int k16 = 0; k16 < 4; k16++) wgmma_n128_ss_ta0_tb1(acc, da + 2 * k16, db + 128 * k16, 1);
            wgmma_commit();
            if (i == 2) d0 = desc_lo((base >> 4) + st * 5 * U4) + P.zero;
            tbad |= lds32((i == 0 ? s0 : s1) + (i == 2 ? 1 : (i == 3 ? 4 : 0)) * UNIT + toff) ^ o_tag(L);
            const uint32_t fn = i < 3 ? fb + 8u * (i + 1) : fb ^ 96u;
            const uint32_t pn = i < 3 ? m >> 1 : m > 0;
            const bool ok = mbar_test(fn, pn) || (i == 3 && m == 3);
            wgmma_wait<1>();
            if (lane0 && (i > 0 || m > 0)) mbar_arrive((i > 0 ? fb + 8u * (i - 1) : (fb ^ 96u) + 24u) + 8u * B_E);
            if (!ok) mbar_wait(fn, pn);
          }
        }
        const bool redo = named_bar_or(1 + ch, 128, tbad & 1u);
        if (redo) {
          wgmma_wait<0>();
          const uint32_t sa = s1 + 4 * UNIT, sb = s1 + 2 * UNIT;
          const uint32_t rb = bars + 8u * (B_REDO + ch);
          if ((fresh_tid() & 127) == 0) {
            mbar_init(rb, 1);
            fence_barrier_init();
          }
          uint32_t rpar = 0;
#pragma unroll 1
          for (int kt = 0, tries = 0; kt < 16;) {
            fence_proxy_async_smem();
            named_bar_sync(1 + ch, 128);
            if ((warp & 3) == 0 && elect_one()) {
                mbar_expect_tx(rb, 3 * UNIT);
              tma_load_2d(sa, &P.o, rb, kt * 64, ch * 1024 + rt * 64);
              tma_load_3d(sb, &P.wo3[L & 1], rb, ct * 128, kt * 64);
            }
            mbar_wait(rb, rpar);
            rpar ^= 1u;
            if (named_bar_or(1 + ch, 128, (lds32(sa + toff) ^ o_tag(L)) & 1u) && ++tries < 4096) continue;
            wgmma_fence();
#pragma unroll
            for (int k16 = 0; k16 < 4; k16++)
              wgmma_n128_ss_ta0_tb1(acc, make_desc(sa + k16 * 32, 16), make_desc(sb + k16 * 2048, UNIT), kt | k16);
            wgmma_commit();
            wgmma_wait<0>();
            kt++;
          }
        }
        wgmma_wait<0>();
        reg_fence<64>(acc);
        if (lane0) mbar_arrive(bars + 8u * (B_WF + B_E + 7));
        GTL(7 + L * 8);
#pragma unroll
        for (int jp = 0; jp < 8; jp++) {
#pragma unroll
          for (int q = 0; q < 4; q++) xv[jp][q] = add_bf16x2(xv[jp][q], pack_bf16x2(acc[8 * jp + 2 * q], acc[8 * jp + 2 * q + 1]));
          const bool tg = (jp & 3) == 0;
          stmatrix_x4((xrow ^ ((jp & 3) << 5)) + (jp >> 2) * UNIT,
                      tg ? set_tag(xv[jp][0], tmx, xt) : xv[jp][0], tg ? set_tag(xv[jp][1], tmx, xt) : xv[jp][1], xv[jp][2], xv[jp][3]);
          if ((jp & 3) == 3) signal_async(bars + 8u * (B_XS + (jp >> 2)), lane0);
        }
        if (L < 3) {
          PHASE_IDS_W
          const int grow = ch * 1024 + rt * 64;
          if (c == 0)
            asm volatile("st.shared.u8 [%0], %1;" ::"r"(base + OFF_LSB + ch * 32 + wwarp * 8 + g),
                         "r"((xv[0][0] & 1u) | ((xv[0][1] & 1u) << 1) | ((xv[4][0] & 1u) << 2) | ((xv[4][1] & 1u) << 3)) : "memory");
          float s1[2] = {0.f, 0.f}, s2[2] = {0.f, 0.f};
#pragma unroll
          for (int jp = 0; jp < 8; jp++)
#pragma unroll
            for (int q = 0; q < 4; q++) {
              const float x0 = bf_lo(xv[jp][q]), x1 = bf_hi(xv[jp][q]);
              s1[q & 1] += x0 + x1;
              s2[q & 1] = fmaf(x0, x0, fmaf(x1, x1, s2[q & 1]));
            }
#pragma unroll
          for (int r = 0; r < 2; r++) {
            s1[r] += __shfl_xor_sync(0xffffffffu, s1[r], 1);
            s2[r] += __shfl_xor_sync(0xffffffffu, s2[r], 1);
            s1[r] += __shfl_xor_sync(0xffffffffu, s1[r], 2);
            s2[r] += __shfl_xor_sync(0xffffffffu, s2[r], 2);
            if (c == 0) st_rec(&g_stats[L + 1][ct][grow + wwarp * 16 + g + 8 * r], s1[r], s2[r], 0.f, ep1);
          }
        }
        GTL(8 + L * 8);
      }
    }
    if (threadIdx.x == 128) atomicAdd(g_done, 1u);
  }
}

typedef CUresult (*PFN_tmEncode)(CUtensorMap*, CUtensorMapDataType, cuuint32_t, void*, const cuuint64_t*,
                                 const cuuint64_t*, const cuuint32_t*, const cuuint32_t*, CUtensorMapInterleave,
                                 CUtensorMapSwizzle, CUtensorMapL2promotion, CUtensorMapFloatOOBfill);

PFN_tmEncode get_encode_fn() {
  static PFN_tmEncode fn = nullptr;
  if (!fn) {
    cudaDriverEntryPointQueryResult qr;
    void* p = nullptr;
    cudaGetDriverEntryPoint("cuTensorMapEncodeTiled", &p, cudaEnableDefault, &qr);
    fn = (PFN_tmEncode)p;
  }
  return fn;
}

CUtensorMap make_map(const void* ptr, int rows, int cols) {
  CUtensorMap m;
  cuuint64_t gdim[2] = {(cuuint64_t)cols, (cuuint64_t)rows};
  cuuint64_t gstr[1] = {(cuuint64_t)cols * 2};
  cuuint32_t box[2] = {64, 64};
  cuuint32_t estr[2] = {1, 1};
  get_encode_fn()(&m, CU_TENSOR_MAP_DATA_TYPE_BFLOAT16, 2, const_cast<void*>(ptr), gdim, gstr, box, estr,
                  CU_TENSOR_MAP_INTERLEAVE_NONE, CU_TENSOR_MAP_SWIZZLE_128B, CU_TENSOR_MAP_L2_PROMOTION_L2_128B,
                  CU_TENSOR_MAP_FLOAT_OOB_FILL_NONE);
  return m;
}

CUtensorMap make_map3(const void* ptr, int rows, int cols, int n, int step) {
  CUtensorMap m;
  cuuint64_t gdim[3] = {(cuuint64_t)(cols - (n - 1) * step), (cuuint64_t)rows, (cuuint64_t)n};
  cuuint64_t gstr[2] = {(cuuint64_t)cols * 2, (cuuint64_t)step * 2};
  cuuint32_t box[3] = {64, 64, (cuuint32_t)n};
  cuuint32_t estr[3] = {1, 1, 1};
  get_encode_fn()(&m, CU_TENSOR_MAP_DATA_TYPE_BFLOAT16, 3, const_cast<void*>(ptr), gdim, gstr, box, estr,
                  CU_TENSOR_MAP_INTERLEAVE_NONE, CU_TENSOR_MAP_SWIZZLE_128B, CU_TENSOR_MAP_L2_PROMOTION_L2_128B,
                  CU_TENSOR_MAP_FLOAT_OOB_FILL_NONE);
  return m;
}

CUtensorMap make_map_q(const void* ptr, int sw, int sr) {
  CUtensorMap m;
  cuuint64_t gdim[5] = {DM, 8, 2, 4, S_LEN / 64};
  cuuint64_t gstr[4] = {DM * 2, (cuuint64_t)sr * DM * 2, (cuuint64_t)sw * DM * 2, 64 * DM * 2};
  cuuint32_t box[5] = {64, 8, 2, 4, 2};
  cuuint32_t estr[5] = {1, 1, 1, 1, 1};
  get_encode_fn()(&m, CU_TENSOR_MAP_DATA_TYPE_BFLOAT16, 5, const_cast<void*>(ptr), gdim, gstr, box, estr,
                  CU_TENSOR_MAP_INTERLEAVE_NONE, CU_TENSOR_MAP_SWIZZLE_128B, CU_TENSOR_MAP_L2_PROMOTION_L2_128B,
                  CU_TENSOR_MAP_FLOAT_OOB_FILL_NONE);
  return m;
}

}

extern "C" void kernel_launch(void* const* d_in, const int* in_sizes, int n_in, void* d_out, int out_size) {
  (void)in_sizes; (void)n_in; (void)out_size;
  void *p_o, *p_x;
  cudaGetSymbolAddress(&p_o, g_o);
  cudaGetSymbolAddress(&p_x, g_x);
  static bool attr_done = false;
  if (!attr_done) {
    cudaFuncSetAttribute(fused_kernel, cudaFuncAttributeMaxDynamicSharedMemorySize, SMEM_BYTES);
    attr_done = true;
  }
  Params P;
  P.in_x = (const __nv_bfloat16*)d_in[0];
  P.wqkv_p[0] = (const __nv_bfloat16*)d_in[1];
  P.wo_p[0] = (const __nv_bfloat16*)d_in[2];
  P.wqkv_p[1] = (const __nv_bfloat16*)d_in[4];
  P.wo_p[1] = (const __nv_bfloat16*)d_in[5];
  P.out = (__nv_bfloat16*)d_out;
  P.zero = 0;
  for (int L = 0; L < 5; L++) {
    const void* px = L == 0 ? (const void*)P.in_x : (L == 4 ? d_out : p_x);
    P.x[L] = make_map(px, S_LEN, DM);
    if (L < 4) P.xq[L] = (L & 1) ? make_map_q(px, 16, 8) : make_map_q(px, 8, 32);
  }
  P.o = make_map(p_o, S_LEN, DM);
  for (int t = 0; t < 2; t++) {
    P.wqkv[t] = make_map(P.wqkv_p[t], DM, NQKV);
    P.wqkv3[t] = make_map3(P.wqkv_p[t], DM, NQKV, 3, 1024);
    P.wo3[t] = make_map3(P.wo_p[t], DM, DM, 2, 64);
  }
  fused_kernel<<<NCTA, 512, SMEM_BYTES>>>(P);
}
```

```cpp
#include <cuda_runtime.h>
#include <cuda_bf16.h>
#include <cuda.h>
#include <stdint.h>

namespace {

constexpr int S_LEN = 2048;
constexpr int DM = 1024;
constexpr int NQKV = 3072;
constexpr int NCTA = 128;

__device__ __align__(1024) uint8_t g_kvA[2][16][16][2][16384];
__device__ __align__(1024) uint8_t g_kvB[2][16][16][4096];
__device__ __align__(1024) uint8_t g_zero[16384];
__device__ __align__(1024) __nv_bfloat16 g_o[S_LEN * DM];
__device__ __align__(1024) __nv_bfloat16 g_x[S_LEN * DM];
__device__ __align__(1024) float4 g_stats[4][8][S_LEN];
__device__ __align__(1024) float4 g_cs[2][16][8][64];
__device__ __align__(128) unsigned g_fx[16][16][4];
__device__ __align__(128) unsigned g_fo[32][16][4];
__device__ __align__(128) unsigned g_fk[16][16][4];
__device__ __align__(128) unsigned g_done[32];

constexpr uint32_t SBASE = 1024;
constexpr int UNIT = 8192;
constexpr int NUNITS = 20;
constexpr int OFF_SLOT = NUNITS * UNIT;
constexpr int OFF_BAR = OFF_SLOT + 4 * 16384;
constexpr int OFF_EPOCH = OFF_BAR + 424;
constexpr int OFF_LSB = OFF_BAR + 432;
constexpr int OFF_CS = OFF_BAR + 496;
constexpr int OFF_RS = OFF_CS + 1536;
constexpr int OFF_ONE = OFF_RS + 1024;
constexpr int SMEM_BYTES = OFF_ONE + 16;
constexpr int B_QF = 0, B_WF = 4, B_RF = 12, B_E = 13, B_PREP = 26, B_LOC = 28, B_HALO = 29, B_REL = 33, B_OS0 = 36,
              B_TURN = 37, B_XS = 39, B_CS = 41, B_CSD = 42, B_GO = 43, B_PRE = 44, B_HV = 45, B_REDO = 46,
              B_RDONE = 48, B_PRE2 = 49, B_HL = 50, B_KV = 52, B_OS1 = B_GO;
static_assert(SMEM_BYTES <= 232448, "shared memory");

__device__ __forceinline__ uint32_t smem_u32(const void* p) { return (uint32_t)__cvta_generic_to_shared(p); }

__device__ __forceinline__ void mbar_init(uint32_t bar, uint32_t cnt) {
  asm volatile("mbarrier.init.shared::cta.b64 [%0], %1;" ::"r"(bar), "r"(cnt));
}
__device__ __forceinline__ void mbar_expect_tx(uint32_t bar, uint32_t bytes) {
  asm volatile("mbarrier.arrive.expect_tx.shared::cta.b64 _, [%0], %1;" ::"r"(bar), "r"(bytes) : "memory");
}
__device__ __forceinline__ void mbar_arrive(uint32_t bar) {
  asm volatile("mbarrier.arrive.shared::cta.b64 _, [%0];" ::"r"(bar) : "memory");
}
__device__ __forceinline__ bool mbar_try_wait(uint32_t bar, uint32_t parity) {
  uint32_t ok;
  asm volatile(
      "{\n.reg .pred p;\nmbarrier.try_wait.parity.shared::cta.b64 p, [%1], %2;\nselp.b32 %0, 1, 0, p;\n}\n"
      : "=r"(ok)
      : "r"(bar), "r"(parity)
      : "memory");
  return ok != 0;
}
__device__ __forceinline__ bool mbar_test(uint32_t bar, uint32_t parity) {
  uint32_t ok;
  asm volatile(
      "{\n.reg .pred p;\nmbarrier.test_wait.parity.shared::cta.b64 p, [%1], %2;\nselp.b32 %0, 1, 0, p;\n}\n"
      : "=r"(ok)
      : "r"(bar), "r"(parity)
      : "memory");
  return ok != 0;
}
__device__ __forceinline__ void mbar_wait(uint32_t bar, uint32_t parity) {
#pragma unroll 1
  for (uint32_t it = 0; it < (1u << 18); ++it) {
    if (mbar_try_wait(bar, parity)) return;
  }
}
__device__ __forceinline__ void mbar_pace(uint32_t bar, uint32_t parity) {
#pragma unroll 1
  for (uint32_t it = 0; it < 24; ++it) {
    if (mbar_try_wait(bar, parity)) return;
  }
}
template <int NS>
__device__ __forceinline__ void mbar_wait_lazy(uint32_t bar, uint32_t parity) {
#pragma unroll 1
  for (uint32_t it = 0; it < (1u << 18); ++it) {
    if (mbar_try_wait(bar, parity)) return;
    __nanosleep(NS);
  }
}
__device__ __forceinline__ bool elect_one() {
  uint32_t ok;
  asm volatile("{\n.reg .pred p;\nelect.sync _|p, 0xffffffff;\nselp.b32 %0, 1, 0, p;\n}\n" : "=r"(ok));
  return ok != 0;
}
__device__ __forceinline__ void fence_barrier_init() { asm volatile("fence.mbarrier_init.release.cluster;" ::: "memory"); }
__device__ __forceinline__ void fence_proxy_async_smem() { asm volatile("fence.proxy.async.shared::cta;" ::: "memory"); }

__device__ __forceinline__ void signal_async(uint32_t bar, bool lane0) {
  fence_proxy_async_smem();
  __syncwarp();
  asm volatile("{\n.reg .pred p;\nsetp.ne.b32 p, %1, 0;\n@p mbarrier.arrive.shared::cta.b64 _, [%0];\n}\n" ::"r"(bar), "r"((int)lane0) : "memory");
}
template <class T>
__device__ __forceinline__ void pin64(T*& p) { asm volatile("" : "+l"(p)); }

__device__ __forceinline__ void tma_load_2d(uint32_t dst, const CUtensorMap* map, uint32_t bar, int c0, int c1) {
  asm volatile(
      "cp.async.bulk.tensor.2d.shared::cluster.global.mbarrier::complete_tx::bytes [%0], [%1, {%3, %4}], [%2];" ::"r"(dst),
      "l"(map), "r"(bar), "r"(c0), "r"(c1)
      : "memory");
}
__device__ __forceinline__ void tma_load_3d(uint32_t dst, const CUtensorMap* map, uint32_t bar, int c0, int c1) {
  asm volatile(
      "cp.async.bulk.tensor.3d.shared::cluster.global.mbarrier::complete_tx::bytes [%0], [%1, {%3, %4, %5}], [%2];" ::"r"(dst),
      "l"(map), "r"(bar), "r"(c0), "r"(c1), "r"(0)
      : "memory");
}
__device__ __forceinline__ void tma_load_5d(uint32_t dst, const CUtensorMap* map, uint32_t bar, int c0, int c4) {
  asm volatile(
      "cp.async.bulk.tensor.5d.shared::cluster.global.mbarrier::complete_tx::bytes [%0], [%1, {%3, %5, %5, %5, %4}], [%2];" ::"r"(dst),
      "l"(map), "r"(bar), "r"(c0), "r"(c4), "r"(0)
      : "memory");
}
__device__ __forceinline__ void bulk_load(uint32_t dst, const void* src, uint32_t bytes, uint32_t bar) {
  asm volatile("cp.async.bulk.shared::cluster.global.mbarrier::complete_tx::bytes [%0], [%1], %2, [%3];" ::"r"(dst),
               "l"(src), "r"(bytes), "r"(bar)
               : "memory");
}
__device__ __forceinline__ void bulk_store(void* dst, uint32_t src, uint32_t bytes) {
  asm volatile("cp.async.bulk.global.shared::cta.bulk_group [%0], [%1], %2;" ::"l"(dst), "r"(src), "r"(bytes) : "memory");
}
__device__ __forceinline__ void tma_store_2d(const CUtensorMap* map, uint32_t src, int c0, int c1) {
  asm volatile("cp.async.bulk.tensor.2d.global.shared::cta.bulk_group [%0, {%2, %3}], [%1];" ::"l"(map), "r"(src),
               "r"(c0), "r"(c1)
               : "memory");
}
__device__ __forceinline__ void bulk_announce(unsigned* p) {
  asm volatile("cp.reduce.async.bulk.global.shared::cta.bulk_group.add.u32 [%0], [%1], 16;" ::"l"(p), "r"(SBASE + OFF_ONE) : "memory");
}
__device__ __forceinline__ void bulk_commit() { asm volatile("cp.async.bulk.commit_group;" ::: "memory"); }
__device__ __forceinline__ void bulk_wait_read0() { asm volatile("cp.async.bulk.wait_group.read 0;" ::: "memory"); }
__device__ __forceinline__ void bulk_wait0() { asm volatile("cp.async.bulk.wait_group 0;" ::: "memory"); }
__device__ __forceinline__ void named_bar_sync(int id, int nthreads) {
  asm volatile("bar.sync %0, %1;" ::"r"(id), "r"(nthreads) : "memory");
}
__device__ __forceinline__ void named_bar_arrive(int id, int nthreads) {
  asm volatile("bar.arrive %0, %1;" ::"r"(id), "r"(nthreads) : "memory");
}

__device__ __forceinline__ bool named_bar_or(int id, int nthreads, bool v) {
  uint32_t r;
  asm volatile("{\n.reg .pred p, q;\nsetp.ne.b32 q, %3, 0;\nbar.red.or.pred p, %1, %2, q;\nselp.b32 %0, 1, 0, p;\n}\n"
               : "=r"(r) : "r"(id), "r"(nthreads), "r"((int)v) : "memory");
  return __any_sync(0xffffffffu, r != 0);
}

__device__ __forceinline__ void wgmma_fence() { asm volatile("wgmma.fence.sync.aligned;\n" ::: "memory"); }
__device__ __forceinline__ void wgmma_commit() { asm volatile("wgmma.commit_group.sync.aligned;\n" ::: "memory"); }
template <int N>
__device__ __forceinline__ void wgmma_wait() {
  asm volatile("wgmma.wait_group.sync.aligned %0;\n" ::"n"(N) : "memory");
}
template <int R>
__device__ __forceinline__ void setmaxnreg_inc() { asm volatile("setmaxnreg.inc.sync.aligned.u32 %0;\n" ::"n"(R)); }
template <int R>
__device__ __forceinline__ void setmaxnreg_dec() { asm volatile("setmaxnreg.dec.sync.aligned.u32 %0;\n" ::"n"(R)); }
template <int N>
__device__ __forceinline__ void reg_fence(float* r) {
#pragma unroll
  for (int i = 0; i < N; i++) asm volatile("" : "+f"(r[i])::"memory");
}

template <int N>
__device__ __forceinline__ void reg_define(float* r) {
#pragma unroll
  for (int i = 0; i < N; i++) r[i] = 0.f;
}

__device__ __forceinline__ uint64_t desc_lo(uint32_t lo) {
  uint64_t d;
  asm("mov.b64 %0, {%1, %2};" : "=l"(d) : "r"(lo), "r"(0x40000040u));
  return d;
}
__device__ __forceinline__ uint64_t make_desc(uint32_t addr, uint32_t lbo_bytes) {
  return desc_lo((addr >> 4) + ((lbo_bytes >> 4) << 16));
}

__device__ __forceinline__ void wgmma_n192_ss_ta0_tb1(float* d, uint64_t descA, uint64_t descB, int scaleD) {
  asm volatile("{\n.reg .pred p;\nsetp.ne.b32 p, %98, 0;\n"
    "wgmma.mma_async.sync.aligned.m64n192k16.f32.bf16.bf16 {%0, %1, %2, %3, %4, %5, %6, %7, %8, %9, %10, %11, %12, %13, %14, %15, %16, %17, %18, %19, %20, %21, %22, %23, %24, %25, %26, %27, %28, %29, %30, %31, %32, %33, %34, %35, %36, %37, %38, %39, %40, %41, %42, %43, %44, %45, %46, %47, %48, %49, %50, %51, %52, %53, %54, %55, %56, %57, %58, %59, %60, %61, %62, %63, %64, %65, %66, %67, %68, %69, %70, %71, %72, %73, %74, %75, %76, %77, %78, %79, %80, %81, %82, %83, %84, %85, %86, %87, %88, %89, %90, %91, %92, %93, %94, %95}, %96, %97, p, 1, 1, 0, 1;\n}\n"
    : "+f"(d[0]), "+f"(d[1]), "+f"(d[2]), "+f"(d[3]), "+f"(d[4]), "+f"(d[5]), "+f"(d[6]), "+f"(d[7]), "+f"(d[8]), "+f"(d[9]), "+f"(d[10]), "+f"(d[11]), "+f"(d[12]), "+f"(d[13]), "+f"(d[14]), "+f"(d[15]), "+f"(d[16]), "+f"(d[17]), "+f"(d[18]), "+f"(d[19]), "+f"(d[20]), "+f"(d[21]), "+f"(d[22]), "+f"(d[23]), "+f"(d[24]), "+f"(d[25]), "+f"(d[26]), "+f"(d[27]), "+f"(d[28]), "+f"(d[29]), "+f"(d[30]), "+f"(d[31]), "+f"(d[32]), "+f"(d[33]), "+f"(d[34]), "+f"(d[35]), "+f"(d[36]), "+f"(d[37]), "+f"(d[38]), "+f"(d[39]), "+f"(d[40]), "+f"(d[41]), "+f"(d[42]), "+f"(d[43]), "+f"(d[44]), "+f"(d[45]), "+f"(d[46]), "+f"(d[47]), "+f"(d[48]), "+f"(d[49]), "+f"(d[50]), "+f"(d[51]), "+f"(d[52]), "+f"(d[53]), "+f"(d[54]), "+f"(d[55]), "+f"(d[56]), "+f"(d[57]), "+f"(d[58]), "+f"(d[59]), "+f"(d[60]), "+f"(d[61]), "+f"(d[62]), "+f"(d[63]), "+f"(d[64]), "+f"(d[65]), "+f"(d[66]), "+f"(d[67]), "+f"(d[68]), "+f"(d[69]), "+f"(d[70]), "+f"(d[71]), "+f"(d[72]), "+f"(d[73]), "+f"(d[74]), "+f"(d[75]), "+f"(d[76]), "+f"(d[77]), "+f"(d[78]), "+f"(d[79]), "+f"(d[80]), "+f"(d[81]), "+f"(d[82]), "+f"(d[83]), "+f"(d[84]), "+f"(d[85]), "+f"(d[86]), "+f"(d[87]), "+f"(d[88]), "+f"(d[89]), "+f"(d[90]), "+f"(d[91]), "+f"(d[92]), "+f"(d[93]), "+f"(d[94]), "+f"(d[95])
    : "l"(descA), "l"(descB), "r"(scaleD));
}

__device__ __forceinline__ void wgmma_n128_ss_ta0_tb1(float* d, uint64_t descA, uint64_t descB, int scaleD) {
  asm volatile("{\n.reg .pred p;\nsetp.ne.b32 p, %66, 0;\n"
    "wgmma.mma_async.sync.aligned.m64n128k16.f32.bf16.bf16 {%0, %1, %2, %3, %4, %5, %6, %7, %8, %9, %10, %11, %12, %13, %14, %15, %16, %17, %18, %19, %20, %21, %22, %23, %24, %25, %26, %27, %28, %29, %30, %31, %32, %33, %34, %35, %36, %37, %38, %39, %40, %41, %42, %43, %44, %45, %46, %47, %48, %49, %50, %51, %52, %53, %54, %55, %56, %57, %58, %59, %60, %61, %62, %63}, %64, %65, p, 1, 1, 0, 1;\n}\n"
    : "+f"(d[0]), "+f"(d[1]), "+f"(d[2]), "+f"(d[3]), "+f"(d[4]), "+f"(d[5]), "+f"(d[6]), "+f"(d[7]), "+f"(d[8]), "+f"(d[9]), "+f"(d[10]), "+f"(d[11]), "+f"(d[12]), "+f"(d[13]), "+f"(d[14]), "+f"(d[15]), "+f"(d[16]), "+f"(d[17]), "+f"(d[18]), "+f"(d[19]), "+f"(d[20]), "+f"(d[21]), "+f"(d[22]), "+f"(d[23]), "+f"(d[24]), "+f"(d[25]), "+f"(d[26]), "+f"(d[27]), "+f"(d[28]), "+f"(d[29]), "+f"(d[30]), "+f"(d[31]), "+f"(d[32]), "+f"(d[33]), "+f"(d[34]), "+f"(d[35]), "+f"(d[36]), "+f"(d[37]), "+f"(d[38]), "+f"(d[39]), "+f"(d[40]), "+f"(d[41]), "+f"(d[42]), "+f"(d[43]), "+f"(d[44]), "+f"(d[45]), "+f"(d[46]), "+f"(d[47]), "+f"(d[48]), "+f"(d[49]), "+f"(d[50]), "+f"(d[51]), "+f"(d[52]), "+f"(d[53]), "+f"(d[54]), "+f"(d[55]), "+f"(d[56]), "+f"(d[57]), "+f"(d[58]), "+f"(d[59]), "+f"(d[60]), "+f"(d[61]), "+f"(d[62]), "+f"(d[63])
    : "l"(descA), "l"(descB), "r"(scaleD));
}

__device__ __forceinline__ void wgmma_n192_ssz_ta0_tb1(float* d, uint64_t descA, uint64_t descB) {
  asm volatile("{\n.reg .pred p;\nsetp.ne.b32 p, 0, 0;\n"
    "wgmma.mma_async.sync.aligned.m64n192k16.f32.bf16.bf16 {%0, %1, %2, %3, %4, %5, %6, %7, %8, %9, %10, %11, %12, %13, %14, %15, %16, %17, %18, %19, %20, %21, %22, %23, %24, %25, %26, %27, %28, %29, %30, %31, %32, %33, %34, %35, %36, %37, %38, %39, %40, %41, %42, %43, %44, %45, %46, %47, %48, %49, %50, %51, %52, %53, %54, %55, %56, %57, %58, %59, %60, %61, %62, %63, %64, %65, %66, %67, %68, %69, %70, %71, %72, %73, %74, %75, %76, %77, %78, %79, %80, %81, %82, %83, %84, %85, %86, %87, %88, %89, %90, %91, %92, %93, %94, %95}, %96, %97, p, 1, 1, 0, 1;\n}\n"
    : "=f"(d[0]), "=f"(d[1]), "=f"(d[2]), "=f"(d[3]), "=f"(d[4]), "=f"(d[5]), "=f"(d[6]), "=f"(d[7]), "=f"(d[8]), "=f"(d[9]), "=f"(d[10]), "=f"(d[11]), "=f"(d[12]), "=f"(d[13]), "=f"(d[14]), "=f"(d[15]), "=f"(d[16]), "=f"(d[17]), "=f"(d[18]), "=f"(d[19]), "=f"(d[20]), "=f"(d[21]), "=f"(d[22]), "=f"(d[23]), "=f"(d[24]), "=f"(d[25]), "=f"(d[26]), "=f"(d[27]), "=f"(d[28]), "=f"(d[29]), "=f"(d[30]), "=f"(d[31]), "=f"(d[32]), "=f"(d[33]), "=f"(d[34]), "=f"(d[35]), "=f"(d[36]), "=f"(d[37]), "=f"(d[38]), "=f"(d[39]), "=f"(d[40]), "=f"(d[41]), "=f"(d[42]), "=f"(d[43]), "=f"(d[44]), "=f"(d[45]), "=f"(d[46]), "=f"(d[47]), "=f"(d[48]), "=f"(d[49]), "=f"(d[50]), "=f"(d[51]), "=f"(d[52]), "=f"(d[53]), "=f"(d[54]), "=f"(d[55]), "=f"(d[56]), "=f"(d[57]), "=f"(d[58]), "=f"(d[59]), "=f"(d[60]), "=f"(d[61]), "=f"(d[62]), "=f"(d[63]), "=f"(d[64]), "=f"(d[65]), "=f"(d[66]), "=f"(d[67]), "=f"(d[68]), "=f"(d[69]), "=f"(d[70]), "=f"(d[71]), "=f"(d[72]), "=f"(d[73]), "=f"(d[74]), "=f"(d[75]), "=f"(d[76]), "=f"(d[77]), "=f"(d[78]), "=f"(d[79]), "=f"(d[80]), "=f"(d[81]), "=f"(d[82]), "=f"(d[83]), "=f"(d[84]), "=f"(d[85]), "=f"(d[86]), "=f"(d[87]), "=f"(d[88]), "=f"(d[89]), "=f"(d[90]), "=f"(d[91]), "=f"(d[92]), "=f"(d[93]), "=f"(d[94]), "=f"(d[95])
    : "l"(descA), "l"(descB));
}

__device__ __forceinline__ void wgmma_n8_ss_ta1_tb0(float* d, uint64_t descA, uint64_t descB, int scaleD) {
  asm volatile("{\n.reg .pred p;\nsetp.ne.b32 p, %6, 0;\n"
    "wgmma.mma_async.sync.aligned.m64n8k16.f32.bf16.bf16 {%0, %1, %2, %3}, %4, %5, p, 1, 1, 1, 0;\n}\n"
    : "+f"(d[0]), "+f"(d[1]), "+f"(d[2]), "+f"(d[3])
    : "l"(descA), "l"(descB), "r"(scaleD));
}

__device__ __forceinline__ void wgmma_n8_ssz_ta1_tb0(float* d, uint64_t descA, uint64_t descB) {
  asm volatile("{\n.reg .pred p;\nsetp.ne.b32 p, 0, 0;\n"
    "wgmma.mma_async.sync.aligned.m64n8k16.f32.bf16.bf16 {%0, %1, %2, %3}, %4, %5, p, 1, 1, 1, 0;\n}\n"
    : "=f"(d[0]), "=f"(d[1]), "=f"(d[2]), "=f"(d[3])
    : "l"(descA), "l"(descB));
}

__device__ __forceinline__ void wgmma_n192_rs_tb1(float* d, const uint32_t* a, uint64_t descB, int scaleD) {
  asm volatile("{\n.reg .pred p;\nsetp.ne.b32 p, %101, 0;\n"
    "wgmma.mma_async.sync.aligned.m64n192k16.f32.bf16.bf16 {%0, %1, %2, %3, %4, %5, %6, %7, %8, %9, %10, %11, %12, %13, %14, %15, %16, %17, %18, %19, %20, %21, %22, %23, %24, %25, %26, %27, %28, %29, %30, %31, %32, %33, %34, %35, %36, %37, %38, %39, %40, %41, %42, %43, %44, %45, %46, %47, %48, %49, %50, %51, %52, %53, %54, %55, %56, %57, %58, %59, %60, %61, %62, %63, %64, %65, %66, %67, %68, %69, %70, %71, %72, %73, %74, %75, %76, %77, %78, %79, %80, %81, %82, %83, %84, %85, %86, %87, %88, %89, %90, %91, %92, %93, %94, %95}, {%96, %97, %98, %99}, %100, p, 1, 1, 1;\n}\n"
    : "+f"(d[0]), "+f"(d[1]), "+f"(d[2]), "+f"(d[3]), "+f"(d[4]), "+f"(d[5]), "+f"(d[6]), "+f"(d[7]), "+f"(d[8]), "+f"(d[9]), "+f"(d[10]), "+f"(d[11]), "+f"(d[12]), "+f"(d[13]), "+f"(d[14]), "+f"(d[15]), "+f"(d[16]), "+f"(d[17]), "+f"(d[18]), "+f"(d[19]), "+f"(d[20]), "+f"(d[21]), "+f"(d[22]), "+f"(d[23]), "+f"(d[24]), "+f"(d[25]), "+f"(d[26]), "+f"(d[27]), "+f"(d[28]), "+f"(d[29]), "+f"(d[30]), "+f"(d[31]), "+f"(d[32]), "+f"(d[33]), "+f"(d[34]), "+f"(d[35]), "+f"(d[36]), "+f"(d[37]), "+f"(d[38]), "+f"(d[39]), "+f"(d[40]), "+f"(d[41]), "+f"(d[42]), "+f"(d[43]), "+f"(d[44]), "+f"(d[45]), "+f"(d[46]), "+f"(d[47]), "+f"(d[48]), "+f"(d[49]), "+f"(d[50]), "+f"(d[51]), "+f"(d[52]), "+f"(d[53]), "+f"(d[54]), "+f"(d[55]), "+f"(d[56]), "+f"(d[57]), "+f"(d[58]), "+f"(d[59]), "+f"(d[60]), "+f"(d[61]), "+f"(d[62]), "+f"(d[63]), "+f"(d[64]), "+f"(d[65]), "+f"(d[66]), "+f"(d[67]), "+f"(d[68]), "+f"(d[69]), "+f"(d[70]), "+f"(d[71]), "+f"(d[72]), "+f"(d[73]), "+f"(d[74]), "+f"(d[75]), "+f"(d[76]), "+f"(d[77]), "+f"(d[78]), "+f"(d[79]), "+f"(d[80]), "+f"(d[81]), "+f"(d[82]), "+f"(d[83]), "+f"(d[84]), "+f"(d[85]), "+f"(d[86]), "+f"(d[87]), "+f"(d[88]), "+f"(d[89]), "+f"(d[90]), "+f"(d[91]), "+f"(d[92]), "+f"(d[93]), "+f"(d[94]), "+f"(d[95])
    : "r"(a[0]), "r"(a[1]), "r"(a[2]), "r"(a[3]), "l"(descB), "r"(scaleD));
}

__device__ __forceinline__ void wgmma_n80_rs_tb0(float* d, const uint32_t* a, uint64_t descB, int scaleD) {
  asm volatile("{\n.reg .pred p;\nsetp.ne.b32 p, %45, 0;\n"
    "wgmma.mma_async.sync.aligned.m64n80k16.f32.bf16.bf16 {%0, %1, %2, %3, %4, %5, %6, %7, %8, %9, %10, %11, %12, %13, %14, %15, %16, %17, %18, %19, %20, %21, %22, %23, %24, %25, %26, %27, %28, %29, %30, %31, %32, %33, %34, %35, %36, %37, %38, %39}, {%40, %41, %42, %43}, %44, p, 1, 1, 0;\n}\n"
    : "+f"(d[0]), "+f"(d[1]), "+f"(d[2]), "+f"(d[3]), "+f"(d[4]), "+f"(d[5]), "+f"(d[6]), "+f"(d[7]), "+f"(d[8]), "+f"(d[9]), "+f"(d[10]), "+f"(d[11]), "+f"(d[12]), "+f"(d[13]), "+f"(d[14]), "+f"(d[15]), "+f"(d[16]), "+f"(d[17]), "+f"(d[18]), "+f"(d[19]), "+f"(d[20]), "+f"(d[21]), "+f"(d[22]), "+f"(d[23]), "+f"(d[24]), "+f"(d[25]), "+f"(d[26]), "+f"(d[27]), "+f"(d[28]), "+f"(d[29]), "+f"(d[30]), "+f"(d[31]), "+f"(d[32]), "+f"(d[33]), "+f"(d[34]), "+f"(d[35]), "+f"(d[36]), "+f"(d[37]), "+f"(d[38]), "+f"(d[39])
    : "r"(a[0]), "r"(a[1]), "r"(a[2]), "r"(a[3]), "l"(descB), "r"(scaleD));
}

__device__ __forceinline__ void wgmma_n80_rsz_tb0(float* d, const uint32_t* a, uint64_t descB) {
  asm volatile("{\n.reg .pred p;\nsetp.ne.b32 p, 0, 0;\n"
    "wgmma.mma_async.sync.aligned.m64n80k16.f32.bf16.bf16 {%0, %1, %2, %3, %4, %5, %6, %7, %8, %9, %10, %11, %12, %13, %14, %15, %16, %17, %18, %19, %20, %21, %22, %23, %24, %25, %26, %27, %28, %29, %30, %31, %32, %33, %34, %35, %36, %37, %38, %39}, {%40, %41, %42, %43}, %44, p, 1, 1, 0;\n}\n"
    : "=f"(d[0]), "=f"(d[1]), "=f"(d[2]), "=f"(d[3]), "=f"(d[4]), "=f"(d[5]), "=f"(d[6]), "=f"(d[7]), "=f"(d[8]), "=f"(d[9]), "=f"(d[10]), "=f"(d[11]), "=f"(d[12]), "=f"(d[13]), "=f"(d[14]), "=f"(d[15]), "=f"(d[16]), "=f"(d[17]), "=f"(d[18]), "=f"(d[19]), "=f"(d[20]), "=f"(d[21]), "=f"(d[22]), "=f"(d[23]), "=f"(d[24]), "=f"(d[25]), "=f"(d[26]), "=f"(d[27]), "=f"(d[28]), "=f"(d[29]), "=f"(d[30]), "=f"(d[31]), "=f"(d[32]), "=f"(d[33]), "=f"(d[34]), "=f"(d[35]), "=f"(d[36]), "=f"(d[37]), "=f"(d[38]), "=f"(d[39])
    : "r"(a[0]), "r"(a[1]), "r"(a[2]), "r"(a[3]), "l"(descB));
}

__device__ __forceinline__ void wgmma_n32_rs_tb1(float* d, const uint32_t* a, uint64_t descB, int scaleD) {
  asm volatile("{\n.reg .pred p;\nsetp.ne.b32 p, %21, 0;\n"
    "wgmma.mma_async.sync.aligned.m64n32k16.f32.bf16.bf16 {%0, %1, %2, %3, %4, %5, %6, %7, %8, %9, %10, %11, %12, %13, %14, %15}, {%16, %17, %18, %19}, %20, p, 1, 1, 1;\n}\n"
    : "+f"(d[0]), "+f"(d[1]), "+f"(d[2]), "+f"(d[3]), "+f"(d[4]), "+f"(d[5]), "+f"(d[6]), "+f"(d[7]), "+f"(d[8]), "+f"(d[9]), "+f"(d[10]), "+f"(d[11]), "+f"(d[12]), "+f"(d[13]), "+f"(d[14]), "+f"(d[15])
    : "r"(a[0]), "r"(a[1]), "r"(a[2]), "r"(a[3]), "l"(descB), "r"(scaleD));
}

__device__ __forceinline__ void wgmma_n32_rsz_tb1(float* d, const uint32_t* a, uint64_t descB) {
  asm volatile("{\n.reg .pred p;\nsetp.ne.b32 p, 0, 0;\n"
    "wgmma.mma_async.sync.aligned.m64n32k16.f32.bf16.bf16 {%0, %1, %2, %3, %4, %5, %6, %7, %8, %9, %10, %11, %12, %13, %14, %15}, {%16, %17, %18, %19}, %20, p, 1, 1, 1;\n}\n"
    : "=f"(d[0]), "=f"(d[1]), "=f"(d[2]), "=f"(d[3]), "=f"(d[4]), "=f"(d[5]), "=f"(d[6]), "=f"(d[7]), "=f"(d[8]), "=f"(d[9]), "=f"(d[10]), "=f"(d[11]), "=f"(d[12]), "=f"(d[13]), "=f"(d[14]), "=f"(d[15])
    : "r"(a[0]), "r"(a[1]), "r"(a[2]), "r"(a[3]), "l"(descB));
}

__device__ __forceinline__ void wgmma_n32_rs_tb0(float* d, const uint32_t* a, uint64_t descB, int scaleD) {
  asm volatile("{\n.reg .pred p;\nsetp.ne.b32 p, %21, 0;\n"
    "wgmma.mma_async.sync.aligned.m64n32k16.f32.bf16.bf16 {%0, %1, %2, %3, %4, %5, %6, %7, %8, %9, %10, %11, %12, %13, %14, %15}, {%16, %17, %18, %19}, %20, p, 1, 1, 0;\n}\n"
    : "+f"(d[0]), "+f"(d[1]), "+f"(d[2]), "+f"(d[3]), "+f"(d[4]), "+f"(d[5]), "+f"(d[6]), "+f"(d[7]), "+f"(d[8]), "+f"(d[9]), "+f"(d[10]), "+f"(d[11]), "+f"(d[12]), "+f"(d[13]), "+f"(d[14]), "+f"(d[15])
    : "r"(a[0]), "r"(a[1]), "r"(a[2]), "r"(a[3]), "l"(descB), "r"(scaleD));
}

__device__ __forceinline__ void wgmma_n32_rsz_tb0(float* d, const uint32_t* a, uint64_t descB) {
  asm volatile("{\n.reg .pred p;\nsetp.ne.b32 p, 0, 0;\n"
    "wgmma.mma_async.sync.aligned.m64n32k16.f32.bf16.bf16 {%0, %1, %2, %3, %4, %5, %6, %7, %8, %9, %10, %11, %12, %13, %14, %15}, {%16, %17, %18, %19}, %20, p, 1, 1, 0;\n}\n"
    : "=f"(d[0]), "=f"(d[1]), "=f"(d[2]), "=f"(d[3]), "=f"(d[4]), "=f"(d[5]), "=f"(d[6]), "=f"(d[7]), "=f"(d[8]), "=f"(d[9]), "=f"(d[10]), "=f"(d[11]), "=f"(d[12]), "=f"(d[13]), "=f"(d[14]), "=f"(d[15])
    : "r"(a[0]), "r"(a[1]), "r"(a[2]), "r"(a[3]), "l"(descB));
}

__device__ __forceinline__ uint32_t pack_bf16x2(float lo, float hi) {
  uint32_t r;
  asm("cvt.rn.bf16x2.f32 %0, %1, %2;" : "=r"(r) : "f"(hi), "f"(lo));
  return r;
}
__device__ __forceinline__ float bf_lo(uint32_t p) { return __uint_as_float(p << 16); }
__device__ __forceinline__ float bf_hi(uint32_t p) { return __uint_as_float(p & 0xffff0000u); }
__device__ __forceinline__ float bf16_round(float v) { return __bfloat162float(__float2bfloat16_rn(v)); }
__device__ __forceinline__ float ex2_approx(float x) {
  float r;
  asm("ex2.approx.ftz.f32 %0, %1;" : "=f"(r) : "f"(x));
  return r;
}
__device__ __forceinline__ float rcp_fast(float x) {
  float r;
  asm("rcp.approx.ftz.f32 %0, %1;" : "=f"(r) : "f"(x));
  return r;
}
__device__ __forceinline__ void ldmatrix_x4(uint32_t (&r)[4], uint32_t addr) {
  asm volatile("ldmatrix.sync.aligned.m8n8.x4.shared.b16 {%0,%1,%2,%3}, [%4];"
               : "=r"(r[0]), "=r"(r[1]), "=r"(r[2]), "=r"(r[3])
               : "r"(addr)
               : "memory");
}
__device__ __forceinline__ void stmatrix_x4(uint32_t addr, uint32_t r0, uint32_t r1, uint32_t r2, uint32_t r3) {
  asm volatile("stmatrix.sync.aligned.m8n8.x4.shared.b16 [%0], {%1,%2,%3,%4};" ::"r"(addr), "r"(r0), "r"(r1), "r"(r2),
               "r"(r3));
}
__device__ __forceinline__ uint32_t add_bf16x2(uint32_t a, uint32_t b) {
  uint32_t r;
  asm("add.rn.bf16x2 %0, %1, %2;" : "=r"(r) : "r"(a), "r"(b));
  return r;
}
__device__ __forceinline__ uint4 lds128(uint32_t addr) {
  uint4 v;
  asm volatile("ld.shared.v4.b32 {%0,%1,%2,%3}, [%4];" : "=r"(v.x), "=r"(v.y), "=r"(v.z), "=r"(v.w) : "r"(addr) : "memory");
  return v;
}
__device__ __forceinline__ uint32_t lds32(uint32_t addr) {
  uint32_t v;
  asm volatile("ld.shared.b32 %0, [%1];" : "=r"(v) : "r"(addr) : "memory");
  return v;
}
__device__ __forceinline__ void sts32(uint32_t addr, uint32_t v) {
  asm volatile("st.shared.b32 [%0], %1;" ::"r"(addr), "r"(v) : "memory");
}

__device__ __forceinline__ unsigned ld_relaxed_u32(const void* p) {
  unsigned v;
  asm volatile("ld.relaxed.gpu.global.u32 %0, [%1];" : "=r"(v) : "l"(p) : "memory");
  return v;
}
__device__ __forceinline__ unsigned launch_epoch() { return (*(volatile unsigned*)g_done) / NCTA + 1u; }
__device__ __forceinline__ uint32_t set_tag(uint32_t w, uint32_t m, uint32_t tag) { return (w & ~m) | (tag & m); }
__device__ __forceinline__ uint32_t o_tag(int L) { return (L + 1) & 1; }
__device__ __forceinline__ uint32_t x_tag(unsigned ep1, int L) { return (ep1 + L + 1) & 1; }

#define PIPEP 0
__device__ __forceinline__ void wait_count(const unsigned* f, unsigned target, int i, uint32_t& seen, int lane) {
  if ((seen >> i) & 1u) return;
  f += (lane & 15) * 4;
#pragma unroll 1
  for (uint32_t it = 0; it < (1u << 17); ++it) {
    seen = __ballot_sync(0xffffffffu, (int)(ld_relaxed_u32(f) - target) >= 0);
    if ((seen >> i) & 1u) break;
  }
}
__device__ __forceinline__ float4 ld_rec(const float4* p) {
  float4 v;
  asm volatile("ld.relaxed.gpu.global.v4.f32 {%0,%1,%2,%3}, [%4];" : "=f"(v.x), "=f"(v.y), "=f"(v.z), "=f"(v.w) : "l"(p) : "memory");
  return v;
}
__device__ __forceinline__ void st_rec(float4* p, float a, float b, float c, unsigned tag) {
  asm volatile("st.relaxed.gpu.global.v4.f32 [%0], {%1,%2,%3,%4};" ::"l"(p), "f"(a), "f"(b), "f"(c), "f"(__uint_as_float(tag)) : "memory");
}
template <int N>
__device__ __forceinline__ float4 sum_recs(const float4* p, int stride, unsigned tag) {
  float4 s;
#pragma unroll 1
  for (uint32_t it = 0; it < (1u << 17); ++it) {
    float4 v[N];
#pragma unroll
    for (int t = 0; t < N; t++) v[t] = ld_rec(p + t * stride);
    bool ok = true;
    s = make_float4(0.f, 0.f, 0.f, 0.f);
#pragma unroll
    for (int t = 0; t < N; t++) {
      ok &= __float_as_uint(v[t].w) == tag;
      s.x += v[t].x;
      s.y += v[t].y;
      s.z += v[t].z;
    }
    if (ok) break;
    __nanosleep(200);
  }
  return s;
}

__device__ __forceinline__ int fresh_tid() {
  int t;
  asm volatile("mov.u32 %0, %%tid.x;" : "=r"(t));
  return t;
}
#define PHASE_IDS                                  \
  const int tid_ = fresh_tid();                    \
  const int lane = tid_ & 31, wwarp = __shfl_sync(0xffffffffu, (tid_ >> 5) & 3, 0), tid = tid_ & 127; \
  const int g = lane >> 2, c = lane & 3;           \
  (void)tid; (void)g; (void)c; (void)wwarp;

#define PHASE_IDS_W                                \
  const int lane = fresh_tid() & 31, wwarp = warp & 3; \
  const int g = lane >> 2, c = lane & 3;

#define GTL(i) do { } while (0)
#define TGET(v) do { } while (0)
#define TPUT(c, i, v) do { } while (0)

constexpr float SM_C = 0.17677669529663687f * 1.4426950408889634f;

__device__ __forceinline__ void stmatrix_x4_if(bool ok, uint32_t addr, uint32_t r0, uint32_t r1, uint32_t r2, uint32_t r3) {
  asm volatile("{\n.reg .pred p;\nsetp.ne.b32 p, %5, 0;\n@p stmatrix.sync.aligned.m8n8.x4.shared.b16 [%0], {%1,%2,%3,%4};\n}\n" ::"r"(addr),
               "r"(r0), "r"(r1), "r"(r2), "r"(r3), "r"((int)ok));
}

__device__ __forceinline__ void attn_a_slow(const uint8_t* __restrict__ kvimg, int L, int gb, int hp, uint32_t bad,
                                            int row0, int lane) {
  constexpr uint32_t sq = SBASE + OFF_SLOT + 3 * 16384;
#pragma unroll 1
  for (int j = 0; j < 8; j++) {
    const uint8_t* tp = kvimg + (size_t)(gb * 16 + hp) * 32768 + (j * 32 + lane) * 128 + ((lane & 7) << 4);
#pragma unroll 1
    for (uint32_t it = 0; it < (1u << 17); ++it)
      if (((ld_relaxed_u32(tp) ^ lds32(SBASE + OFF_EPOCH)) & 1u) == 0u) break;
  }
  __syncwarp();
#pragma unroll 1
  for (int t = 0; t < 32; t++) {
    const int hh = t >> 4, row = row0 + (t & 7) + (t & 8) * 4;
    if (!((bad >> hh) & 1u)) continue;
    const int qpos = gb * 128 + row;
    const uint32_t qaddr = sq + row * 128;
    float mx = -INFINITY, sum = 0.f, acc = 0.f;
#pragma unroll 1
    for (int pass = 0; pass < 2; pass++) {
#pragma unroll 1
      for (int j = 0; j < 8; j++) {
        const int kp = qpos - (lane + 32 * j);
        const uint8_t* kr = kvimg + ((size_t)((kp >> 7) * 16 + hp) * 2 + ((kp >> 6) & 1)) * 16384 + (kp & 63) * 128;
        float d = -INFINITY;
        if (kp >= 0) {
          d = 0.f;
#pragma unroll 1
          for (int q = 0; q < 4; q++) {
            const uint4 kv = __ldcg(reinterpret_cast<const uint4*>(kr + (((hh * 4 + q) ^ (kp & 7)) << 4)));
            const uint4 qv = lds128(qaddr + (((hh * 4 + q) ^ (row & 7)) << 4));
            const uint32_t kw[4] = {kv.x, kv.y, kv.z, kv.w}, qw[4] = {qv.x, qv.y, qv.z, qv.w};
#pragma unroll
            for (int e = 0; e < 4; e++) d = fmaf(bf_lo(kw[e]), bf_lo(qw[e]), fmaf(bf_hi(kw[e]), bf_hi(qw[e]), d));
          }
        }
        if (pass == 0) {
          mx = fmaxf(mx, d);
        } else {
          const float ev = ex2_approx(d - mx);
          sum += ev;
          const float pv = bf16_round(ev);
#pragma unroll 1
          for (int kk = 0; kk < 32; kk++) {
            const float pk = __shfl_sync(0xffffffffu, pv, kk);
            const int k2 = qpos - (kk + 32 * j);
            if (k2 >= 0) {
              const uint8_t* vr = kvimg + ((size_t)((k2 >> 7) * 16 + hp) * 2 + ((k2 >> 6) & 1)) * 16384 + 8192 + (k2 & 63) * 128;
              const unsigned short vv =
                  __ldcg(reinterpret_cast<const unsigned short*>(vr + (((hh * 4 + (lane >> 3)) ^ (k2 & 7)) << 4) + (lane & 7) * 2));
              acc = fmaf(pk, __uint_as_float((uint32_t)vv << 16), acc);
            }
          }
        }
      }
      if (pass == 0) {
#pragma unroll
        for (int o = 16; o > 0; o >>= 1) mx = fmaxf(mx, __shfl_xor_sync(0xffffffffu, mx, o));
      }
    }
#pragma unroll
    for (int o = 16; o > 0; o >>= 1) sum += __shfl_xor_sync(0xffffffffu, sum, o);
    acc *= rcp_fast(sum);
    const float hi = __shfl_down_sync(0xffffffffu, acc, 1);
    __syncwarp();
    if ((lane & 1) == 0) sts32(qaddr + (((hh * 4 + (lane >> 3)) ^ (row & 7)) << 4) + (lane & 7) * 2,
                               set_tag(pack_bf16x2(acc, hi), hh == 0 && lane == 0, o_tag(L)));
    __syncwarp();
  }
}

template <int HH>
__device__ __forceinline__ void store_o(const float (&o)[16], const float (&inv)[2], uint32_t ra, uint32_t tag, bool ok) {
  const uint32_t m = HH == 0 && (fresh_tid() & 3) == 0;
#pragma unroll
  for (int jp = 0; jp < 2; jp++) {
    uint32_t w0 = pack_bf16x2(o[8 * jp] * inv[0], o[8 * jp + 1] * inv[0]);
    uint32_t w1 = pack_bf16x2(o[8 * jp + 2] * inv[1], o[8 * jp + 3] * inv[1]);
    if (HH == 0 && jp == 0) {
      w0 = set_tag(w0, m, tag);
      w1 = set_tag(w1, m, tag);
    }
    stmatrix_x4_if(ok, ra ^ ((HH * 4 + 2 * jp) << 4), w0, w1, pack_bf16x2(o[8 * jp + 4] * inv[0], o[8 * jp + 5] * inv[0]),
                   pack_bf16x2(o[8 * jp + 6] * inv[1], o[8 * jp + 7] * inv[1]));
  }
}
__device__ __forceinline__ int tile_row(bool B, int w, int r, int g) { return (B ? 16 * w + 8 * r : 8 * w + 32 * r) + g; }
__device__ __forceinline__ uint32_t q_row_addr(bool B, int R, int w, int lane) {
  return SBASE + OFF_SLOT + 3 * 16384 + R * 8192 + tile_row(B, w, (lane >> 3) & 1, lane & 7) * 128 + (((lane >> 4) ^ (lane & 7)) << 4);
}

struct AttnA {
  float s[2][16], o[2][16], l[2][2], sh[2][3];
  uint32_t p[2][4], t[2], me[4], ra, bad, zero;
};
#define ATS_(i) do { } while (0)
template <int V>
__device__ __forceinline__ void attn_sum(AttnA& a, int nv) {
  constexpr int hh = (V >> 1) & 1, kh = V & 1, i = V >> 2;
#pragma unroll
  for (int r = 0; r < 2; r++) {
    const uint32_t t1 = add_bf16x2(add_bf16x2(a.p[0][r], a.p[0][2 + r]), add_bf16x2(a.p[1][r], a.p[1][2 + r]));
    if (kh == 0) {
      a.t[r] = t1;
    } else {
      uint32_t tt = add_bf16x2(a.t[r], t1);
      if (i > 0) tt = i <= nv ? tt : 0u;
      const float v = bf_lo(tt) + bf_hi(tt);
      a.l[hh][r] = i == 0 ? v : a.l[hh][r] + v;
    }
  }
}
template <int HH>
__device__ __forceinline__ void attn_shfl(AttnA& a) {
#pragma unroll
  for (int r = 0; r < 2; r++)
#pragma unroll
    for (int j = 0; j < 3; j++) a.sh[r][j] = __shfl_xor_sync(0xffffffffu, a.l[HH][r], j + 1);
}
template <int HH>
__device__ __forceinline__ void attn_fin(AttnA& a) {
  bool bad = false;
  float inv[2];
#pragma unroll
  for (int r = 0; r < 2; r++) {
    const float v = (a.l[HH][r] + a.sh[r][0]) + (a.sh[r][1] + a.sh[r][2]);
    bad |= !(v <= 1.152921504606846976e18f && v >= 8.673617379884035e-19f);
    inv[r] = rcp_fast(v);
  }
  bad = __any_sync(0xffffffffu, bad);
  if (HH == 1) wgmma_wait<0>();
  reg_fence<16>(a.o[HH]);
  store_o<HH>(a.o[HH], inv, a.ra, o_tag(0), !bad);
  a.bad = (HH == 0 ? 0u : a.bad) | (bad ? 1u << HH : 0u);
}
__device__ __forceinline__ void attn_masks(AttnA& a, int wr) {
  const int lane = fresh_tid() & 31, d = (lane >> 2) - 2 * (lane & 3);
  const uint32_t tri = d >= 1 ? 0xffffffffu : (d == 0 ? 0xffffu : 0u);
#pragma unroll
  for (int t = 0; t < 4; t++) a.me[t] = wr > t ? 0xffffffffu : (wr == t ? tri : 0u);
}
template <int V, int K>
__device__ __forceinline__ uint32_t attn_exp(AttnA& a) {
  constexpr int i = V >> 2, kh = V & 1, r = K & 1;
  if ((i == 0 && kh > r) || (i == 4 && kh < r)) return 0u;
  const uint32_t w = pack_bf16x2(ex2_approx(a.s[V & 1][2 * K]), ex2_approx(a.s[V & 1][2 * K + 1]));
  if (i == 0 && kh == r) return w & a.me[K >> 1];
  if (i == 4 && kh == r) return w & ~a.me[K >> 1];
  return w;
}
template <int V>
__device__ __forceinline__ void attn_unit(AttnA& a, const uint32_t (&q)[2][2][4], uint64_t dcur, uint64_t dnext, int R, int wr, int nv,
                                          uint32_t hbar, uint32_t hpar, uint32_t rbar, bool rel) {
  constexpr int hh = (V >> 1) & 1, kh = V & 1, i = V >> 2;
  ATS_(V + 1);
  asm volatile("" : "+l"(dcur), "+l"(dnext));
  wgmma_wait<1>();
  reg_fence<16>(a.s[V & 1]);
  bool hok = true;
  if (V == 4) hbar = SBASE + OFF_BAR + 8u * (R ? B_LOC : B_HV);
  if (((V & 3) == 2 && V < 16) || V == 4) hok = mbar_test(hbar, hpar);
  const uint64_t d0 = ((V & 3) >= 2 ? dnext : dcur) + ((hh ^ 1) * 4 + kh * 256), d1 = ((V & 3) >= 2 ? dnext : dcur) + ((hh ^ 1) * 4 + kh * 256 + 2);
  const uint64_t d2 = dcur + (512 + hh * 4 + kh * 256), d3 = dcur + (640 + hh * 4 + kh * 256);
  if ((V & 3) == 1 && V > 4 && rel) mbar_arrive(rbar);
  if (V > 0) attn_sum<V - 1>(a, nv);
  if (V == 15) attn_masks(a, wr);
  if (V == 18) {
    attn_shfl<0>(a);
    a.ra = q_row_addr(false, R, wr, fresh_tid() & 31);
  }
  if (V == 19) attn_fin<0>(a);
  uint32_t p[2][4];
  p[0][0] = attn_exp<V, 0>(a);
  p[0][1] = attn_exp<V, 1>(a);
  p[0][2] = attn_exp<V, 2>(a);
  p[0][3] = attn_exp<V, 3>(a);
  p[1][0] = attn_exp<V, 4>(a);
  p[1][1] = attn_exp<V, 5>(a);
  p[1][2] = attn_exp<V, 6>(a);
  p[1][3] = attn_exp<V, 7>(a);
  if (V > 0) {
#pragma unroll
    for (int r = 0; r < 2; r++) p[1][r] ^= (kh ? a.t[r] : __float_as_uint(a.l[hh ^ 1][r])) & a.zero;
  }
#pragma unroll
  for (int k = 0; k < 8; k++) {
    asm volatile("" : "+r"(p[k >> 2][k & 3]));
    a.p[k >> 2][k & 3] = p[k >> 2][k & 3];
  }
  if (!hok) mbar_wait(hbar, hpar);
  wgmma_fence();
  if (V < 18) wgmma_n32_rsz_tb0(a.s[V & 1], q[hh ^ 1][0], d0);
  if (i == 0 && kh == 0) wgmma_n32_rsz_tb1(a.o[hh], a.p[0], d2);
  else wgmma_n32_rs_tb1(a.o[hh], a.p[0], d2, 1);
  if (V < 18) wgmma_n32_rs_tb0(a.s[V & 1], q[hh ^ 1][1], d1, 1);
  wgmma_n32_rs_tb1(a.o[hh], a.p[1], d3, 1);
  wgmma_commit();
}
template <int I>
__device__ __forceinline__ void attn_step(AttnA& a, const uint32_t (&q)[2][2][4], uint64_t dcur, uint64_t dnext, int R, int wr, int nv,
                                          uint32_t hbar, uint32_t hpar, uint32_t rbar, bool rel) {
  attn_unit<4 * I>(a, q, dcur, dnext, R, wr, nv, hbar, hpar, rbar, rel);
  attn_unit<4 * I + 1>(a, q, dcur, dnext, R, wr, nv, hbar, hpar, rbar, rel);
  attn_unit<4 * I + 2>(a, q, dcur, dnext, R, wr, nv, hbar, hpar, rbar, rel);
  attn_unit<4 * I + 3>(a, q, dcur, dnext, R, wr, nv, hbar, hpar, rbar, rel);
}

__device__ __forceinline__ void attention_a(const uint32_t (&q)[2][2][4], int R, int L, int gb, int hp, uint32_t par, int wr,
                                            uint32_t zero) {
  constexpr uint32_t bars = SBASE + OFF_BAR;
  constexpr uint32_t dslot = ((SBASE + OFF_SLOT) >> 4) + 0x10000u;
  auto next = [&](uint64_t d) { return desc_lo((uint32_t)d == dslot ? dslot + 2048 : (uint32_t)d - 1024) + zero; };
  uint64_t d0 = desc_lo(dslot + R * 1024) + zero, d1 = next(d0);
  AttnA a;
  ATS_(0);
  wgmma_fence();
#pragma unroll
  for (int v = 0; v < 2; v++) {
    wgmma_n32_rsz_tb0(a.s[v], q[0][0], d0 + v * 256);
    wgmma_n32_rs_tb0(a.s[v], q[0][1], d0 + (v * 256 + 2), 1);
    wgmma_commit();
  }
  a.zero = zero;
  const bool lane0 = (fresh_tid() & 31) == 0;
  attn_masks(a, wr);
  const int nv = 2 * gb + R;
  const uint32_t hb = bars + 8u * (B_HALO - R), rb = bars + 8u * (B_REL - R);
  attn_step<0>(a, q, d0, d1, R, wr, nv, hb, par, 0, false);
  d0 = next(d1);
  attn_step<1>(a, q, d1, d0, R, wr, nv, R ? bars + 8u * B_HV : hb + 8, par, rb + 8, lane0);
  d1 = next(d0);
  attn_step<2>(a, q, d0, d1, R, wr, nv, hb + 16, par, rb + 16, lane0);
  d0 = next(d1);
  attn_step<3>(a, q, d1, d0, R, wr, nv, hb + 24, par, rb + 24, lane0 && R);
  attn_step<4>(a, q, d0, d0, R, wr, nv, 0, 0, rb, false);
  ATS_(21);
  attn_sum<19>(a, nv);
  attn_shfl<1>(a);
  attn_fin<1>(a);
  ATS_(22);
  if (a.bad != 0u) {
    attn_a_slow(g_kvA[L >> 1][0][0][0], L, gb, hp, a.bad, R * 64 + wr * 8, fresh_tid() & 31);
    named_bar_sync(8 + R * 4 + wr, 32);
  }
}

constexpr uint32_t KB_ROW0 = SBASE + OFF_SLOT + 2048, VB_ROW0 = SBASE + OFF_SLOT + 24576 + 2048;

__device__ __forceinline__ void attention_b(const uint32_t (&q)[2][2][4], int R, int gb, uint32_t par0, int wr) {
  constexpr uint32_t bars = SBASE + OFF_BAR;
  const uint32_t dk = ((KB_ROW0 - 2048) >> 4) + 0x10000u + R * 512, dv = dk + ((VB_ROW0 - KB_ROW0) >> 4);
  float s[2][40];
  mbar_wait(bars + 8u * (B_HALO - R), par0);
  wgmma_fence();
#pragma unroll
  for (int hh = 0; hh < 2; hh++) {
    wgmma_n80_rsz_tb0(s[hh], q[hh][0], desc_lo(dk + hh * 4));
    wgmma_n80_rs_tb0(s[hh], q[hh][1], desc_lo(dk + hh * 4 + 2), 1);
  }
  wgmma_commit();
  const int lane = fresh_tid() & 31, g = lane >> 2;
  const bool odd = g & 1, edge = R == 0 && gb == 0 && wr == 0;
  const int D = 2 * (lane & 3) + (g & 1) - g;
  const uint32_t ra = q_row_addr(true, R, wr, lane);
  wgmma_wait<0>();
  reg_fence<40>(s[0]);
  reg_fence<40>(s[1]);
  float z[2][2], y[2][2];
#define GATHER_(W)                                                                                          \
  _Pragma("unroll") for (int hh = 0; hh < 2; hh++) _Pragma("unroll") for (int r = 0; r < 2; r++) {          \
    const float* e = &s[hh][4 * (2 * W + r) + 2 * r];                                                       \
    z[hh][r] = odd ? e[5] : e[4];                                                                           \
    y[hh][r] = D >= 2 ? (odd ? e[1] : e[0]) : (odd ? e[9] : e[8]);                                          \
  }
  if (wr < 2) {
    if (wr == 0) { GATHER_(0) } else { GATHER_(1) }
  } else {
    if (wr == 2) { GATHER_(2) } else { GATHER_(3) }
  }
#undef GATHER_
  float o[2][16], inv[2][2];
  uint32_t p[2][5][4];
  const int sh = odd ? 16 : 0, kb = wr + (D >= 2 ? 0 : 1);
#pragma unroll
  for (int hh = 0; hh < 2; hh++) {
    if (edge) {
      z[hh][0] = -INFINITY;
      if (D >= 2) y[hh][0] = y[hh][1] = -INFINITY;
    }
    uint32_t ab[2][2];
#pragma unroll
    for (int r = 0; r < 2; r++) {
      float m = fmaxf(z[hh][r], y[hh][r]);
      m = fmaxf(m, __shfl_xor_sync(0xffffffffu, m, 1));
      m = fmaxf(m, __shfl_xor_sync(0xffffffffu, m, 2));
      const float e0 = ex2_approx(z[hh][r] - m), e1 = ex2_approx(y[hh][r] - m);
      inv[hh][r] = e0 + e1;
      ab[r][0] = pack_bf16x2(e0, 0.f) << sh;
      ab[r][1] = pack_bf16x2(e1, 0.f) << sh;
    }
#pragma unroll
    for (int k = 0; k < 5; k++) {
      p[hh][k][0] = k == kb ? ab[0][1] : 0u;
      p[hh][k][1] = k == wr + 1 ? ab[1][0] : 0u;
      p[hh][k][2] = k == wr ? ab[0][0] : 0u;
      p[hh][k][3] = k == kb ? ab[1][1] : 0u;
#pragma unroll
      for (int j = 0; j < 4; j++) asm volatile("" : "+r"(p[hh][k][j]));
    }
  }
  wgmma_fence();
#pragma unroll
  for (int hh = 0; hh < 2; hh++) {
    wgmma_n32_rsz_tb1(o[hh], p[hh][0], desc_lo(dv + hh * 4));
#pragma unroll
    for (int k = 1; k < 5; k++) wgmma_n32_rs_tb1(o[hh], p[hh][k], desc_lo(dv + hh * 4 + k * 128), 1);
  }
  wgmma_commit();
#pragma unroll
  for (int hh = 0; hh < 2; hh++)
#pragma unroll
    for (int r = 0; r < 2; r++) {
      inv[hh][r] += __shfl_xor_sync(0xffffffffu, inv[hh][r], 1);
      inv[hh][r] += __shfl_xor_sync(0xffffffffu, inv[hh][r], 2);
      inv[hh][r] = rcp_fast(inv[hh][r]);
    }
  wgmma_wait<0>();
  reg_fence<16>(o[0]);
  reg_fence<16>(o[1]);
  store_o<0>(o[0], inv[0], ra, o_tag(1), true);
  store_o<1>(o[1], inv[1], ra, o_tag(1), true);
}

#define KTQM 0
#define TRICKLE 300
#define WTURN 15
#define QREL 8
#define PRESLEEP 200
#define CSA 3
#define TLAZY 100
#define QTURN 2
#define HTS(i) do { } while (0)
struct Params {
  CUtensorMap x[5], xq[4], o, wqkv[2], wqkv3[2], wo3[2];
  const __nv_bfloat16* in_x;
  const __nv_bfloat16* wqkv_p[2];
  const __nv_bfloat16* wo_p[2];
  __nv_bfloat16* out;
  uint32_t zero;
};

__device__ __forceinline__ void colsum_part(const CUtensorMap* wmap, int ty, int qr, int hp) {
  constexpr uint32_t bars = SBASE + OFF_BAR, slots = SBASE + OFF_SLOT;
  PHASE_IDS
  const unsigned ep1 = launch_epoch();
  if (wwarp == 0 && elect_one()) {
    mbar_expect_tx(bars + 8u * B_CS, 6 * UNIT);
#pragma unroll 1
    for (int j = 0; j < 6; j++) {
      if (ty == 0) mbar_pace(bars + 8u * (B_QF + B_E + ((j * CSA / 6) & 3)), (j * CSA / 6) >> 2);
      else mbar_wait_lazy<100>(bars + 8u * (B_WF + B_E + ((2 * j + 3 - (j & 1)) & 7)), j >= 3);
      tma_load_2d(slots + j * UNIT, wmap, bars + 8u * B_CS, (j >> 1) * 1024 + hp * 64, qr * 128 + (j & 1) * 64);
    }
  }
  constexpr uint64_t ones = (SBASE + OFF_LSB + 32) >> 4;
  float s[3][4];
  mbar_wait_lazy<100>(bars + 8u * B_CS, ty);
  wgmma_fence();
#pragma unroll
  for (int p = 0; p < 3; p++) {
    wgmma_n8_ssz_ta1_tb0(s[p], make_desc(slots + p * 2 * UNIT, 16), ones);
#pragma unroll
    for (int k = 1; k < 8; k++) wgmma_n8_ss_ta1_tb0(s[p], make_desc(slots + p * 2 * UNIT + k * 2048, 16), ones, 1);
  }
  wgmma_commit();
  wgmma_wait<0>();
  reg_fence<12>(&s[0][0]);
  if (lane == 0) mbar_arrive(bars + 8u * (ty ? B_CSD : B_RDONE));
  if (c == 0) {
#pragma unroll
    for (int r = 0; r < 2; r++) st_rec(&g_cs[ty][hp][qr][wwarp * 16 + 8 * r + g], s[0][2 * r], s[1][2 * r], s[2][2 * r], ep1);
  }
}

__device__ __forceinline__ void put_colsums(int ty, int col, const float4& s) {
  const float v[3] = {s.x, s.y, s.z};
#pragma unroll
  for (int p = 0; p < 3; p++) {
    const uint32_t a = SBASE + OFF_CS + (p * 8 + (col >> 3)) * 64 + ty * 32 + (col & 7) * 2;
    const float hi = bf16_round(v[p]);
    const uint32_t w = pack_bf16x2(hi, v[p] - hi);
    asm volatile("st.shared.b16 [%0], %1;" ::"r"(a), "h"((unsigned short)w) : "memory");
    asm volatile("st.shared.b16 [%0], %1;" ::"r"(a + 16), "h"((unsigned short)(w >> 16)) : "memory");
  }
}

__device__ __forceinline__ uint32_t ln_params(float s1, float s2) {
  const float mean = s1 * (1.0f / DM);
  const float var = fmaxf(fmaf(-mean, mean, s2 * (1.0f / DM)), 0.f);
  float sd;
  asm("sqrt.approx.f32 %0, %1;" : "=f"(sd) : "f"(bf16_round(bf16_round(var) + 1e-5f)));
  return pack_bf16x2(mean, sd);
}

struct RingProd {
  uint32_t rel = ((B_QF << 1) | 1) * 0x01010101u + 0x06040200u;
  int st = 0;
  __device__ __forceinline__ uint32_t next(uint32_t bar, uint32_t par, bool wait) {
    const uint32_t e = (rel >> (8 * st)) & 255u, a = SBASE + st * 5 * UNIT;
    if (wait) mbar_wait(SBASE + OFF_BAR + 8u * B_E + 8u * (e >> 1), e & 1u);
    rel ^= (e ^ ((bar << 1) | par)) << (8 * st);
    st = (st + 1) & 3;
    return a;
  }
};

#define SP1 15
#define SP2 14
#define SP3 12
#define SP4 12
#define SP5 15
#define SP6 14
#define SP7 16
__device__ __forceinline__ int q_split(int inst) {
  constexpr uint32_t T = 15u | ((SP1 - 1) << 4) | ((SP2 - 1) << 8) | ((SP3 - 1) << 12) | ((SP4 - 1) << 16) | ((SP5 - 1) << 20) |
                         ((SP6 - 1) << 24) | ((uint32_t)(SP7 - 1) << 28);
  return (int)((T >> (4 * inst)) & 15u) + 1;
}
__host__ __device__ constexpr uint32_t turn_par(int kind) {
  const int sp[8] = {16, SP1, SP2, SP3, SP4, SP5, SP6, SP7};
  int cnt[2] = {0, 0};
  uint32_t m = 0;
  for (int i = 0; i < 8; i++)
    for (int k = 0; k < 3; k++) {
      if (k == kind) m |= (uint32_t)(cnt[i & 1] & 1) << i;
      if (k == 0 ? (i == 1 || (i > 1 && sp[i - 1] < 16)) : (k == 2 || sp[i] < 16)) cnt[i & 1]++;
    }
  return m;
}
#define PREMASK 0xBFu
__device__ __forceinline__ bool w_pre(int inst) { return (PREMASK >> inst) & 1u; }
__host__ __device__ constexpr unsigned long long bar_counts(int i0) {
  unsigned long long t = 0;
  for (int i = i0; i < i0 + 32; i++) {
    int l = 0;
    if (i < B_RF) l = 1;
    if ((i >= B_E && i < B_E + B_RF) || i == B_LOC || i == B_REL || i == B_OS0 || i == B_TURN || i == B_TURN + 1 || i == B_XS ||
        i == B_XS + 1 || i == B_CSD || i == B_GO || i == B_RDONE || i == B_KV)
      l = 2;
    if (i == B_REL + 1 || i == B_REL + 2) l = 3;
    t |= (unsigned long long)l << (2 * (i - i0));
  }
  return t;
}

__global__ void __launch_bounds__(512, 1) fused_kernel(const __grid_constant__ Params P) {
  extern __shared__ __align__(1024) uint8_t smem_raw[];
  constexpr uint32_t base = SBASE, bars = base + OFF_BAR, slots = base + OFF_SLOT;
  if (smem_u32(smem_raw) != base) __trap();
  const int warp = __shfl_sync(0xffffffffu, threadIdx.x >> 5, 0), lane = threadIdx.x & 31;
  const int b = blockIdx.x;
#define QS 0
#define WS 1
  const int qr = ((b & ((8 << QS) - 1)) >> QS) ^ (((b >> (3 + QS)) & 1) * 7);
  const int hp = ((b >> (3 + QS)) << QS) + (b & ((1 << QS) - 1));
  const int rt = ((b & ((16 << WS) - 1)) >> WS) ^ (((b >> (4 + WS)) & 1) * 15);
  const int ct = ((b >> (4 + WS)) << WS) + (b & ((1 << WS) - 1));

  if (warp == 12) {
    if (elect_one()) {
#pragma unroll 1
      for (int s = 0; s < 4; s++) {
        const uint32_t fb = bars + 8u * (B_QF + s), sa = base + s * 5 * UNIT;
        mbar_init(fb, 2);
        fence_barrier_init();
        mbar_expect_tx(fb, 5 * UNIT);
        mbar_arrive(fb);
        tma_load_5d(sa + 3 * UNIT, &P.xq[0], fb, s * 64, qr * 2);
        tma_load_3d(sa, &P.wqkv3[0], fb, hp * 64, s * 64);
      }
    }
    __syncwarp();
  } else if (warp >= 4 && warp < 12) {
    if (elect_one()) {
#pragma unroll 1
      for (int i = warp; i <= B_KV; i += 8) mbar_init(bars + 8u * i, 1u << (((i < 32 ? bar_counts(0) : bar_counts(32)) >> (2 * (i & 31))) & 3u));
      sts32(warp < 8 ? base + OFF_ONE - 16 + 4 * warp : base + OFF_LSB + 4 * warp, warp < 8 ? warp == 4 : 0x3f803f80u);
      fence_proxy_async_smem();
      fence_barrier_init();
    }
    __syncwarp();
  }

  if (warp >= 12) {
    setmaxnreg_dec<32>();
    if (warp == 12) {
      named_bar_sync(0, 512);
      if (elect_one()) {
#pragma unroll 1
        for (int s = 4; s < 16; s++) {
          const uint32_t fb = bars + 8u * (B_QF + (s & 3)), sa = base + (s & 3) * 5 * UNIT;
          mbar_wait(fb + 8u * B_E, ((s >> 2) & 1) ^ 1);
          mbar_expect_tx(fb, 5 * UNIT);
          mbar_arrive(fb);
          tma_load_5d(sa + 3 * UNIT, &P.xq[0], fb, s * 64, qr * 2);
          tma_load_3d(sa, &P.wqkv3[0], fb, hp * 64, s * 64);
        }
#pragma unroll
        for (int s = 0; s < 4; s++) mbar_arrive(bars + 8u * B_GO);
        RingProd rp;
#pragma unroll 1
        for (int sg = 4; sg < 34; sg++) {
          const int part = sg & 3, inst = (sg >> 2) - (part & 1);
          if (part == 3 || inst == 8) continue;
          const int ty = (inst >> 1) & 1;
          if (part != 1) {
            const int k0 = part ? q_split(inst) : 0, k1 = part ? 16 : q_split(inst);
#pragma unroll 1
            for (int kt = k0; kt < k1; kt++) {
              const uint32_t sa = rp.next(B_QF + (kt & 3), (kt >> 2) & 1, true), fb = bars + 8u * (B_QF + (kt & 3));
              mbar_expect_tx(fb, 3 * UNIT);
              tma_load_3d(sa, &P.wqkv3[ty], fb, hp * 64, kt * 64);
            }
          } else {
            const bool pre = w_pre(inst);
            const int lag = pre ? 8 : 5;
            uint32_t sa = 0;
#pragma unroll 1
            for (int kt = 0; kt < 16; kt++) {
              const int i = kt & 3;
              const uint32_t fb = bars + 8u * (B_WF + (kt & 7));
              if (i == 1) sa += 2 * UNIT;
              else if (i != 3 || !pre) sa = rp.next(kt == 14 ? B_RF : B_WF + ((kt | 1) & 7), kt == 14 ? inst & 1 : kt >> 3, kt < lag) + ((0x21 >> (2 * i)) & 3) * UNIT;
              if (kt >= lag) mbar_wait(bars + 8u * (B_WF + B_E + ((kt - lag) & 7)), (kt - lag) >> 3);
              if (i == 3 && pre) {
                mbar_arrive(fb);
              } else {
                mbar_expect_tx(fb, 2 * UNIT);
                tma_load_3d(sa, &P.wo3[ty], fb, ct * 128, kt * 64);
              }
            }
          }
        }
      }
    } else if (warp == 13) {
      RingProd rp;
      unsigned ep1 = 0;
      uint32_t seenx = 0;
      named_bar_sync(0, 512);
      mbar_wait(bars + 8u * B_GO, 0);
#pragma unroll 1
      for (int sg = 4; sg < 34; sg++) {
        const int part = sg & 3, inst = (sg >> 2) - (part & 1);
        if (part == 3 || inst == 8) continue;
        const int L = inst >> 1, ch = inst & 1;
        uint32_t seen = 0;
        if (part != 1) {
          const CUtensorMap* tx = &P.xq[L];
          const int k0 = part ? q_split(inst) : 0, k1 = part ? 16 : q_split(inst);
          if (part == 0) seenx = L == 0 ? 0xffffffffu : 0u;
          if (sg == 4) ep1 = launch_epoch();
          const int m0 = ch * 16 + qr * 2;
#pragma unroll 1
          for (int kt = k0; kt < k1; kt++) {
            wait_count(g_fx[ch * 8 + qr][0], 6u * ep1 - 6u + 2u * L, kt, seenx, lane);
            TGET(t38);
            const uint32_t sa = rp.next(B_QF + (kt & 3), (kt >> 2) & 1, true);
            TGET(t39);
            if (elect_one()) {
              const uint32_t fb = bars + 8u * (B_QF + (kt & 3));
              mbar_expect_tx(fb, 2 * UNIT);
              tma_load_5d(sa + 3 * UNIT, tx, fb, kt * 64, m0);
            }
            if (L == 3 && kt == 0 && lane == 0) { TPUT(ch, 38, t38); TPUT(ch, 39, t39); }
          }
        } else {
          const int m0 = ch * 1024 + rt * 64;
          const bool pre = w_pre(inst);
          const int lag = pre ? 8 : 5;
          uint32_t sa = 0;
#pragma unroll 1
          for (int kt = 0; kt < 16; kt++) {
            const int i = kt & 3;
            const uint32_t fb = bars + 8u * (B_WF + (kt & 7));
            wait_count(g_fo[ch * 16 + rt][0], 4u * ep1 - 3u + L, kt, seen, lane);
            const bool stg = kt == 13 && inst == 6 && SP7 == 16;
            if (i < 2) sa = rp.next(stg ? B_RF : B_WF + (kt & 7) + i + 1, stg ? inst & 1 : kt >> 3, kt < lag);
            else sa += (2 * i - 3) * UNIT;
            if (kt >= lag) mbar_wait(bars + 8u * (B_WF + B_E + ((kt - lag) & 7)), (kt - lag) >> 3);
            if (elect_one()) {
              mbar_expect_tx(fb, UNIT);
              tma_load_2d(sa, &P.o, fb, kt * 64, m0);
            }
            if (i == 3 && !pre) rp.next(B_WF + (kt & 7), kt >> 3, false);
          }
        }
      }
    } else if (warp == 14) {
      const unsigned ep1 = launch_epoch();
      uint32_t hpar = 0;
      named_bar_sync(0, 512);
#pragma unroll 1
      for (int inst = 0; inst < 8; inst++) {
        const int L = inst >> 1, ch = inst & 1, gb = ch * 8 + qr;
        const unsigned kv0 = 8u * ep1 - 8u + 2u * L + (L & 1);
        if ((L & 1) == 0) {
          uint8_t* img = g_kvA[L >> 1][gb][hp][0];
          const uint8_t* s1 = gb > 0 ? img - 16 * 32768 : g_zero;
          const uint8_t* s2 = gb > 1 ? img - 32 * 32768 : g_zero;
          const uint32_t h1 = gb > 0 ? 16384 : 0, h2 = gb > 1 ? 16384 : 0;
          const unsigned* cp = g_fk[hp][max(gb - 1 - (lane >= 3), 0)];
          const unsigned ct0 = kv0 + ((0x32321u >> (4 * (lane & 7))) & 3u);
          uint32_t fr = gb == 0 ? 31u : (gb == 1 ? 24u : 0u);
          const uint32_t toff = slots + lane * 128 + ((lane & 7) << 4);
          auto seen = [&](uint32_t m) {
#pragma unroll 1
            for (uint32_t it = 0; it < (1u << 17) && !(fr & m); ++it)
              fr |= __ballot_sync(0xffffffffu, (int)(ld_relaxed_u32(cp) - ct0) >= 0);
          };
          auto load = [&](uint32_t off, const uint8_t* src, uint32_t bytes, int bi) {
            if (elect_one()) {
              mbar_expect_tx(bars + 8u * (B_HL + bi), bytes);
              bulk_load(slots + off, src, bytes, bars + 8u * (B_HL + bi));
            }
          };
          auto check = [&](uint32_t off, const uint8_t* src, uint32_t bytes, int bi, bool real, int done) {
#pragma unroll 1
            for (int tries = 0; tries < 4096; tries++) {
              mbar_wait(bars + 8u * (B_HL + bi), (hpar >> bi) & 1u);
              hpar ^= 1u << bi;
              uint32_t t = (lds32(toff + off) ^ ep1) | (lds32(toff + off + 4096) ^ ep1);
              if (bytes > 8192) t |= (lds32(toff + off + 8192) ^ ep1) | (lds32(toff + off + 12288) ^ ep1);
              if (!__any_sync(0xffffffffu, real && (t & 1u))) break;
              fence_proxy_async_smem();
              load(off, src, bytes, bi);
            }
            if (lane == 0) mbar_arrive(bars + 8u * done);
          };
          uint8_t *pk = img + 16384, *pv = img + 24576;
          unsigned* f = g_fk[hp][gb];
          pin64(pk), pin64(pv), pin64(f);
          mbar_wait(bars + 8u * B_KV, inst & 1);
          if (elect_one()) {
            bulk_store(pk, slots + 16384, 8192);
            bulk_announce(f);
            bulk_store(pv, slots + 24576, 8192);
            bulk_announce(f);
            bulk_commit();
          }
          HTS(44);
          seen(1);
          HTS(46);
          load(32768, s1 + h1, 8192, 0);
          seen(2);
          HTS(47);
          load(40960, s1 + h1 + 8192, 8192, 1);
          mbar_wait(bars + 8u * B_LOC, inst & 1);
          HTS(45);
          if (elect_one()) {
            bulk_store(img, slots, 16384);
            bulk_announce(g_fk[hp][gb]);
            bulk_commit();
            asm volatile("cp.async.bulk.wait_group.read 1;" ::: "memory");
          }
          check(32768, s1 + h1, 8192, 0, gb > 0, B_HALO);
          HTS(52);
          check(40960, s1 + h1 + 8192, 8192, 1, gb > 0, B_HV);
          HTS(53);
#pragma unroll 1
          for (int n = 1; n < 4; n++) {
            const uint8_t* src = n == 1 ? s1 : (n == 2 ? s2 + h2 : s2);
            const uint32_t off = n == 3 ? 32768 : 32768 - n * 16384;
            seen(2u << n);
            if (n == 2 && elect_one()) bulk_wait_read0();
            mbar_wait(bars + 8u * (B_REL - 1) + 8u * n, ch);
            HTS(47 + n);
            load(off, src, 16384, 0);
            check(off, src, 16384, 0, gb > (n >> 1), B_HALO + n);
            HTS(53 + n);
          }
        } else {
          uint8_t* img = g_kvB[L >> 1][gb][hp];
          uint8_t *pk = img, *pv = img + 2048;
          unsigned* f = g_fk[hp][gb];
          pin64(pk), pin64(pv), pin64(f);
          mbar_wait(bars + 8u * B_KV, inst & 1);
          if (elect_one()) {
            bulk_store(pk, KB_ROW0 + 112 * 128, 2048);
            bulk_store(pv, VB_ROW0 + 112 * 128, 2048);
            bulk_announce(f);
            bulk_commit();
          }
          HTS(44);
          const uint8_t* src = gb >= 1 ? img - 16 * 4096 : g_zero;
#pragma unroll 1
          for (uint32_t it = 0; it < (1u << 17); ++it)
            if (gb == 0 || (int)(ld_relaxed_u32(g_fk[hp][gb - 1]) - kv0) > 0) break;
          HTS(46);
#pragma unroll 1
          for (uint32_t it = 0; it < 4096; ++it) {
            if (elect_one()) {
              mbar_expect_tx(bars + 8u * B_HL, 4096);
              bulk_load(KB_ROW0 - 2048, src, 2048, bars + 8u * B_HL);
              bulk_load(VB_ROW0 - 2048, src + 2048, 2048, bars + 8u * B_HL);
              bulk_wait_read0();
            }
            mbar_wait(bars + 8u * B_HL, hpar & 1u);
            hpar ^= 1u;
            const uint32_t t = lds32((lane < 16 ? KB_ROW0 - 2048 : VB_ROW0 - 4096) + lane * 128 + ((lane & 7) << 4)) ^ ep1;
            if (gb == 0 || !__any_sync(0xffffffffu, t & 1u)) break;
            fence_proxy_async_smem();
          }
          if (lane == 0) mbar_arrive(bars + 8u * B_HALO);
          HTS(52);
        }
        if (elect_one()) {
          const CUtensorMap* mo = &P.o;
          unsigned *f1 = g_fo[gb * 2 + 1][hp], *f0 = g_fo[gb * 2][hp];
          int c0 = hp * 64, r0 = gb * 128, r1 = r0 + 64;
          pin64(mo), pin64(f1), pin64(f0);
          asm volatile("" : "+r"(c0), "+r"(r0), "+r"(r1));
          mbar_wait(bars + 8u * B_OS1, (inst & 1) ^ 1);
          tma_store_2d(mo, slots + 7 * UNIT, c0, r1);
          bulk_announce(f1);
          bulk_commit();
          mbar_wait(bars + 8u * B_OS0, inst & 1);
          tma_store_2d(mo, slots + 6 * UNIT, c0, r0);
          bulk_announce(f0);
          bulk_commit();
          bulk_wait_read0();
          mbar_expect_tx(bars + 8u * B_RF, 2 * UNIT);
          tma_load_2d(slots + 6 * UNIT, &P.x[L], bars + 8u * B_RF, ct * 128, ch * 1024 + rt * 64);
          tma_load_2d(slots + 7 * UNIT, &P.x[L], bars + 8u * B_RF, ct * 128 + 64, ch * 1024 + rt * 64);
          if (w_pre(inst)) {
            mbar_expect_tx(bars + 8u * B_PRE, 6 * UNIT);
            mbar_expect_tx(bars + 8u * B_PRE2, 2 * UNIT);
#pragma unroll 1
            for (int j = 0; j < 4; j++) {
              __nanosleep(PRESLEEP);
              if (j == 3) mbar_wait(bars + 8u * B_RDONE, (inst & 1) ^ 1);
              tma_load_3d(slots + j * 2 * UNIT, &P.wo3[L & 1], bars + 8u * (j == 3 ? B_PRE2 : B_PRE), ct * 128, (4 * j + 3) * 64);
            }
          }
        }
        __syncwarp();
      }
    } else {
      const unsigned ep1 = launch_epoch();
      named_bar_sync(0, 512);
      mbar_wait(bars + 8u * B_GO, 0);
#pragma unroll 1
      for (int i = 0; i < 20; i++) {
        const char* src = i < 4 ? reinterpret_cast<const char*>(P.wo_p[0]) + (size_t)b * 16384 + i * 4096
                                : (i < 16 ? reinterpret_cast<const char*>(P.wqkv_p[1]) + (size_t)b * 49152 + (i - 4) * 4096
                                          : reinterpret_cast<const char*>(P.wo_p[1]) + (size_t)b * 16384 + (i - 16) * 4096);
        asm volatile("prefetch.global.L2 [%0];" ::"l"(src + lane * 128));
        __nanosleep(TRICKLE);
      }
#pragma unroll 1
      for (int inst = 2; inst < 10; inst++) {
        const int L = inst >> 1, ch = inst & 1, gb = ch * 8 + qr;
        {
          uint32_t xb = base + (((inst < 9 ? q_split(inst - 1) : 0) + (w_pre(inst - 2) ? 3 : 2)) & 3) * 5 * UNIT;
          unsigned* f = g_fx[ch * 8 + (rt >> 1)][ct * 2];
          const CUtensorMap* mx = &P.x[L];
          int c0 = ct * 128, r0 = ch * 1024 + rt * 64;
          pin64(f), pin64(mx);
          asm volatile("" : "+r"(xb), "+r"(c0), "+r"(r0));
#pragma unroll
          for (int h = 0; h < 2; h++) {
            mbar_wait(bars + 8u * (B_XS + h), ch);
            if (elect_one()) {
              tma_store_2d(mx, xb + h * UNIT, c0 + h * 64, r0);
              if (L < 4) bulk_announce(f + 4 * h);
              bulk_commit();
              if (h == 1) {
                bulk_wait_read0();
                mbar_arrive(bars + 8u * (B_RF + B_E));
              }
            }
          }
          if (L == 4) continue;
        }
#pragma unroll 1
        for (int h = 0; h < 4; h++) {
          const float4* sp = &g_stats[L][0][gb * 128 + h * 32 + lane];
          const float4 s0 = sum_recs<4>(sp, S_LEN, ep1), s1 = sum_recs<4>(sp + 4 * S_LEN, S_LEN, ep1);
          sts32(base + OFF_RS + (ch * 128 + h * 32 + lane) * 4, ln_params(s0.x + s1.x, s0.y + s1.y));
        }
        if (inst == 2) {
#pragma unroll 1
          for (int hf = 0; hf < 2; hf++) {
            const float4* cp = &g_cs[1][hp][0][hf * 32 + lane];
            const float4 s0 = sum_recs<4>(cp, 64, ep1), s1 = sum_recs<4>(cp + 4 * 64, 64, ep1);
            put_colsums(1, hf * 32 + lane, make_float4(s0.x + s1.x, s0.y + s1.y, s0.z + s1.z, 0.f));
          }
        }
        fence_proxy_async_smem();
        __syncwarp();
        if (lane == 0) mbar_arrive(bars + 8u * (B_PREP + ch));
      }
    }
  } else {
    const bool asst = warp >= 8;
    GTL(0);
    if (warp >= 4) named_bar_sync(0, 512);
    if (warp >= 4 && !asst) {
      PHASE_IDS
      {
        const unsigned ep1 = launch_epoch();
        const int row = b * 16 + (tid >> 3);
        const uint4* src = reinterpret_cast<const uint4*>(P.in_x + (size_t)row * DM) + (tid & 7);
        float s1 = 0.f, s2 = 0.f;
#pragma unroll 1
        for (int k = 0; k < 4; k++) {
          mbar_pace(bars + 8u * (B_QF + B_E + ((2 * k) & 3)), k >> 1);
          uint4 v[4];
#pragma unroll
          for (int j = 0; j < 4; j++) v[j] = __ldg(src + (k * 4 + j) * 8);
#pragma unroll
          for (int j = 0; j < 4; j++) {
            const uint32_t w[4] = {v[j].x, v[j].y, v[j].z, v[j].w};
#pragma unroll
            for (int e = 0; e < 4; e++) {
              const float x0 = bf_lo(w[e]), x1 = bf_hi(w[e]);
              s1 += x0 + x1;
              s2 = fmaf(x0, x0, fmaf(x1, x1, s2));
            }
          }
        }
#pragma unroll
        for (int o = 1; o < 8; o <<= 1) {
          s1 += __shfl_xor_sync(0xffffffffu, s1, o);
          s2 += __shfl_xor_sync(0xffffffffu, s2, o);
        }
        if ((tid & 7) == 0) st_rec(&g_stats[0][0][row], s1, s2, 0.f, ep1);
        if (tid == 0) sts32(base + OFF_EPOCH, ep1);
        if (tid < 64) {
          const float4 s0 = sum_recs<8>(&g_cs[0][hp][0][tid], 64, ep1);
          put_colsums(0, tid, s0);
        } else {
          put_colsums(1, tid - 64, make_float4(0.f, 0.f, 0.f, 0.f));
        }
#pragma unroll 1
        for (int cc = 0; cc < 2; cc++) {
          const float4 s0 = sum_recs<1>(&g_stats[0][0][(cc * 8 + qr) * 128 + tid], 0, ep1);
          sts32(base + OFF_RS + (cc * 128 + tid) * 4, ln_params(s0.x, s0.y));
        }
        fence_proxy_async_smem();
        named_bar_sync(2, 128);
        if (tid < 2) mbar_arrive(bars + 8u * (B_PREP + tid));
      }
    }
#pragma unroll 1
    for (int inst = asst ? 0 : warp >> 2; inst < 8; inst += asst ? 1 : 2) {
      const int L = inst >> 1, ch = inst & 1, gb = ch * 8 + qr;
      uint32_t q[2][2][4];
      if (asst) {
        if (inst < 2) colsum_part(&P.wqkv[inst], inst, qr, hp);
        setmaxnreg_dec<24>();
        named_bar_sync(4, 256);
        setmaxnreg_inc<128>();
        const uint32_t ra = q_row_addr(L & 1, 1, warp & 3, fresh_tid() & 31);
#pragma unroll
        for (int j = 0; j < 4; j++) ldmatrix_x4(q[j >> 1][j & 1], ra ^ (j << 5));
      } else {
      setmaxnreg_inc<224>();
      {
        float acc[2][96];
        const int ksp = q_split(inst);
        constexpr uint32_t STG = 5 * (UNIT >> 4), D0 = ((base + 3 * UNIT) >> 4) + 0x10000u;
        constexpr uint32_t DB = ((UNIT >> 4) << 16) - 0x10000u - 3 * (UNIT >> 4);
        uint32_t sd = D0;
        const uint32_t toff = ((fresh_tid() & 127) << 7) + ((fresh_tid() & 7) << 4);
        const bool lane0 = (toff & 0xf80u) == 0u;
        uint32_t tbad = 0u, tw, xt = x_tag(lds32(base + OFF_EPOCH), L);
        uint32_t rsa = base + OFF_RS + (ch * 128 + tile_row(L & 1, warp & 3, 0, (toff >> 9) & 7)) * 4;
        uint32_t rsb = rsa + ((L & 1) ? 32 : 128);
        uint32_t lnm = ((toff >> 7) & 3) == (L & 1) ? 0xffffffffu : 0u, tmk = L > 0;
        uint32_t soff = tile_row(L & 1, warp & 3, (toff >> 10) & 1, (toff >> 7) & 7) * 128 + ((toff ^ (toff >> 7)) & 0x10u) + (toff & 0x60u);
        uint32_t bprep = bars + 8u * (B_PREP + ch), bturn = bars + 8u * (B_TURN + (ch ^ 1));
        uint32_t bfree = bars + 8u * (inst == 1 ? B_CSD : B_RDONE), pfree = inst == 1 ? 0 : inst & 1, pprep = L & 1;
        asm volatile("" : "+r"(rsa), "+r"(rsb), "+r"(lnm), "+r"(soff), "+r"(xt), "+r"(tmk));
        asm volatile("" : "+r"(bprep), "+r"(bturn), "+r"(bfree), "+r"(pfree), "+r"(pprep));
        if (inst == 0) named_bar_sync(0, 512);
        if (inst == 1 || (inst > 1 && q_split(inst - 1) < 16)) mbar_wait_lazy<TLAZY>(bars + 8u * (B_TURN + ch), (turn_par(0) >> inst) & 1u);
        if (L == 3) GTL(37);
        mbar_wait(bars + 8u * B_QF, 0);
        GTL(1 + L * 8);
        {
          const uint64_t da = desc_lo(sd) + P.zero;
          wgmma_fence();
          wgmma_n192_ssz_ta0_tb1(acc[1], da + (UNIT >> 4), da + DB);
          wgmma_commit();
          wgmma_n192_ssz_ta0_tb1(acc[0], da, da + DB);
          wgmma_commit();
        }
#pragma unroll 1
        for (int kt = 0; kt < 15; kt++) {
          const bool last = kt + 1 == ksp;
          const uint64_t da = desc_lo(sd) + P.zero;
          const uint32_t fn = bars + 8u * (B_QF + ((kt + 1) & 3)), pn = ((kt + 1) >> 2) & 1;
#pragma unroll
          for (int k16 = 0; k16 < 4; k16++) {
            if (k16 == 0 && kt == 0) continue;
            wgmma_fence();
            wgmma_n192_ss_ta0_tb1(acc[1], da + ((UNIT >> 4) + k16 * 2), da + (DB + k16 * 128), 1);
            wgmma_commit();
            wgmma_wait<1>();
            if (k16 == 0 && lane0 && kt != ksp) mbar_arrive(bars + 8u * (B_QF + B_E + ((kt - 1) & 3)));
            wgmma_fence();
            wgmma_n192_ss_ta0_tb1(acc[0], da + k16 * 2, da + (DB + k16 * 128), 1);
            wgmma_commit();
            if (k16 == 1) tw = lds32(((sd & 0xffffu) << 4) + toff);
            if (k16 == 2) tbad |= tw ^ xt;
            bool ok = true;
            if (k16 == 2) ok = mbar_test(fn, pn) || last;
            if (k16 == QTURN && last && lane0) mbar_arrive(bturn);
            if (k16 < 3) wgmma_wait<1>();
            if (k16 == 2 && !ok) mbar_wait(fn, pn);
          }
          sd = sd == D0 + 3 * STG ? D0 : sd + STG;
          if (last) {
            wgmma_wait<0>();
            if (lane0) mbar_arrive(bars + 8u * (B_QF + B_E + (kt & 3)));
            mbar_wait_lazy<TLAZY>(bars + 8u * (B_TURN + ch), (turn_par(1) >> inst) & 1u);
            mbar_wait(fn, pn);
          }
        }
        constexpr uint32_t DL = D0 + 3 * STG;
        wgmma_fence();
#pragma unroll
        for (int k16 = 0; k16 < 4; k16++) wgmma_n192_ss_ta0_tb1(acc[1], desc_lo(DL + (UNIT >> 4) + k16 * 2), desc_lo(DL + DB + k16 * 128), 1);
        wgmma_commit();
        tw = lds32(((DL & 0xffffu) << 4) + toff);
        mbar_wait(bprep, pprep);
        uint32_t rs[2][2];
        constexpr uint64_t DCS = (uint64_t)((base + OFF_CS) >> 4) | (4ull << 32);
        auto ln_mma = [&](float (&d)[96], uint32_t (&r)[2], int h) {
          uint32_t a[4];
#pragma unroll
          for (int i = 0; i < 2; i++) {
            if (h) r[i] = lds32((i ? rsb : rsa) + 256);
            a[i] = (__byte_perm(r[i], 0u, 0x1010) ^ 0x80008000u) & lnm;
            a[i + 2] = r[i] & P.zero;
          }
#pragma unroll
          for (int i = 0; i < 4; i++) asm volatile("" : "+r"(a[i]));
          wgmma_fence();
          wgmma_n192_rs_tb1(d, a, DCS, 1);
          wgmma_commit();
        };
        ln_mma(acc[1], rs[1], 1);
        wgmma_wait<2>();
        if (lane0 && ksp != 15) mbar_arrive(bars + 8u * (B_QF + B_E + 2));
        wgmma_fence();
#pragma unroll
        for (int k16 = 0; k16 < 4; k16++) wgmma_n192_ss_ta0_tb1(acc[0], desc_lo(DL + k16 * 2), desc_lo(DL + DB + k16 * 128), 1);
        wgmma_commit();
        if (lane0) mbar_arrive(bturn);
        const uint32_t ep1 = lds32(base + OFF_EPOCH);
        rs[0][0] = lds32(rsa);
        rs[0][1] = lds32(rsb);
        static_assert(SP1 < 16 && (PREMASK & 1u), "column sums of B");
        const bool afree = mbar_test(bfree, pfree) & (mbar_test(bars + 8u * (B_WF + B_E + 7), 1) | (ksp == 16));
        const bool redo = named_bar_or(1 + ch, 128, (tbad | (tw ^ xt)) & tmk);
        float rinv[2];
#pragma unroll
        for (int r = 0; r < 2; r++) {
          rinv[r] = rcp_fast(bf_hi(rs[1][r]));
          asm volatile("" : "+f"(rinv[r]));
        }
        const uint32_t kdst = ((L & 1) ? KB_ROW0 : slots) + soff, vdst = ((L & 1) ? VB_ROW0 : slots + 8192) + soff;
        const uint32_t hs = (L & 1) ? 8192 : 16384, c0 = (toff & 0x180u) == 0u;
        wgmma_wait<1>();
        if (redo) {
          wgmma_wait<0>();
          constexpr uint32_t sa = (DL & 0xffffu) << 4;
          const uint32_t rb = bars + 8u * (B_REDO + ch);
          if (toff == 0) {
            mbar_init(rb, 1);
            fence_barrier_init();
          }
          uint32_t rpar = 0;
#pragma unroll 1
          for (int kt = 0, tries = 0; kt < 16;) {
            fence_proxy_async_smem();
            named_bar_sync(1 + ch, 128);
            if ((warp & 3) == 0 && elect_one()) {
                mbar_expect_tx(rb, 5 * UNIT);
              tma_load_5d(sa, &P.xq[L], rb, kt * 64, gb * 2);
              tma_load_3d(sa - 3 * UNIT, &P.wqkv3[L & 1], rb, hp * 64, kt * 64);
            }
            mbar_wait(rb, rpar);
            rpar ^= 1u;
            if (named_bar_or(1 + ch, 128, (lds32(sa + toff) ^ xt) & 1u) && ++tries < 4096) continue;
            wgmma_fence();
#pragma unroll
            for (int k16 = 0; k16 < 4; k16++) {
              const uint64_t db = make_desc(sa - 3 * UNIT + k16 * 2048, UNIT);
              wgmma_n192_ss_ta0_tb1(acc[1], make_desc(sa + UNIT + k16 * 32, 16), db, kt | k16);
              wgmma_n192_ss_ta0_tb1(acc[0], make_desc(sa + k16 * 32, 16), db, kt | k16);
            }
            wgmma_commit();
            wgmma_wait<0>();
            kt++;
          }
          ln_mma(acc[1], rs[1], 1);
          wgmma_wait<0>();
        }
        ln_mma(acc[0], rs[0], 0);
        reg_fence<96>(acc[1]);
        GTL(2 + L * 8);
        if (!afree) {
          mbar_wait(bfree, pfree);
          if (ksp < 16) mbar_wait(bars + 8u * (B_WF + B_E + 7), 1);
        }
#pragma unroll
        for (int t = 0; t < 24; t++) {
          const int h = t < 12 ? 1 : 0, p = ((t % 12) / 4 + 1) % 3, jp = t & 3;
          if (t == QREL) {
            wgmma_wait<0>();
            reg_fence<96>(acc[0]);
            if (lane0) mbar_arrive(bars + 8u * (B_QF + B_E + 3));
          }
          if (t == 8 || t == 20) {
            rinv[0] *= SM_C;
            rinv[1] *= SM_C;
          }
          const float* a = &acc[h][4 * (p * 8 + 2 * jp)];
          uint32_t r0 = pack_bf16x2(a[0] * rinv[0], a[1] * rinv[0]);
          uint32_t r1 = pack_bf16x2(a[2] * rinv[1], a[3] * rinv[1]);
          if (p != 0 && jp == 0) {
            r0 = set_tag(r0, c0, ep1);
            r1 = set_tag(r1, c0, ep1);
          }
          const uint32_t r2 = pack_bf16x2(a[4] * rinv[0], a[5] * rinv[0]);
          const uint32_t r3 = pack_bf16x2(a[6] * rinv[1], a[7] * rinv[1]);
          const uint32_t dst = p == 0 ? slots + 3 * 16384 + soff + h * 8192 : (p == 1 ? kdst : vdst) + h * hs;
          stmatrix_x4(dst ^ (jp << 5), r0, r1, r2, r3);
          if (t >= 20) {
            q[jp >> 1][jp & 1][0] = r0;
            q[jp >> 1][jp & 1][1] = r1;
            q[jp >> 1][jp & 1][2] = r2;
            q[jp >> 1][jp & 1][3] = r3;
          }
          if (t == 7 || t == 19) signal_async(bars + 8u * (t == 7 ? B_KV : B_LOC), lane0);
          if (t == 11) {
            setmaxnreg_dec<128>();
            named_bar_arrive(4, 256);
#pragma unroll
            for (int r = 0; r < 2; r++) rinv[r] = rcp_fast(bf_hi(rs[0][r]));
          }
        }
        mbar_wait(bars + 8u * B_LOC, inst & 1);
      }
      }
      GTL(3 + L * 8);
      if ((L & 1) == 0) attention_a(q, asst, L, gb, hp, ch, warp & 3, P.zero);
      else attention_b(q, asst, gb, inst & 1, warp & 3);
      GTL(4 + L * 8);
      signal_async(bars + 8u * (asst ? B_OS1 : B_OS0), (fresh_tid() & 31) == 0);
      if (asst) continue;
      GTL(5 + L * 8);

      {
        float acc[64];
        const int sp = inst < 7 ? q_split(inst + 1) : 0;
        int st = sp & 3;
        const bool pre = w_pre(inst);
        uint32_t tbad = 0u;
        const uint32_t toff = ((fresh_tid() & 63) << 7) + ((fresh_tid() & 7) << 4);
        const bool lane0 = (toff & 0xf80u) == 0u;
        constexpr uint32_t U4 = UNIT >> 4, LA = 0x10000u, LB = U4 << 16;
        reg_define<64>(acc);
        reg_fence<64>(acc);
        uint32_t xv[8][4];
        {
          PHASE_IDS_W
          const uint32_t xr = slots + 6 * UNIT + (wwarp * 16 + (lane & 15)) * 128 + (((lane >> 4) ^ (lane & 7)) << 4);
          mbar_wait(bars + 8u * B_RF, inst & 1);
#pragma unroll
          for (int jp = 0; jp < 8; jp++) ldmatrix_x4(xv[jp], (xr ^ ((jp & 3) << 5)) + (jp >> 2) * UNIT);
          signal_async(bars + 8u * B_RDONE, lane0);
          if (L > 0) {
            uint32_t lsb;
            asm volatile("ld.shared.u8 %0, [%1];" : "=r"(lsb) : "r"(base + OFF_LSB + ch * 32 + wwarp * 8 + g) : "memory");
#pragma unroll
            for (int k = 0; k < 4; k++) xv[(k >> 1) * 4][k & 1] = set_tag(xv[(k >> 1) * 4][k & 1], c == 0, lsb >> k);
          }
        }
        const unsigned ep1 = lds32(base + OFF_EPOCH);
        uint32_t tmx = L < 3 && (toff & 0x180u) == 0u, xt = x_tag(ep1, L + 1);
        uint32_t xrow = base + ((st + (pre ? 3 : 2)) & 3) * 5 * UNIT + (warp & 3) * 2048 + (toff & 0x7e0u) + ((toff ^ (toff >> 7)) & 0x10u);
        asm volatile("" : "+r"(tmx), "+r"(xt), "+r"(xrow));
        uint64_t d0 = desc_lo((base >> 4) + st * 5 * U4) + P.zero;
        if (inst < 7 || SP7 == 16) mbar_wait_lazy<TLAZY>(bars + 8u * (B_TURN + ch), (turn_par(2) >> inst) & 1u);
        mbar_wait(bars + 8u * B_WF, 0);
        GTL(6 + L * 8);
        uint32_t s1 = 0;
#pragma unroll 1
        for (int m = 0; m < 4; m++) {
          const uint32_t s0 = base + st * 5 * UNIT, fb = bars + 8u * (B_WF + 4 * (m & 1));
          s1 = base + ((st + 1) & 3) * 5 * UNIT;
          const uint64_t d1 = desc_lo(s1 >> 4) + P.zero;
          const uint64_t d2 = desc_lo((pre ? slots + m * 2 * UNIT : base + ((st + 2) & 3) * 5 * UNIT) >> 4) + P.zero;
          st = (st + (pre ? 2 : 3)) & 3;
#pragma unroll
          for (int i = 0; i < 4; i++) {
            const uint64_t da = (i == 0 ? d0 : d1) + (LA + (i == 2 ? 1 : (i == 3 ? 4 : 0)) * U4);
            const uint64_t db = (i < 2 ? d0 : (i == 2 ? d1 : d2)) + (LB + (i == 0 ? 1 : (i == 1 ? 3 : (i == 2 ? 2 : 0))) * U4);
            if (i == 3 && (m == 0 || m == 3) && pre) mbar_wait(bars + 8u * (m ? B_PRE2 : B_PRE), __popc(PREMASK & ((1u << inst) - 1u)) & 1);
            if (i == (WTURN & 3) && m == 3 && lane0 && (sp < 16 || inst == 6)) mbar_arrive(bars + 8u * (B_TURN + (ch ^ 1)));
            wgmma_fence();
#pragma unroll
            for (int k16 = 0; k16 < 4; k16++) wgmma_n128_ss_ta0_tb1(acc, da + 2 * k16, db + 128 * k16, 1);
            wgmma_commit();
            if (i == 2) d0 = desc_lo((base >> 4) + st * 5 * U4) + P.zero;
            tbad |= lds32((i == 0 ? s0 : s1) + (i == 2 ? 1 : (i == 3 ? 4 : 0)) * UNIT + toff) ^ o_tag(L);
            const uint32_t fn = i < 3 ? fb + 8u * (i + 1) : fb ^ 96u;
            const uint32_t pn = i < 3 ? m >> 1 : m > 0;
            const bool ok = mbar_test(fn, pn) || (i == 3 && m == 3);
            wgmma_wait<1>();
            if (lane0 && (i > 0 || m > 0)) mbar_arrive((i > 0 ? fb + 8u * (i - 1) : (fb ^ 96u) + 24u) + 8u * B_E);
            if (!ok) mbar_wait(fn, pn);
          }
        }
        const bool redo = named_bar_or(1 + ch, 128, tbad & 1u);
        if (redo) {
          wgmma_wait<0>();
          const uint32_t sa = s1 + 4 * UNIT, sb = s1 + 2 * UNIT;
          const uint32_t rb = bars + 8u * (B_REDO + ch);
          if ((fresh_tid() & 127) == 0) {
            mbar_init(rb, 1);
            fence_barrier_init();
          }
          uint32_t rpar = 0;
#pragma unroll 1
          for (int kt = 0, tries = 0; kt < 16;) {
            fence_proxy_async_smem();
            named_bar_sync(1 + ch, 128);
            if ((warp & 3) == 0 && elect_one()) {
                mbar_expect_tx(rb, 3 * UNIT);
              tma_load_2d(sa, &P.o, rb, kt * 64, ch * 1024 + rt * 64);
              tma_load_3d(sb, &P.wo3[L & 1], rb, ct * 128, kt * 64);
            }
            mbar_wait(rb, rpar);
            rpar ^= 1u;
            if (named_bar_or(1 + ch, 128, (lds32(sa + toff) ^ o_tag(L)) & 1u) && ++tries < 4096) continue;
            wgmma_fence();
#pragma unroll
            for (int k16 = 0; k16 < 4; k16++)
              wgmma_n128_ss_ta0_tb1(acc, make_desc(sa + k16 * 32, 16), make_desc(sb + k16 * 2048, UNIT), kt | k16);
            wgmma_commit();
            wgmma_wait<0>();
            kt++;
          }
        }
        wgmma_wait<0>();
        reg_fence<64>(acc);
        if (lane0) mbar_arrive(bars + 8u * (B_WF + B_E + 7));
        GTL(7 + L * 8);
#pragma unroll
        for (int jp = 0; jp < 8; jp++) {
#pragma unroll
          for (int q = 0; q < 4; q++) xv[jp][q] = add_bf16x2(xv[jp][q], pack_bf16x2(acc[8 * jp + 2 * q], acc[8 * jp + 2 * q + 1]));
          const bool tg = (jp & 3) == 0;
          stmatrix_x4((xrow ^ ((jp & 3) << 5)) + (jp >> 2) * UNIT,
                      tg ? set_tag(xv[jp][0], tmx, xt) : xv[jp][0], tg ? set_tag(xv[jp][1], tmx, xt) : xv[jp][1], xv[jp][2], xv[jp][3]);
          if ((jp & 3) == 3) signal_async(bars + 8u * (B_XS + (jp >> 2)), lane0);
        }
        if (L < 3) {
          PHASE_IDS_W
          const int grow = ch * 1024 + rt * 64;
          if (c == 0)
            asm volatile("st.shared.u8 [%0], %1;" ::"r"(base + OFF_LSB + ch * 32 + wwarp * 8 + g),
                         "r"((xv[0][0] & 1u) | ((xv[0][1] & 1u) << 1) | ((xv[4][0] & 1u) << 2) | ((xv[4][1] & 1u) << 3)) : "memory");
          float s1[2] = {0.f, 0.f}, s2[2] = {0.f, 0.f};
#pragma unroll
          for (int jp = 0; jp < 8; jp++)
#pragma unroll
            for (int q = 0; q < 4; q++) {
              const float x0 = bf_lo(xv[jp][q]), x1 = bf_hi(xv[jp][q]);
              s1[q & 1] += x0 + x1;
              s2[q & 1] = fmaf(x0, x0, fmaf(x1, x1, s2[q & 1]));
            }
#pragma unroll
          for (int r = 0; r < 2; r++) {
            s1[r] += __shfl_xor_sync(0xffffffffu, s1[r], 1);
            s2[r] += __shfl_xor_sync(0xffffffffu, s2[r], 1);
            s1[r] += __shfl_xor_sync(0xffffffffu, s1[r], 2);
            s2[r] += __shfl_xor_sync(0xffffffffu, s2[r], 2);
            if (c == 0) st_rec(&g_stats[L + 1][ct][grow + wwarp * 16 + g + 8 * r], s1[r], s2[r], 0.f, ep1);
          }
        }
        GTL(8 + L * 8);
      }
    }
    if (threadIdx.x == 128) atomicAdd(g_done, 1u);
  }
}

typedef CUresult (*PFN_tmEncode)(CUtensorMap*, CUtensorMapDataType, cuuint32_t, void*, const cuuint64_t*,
                                 const cuuint64_t*, const cuuint32_t*, const cuuint32_t*, CUtensorMapInterleave,
                                 CUtensorMapSwizzle, CUtensorMapL2promotion, CUtensorMapFloatOOBfill);

PFN_tmEncode get_encode_fn() {
  static PFN_tmEncode fn = nullptr;
  if (!fn) {
    cudaDriverEntryPointQueryResult qr;
    void* p = nullptr;
    cudaGetDriverEntryPoint("cuTensorMapEncodeTiled", &p, cudaEnableDefault, &qr);
    fn = (PFN_tmEncode)p;
  }
  return fn;
}

CUtensorMap make_map(const void* ptr, int rows, int cols) {
  CUtensorMap m;
  cuuint64_t gdim[2] = {(cuuint64_t)cols, (cuuint64_t)rows};
  cuuint64_t gstr[1] = {(cuuint64_t)cols * 2};
  cuuint32_t box[2] = {64, 64};
  cuuint32_t estr[2] = {1, 1};
  get_encode_fn()(&m, CU_TENSOR_MAP_DATA_TYPE_BFLOAT16, 2, const_cast<void*>(ptr), gdim, gstr, box, estr,
                  CU_TENSOR_MAP_INTERLEAVE_NONE, CU_TENSOR_MAP_SWIZZLE_128B, CU_TENSOR_MAP_L2_PROMOTION_L2_128B,
                  CU_TENSOR_MAP_FLOAT_OOB_FILL_NONE);
  return m;
}

CUtensorMap make_map3(const void* ptr, int rows, int cols, int n, int step) {
  CUtensorMap m;
  cuuint64_t gdim[3] = {(cuuint64_t)(cols - (n - 1) * step), (cuuint64_t)rows, (cuuint64_t)n};
  cuuint64_t gstr[2] = {(cuuint64_t)cols * 2, (cuuint64_t)step * 2};
  cuuint32_t box[3] = {64, 64, (cuuint32_t)n};
  cuuint32_t estr[3] = {1, 1, 1};
  get_encode_fn()(&m, CU_TENSOR_MAP_DATA_TYPE_BFLOAT16, 3, const_cast<void*>(ptr), gdim, gstr, box, estr,
                  CU_TENSOR_MAP_INTERLEAVE_NONE, CU_TENSOR_MAP_SWIZZLE_128B, CU_TENSOR_MAP_L2_PROMOTION_L2_128B,
                  CU_TENSOR_MAP_FLOAT_OOB_FILL_NONE);
  return m;
}

CUtensorMap make_map_q(const void* ptr, int sw, int sr) {
  CUtensorMap m;
  cuuint64_t gdim[5] = {DM, 8, 2, 4, S_LEN / 64};
  cuuint64_t gstr[4] = {DM * 2, (cuuint64_t)sr * DM * 2, (cuuint64_t)sw * DM * 2, 64 * DM * 2};
  cuuint32_t box[5] = {64, 8, 2, 4, 2};
  cuuint32_t estr[5] = {1, 1, 1, 1, 1};
  get_encode_fn()(&m, CU_TENSOR_MAP_DATA_TYPE_BFLOAT16, 5, const_cast<void*>(ptr), gdim, gstr, box, estr,
                  CU_TENSOR_MAP_INTERLEAVE_NONE, CU_TENSOR_MAP_SWIZZLE_128B, CU_TENSOR_MAP_L2_PROMOTION_L2_128B,
                  CU_TENSOR_MAP_FLOAT_OOB_FILL_NONE);
  return m;
}

}

extern "C" void kernel_launch(void* const* d_in, const int* in_sizes, int n_in, void* d_out, int out_size) {
  (void)in_sizes; (void)n_in; (void)out_size;
  void *p_o, *p_x;
  cudaGetSymbolAddress(&p_o, g_o);
  cudaGetSymbolAddress(&p_x, g_x);
  static bool attr_done = false;
  if (!attr_done) {
    cudaFuncSetAttribute(fused_kernel, cudaFuncAttributeMaxDynamicSharedMemorySize, SMEM_BYTES);
    attr_done = true;
  }
  Params P;
  P.in_x = (const __nv_bfloat16*)d_in[0];
  P.wqkv_p[0] = (const __nv_bfloat16*)d_in[1];
  P.wo_p[0] = (const __nv_bfloat16*)d_in[2];
  P.wqkv_p[1] = (const __nv_bfloat16*)d_in[4];
  P.wo_p[1] = (const __nv_bfloat16*)d_in[5];
  P.out = (__nv_bfloat16*)d_out;
  P.zero = 0;
  for (int L = 0; L < 5; L++) {
    const void* px = L == 0 ? (const void*)P.in_x : (L == 4 ? d_out : p_x);
    P.x[L] = make_map(px, S_LEN, DM);
    if (L < 4) P.xq[L] = (L & 1) ? make_map_q(px, 16, 8) : make_map_q(px, 8, 32);
  }
  P.o = make_map(p_o, S_LEN, DM);
  for (int t = 0; t < 2; t++) {
    P.wqkv[t] = make_map(P.wqkv_p[t], DM, NQKV);
    P.wqkv3[t] = make_map3(P.wqkv_p[t], DM, NQKV, 3, 1024);
    P.wo3[t] = make_map3(P.wo_p[t], DM, DM, 2, 64);
  }
  fused_kernel<<<NCTA, 512, SMEM_BYTES>>>(P);
}
```

```cpp
#include <cuda_runtime.h>
#include <cuda_bf16.h>
#include <cuda.h>
#include <stdint.h>

namespace {

constexpr int S_LEN = 2048;
constexpr int DM = 1024;
constexpr int NQKV = 3072;
constexpr int NCTA = 128;

__device__ __align__(1024) uint8_t g_kvA[16][16][2][16384];
__device__ __align__(1024) uint8_t g_kvB[16][16][4096];
__device__ __align__(1024) uint8_t g_zero[16384];
__device__ __align__(1024) __nv_bfloat16 g_o[S_LEN * DM];
__device__ __align__(1024) __nv_bfloat16 g_x[S_LEN * DM];
__device__ __align__(1024) float4 g_stats[4][8][S_LEN];
__device__ __align__(1024) float4 g_cs[2][16][8][64];
__device__ __align__(128) unsigned g_fx[16][16][4];
__device__ __align__(128) unsigned g_fo[32][16][4];
__device__ __align__(128) unsigned g_fk[16][16][4];
__device__ __align__(128) unsigned g_done[32];

constexpr uint32_t SBASE = 1024;
constexpr int UNIT = 8192;
constexpr int NUNITS = 20;
constexpr int OFF_SLOT = NUNITS * UNIT;
constexpr int OFF_BAR = OFF_SLOT + 4 * 16384;
constexpr int OFF_EPOCH = OFF_BAR + 424;
constexpr int OFF_LSB = OFF_BAR + 432;
constexpr int OFF_CS = OFF_BAR + 496;
constexpr int OFF_RS = OFF_CS + 1536;
constexpr int OFF_ONE = OFF_RS + 1024;
constexpr int SMEM_BYTES = OFF_ONE + 16;
constexpr int B_QF = 0, B_WF = 4, B_RF = 12, B_E = 13, B_PREP = 26, B_LOC = 28, B_HALO = 29, B_REL = 33, B_OS0 = 36,
              B_TURN = 37, B_XS = 39, B_CS = 41, B_CSD = 42, B_GO = 43, B_PRE = 44, B_HV = 45, B_REDO = 46,
              B_RDONE = 48, B_PRE2 = 49, B_HL = 50, B_KV = 52, B_OS1 = B_GO;
static_assert(SMEM_BYTES <= 232448, "shared memory");

__device__ __forceinline__ uint32_t smem_u32(const void* p) { return (uint32_t)__cvta_generic_to_shared(p); }

__device__ __forceinline__ void mbar_init(uint32_t bar, uint32_t cnt) {
  asm volatile("mbarrier.init.shared::cta.b64 [%0], %1;" ::"r"(bar), "r"(cnt));
}
__device__ __forceinline__ void mbar_expect_tx(uint32_t bar, uint32_t bytes) {
  asm volatile("mbarrier.arrive.expect_tx.shared::cta.b64 _, [%0], %1;" ::"r"(bar), "r"(bytes) : "memory");
}
__device__ __forceinline__ void mbar_arrive(uint32_t bar) {
  asm volatile("mbarrier.arrive.shared::cta.b64 _, [%0];" ::"r"(bar) : "memory");
}
__device__ __forceinline__ bool mbar_try_wait(uint32_t bar, uint32_t parity) {
  uint32_t ok;
  asm volatile(
      "{\n.reg .pred p;\nmbarrier.try_wait.parity.shared::cta.b64 p, [%1], %2;\nselp.b32 %0, 1, 0, p;\n}\n"
      : "=r"(ok)
      : "r"(bar), "r"(parity)
      : "memory");
  return ok != 0;
}
__device__ __forceinline__ bool mbar_test(uint32_t bar, uint32_t parity) {
  uint32_t ok;
  asm volatile(
      "{\n.reg .pred p;\nmbarrier.test_wait.parity.shared::cta.b64 p, [%1], %2;\nselp.b32 %0, 1, 0, p;\n}\n"
      : "=r"(ok)
      : "r"(bar), "r"(parity)
      : "memory");
  return ok != 0;
}
__device__ __forceinline__ void mbar_wait(uint32_t bar, uint32_t parity) {
#pragma unroll 1
  for (uint32_t it = 0; it < (1u << 18); ++it) {
    if (mbar_try_wait(bar, parity)) return;
  }
}
__device__ __forceinline__ void mbar_pace(uint32_t bar, uint32_t parity) {
#pragma unroll 1
  for (uint32_t it = 0; it < 24; ++it) {
    if (mbar_try_wait(bar, parity)) return;
  }
}
template <int NS>
__device__ __forceinline__ void mbar_wait_lazy(uint32_t bar, uint32_t parity) {
#pragma unroll 1
  for (uint32_t it = 0; it < (1u << 18); ++it) {
    if (mbar_try_wait(bar, parity)) return;
    __nanosleep(NS);
  }
}
__device__ __forceinline__ bool elect_one() {
  uint32_t ok;
  asm volatile("{\n.reg .pred p;\nelect.sync _|p, 0xffffffff;\nselp.b32 %0, 1, 0, p;\n}\n" : "=r"(ok));
  return ok != 0;
}
__device__ __forceinline__ void fence_barrier_init() { asm volatile("fence.mbarrier_init.release.cluster;" ::: "memory"); }
__device__ __forceinline__ void fence_proxy_async_smem() { asm volatile("fence.proxy.async.shared::cta;" ::: "memory"); }

__device__ __forceinline__ void signal_async(uint32_t bar, bool lane0) {
  fence_proxy_async_smem();
  __syncwarp();
  asm volatile("{\n.reg .pred p;\nsetp.ne.b32 p, %1, 0;\n@p mbarrier.arrive.shared::cta.b64 _, [%0];\n}\n" ::"r"(bar), "r"((int)lane0) : "memory");
}
template <class T>
__device__ __forceinline__ void pin64(T*& p) { asm volatile("" : "+l"(p)); }

__device__ __forceinline__ void tma_load_2d(uint32_t dst, const CUtensorMap* map, uint32_t bar, int c0, int c1) {
  asm volatile(
      "cp.async.bulk.tensor.2d.shared::cluster.global.mbarrier::complete_tx::bytes [%0], [%1, {%3, %4}], [%2];" ::"r"(dst),
      "l"(map), "r"(bar), "r"(c0), "r"(c1)
      : "memory");
}
__device__ __forceinline__ void tma_load_3d(uint32_t dst, const CUtensorMap* map, uint32_t bar, int c0, int c1) {
  asm volatile(
      "cp.async.bulk.tensor.3d.shared::cluster.global.mbarrier::complete_tx::bytes [%0], [%1, {%3, %4, %5}], [%2];" ::"r"(dst),
      "l"(map), "r"(bar), "r"(c0), "r"(c1), "r"(0)
      : "memory");
}
__device__ __forceinline__ void tma_load_5d(uint32_t dst, const CUtensorMap* map, uint32_t bar, int c0, int c4) {
  asm volatile(
      "cp.async.bulk.tensor.5d.shared::cluster.global.mbarrier::complete_tx::bytes [%0], [%1, {%3, %5, %5, %5, %4}], [%2];" ::"r"(dst),
      "l"(map), "r"(bar), "r"(c0), "r"(c4), "r"(0)
      : "memory");
}
__device__ __forceinline__ void bulk_load(uint32_t dst, const void* src, uint32_t bytes, uint32_t bar) {
  asm volatile("cp.async.bulk.shared::cluster.global.mbarrier::complete_tx::bytes [%0], [%1], %2, [%3];" ::"r"(dst),
               "l"(src), "r"(bytes), "r"(bar)
               : "memory");
}
__device__ __forceinline__ void bulk_store(void* dst, uint32_t src, uint32_t bytes) {
  asm volatile("cp.async.bulk.global.shared::cta.bulk_group [%0], [%1], %2;" ::"l"(dst), "r"(src), "r"(bytes) : "memory");
}
__device__ __forceinline__ void tma_store_2d(const CUtensorMap* map, uint32_t src, int c0, int c1) {
  asm volatile("cp.async.bulk.tensor.2d.global.shared::cta.bulk_group [%0, {%2, %3}], [%1];" ::"l"(map), "r"(src),
               "r"(c0), "r"(c1)
               : "memory");
}
__device__ __forceinline__ void bulk_announce(unsigned* p) {
  asm volatile("cp.reduce.async.bulk.global.shared::cta.bulk_group.add.u32 [%0], [%1], 16;" ::"l"(p), "r"(SBASE + OFF_ONE) : "memory");
}
__device__ __forceinline__ void bulk_commit() { asm volatile("cp.async.bulk.commit_group;" ::: "memory"); }
__device__ __forceinline__ void bulk_wait_read0() { asm volatile("cp.async.bulk.wait_group.read 0;" ::: "memory"); }
__device__ __forceinline__ void bulk_wait0() { asm volatile("cp.async.bulk.wait_group 0;" ::: "memory"); }
__device__ __forceinline__ void named_bar_sync(int id, int nthreads) {
  asm volatile("bar.sync %0, %1;" ::"r"(id), "r"(nthreads) : "memory");
}
__device__ __forceinline__ void named_bar_arrive(int id, int nthreads) {
  asm volatile("bar.arrive %0, %1;" ::"r"(id), "r"(nthreads) : "memory");
}

__device__ __forceinline__ bool named_bar_or(int id, int nthreads, bool v) {
  uint32_t r;
  asm volatile("{\n.reg .pred p, q;\nsetp.ne.b32 q, %3, 0;\nbar.red.or.pred p, %1, %2, q;\nselp.b32 %0, 1, 0, p;\n}\n"
               : "=r"(r) : "r"(id), "r"(nthreads), "r"((int)v) : "memory");
  return __any_sync(0xffffffffu, r != 0);
}

__device__ __forceinline__ void wgmma_fence() { asm volatile("wgmma.fence.sync.aligned;\n" ::: "memory"); }
__device__ __forceinline__ void wgmma_commit() { asm volatile("wgmma.commit_group.sync.aligned;\n" ::: "memory"); }
template <int N>
__device__ __forceinline__ void wgmma_wait() {
  asm volatile("wgmma.wait_group.sync.aligned %0;\n" ::"n"(N) : "memory");
}
template <int R>
__device__ __forceinline__ void setmaxnreg_inc() { asm volatile("setmaxnreg.inc.sync.aligned.u32 %0;\n" ::"n"(R)); }
template <int R>
__device__ __forceinline__ void setmaxnreg_dec() { asm volatile("setmaxnreg.dec.sync.aligned.u32 %0;\n" ::"n"(R)); }
template <int N>
__device__ __forceinline__ void reg_fence(float* r) {
#pragma unroll
  for (int i = 0; i < N; i++) asm volatile("" : "+f"(r[i])::"memory");
}

template <int N>
__device__ __forceinline__ void reg_define(float* r) {
#pragma unroll
  for (int i = 0; i < N; i++) r[i] = 0.f;
}

__device__ __forceinline__ uint64_t desc_lo(uint32_t lo) {
  uint64_t d;
  asm("mov.b64 %0, {%1, %2};" : "=l"(d) : "r"(lo), "r"(0x40000040u));
  return d;
}
__device__ __forceinline__ uint64_t make_desc(uint32_t addr, uint32_t lbo_bytes) {
  return desc_lo((addr >> 4) + ((lbo_bytes >> 4) << 16));
}

__device__ __forceinline__ void wgmma_n192_ss_ta0_tb1(float* d, uint64_t descA, uint64_t descB, int scaleD) {
  asm volatile("{\n.reg .pred p;\nsetp.ne.b32 p, %98, 0;\n"
    "wgmma.mma_async.sync.aligned.m64n192k16.f32.bf16.bf16 {%0, %1, %2, %3, %4, %5, %6, %7, %8, %9, %10, %11, %12, %13, %14, %15, %16, %17, %18, %19, %20, %21, %22, %23, %24, %25, %26, %27, %28, %29, %30, %31, %32, %33, %34, %35, %36, %37, %38, %39, %40, %41, %42, %43, %44, %45, %46, %47, %48, %49, %50, %51, %52, %53, %54, %55, %56, %57, %58, %59, %60, %61, %62, %63, %64, %65, %66, %67, %68, %69, %70, %71, %72, %73, %74, %75, %76, %77, %78, %79, %80, %81, %82, %83, %84, %85, %86, %87, %88, %89, %90, %91, %92, %93, %94, %95}, %96, %97, p, 1, 1, 0, 1;\n}\n"
    : "+f"(d[0]), "+f"(d[1]), "+f"(d[2]), "+f"(d[3]), "+f"(d[4]), "+f"(d[5]), "+f"(d[6]), "+f"(d[7]), "+f"(d[8]), "+f"(d[9]), "+f"(d[10]), "+f"(d[11]), "+f"(d[12]), "+f"(d[13]), "+f"(d[14]), "+f"(d[15]), "+f"(d[16]), "+f"(d[17]), "+f"(d[18]), "+f"(d[19]), "+f"(d[20]), "+f"(d[21]), "+f"(d[22]), "+f"(d[23]), "+f"(d[24]), "+f"(d[25]), "+f"(d[26]), "+f"(d[27]), "+f"(d[28]), "+f"(d[29]), "+f"(d[30]), "+f"(d[31]), "+f"(d[32]), "+f"(d[33]), "+f"(d[34]), "+f"(d[35]), "+f"(d[36]), "+f"(d[37]), "+f"(d[38]), "+f"(d[39]), "+f"(d[40]), "+f"(d[41]), "+f"(d[42]), "+f"(d[43]), "+f"(d[44]), "+f"(d[45]), "+f"(d[46]), "+f"(d[47]), "+f"(d[48]), "+f"(d[49]), "+f"(d[50]), "+f"(d[51]), "+f"(d[52]), "+f"(d[53]), "+f"(d[54]), "+f"(d[55]), "+f"(d[56]), "+f"(d[57]), "+f"(d[58]), "+f"(d[59]), "+f"(d[60]), "+f"(d[61]), "+f"(d[62]), "+f"(d[63]), "+f"(d[64]), "+f"(d[65]), "+f"(d[66]), "+f"(d[67]), "+f"(d[68]), "+f"(d[69]), "+f"(d[70]), "+f"(d[71]), "+f"(d[72]), "+f"(d[73]), "+f"(d[74]), "+f"(d[75]), "+f"(d[76]), "+f"(d[77]), "+f"(d[78]), "+f"(d[79]), "+f"(d[80]), "+f"(d[81]), "+f"(d[82]), "+f"(d[83]), "+f"(d[84]), "+f"(d[85]), "+f"(d[86]), "+f"(d[87]), "+f"(d[88]), "+f"(d[89]), "+f"(d[90]), "+f"(d[91]), "+f"(d[92]), "+f"(d[93]), "+f"(d[94]), "+f"(d[95])
    : "l"(descA), "l"(descB), "r"(scaleD));
}

__device__ __forceinline__ void wgmma_n128_ss_ta0_tb1(float* d, uint64_t descA, uint64_t descB, int scaleD) {
  asm volatile("{\n.reg .pred p;\nsetp.ne.b32 p, %66, 0;\n"
    "wgmma.mma_async.sync.aligned.m64n128k16.f32.bf16.bf16 {%0, %1, %2, %3, %4, %5, %6, %7, %8, %9, %10, %11, %12, %13, %14, %15, %16, %17, %18, %19, %20, %21, %22, %23, %24, %25, %26, %27, %28, %29, %30, %31, %32, %33, %34, %35, %36, %37, %38, %39, %40, %41, %42, %43, %44, %45, %46, %47, %48, %49, %50, %51, %52, %53, %54, %55, %56, %57, %58, %59, %60, %61, %62, %63}, %64, %65, p, 1, 1, 0, 1;\n}\n"
    : "+f"(d[0]), "+f"(d[1]), "+f"(d[2]), "+f"(d[3]), "+f"(d[4]), "+f"(d[5]), "+f"(d[6]), "+f"(d[7]), "+f"(d[8]), "+f"(d[9]), "+f"(d[10]), "+f"(d[11]), "+f"(d[12]), "+f"(d[13]), "+f"(d[14]), "+f"(d[15]), "+f"(d[16]), "+f"(d[17]), "+f"(d[18]), "+f"(d[19]), "+f"(d[20]), "+f"(d[21]), "+f"(d[22]), "+f"(d[23]), "+f"(d[24]), "+f"(d[25]), "+f"(d[26]), "+f"(d[27]), "+f"(d[28]), "+f"(d[29]), "+f"(d[30]), "+f"(d[31]), "+f"(d[32]), "+f"(d[33]), "+f"(d[34]), "+f"(d[35]), "+f"(d[36]), "+f"(d[37]), "+f"(d[38]), "+f"(d[39]), "+f"(d[40]), "+f"(d[41]), "+f"(d[42]), "+f"(d[43]), "+f"(d[44]), "+f"(d[45]), "+f"(d[46]), "+f"(d[47]), "+f"(d[48]), "+f"(d[49]), "+f"(d[50]), "+f"(d[51]), "+f"(d[52]), "+f"(d[53]), "+f"(d[54]), "+f"(d[55]), "+f"(d[56]), "+f"(d[57]), "+f"(d[58]), "+f"(d[59]), "+f"(d[60]), "+f"(d[61]), "+f"(d[62]), "+f"(d[63])
    : "l"(descA), "l"(descB), "r"(scaleD));
}

__device__ __forceinline__ void wgmma_n192_ssz_ta0_tb1(float* d, uint64_t descA, uint64_t descB) {
  asm volatile("{\n.reg .pred p;\nsetp.ne.b32 p, 0, 0;\n"
    "wgmma.mma_async.sync.aligned.m64n192k16.f32.bf16.bf16 {%0, %1, %2, %3, %4, %5, %6, %7, %8, %9, %10, %11, %12, %13, %14, %15, %16, %17, %18, %19, %20, %21, %22, %23, %24, %25, %26, %27, %28, %29, %30, %31, %32, %33, %34, %35, %36, %37, %38, %39, %40, %41, %42, %43, %44, %45, %46, %47, %48, %49, %50, %51, %52, %53, %54, %55, %56, %57, %58, %59, %60, %61, %62, %63, %64, %65, %66, %67, %68, %69, %70, %71, %72, %73, %74, %75, %76, %77, %78, %79, %80, %81, %82, %83, %84, %85, %86, %87, %88, %89, %90, %91, %92, %93, %94, %95}, %96, %97, p, 1, 1, 0, 1;\n}\n"
    : "=f"(d[0]), "=f"(d[1]), "=f"(d[2]), "=f"(d[3]), "=f"(d[4]), "=f"(d[5]), "=f"(d[6]), "=f"(d[7]), "=f"(d[8]), "=f"(d[9]), "=f"(d[10]), "=f"(d[11]), "=f"(d[12]), "=f"(d[13]), "=f"(d[14]), "=f"(d[15]), "=f"(d[16]), "=f"(d[17]), "=f"(d[18]), "=f"(d[19]), "=f"(d[20]), "=f"(d[21]), "=f"(d[22]), "=f"(d[23]), "=f"(d[24]), "=f"(d[25]), "=f"(d[26]), "=f"(d[27]), "=f"(d[28]), "=f"(d[29]), "=f"(d[30]), "=f"(d[31]), "=f"(d[32]), "=f"(d[33]), "=f"(d[34]), "=f"(d[35]), "=f"(d[36]), "=f"(d[37]), "=f"(d[38]), "=f"(d[39]), "=f"(d[40]), "=f"(d[41]), "=f"(d[42]), "=f"(d[43]), "=f"(d[44]), "=f"(d[45]), "=f"(d[46]), "=f"(d[47]), "=f"(d[48]), "=f"(d[49]), "=f"(d[50]), "=f"(d[51]), "=f"(d[52]), "=f"(d[53]), "=f"(d[54]), "=f"(d[55]), "=f"(d[56]), "=f"(d[57]), "=f"(d[58]), "=f"(d[59]), "=f"(d[60]), "=f"(d[61]), "=f"(d[62]), "=f"(d[63]), "=f"(d[64]), "=f"(d[65]), "=f"(d[66]), "=f"(d[67]), "=f"(d[68]), "=f"(d[69]), "=f"(d[70]), "=f"(d[71]), "=f"(d[72]), "=f"(d[73]), "=f"(d[74]), "=f"(d[75]), "=f"(d[76]), "=f"(d[77]), "=f"(d[78]), "=f"(d[79]), "=f"(d[80]), "=f"(d[81]), "=f"(d[82]), "=f"(d[83]), "=f"(d[84]), "=f"(d[85]), "=f"(d[86]), "=f"(d[87]), "=f"(d[88]), "=f"(d[89]), "=f"(d[90]), "=f"(d[91]), "=f"(d[92]), "=f"(d[93]), "=f"(d[94]), "=f"(d[95])
    : "l"(descA), "l"(descB));
}

__device__ __forceinline__ void wgmma_n8_ss_ta1_tb0(float* d, uint64_t descA, uint64_t descB, int scaleD) {
  asm volatile("{\n.reg .pred p;\nsetp.ne.b32 p, %6, 0;\n"
    "wgmma.mma_async.sync.aligned.m64n8k16.f32.bf16.bf16 {%0, %1, %2, %3}, %4, %5, p, 1, 1, 1, 0;\n}\n"
    : "+f"(d[0]), "+f"(d[1]), "+f"(d[2]), "+f"(d[3])
    : "l"(descA), "l"(descB), "r"(scaleD));
}

__device__ __forceinline__ void wgmma_n8_ssz_ta1_tb0(float* d, uint64_t descA, uint64_t descB) {
  asm volatile("{\n.reg .pred p;\nsetp.ne.b32 p, 0, 0;\n"
    "wgmma.mma_async.sync.aligned.m64n8k16.f32.bf16.bf16 {%0, %1, %2, %3}, %4, %5, p, 1, 1, 1, 0;\n}\n"
    : "=f"(d[0]), "=f"(d[1]), "=f"(d[2]), "=f"(d[3])
    : "l"(descA), "l"(descB));
}

__device__ __forceinline__ void wgmma_n192_rs_tb1(float* d, const uint32_t* a, uint64_t descB, int scaleD) {
  asm volatile("{\n.reg .pred p;\nsetp.ne.b32 p, %101, 0;\n"
    "wgmma.mma_async.sync.aligned.m64n192k16.f32.bf16.bf16 {%0, %1, %2, %3, %4, %5, %6, %7, %8, %9, %10, %11, %12, %13, %14, %15, %16, %17, %18, %19, %20, %21, %22, %23, %24, %25, %26, %27, %28, %29, %30, %31, %32, %33, %34, %35, %36, %37, %38, %39, %40, %41, %42, %43, %44, %45, %46, %47, %48, %49, %50, %51, %52, %53, %54, %55, %56, %57, %58, %59, %60, %61, %62, %63, %64, %65, %66, %67, %68, %69, %70, %71, %72, %73, %74, %75, %76, %77, %78, %79, %80, %81, %82, %83, %84, %85, %86, %87, %88, %89, %90, %91, %92, %93, %94, %95}, {%96, %97, %98, %99}, %100, p, 1, 1, 1;\n}\n"
    : "+f"(d[0]), "+f"(d[1]), "+f"(d[2]), "+f"(d[3]), "+f"(d[4]), "+f"(d[5]), "+f"(d[6]), "+f"(d[7]), "+f"(d[8]), "+f"(d[9]), "+f"(d[10]), "+f"(d[11]), "+f"(d[12]), "+f"(d[13]), "+f"(d[14]), "+f"(d[15]), "+f"(d[16]), "+f"(d[17]), "+f"(d[18]), "+f"(d[19]), "+f"(d[20]), "+f"(d[21]), "+f"(d[22]), "+f"(d[23]), "+f"(d[24]), "+f"(d[25]), "+f"(d[26]), "+f"(d[27]), "+f"(d[28]), "+f"(d[29]), "+f"(d[30]), "+f"(d[31]), "+f"(d[32]), "+f"(d[33]), "+f"(d[34]), "+f"(d[35]), "+f"(d[36]), "+f"(d[37]), "+f"(d[38]), "+f"(d[39]), "+f"(d[40]), "+f"(d[41]), "+f"(d[42]), "+f"(d[43]), "+f"(d[44]), "+f"(d[45]), "+f"(d[46]), "+f"(d[47]), "+f"(d[48]), "+f"(d[49]), "+f"(d[50]), "+f"(d[51]), "+f"(d[52]), "+f"(d[53]), "+f"(d[54]), "+f"(d[55]), "+f"(d[56]), "+f"(d[57]), "+f"(d[58]), "+f"(d[59]), "+f"(d[60]), "+f"(d[61]), "+f"(d[62]), "+f"(d[63]), "+f"(d[64]), "+f"(d[65]), "+f"(d[66]), "+f"(d[67]), "+f"(d[68]), "+f"(d[69]), "+f"(d[70]), "+f"(d[71]), "+f"(d[72]), "+f"(d[73]), "+f"(d[74]), "+f"(d[75]), "+f"(d[76]), "+f"(d[77]), "+f"(d[78]), "+f"(d[79]), "+f"(d[80]), "+f"(d[81]), "+f"(d[82]), "+f"(d[83]), "+f"(d[84]), "+f"(d[85]), "+f"(d[86]), "+f"(d[87]), "+f"(d[88]), "+f"(d[89]), "+f"(d[90]), "+f"(d[91]), "+f"(d[92]), "+f"(d[93]), "+f"(d[94]), "+f"(d[95])
    : "r"(a[0]), "r"(a[1]), "r"(a[2]), "r"(a[3]), "l"(descB), "r"(scaleD));
}

__device__ __forceinline__ void wgmma_n80_rs_tb0(float* d, const uint32_t* a, uint64_t descB, int scaleD) {
  asm volatile("{\n.reg .pred p;\nsetp.ne.b32 p, %45, 0;\n"
    "wgmma.mma_async.sync.aligned.m64n80k16.f32.bf16.bf16 {%0, %1, %2, %3, %4, %5, %6, %7, %8, %9, %10, %11, %12, %13, %14, %15, %16, %17, %18, %19, %20, %21, %22, %23, %24, %25, %26, %27, %28, %29, %30, %31, %32, %33, %34, %35, %36, %37, %38, %39}, {%40, %41, %42, %43}, %44, p, 1, 1, 0;\n}\n"
    : "+f"(d[0]), "+f"(d[1]), "+f"(d[2]), "+f"(d[3]), "+f"(d[4]), "+f"(d[5]), "+f"(d[6]), "+f"(d[7]), "+f"(d[8]), "+f"(d[9]), "+f"(d[10]), "+f"(d[11]), "+f"(d[12]), "+f"(d[13]), "+f"(d[14]), "+f"(d[15]), "+f"(d[16]), "+f"(d[17]), "+f"(d[18]), "+f"(d[19]), "+f"(d[20]), "+f"(d[21]), "+f"(d[22]), "+f"(d[23]), "+f"(d[24]), "+f"(d[25]), "+f"(d[26]), "+f"(d[27]), "+f"(d[28]), "+f"(d[29]), "+f"(d[30]), "+f"(d[31]), "+f"(d[32]), "+f"(d[33]), "+f"(d[34]), "+f"(d[35]), "+f"(d[36]), "+f"(d[37]), "+f"(d[38]), "+f"(d[39])
    : "r"(a[0]), "r"(a[1]), "r"(a[2]), "r"(a[3]), "l"(descB), "r"(scaleD));
}

__device__ __forceinline__ void wgmma_n80_rsz_tb0(float* d, const uint32_t* a, uint64_t descB) {
  asm volatile("{\n.reg .pred p;\nsetp.ne.b32 p, 0, 0;\n"
    "wgmma.mma_async.sync.aligned.m64n80k16.f32.bf16.bf16 {%0, %1, %2, %3, %4, %5, %6, %7, %8, %9, %10, %11, %12, %13, %14, %15, %16, %17, %18, %19, %20, %21, %22, %23, %24, %25, %26, %27, %28, %29, %30, %31, %32, %33, %34, %35, %36, %37, %38, %39}, {%40, %41, %42, %43}, %44, p, 1, 1, 0;\n}\n"
    : "=f"(d[0]), "=f"(d[1]), "=f"(d[2]), "=f"(d[3]), "=f"(d[4]), "=f"(d[5]), "=f"(d[6]), "=f"(d[7]), "=f"(d[8]), "=f"(d[9]), "=f"(d[10]), "=f"(d[11]), "=f"(d[12]), "=f"(d[13]), "=f"(d[14]), "=f"(d[15]), "=f"(d[16]), "=f"(d[17]), "=f"(d[18]), "=f"(d[19]), "=f"(d[20]), "=f"(d[21]), "=f"(d[22]), "=f"(d[23]), "=f"(d[24]), "=f"(d[25]), "=f"(d[26]), "=f"(d[27]), "=f"(d[28]), "=f"(d[29]), "=f"(d[30]), "=f"(d[31]), "=f"(d[32]), "=f"(d[33]), "=f"(d[34]), "=f"(d[35]), "=f"(d[36]), "=f"(d[37]), "=f"(d[38]), "=f"(d[39])
    : "r"(a[0]), "r"(a[1]), "r"(a[2]), "r"(a[3]), "l"(descB));
}

__device__ __forceinline__ void wgmma_n32_rs_tb1(float* d, const uint32_t* a, uint64_t descB, int scaleD) {
  asm volatile("{\n.reg .pred p;\nsetp.ne.b32 p, %21, 0;\n"
    "wgmma.mma_async.sync.aligned.m64n32k16.f32.bf16.bf16 {%0, %1, %2, %3, %4, %5, %6, %7, %8, %9, %10, %11, %12, %13, %14, %15}, {%16, %17, %18, %19}, %20, p, 1, 1, 1;\n}\n"
    : "+f"(d[0]), "+f"(d[1]), "+f"(d[2]), "+f"(d[3]), "+f"(d[4]), "+f"(d[5]), "+f"(d[6]), "+f"(d[7]), "+f"(d[8]), "+f"(d[9]), "+f"(d[10]), "+f"(d[11]), "+f"(d[12]), "+f"(d[13]), "+f"(d[14]), "+f"(d[15])
    : "r"(a[0]), "r"(a[1]), "r"(a[2]), "r"(a[3]), "l"(descB), "r"(scaleD));
}

__device__ __forceinline__ void wgmma_n32_rsz_tb1(float* d, const uint32_t* a, uint64_t descB) {
  asm volatile("{\n.reg .pred p;\nsetp.ne.b32 p, 0, 0;\n"
    "wgmma.mma_async.sync.aligned.m64n32k16.f32.bf16.bf16 {%0, %1, %2, %3, %4, %5, %6, %7, %8, %9, %10, %11, %12, %13, %14, %15}, {%16, %17, %18, %19}, %20, p, 1, 1, 1;\n}\n"
    : "=f"(d[0]), "=f"(d[1]), "=f"(d[2]), "=f"(d[3]), "=f"(d[4]), "=f"(d[5]), "=f"(d[6]), "=f"(d[7]), "=f"(d[8]), "=f"(d[9]), "=f"(d[10]), "=f"(d[11]), "=f"(d[12]), "=f"(d[13]), "=f"(d[14]), "=f"(d[15])
    : "r"(a[0]), "r"(a[1]), "r"(a[2]), "r"(a[3]), "l"(descB));
}

__device__ __forceinline__ void wgmma_n32_rs_tb0(float* d, const uint32_t* a, uint64_t descB, int scaleD) {
  asm volatile("{\n.reg .pred p;\nsetp.ne.b32 p, %21, 0;\n"
    "wgmma.mma_async.sync.aligned.m64n32k16.f32.bf16.bf16 {%0, %1, %2, %3, %4, %5, %6, %7, %8, %9, %10, %11, %12, %13, %14, %15}, {%16, %17, %18, %19}, %20, p, 1, 1, 0;\n}\n"
    : "+f"(d[0]), "+f"(d[1]), "+f"(d[2]), "+f"(d[3]), "+f"(d[4]), "+f"(d[5]), "+f"(d[6]), "+f"(d[7]), "+f"(d[8]), "+f"(d[9]), "+f"(d[10]), "+f"(d[11]), "+f"(d[12]), "+f"(d[13]), "+f"(d[14]), "+f"(d[15])
    : "r"(a[0]), "r"(a[1]), "r"(a[2]), "r"(a[3]), "l"(descB), "r"(scaleD));
}

__device__ __forceinline__ void wgmma_n32_rsz_tb0(float* d, const uint32_t* a, uint64_t descB) {
  asm volatile("{\n.reg .pred p;\nsetp.ne.b32 p, 0, 0;\n"
    "wgmma.mma_async.sync.aligned.m64n32k16.f32.bf16.bf16 {%0, %1, %2, %3, %4, %5, %6, %7, %8, %9, %10, %11, %12, %13, %14, %15}, {%16, %17, %18, %19}, %20, p, 1, 1, 0;\n}\n"
    : "=f"(d[0]), "=f"(d[1]), "=f"(d[2]), "=f"(d[3]), "=f"(d[4]), "=f"(d[5]), "=f"(d[6]), "=f"(d[7]), "=f"(d[8]), "=f"(d[9]), "=f"(d[10]), "=f"(d[11]), "=f"(d[12]), "=f"(d[13]), "=f"(d[14]), "=f"(d[15])
    : "r"(a[0]), "r"(a[1]), "r"(a[2]), "r"(a[3]), "l"(descB));
}

__device__ __forceinline__ uint32_t pack_bf16x2(float lo, float hi) {
  uint32_t r;
  asm("cvt.rn.bf16x2.f32 %0, %1, %2;" : "=r"(r) : "f"(hi), "f"(lo));
  return r;
}
__device__ __forceinline__ float bf_lo(uint32_t p) { return __uint_as_float(p << 16); }
__device__ __forceinline__ float bf_hi(uint32_t p) { return __uint_as_float(p & 0xffff0000u); }
__device__ __forceinline__ float bf16_round(float v) { return __bfloat162float(__float2bfloat16_rn(v)); }
__device__ __forceinline__ float ex2_approx(float x) {
  float r;
  asm("ex2.approx.ftz.f32 %0, %1;" : "=f"(r) : "f"(x));
  return r;
}
__device__ __forceinline__ float rcp_fast(float x) {
  float r;
  asm("rcp.approx.ftz.f32 %0, %1;" : "=f"(r) : "f"(x));
  return r;
}
__device__ __forceinline__ void ldmatrix_x4(uint32_t (&r)[4], uint32_t addr) {
  asm volatile("ldmatrix.sync.aligned.m8n8.x4.shared.b16 {%0,%1,%2,%3}, [%4];"
               : "=r"(r[0]), "=r"(r[1]), "=r"(r[2]), "=r"(r[3])
               : "r"(addr)
               : "memory");
}
__device__ __forceinline__ void stmatrix_x4(uint32_t addr, uint32_t r0, uint32_t r1, uint32_t r2, uint32_t r3) {
  asm volatile("stmatrix.sync.aligned.m8n8.x4.shared.b16 [%0], {%1,%2,%3,%4};" ::"r"(addr), "r"(r0), "r"(r1), "r"(r2),
               "r"(r3));
}
__device__ __forceinline__ uint32_t add_bf16x2(uint32_t a, uint32_t b) {
  uint32_t r;
  asm("add.rn.bf16x2 %0, %1, %2;" : "=r"(r) : "r"(a), "r"(b));
  return r;
}
__device__ __forceinline__ uint4 lds128(uint32_t addr) {
  uint4 v;
  asm volatile("ld.shared.v4.b32 {%0,%1,%2,%3}, [%4];" : "=r"(v.x), "=r"(v.y), "=r"(v.z), "=r"(v.w) : "r"(addr) : "memory");
  return v;
}
__device__ __forceinline__ uint32_t lds32(uint32_t addr) {
  uint32_t v;
  asm volatile("ld.shared.b32 %0, [%1];" : "=r"(v) : "r"(addr) : "memory");
  return v;
}
__device__ __forceinline__ void sts32(uint32_t addr, uint32_t v) {
  asm volatile("st.shared.b32 [%0], %1;" ::"r"(addr), "r"(v) : "memory");
}

__device__ __forceinline__ unsigned ld_relaxed_u32(const void* p) {
  unsigned v;
  asm volatile("ld.relaxed.gpu.global.u32 %0, [%1];" : "=r"(v) : "l"(p) : "memory");
  return v;
}
__device__ __forceinline__ unsigned launch_epoch() { return (*(volatile unsigned*)g_done) / NCTA + 1u; }
__device__ __forceinline__ uint32_t set_tag(uint32_t w, uint32_t m, uint32_t tag) { return (w & ~m) | (tag & m); }
__device__ __forceinline__ uint32_t o_tag(int L) { return (L + 1) & 1; }
__device__ __forceinline__ uint32_t x_tag(int L) { return L & 1; }
__device__ __forceinline__ uint32_t kv_tag(int L) { return L < 2; }

#define PIPEP 0
__device__ __forceinline__ void wait_count(const unsigned* f, unsigned target, int i, uint32_t& seen, int lane) {
  if ((seen >> i) & 1u) return;
  f += (lane & 15) * 4;
#pragma unroll 1
  for (uint32_t it = 0; it < (1u << 17); ++it) {
    seen = __ballot_sync(0xffffffffu, (int)(ld_relaxed_u32(f) - target) >= 0);
    if ((seen >> i) & 1u) break;
  }
}
__device__ __forceinline__ float4 ld_rec(const float4* p) {
  float4 v;
  asm volatile("ld.relaxed.gpu.global.v4.f32 {%0,%1,%2,%3}, [%4];" : "=f"(v.x), "=f"(v.y), "=f"(v.z), "=f"(v.w) : "l"(p) : "memory");
  return v;
}
__device__ __forceinline__ void st_rec(float4* p, float a, float b, float c, unsigned tag) {
  asm volatile("st.relaxed.gpu.global.v4.f32 [%0], {%1,%2,%3,%4};" ::"l"(p), "f"(a), "f"(b), "f"(c), "f"(__uint_as_float(tag)) : "memory");
}
template <int N>
__device__ __forceinline__ float4 sum_recs(const float4* p, int stride, unsigned tag) {
  float4 s;
#pragma unroll 1
  for (uint32_t it = 0; it < (1u << 17); ++it) {
    float4 v[N];
#pragma unroll
    for (int t = 0; t < N; t++) v[t] = ld_rec(p + t * stride);
    bool ok = true;
    s = make_float4(0.f, 0.f, 0.f, 0.f);
#pragma unroll
    for (int t = 0; t < N; t++) {
      ok &= __float_as_uint(v[t].w) == tag;
      s.x += v[t].x;
      s.y += v[t].y;
      s.z += v[t].z;
    }
    if (ok) break;
    __nanosleep(200);
  }
  return s;
}

__device__ __forceinline__ int fresh_tid() {
  int t;
  asm volatile("mov.u32 %0, %%tid.x;" : "=r"(t));
  return t;
}
#define PHASE_IDS                                  \
  const int tid_ = fresh_tid();                    \
  const int lane = tid_ & 31, wwarp = __shfl_sync(0xffffffffu, (tid_ >> 5) & 3, 0), tid = tid_ & 127; \
  const int g = lane >> 2, c = lane & 3;           \
  (void)tid; (void)g; (void)c; (void)wwarp;

#define PHASE_IDS_W                                \
  const int lane = fresh_tid() & 31, wwarp = warp & 3; \
  const int g = lane >> 2, c = lane & 3;

#define GTL(i) do { } while (0)
#define TGET(v) do { } while (0)
#define TPUT(c, i, v) do { } while (0)

constexpr float SM_C = 0.17677669529663687f * 1.4426950408889634f;

__device__ __forceinline__ void stmatrix_x4_if(bool ok, uint32_t addr, uint32_t r0, uint32_t r1, uint32_t r2, uint32_t r3) {
  asm volatile("{\n.reg .pred p;\nsetp.ne.b32 p, %5, 0;\n@p stmatrix.sync.aligned.m8n8.x4.shared.b16 [%0], {%1,%2,%3,%4};\n}\n" ::"r"(addr),
               "r"(r0), "r"(r1), "r"(r2), "r"(r3), "r"((int)ok));
}

__device__ __forceinline__ void attn_a_slow(const uint8_t* __restrict__ kvimg, int L, int gb, int hp, uint32_t bad,
                                            int row0, int lane) {
  constexpr uint32_t sq = SBASE + OFF_SLOT + 3 * 16384;
#pragma unroll 1
  for (int j = 0; j < 8; j++) {
    const uint8_t* tp = kvimg + (size_t)(gb * 16 + hp) * 32768 + (j * 32 + lane) * 128 + ((lane & 7) << 4);
#pragma unroll 1
    for (uint32_t it = 0; it < (1u << 17); ++it)
      if (((ld_relaxed_u32(tp) ^ kv_tag(L)) & 1u) == 0u) break;
  }
  __syncwarp();
#pragma unroll 1
  for (int t = 0; t < 32; t++) {
    const int hh = t >> 4, row = row0 + (t & 7) + (t & 8) * 4;
    if (!((bad >> hh) & 1u)) continue;
    const int qpos = gb * 128 + row;
    const uint32_t qaddr = sq + row * 128;
    float mx = -INFINITY, sum = 0.f, acc = 0.f;
#pragma unroll 1
    for (int pass = 0; pass < 2; pass++) {
#pragma unroll 1
      for (int j = 0; j < 8; j++) {
        const int kp = qpos - (lane + 32 * j);
        const uint8_t* kr = kvimg + ((size_t)((kp >> 7) * 16 + hp) * 2 + ((kp >> 6) & 1)) * 16384 + (kp & 63) * 128;
        float d = -INFINITY;
        if (kp >= 0) {
          d = 0.f;
#pragma unroll 1
          for (int q = 0; q < 4; q++) {
            const uint4 kv = __ldcg(reinterpret_cast<const uint4*>(kr + (((hh * 4 + q) ^ (kp & 7)) << 4)));
            const uint4 qv = lds128(qaddr + (((hh * 4 + q) ^ (row & 7)) << 4));
            const uint32_t kw[4] = {kv.x, kv.y, kv.z, kv.w}, qw[4] = {qv.x, qv.y, qv.z, qv.w};
#pragma unroll
            for (int e = 0; e < 4; e++) d = fmaf(bf_lo(kw[e]), bf_lo(qw[e]), fmaf(bf_hi(kw[e]), bf_hi(qw[e]), d));
          }
        }
        if (pass == 0) {
          mx = fmaxf(mx, d);
        } else {
          const float ev = ex2_approx(d - mx);
          sum += ev;
          const float pv = bf16_round(ev);
#pragma unroll 1
          for (int kk = 0; kk < 32; kk++) {
            const float pk = __shfl_sync(0xffffffffu, pv, kk);
            const int k2 = qpos - (kk + 32 * j);
            if (k2 >= 0) {
              const uint8_t* vr = kvimg + ((size_t)((k2 >> 7) * 16 + hp) * 2 + ((k2 >> 6) & 1)) * 16384 + 8192 + (k2 & 63) * 128;
              const unsigned short vv =
                  __ldcg(reinterpret_cast<const unsigned short*>(vr + (((hh * 4 + (lane >> 3)) ^ (k2 & 7)) << 4) + (lane & 7) * 2));
              acc = fmaf(pk, __uint_as_float((uint32_t)vv << 16), acc);
            }
          }
        }
      }
      if (pass == 0) {
#pragma unroll
        for (int o = 16; o > 0; o >>= 1) mx = fmaxf(mx, __shfl_xor_sync(0xffffffffu, mx, o));
      }
    }
#pragma unroll
    for (int o = 16; o > 0; o >>= 1) sum += __shfl_xor_sync(0xffffffffu, sum, o);
    acc *= rcp_fast(sum);
    const float hi = __shfl_down_sync(0xffffffffu, acc, 1);
    __syncwarp();
    if ((lane & 1) == 0) sts32(qaddr + (((hh * 4 + (lane >> 3)) ^ (row & 7)) << 4) + (lane & 7) * 2,
                               set_tag(pack_bf16x2(acc, hi), hh == 0 && lane == 0, o_tag(L)));
    __syncwarp();
  }
}

template <int HH>
__device__ __forceinline__ void store_o(const float (&o)[16], const float (&inv)[2], uint32_t ra, uint32_t tag, bool ok) {
  const uint32_t m = HH == 0 && (fresh_tid() & 3) == 0;
#pragma unroll
  for (int jp = 0; jp < 2; jp++) {
    uint32_t w0 = pack_bf16x2(o[8 * jp] * inv[0], o[8 * jp + 1] * inv[0]);
    uint32_t w1 = pack_bf16x2(o[8 * jp + 2] * inv[1], o[8 * jp + 3] * inv[1]);
    if (HH == 0 && jp == 0) {
      w0 = set_tag(w0, m, tag);
      w1 = set_tag(w1, m, tag);
    }
    stmatrix_x4_if(ok, ra ^ ((HH * 4 + 2 * jp) << 4), w0, w1, pack_bf16x2(o[8 * jp + 4] * inv[0], o[8 * jp + 5] * inv[0]),
                   pack_bf16x2(o[8 * jp + 6] * inv[1], o[8 * jp + 7] * inv[1]));
  }
}
__device__ __forceinline__ int tile_row(bool B, int w, int r, int g) { return (B ? 16 * w + 8 * r : 8 * w + 32 * r) + g; }
__device__ __forceinline__ uint32_t q_row_addr(bool B, int R, int w, int lane) {
  return SBASE + OFF_SLOT + 3 * 16384 + R * 8192 + tile_row(B, w, (lane >> 3) & 1, lane & 7) * 128 + (((lane >> 4) ^ (lane & 7)) << 4);
}

struct AttnA {
  float s[2][16], o[2][16], l[2][2], sh[2][3];
  uint32_t p[2][4], t[2], me[4], ra, bad, zero;
};
#define ATS_(i) do { } while (0)
template <int V>
__device__ __forceinline__ void attn_sum(AttnA& a, int nv) {
  constexpr int hh = (V >> 1) & 1, kh = V & 1, i = V >> 2;
#pragma unroll
  for (int r = 0; r < 2; r++) {
    const uint32_t t1 = add_bf16x2(add_bf16x2(a.p[0][r], a.p[0][2 + r]), add_bf16x2(a.p[1][r], a.p[1][2 + r]));
    if (kh == 0) {
      a.t[r] = t1;
    } else {
      uint32_t tt = add_bf16x2(a.t[r], t1);
      if (i > 0) tt = i <= nv ? tt : 0u;
      const float v = bf_lo(tt) + bf_hi(tt);
      a.l[hh][r] = i == 0 ? v : a.l[hh][r] + v;
    }
  }
}
template <int HH>
__device__ __forceinline__ void attn_shfl(AttnA& a) {
#pragma unroll
  for (int r = 0; r < 2; r++)
#pragma unroll
    for (int j = 0; j < 3; j++) a.sh[r][j] = __shfl_xor_sync(0xffffffffu, a.l[HH][r], j + 1);
}
template <int HH>
__device__ __forceinline__ void attn_fin(AttnA& a) {
  bool bad = false;
  float inv[2];
#pragma unroll
  for (int r = 0; r < 2; r++) {
    const float v = (a.l[HH][r] + a.sh[r][0]) + (a.sh[r][1] + a.sh[r][2]);
    bad |= !(v <= 1.152921504606846976e18f && v >= 8.673617379884035e-19f);
    inv[r] = rcp_fast(v);
  }
  bad = __any_sync(0xffffffffu, bad);
  if (HH == 1) wgmma_wait<0>();
  reg_fence<16>(a.o[HH]);
  store_o<HH>(a.o[HH], inv, a.ra, o_tag(0), !bad);
  a.bad = (HH == 0 ? 0u : a.bad) | (bad ? 1u << HH : 0u);
}
__device__ __forceinline__ void attn_masks(AttnA& a, int wr) {
  const int lane = fresh_tid() & 31, d = (lane >> 2) - 2 * (lane & 3);
  const uint32_t tri = d >= 1 ? 0xffffffffu : (d == 0 ? 0xffffu : 0u);
#pragma unroll
  for (int t = 0; t < 4; t++) a.me[t] = wr > t ? 0xffffffffu : (wr == t ? tri : 0u);
}
template <int V, int K>
__device__ __forceinline__ uint32_t attn_exp(AttnA& a) {
  constexpr int i = V >> 2, kh = V & 1, r = K & 1;
  if ((i == 0 && kh > r) || (i == 4 && kh < r)) return 0u;
  const uint32_t w = pack_bf16x2(ex2_approx(a.s[V & 1][2 * K]), ex2_approx(a.s[V & 1][2 * K + 1]));
  if (i == 0 && kh == r) return w & a.me[K >> 1];
  if (i == 4 && kh == r) return w & ~a.me[K >> 1];
  return w;
}
template <int V>
__device__ __forceinline__ void attn_unit(AttnA& a, const uint32_t (&q)[2][2][4], uint64_t dcur, uint64_t dnext, int R, int wr, int nv,
                                          uint32_t hbar, uint32_t hpar, uint32_t rbar, bool rel) {
  constexpr int hh = (V >> 1) & 1, kh = V & 1, i = V >> 2;
  ATS_(V + 1);
  asm volatile("" : "+l"(dcur), "+l"(dnext));
  wgmma_wait<1>();
  reg_fence<16>(a.s[V & 1]);
  bool hok = true;
  if (V == 4) hbar = SBASE + OFF_BAR + 8u * (R ? B_LOC : B_HV);
  if (((V & 3) == 2 && V < 16) || V == 4) hok = mbar_test(hbar, hpar);
  const uint64_t d0 = ((V & 3) >= 2 ? dnext : dcur) + ((hh ^ 1) * 4 + kh * 256), d1 = ((V & 3) >= 2 ? dnext : dcur) + ((hh ^ 1) * 4 + kh * 256 + 2);
  const uint64_t d2 = dcur + (512 + hh * 4 + kh * 256), d3 = dcur + (640 + hh * 4 + kh * 256);
  if ((V & 3) == 1 && V > 4 && rel) mbar_arrive(rbar);
  if (V > 0) attn_sum<V - 1>(a, nv);
  if (V == 15) attn_masks(a, wr);
  if (V == 18) {
    attn_shfl<0>(a);
    a.ra = q_row_addr(false, R, wr, fresh_tid() & 31);
  }
  if (V == 19) attn_fin<0>(a);
  uint32_t p[2][4];
  p[0][0] = attn_exp<V, 0>(a);
  p[0][1] = attn_exp<V, 1>(a);
  p[0][2] = attn_exp<V, 2>(a);
  p[0][3] = attn_exp<V, 3>(a);
  p[1][0] = attn_exp<V, 4>(a);
  p[1][1] = attn_exp<V, 5>(a);
  p[1][2] = attn_exp<V, 6>(a);
  p[1][3] = attn_exp<V, 7>(a);
  if (V > 0) {
#pragma unroll
    for (int r = 0; r < 2; r++) p[1][r] ^= (kh ? a.t[r] : __float_as_uint(a.l[hh ^ 1][r])) & a.zero;
  }
#pragma unroll
  for (int k = 0; k < 8; k++) {
    asm volatile("" : "+r"(p[k >> 2][k & 3]));
    a.p[k >> 2][k & 3] = p[k >> 2][k & 3];
  }
  if (!hok) mbar_wait(hbar, hpar);
  wgmma_fence();
  if (V < 18) wgmma_n32_rsz_tb0(a.s[V & 1], q[hh ^ 1][0], d0);
  if (i == 0 && kh == 0) wgmma_n32_rsz_tb1(a.o[hh], a.p[0], d2);
  else wgmma_n32_rs_tb1(a.o[hh], a.p[0], d2, 1);
  if (V < 18) wgmma_n32_rs_tb0(a.s[V & 1], q[hh ^ 1][1], d1, 1);
  wgmma_n32_rs_tb1(a.o[hh], a.p[1], d3, 1);
  wgmma_commit();
}
template <int I>
__device__ __forceinline__ void attn_step(AttnA& a, const uint32_t (&q)[2][2][4], uint64_t dcur, uint64_t dnext, int R, int wr, int nv,
                                          uint32_t hbar, uint32_t hpar, uint32_t rbar, bool rel) {
  attn_unit<4 * I>(a, q, dcur, dnext, R, wr, nv, hbar, hpar, rbar, rel);
  attn_unit<4 * I + 1>(a, q, dcur, dnext, R, wr, nv, hbar, hpar, rbar, rel);
  attn_unit<4 * I + 2>(a, q, dcur, dnext, R, wr, nv, hbar, hpar, rbar, rel);
  attn_unit<4 * I + 3>(a, q, dcur, dnext, R, wr, nv, hbar, hpar, rbar, rel);
}

__device__ __forceinline__ void attention_a(const uint32_t (&q)[2][2][4], int R, int L, int gb, int hp, uint32_t par, int wr,
                                            uint32_t zero) {
  constexpr uint32_t bars = SBASE + OFF_BAR;
  constexpr uint32_t dslot = ((SBASE + OFF_SLOT) >> 4) + 0x10000u;
  auto next = [&](uint64_t d) { return desc_lo((uint32_t)d == dslot ? dslot + 2048 : (uint32_t)d - 1024) + zero; };
  uint64_t d0 = desc_lo(dslot + R * 1024) + zero, d1 = next(d0);
  AttnA a;
  ATS_(0);
  wgmma_fence();
#pragma unroll
  for (int v = 0; v < 2; v++) {
    wgmma_n32_rsz_tb0(a.s[v], q[0][0], d0 + v * 256);
    wgmma_n32_rs_tb0(a.s[v], q[0][1], d0 + (v * 256 + 2), 1);
    wgmma_commit();
  }
  a.zero = zero;
  const bool lane0 = (fresh_tid() & 31) == 0;
  attn_masks(a, wr);
  const int nv = 2 * gb + R;
  const uint32_t hb = bars + 8u * (B_HALO - R), rb = bars + 8u * (B_REL - R);
  attn_step<0>(a, q, d0, d1, R, wr, nv, hb, par, 0, false);
  d0 = next(d1);
  attn_step<1>(a, q, d1, d0, R, wr, nv, R ? bars + 8u * B_HV : hb + 8, par, rb + 8, lane0);
  d1 = next(d0);
  attn_step<2>(a, q, d0, d1, R, wr, nv, hb + 16, par, rb + 16, lane0);
  d0 = next(d1);
  attn_step<3>(a, q, d1, d0, R, wr, nv, hb + 24, par, rb + 24, lane0 && R);
  attn_step<4>(a, q, d0, d0, R, wr, nv, 0, 0, rb, false);
  ATS_(21);
  attn_sum<19>(a, nv);
  attn_shfl<1>(a);
  attn_fin<1>(a);
  ATS_(22);
  if (a.bad != 0u) {
    attn_a_slow(g_kvA[0][0][0], L, gb, hp, a.bad, R * 64 + wr * 8, fresh_tid() & 31);
    named_bar_sync(8 + R * 4 + wr, 32);
  }
}

constexpr uint32_t KB_ROW0 = SBASE + OFF_SLOT + 2048, VB_ROW0 = SBASE + OFF_SLOT + 24576 + 2048;

__device__ __forceinline__ void attention_b(const uint32_t (&q)[2][2][4], int R, int gb, uint32_t par0, int wr) {
  constexpr uint32_t bars = SBASE + OFF_BAR;
  const uint32_t dk = ((KB_ROW0 - 2048) >> 4) + 0x10000u + R * 512, dv = dk + ((VB_ROW0 - KB_ROW0) >> 4);
  float s[2][40];
  mbar_wait(bars + 8u * (B_HALO - R), par0);
  wgmma_fence();
#pragma unroll
  for (int hh = 0; hh < 2; hh++) {
    wgmma_n80_rsz_tb0(s[hh], q[hh][0], desc_lo(dk + hh * 4));
    wgmma_n80_rs_tb0(s[hh], q[hh][1], desc_lo(dk + hh * 4 + 2), 1);
  }
  wgmma_commit();
  const int lane = fresh_tid() & 31, g = lane >> 2;
  const bool odd = g & 1, edge = R == 0 && gb == 0 && wr == 0;
  const int D = 2 * (lane & 3) + (g & 1) - g;
  const uint32_t ra = q_row_addr(true, R, wr, lane);
  wgmma_wait<0>();
  reg_fence<40>(s[0]);
  reg_fence<40>(s[1]);
  float z[2][2], y[2][2];
#define GATHER_(W)                                                                                          \
  _Pragma("unroll") for (int hh = 0; hh < 2; hh++) _Pragma("unroll") for (int r = 0; r < 2; r++) {          \
    const float* e = &s[hh][4 * (2 * W + r) + 2 * r];                                                       \
    z[hh][r] = odd ? e[5] : e[4];                                                                           \
    y[hh][r] = D >= 2 ? (odd ? e[1] : e[0]) : (odd ? e[9] : e[8]);                                          \
  }
  if (wr < 2) {
    if (wr == 0) { GATHER_(0) } else { GATHER_(1) }
  } else {
    if (wr == 2) { GATHER_(2) } else { GATHER_(3) }
  }
#undef GATHER_
  float o[2][16], inv[2][2];
  uint32_t p[2][5][4];
  const int sh = odd ? 16 : 0, kb = wr + (D >= 2 ? 0 : 1);
#pragma unroll
  for (int hh = 0; hh < 2; hh++) {
    if (edge) {
      z[hh][0] = -INFINITY;
      if (D >= 2) y[hh][0] = y[hh][1] = -INFINITY;
    }
    uint32_t ab[2][2];
#pragma unroll
    for (int r = 0; r < 2; r++) {
      float m = fmaxf(z[hh][r], y[hh][r]);
      m = fmaxf(m, __shfl_xor_sync(0xffffffffu, m, 1));
      m = fmaxf(m, __shfl_xor_sync(0xffffffffu, m, 2));
      const float e0 = ex2_approx(z[hh][r] - m), e1 = ex2_approx(y[hh][r] - m);
      inv[hh][r] = e0 + e1;
      ab[r][0] = pack_bf16x2(e0, 0.f) << sh;
      ab[r][1] = pack_bf16x2(e1, 0.f) << sh;
    }
#pragma unroll
    for (int k = 0; k < 5; k++) {
      p[hh][k][0] = k == kb ? ab[0][1] : 0u;
      p[hh][k][1] = k == wr + 1 ? ab[1][0] : 0u;
      p[hh][k][2] = k == wr ? ab[0][0] : 0u;
      p[hh][k][3] = k == kb ? ab[1][1] : 0u;
#pragma unroll
      for (int j = 0; j < 4; j++) asm volatile("" : "+r"(p[hh][k][j]));
    }
  }
  wgmma_fence();
#pragma unroll
  for (int hh = 0; hh < 2; hh++) {
    wgmma_n32_rsz_tb1(o[hh], p[hh][0], desc_lo(dv + hh * 4));
#pragma unroll
    for (int k = 1; k < 5; k++) wgmma_n32_rs_tb1(o[hh], p[hh][k], desc_lo(dv + hh * 4 + k * 128), 1);
  }
  wgmma_commit();
#pragma unroll
  for (int hh = 0; hh < 2; hh++)
#pragma unroll
    for (int r = 0; r < 2; r++) {
      inv[hh][r] += __shfl_xor_sync(0xffffffffu, inv[hh][r], 1);
      inv[hh][r] += __shfl_xor_sync(0xffffffffu, inv[hh][r], 2);
      inv[hh][r] = rcp_fast(inv[hh][r]);
    }
  wgmma_wait<0>();
  reg_fence<16>(o[0]);
  reg_fence<16>(o[1]);
  store_o<0>(o[0], inv[0], ra, o_tag(1), true);
  store_o<1>(o[1], inv[1], ra, o_tag(1), true);
}

#define KTQM 0
#define TRICKLE 300
#define WTURN 15
#define QREL 8
#define PRESLEEP 200
#define CSA 3
#define TLAZY 100
#define QTURN 2
#define HTS(i) do { } while (0)
struct Params {
  CUtensorMap x[5], xq[4], o, wqkv[2], wqkv3[2], wo3[2];
  const __nv_bfloat16* in_x;
  const __nv_bfloat16* wqkv_p[2];
  const __nv_bfloat16* wo_p[2];
  __nv_bfloat16* out;
  uint32_t zero;
};

__device__ __forceinline__ void colsum_part(const CUtensorMap* wmap, int ty, int qr, int hp) {
  constexpr uint32_t bars = SBASE + OFF_BAR, slots = SBASE + OFF_SLOT;
  PHASE_IDS
  const unsigned ep1 = launch_epoch();
  if (wwarp == 0 && elect_one()) {
    mbar_expect_tx(bars + 8u * B_CS, 6 * UNIT);
#pragma unroll 1
    for (int j = 0; j < 6; j++) {
      if (ty == 0) mbar_pace(bars + 8u * (B_QF + B_E + ((j * CSA / 6) & 3)), (j * CSA / 6) >> 2);
      else mbar_wait_lazy<100>(bars + 8u * (B_WF + B_E + ((2 * j + 3 - (j & 1)) & 7)), j >= 3);
      tma_load_2d(slots + j * UNIT, wmap, bars + 8u * B_CS, (j >> 1) * 1024 + hp * 64, qr * 128 + (j & 1) * 64);
    }
  }
  constexpr uint64_t ones = (SBASE + OFF_LSB + 32) >> 4;
  float s[3][4];
  mbar_wait_lazy<100>(bars + 8u * B_CS, ty);
  wgmma_fence();
#pragma unroll
  for (int p = 0; p < 3; p++) {
    wgmma_n8_ssz_ta1_tb0(s[p], make_desc(slots + p * 2 * UNIT, 16), ones);
#pragma unroll
    for (int k = 1; k < 8; k++) wgmma_n8_ss_ta1_tb0(s[p], make_desc(slots + p * 2 * UNIT + k * 2048, 16), ones, 1);
  }
  wgmma_commit();
  wgmma_wait<0>();
  reg_fence<12>(&s[0][0]);
  if (lane == 0) mbar_arrive(bars + 8u * (ty ? B_CSD : B_RDONE));
  if (c == 0) {
#pragma unroll
    for (int r = 0; r < 2; r++) st_rec(&g_cs[ty][hp][qr][wwarp * 16 + 8 * r + g], s[0][2 * r], s[1][2 * r], s[2][2 * r], ep1);
  }
}

__device__ __forceinline__ void put_colsums(int ty, int col, const float4& s) {
  const float v[3] = {s.x, s.y, s.z};
#pragma unroll
  for (int p = 0; p < 3; p++) {
    const uint32_t a = SBASE + OFF_CS + (p * 8 + (col >> 3)) * 64 + ty * 32 + (col & 7) * 2;
    const float hi = bf16_round(v[p]);
    const uint32_t w = pack_bf16x2(hi, v[p] - hi);
    asm volatile("st.shared.b16 [%0], %1;" ::"r"(a), "h"((unsigned short)w) : "memory");
    asm volatile("st.shared.b16 [%0], %1;" ::"r"(a + 16), "h"((unsigned short)(w >> 16)) : "memory");
  }
}

__device__ __forceinline__ uint32_t ln_params(float s1, float s2) {
  const float mean = s1 * (1.0f / DM);
  const float var = fmaxf(fmaf(-mean, mean, s2 * (1.0f / DM)), 0.f);
  float sd;
  asm("sqrt.approx.f32 %0, %1;" : "=f"(sd) : "f"(bf16_round(bf16_round(var) + 1e-5f)));
  return pack_bf16x2(mean, sd);
}

struct RingProd {
  uint32_t rel = ((B_QF << 1) | 1) * 0x01010101u + 0x06040200u;
  int st = 0;
  __device__ __forceinline__ uint32_t next(uint32_t bar, uint32_t par, bool wait) {
    const uint32_t e = (rel >> (8 * st)) & 255u, a = SBASE + st * 5 * UNIT;
    if (wait) mbar_wait(SBASE + OFF_BAR + 8u * B_E + 8u * (e >> 1), e & 1u);
    rel ^= (e ^ ((bar << 1) | par)) << (8 * st);
    st = (st + 1) & 3;
    return a;
  }
};

#define SP1 15
#define SP2 14
#define SP3 12
#define SP4 12
#define SP5 15
#define SP6 14
#define SP7 16
__device__ __forceinline__ int q_split(int inst) {
  constexpr uint32_t T = 15u | ((SP1 - 1) << 4) | ((SP2 - 1) << 8) | ((SP3 - 1) << 12) | ((SP4 - 1) << 16) | ((SP5 - 1) << 20) |
                         ((SP6 - 1) << 24) | ((uint32_t)(SP7 - 1) << 28);
  return (int)((T >> (4 * inst)) & 15u) + 1;
}
__host__ __device__ constexpr uint32_t turn_par(int kind) {
  const int sp[8] = {16, SP1, SP2, SP3, SP4, SP5, SP6, SP7};
  int cnt[2] = {0, 0};
  uint32_t m = 0;
  for (int i = 0; i < 8; i++)
    for (int k = 0; k < 3; k++) {
      if (k == kind) m |= (uint32_t)(cnt[i & 1] & 1) << i;
      if (k == 0 ? (i == 1 || (i > 1 && sp[i - 1] < 16)) : (k == 2 || sp[i] < 16)) cnt[i & 1]++;
    }
  return m;
}
#define PREMASK 0xBFu
__device__ __forceinline__ bool w_pre(int inst) { return (PREMASK >> inst) & 1u; }
__host__ __device__ constexpr unsigned long long bar_counts(int i0) {
  unsigned long long t = 0;
  for (int i = i0; i < i0 + 32; i++) {
    int l = 0;
    if (i < B_RF) l = 1;
    if ((i >= B_E && i < B_E + B_RF) || i == B_LOC || i == B_REL || i == B_OS0 || i == B_TURN || i == B_TURN + 1 || i == B_XS ||
        i == B_XS + 1 || i == B_CSD || i == B_GO || i == B_RDONE || i == B_KV)
      l = 2;
    if (i == B_REL + 1 || i == B_REL + 2) l = 3;
    t |= (unsigned long long)l << (2 * (i - i0));
  }
  return t;
}

__global__ void __launch_bounds__(512, 1) fused_kernel(const __grid_constant__ Params P) {
  extern __shared__ __align__(1024) uint8_t smem_raw[];
  constexpr uint32_t base = SBASE, bars = base + OFF_BAR, slots = base + OFF_SLOT;
  if (smem_u32(smem_raw) != base) __trap();
  const int warp = __shfl_sync(0xffffffffu, threadIdx.x >> 5, 0), lane = threadIdx.x & 31;
  const int b = blockIdx.x;
#define QS 0
#define WS 1
  const int qr = ((b & ((8 << QS) - 1)) >> QS) ^ (((b >> (3 + QS)) & 1) * 7);
  const int hp = ((b >> (3 + QS)) << QS) + (b & ((1 << QS) - 1));
  const int rt = ((b & ((16 << WS) - 1)) >> WS) ^ (((b >> (4 + WS)) & 1) * 15);
  const int ct = ((b >> (4 + WS)) << WS) + (b & ((1 << WS) - 1));

  if (warp == 12) {
    if (elect_one()) {
#pragma unroll 1
      for (int s = 0; s < 4; s++) {
        const uint32_t fb = bars + 8u * (B_QF + s), sa = base + s * 5 * UNIT;
        mbar_init(fb, 2);
        fence_barrier_init();
        mbar_expect_tx(fb, 5 * UNIT);
        mbar_arrive(fb);
        tma_load_5d(sa + 3 * UNIT, &P.xq[0], fb, s * 64, qr * 2);
        tma_load_3d(sa, &P.wqkv3[0], fb, hp * 64, s * 64);
      }
    }
    __syncwarp();
  } else if (warp >= 4 && warp < 12) {
    if (elect_one()) {
#pragma unroll 1
      for (int i = warp; i <= B_KV; i += 8) mbar_init(bars + 8u * i, 1u << (((i < 32 ? bar_counts(0) : bar_counts(32)) >> (2 * (i & 31))) & 3u));
      sts32(warp < 8 ? base + OFF_ONE - 16 + 4 * warp : base + OFF_LSB + 4 * warp, warp < 8 ? warp == 4 : 0x3f803f80u);
      fence_proxy_async_smem();
      fence_barrier_init();
    }
    __syncwarp();
  }

  if (warp >= 12) {
    setmaxnreg_dec<32>();
    if (warp == 12) {
      named_bar_sync(0, 512);
      if (elect_one()) {
#pragma unroll 1
        for (int s = 4; s < 16; s++) {
          const uint32_t fb = bars + 8u * (B_QF + (s & 3)), sa = base + (s & 3) * 5 * UNIT;
          mbar_wait(fb + 8u * B_E, ((s >> 2) & 1) ^ 1);
          mbar_expect_tx(fb, 5 * UNIT);
          mbar_arrive(fb);
          tma_load_5d(sa + 3 * UNIT, &P.xq[0], fb, s * 64, qr * 2);
          tma_load_3d(sa, &P.wqkv3[0], fb, hp * 64, s * 64);
        }
#pragma unroll
        for (int s = 0; s < 4; s++) mbar_arrive(bars + 8u * B_GO);
        RingProd rp;
#pragma unroll 1
        for (int sg = 4; sg < 34; sg++) {
          const int part = sg & 3, inst = (sg >> 2) - (part & 1);
          if (part == 3 || inst == 8) continue;
          const int ty = (inst >> 1) & 1;
          if (part != 1) {
            const int k0 = part ? q_split(inst) : 0, k1 = part ? 16 : q_split(inst);
#pragma unroll 1
            for (int kt = k0; kt < k1; kt++) {
              const uint32_t sa = rp.next(B_QF + (kt & 3), (kt >> 2) & 1, true), fb = bars + 8u * (B_QF + (kt & 3));
              mbar_expect_tx(fb, 3 * UNIT);
              tma_load_3d(sa, &P.wqkv3[ty], fb, hp * 64, kt * 64);
            }
          } else {
            const bool pre = w_pre(inst);
            const int lag = pre ? 8 : 5;
            uint32_t sa = 0;
#pragma unroll 1
            for (int kt = 0; kt < 16; kt++) {
              const int i = kt & 3;
              const uint32_t fb = bars + 8u * (B_WF + (kt & 7));
              if (i == 1) sa += 2 * UNIT;
              else if (i != 3 || !pre) sa = rp.next(kt == 14 ? B_RF : B_WF + ((kt | 1) & 7), kt == 14 ? inst & 1 : kt >> 3, kt < lag) + ((0x21 >> (2 * i)) & 3) * UNIT;
              if (kt >= lag) mbar_wait(bars + 8u * (B_WF + B_E + ((kt - lag) & 7)), (kt - lag) >> 3);
              if (i == 3 && pre) {
                mbar_arrive(fb);
              } else {
                mbar_expect_tx(fb, 2 * UNIT);
                tma_load_3d(sa, &P.wo3[ty], fb, ct * 128, kt * 64);
              }
            }
          }
        }
      }
    } else if (warp == 13) {
      RingProd rp;
      unsigned ep1 = 0;
      uint32_t seenx = 0;
      named_bar_sync(0, 512);
      mbar_wait(bars + 8u * B_GO, 0);
#pragma unroll 1
      for (int sg = 4; sg < 34; sg++) {
        const int part = sg & 3, inst = (sg >> 2) - (part & 1);
        if (part == 3 || inst == 8) continue;
        const int L = inst >> 1, ch = inst & 1;
        uint32_t seen = 0;
        if (part != 1) {
          const CUtensorMap* tx = &P.xq[L];
          const int k0 = part ? q_split(inst) : 0, k1 = part ? 16 : q_split(inst);
          if (part == 0) seenx = L == 0 ? 0xffffffffu : 0u;
          if (sg == 4) ep1 = launch_epoch();
          const int m0 = ch * 16 + qr * 2;
#pragma unroll 1
          for (int kt = k0; kt < k1; kt++) {
            wait_count(g_fx[ch * 8 + qr][0], 6u * ep1 - 6u + 2u * L, kt, seenx, lane);
            TGET(t38);
            const uint32_t sa = rp.next(B_QF + (kt & 3), (kt >> 2) & 1, true);
            TGET(t39);
            if (elect_one()) {
              const uint32_t fb = bars + 8u * (B_QF + (kt & 3));
              mbar_expect_tx(fb, 2 * UNIT);
              tma_load_5d(sa + 3 * UNIT, tx, fb, kt * 64, m0);
            }
            if (L == 3 && kt == 0 && lane == 0) { TPUT(ch, 38, t38); TPUT(ch, 39, t39); }
          }
        } else {
          const int m0 = ch * 1024 + rt * 64;
          const bool pre = w_pre(inst);
          const int lag = pre ? 8 : 5;
          uint32_t sa = 0;
#pragma unroll 1
          for (int kt = 0; kt < 16; kt++) {
            const int i = kt & 3;
            const uint32_t fb = bars + 8u * (B_WF + (kt & 7));
            wait_count(g_fo[ch * 16 + rt][0], 4u * ep1 - 3u + L, kt, seen, lane);
            const bool stg = kt == 13 && inst == 6 && SP7 == 16;
            if (i < 2) sa = rp.next(stg ? B_RF : B_WF + (kt & 7) + i + 1, stg ? inst & 1 : kt >> 3, kt < lag);
            else sa += (2 * i - 3) * UNIT;
            if (kt >= lag) mbar_wait(bars + 8u * (B_WF + B_E + ((kt - lag) & 7)), (kt - lag) >> 3);
            if (elect_one()) {
              mbar_expect_tx(fb, UNIT);
              tma_load_2d(sa, &P.o, fb, kt * 64, m0);
            }
            if (i == 3 && !pre) rp.next(B_WF + (kt & 7), kt >> 3, false);
          }
          if (L == 3) {
#pragma unroll 1
            for (int j = 0; j < 4; j++) {
              g_x[(size_t)(m0 + j * 16 + (lane >> 1)) * DM + ct * 128 + (lane & 1) * 64] = __ushort_as_bfloat16(0);
              __syncwarp();
            }
          }
        }
      }
    } else if (warp == 14) {
      const unsigned ep1 = launch_epoch();
      uint32_t hpar = 0;
      named_bar_sync(0, 512);
#pragma unroll 1
      for (int inst = 0; inst < 8; inst++) {
        const int L = inst >> 1, ch = inst & 1, gb = ch * 8 + qr;
        const unsigned kv0 = 8u * ep1 - 8u + 2u * L + (L & 1);
        const uint32_t tag = kv_tag(L);
        if (L >= 2) {
#pragma unroll 1
          for (uint32_t it = 0; it < (1u << 17); ++it)
            if (__all_sync(0xffffffffu, (int)(ld_relaxed_u32(g_fk[hp][min(gb + 1 + (lane & 1), 15)]) - kv0) >= 0)) break;
        }
        if ((L & 1) == 0) {
          uint8_t* img = g_kvA[gb][hp][0];
          const uint8_t* s1 = gb > 0 ? img - 16 * 32768 : g_zero;
          const uint8_t* s2 = gb > 1 ? img - 32 * 32768 : g_zero;
          const uint32_t h1 = gb > 0 ? 16384 : 0, h2 = gb > 1 ? 16384 : 0;
          const unsigned* cp = g_fk[hp][max(gb - 1 - (lane >= 3), 0)];
          const unsigned ct0 = kv0 + ((0x32321u >> (4 * (lane & 7))) & 3u);
          uint32_t fr = gb == 0 ? 31u : (gb == 1 ? 24u : 0u);
          const uint32_t toff = slots + lane * 128 + ((lane & 7) << 4);
          auto seen = [&](uint32_t m) {
#pragma unroll 1
            for (uint32_t it = 0; it < (1u << 17) && !(fr & m); ++it)
              fr |= __ballot_sync(0xffffffffu, (int)(ld_relaxed_u32(cp) - ct0) >= 0);
          };
          auto load = [&](uint32_t off, const uint8_t* src, uint32_t bytes, int bi) {
            if (elect_one()) {
              mbar_expect_tx(bars + 8u * (B_HL + bi), bytes);
              bulk_load(slots + off, src, bytes, bars + 8u * (B_HL + bi));
            }
          };
          auto check = [&](uint32_t off, const uint8_t* src, uint32_t bytes, int bi, bool real, int done) {
#pragma unroll 1
            for (int tries = 0; tries < 4096; tries++) {
              mbar_wait(bars + 8u * (B_HL + bi), (hpar >> bi) & 1u);
              hpar ^= 1u << bi;
              uint32_t t = (lds32(toff + off) ^ tag) | (lds32(toff + off + 4096) ^ tag);
              if (bytes > 8192) t |= (lds32(toff + off + 8192) ^ tag) | (lds32(toff + off + 12288) ^ tag);
              if (!__any_sync(0xffffffffu, real && (t & 1u))) break;
              fence_proxy_async_smem();
              load(off, src, bytes, bi);
            }
            if (lane == 0) mbar_arrive(bars + 8u * done);
          };
          uint8_t *pk = img + 16384, *pv = img + 24576;
          unsigned* f = g_fk[hp][gb];
          pin64(pk), pin64(pv), pin64(f);
          mbar_wait(bars + 8u * B_KV, inst & 1);
          if (elect_one()) {
            bulk_store(pk, slots + 16384, 8192);
            bulk_announce(f);
            bulk_store(pv, slots + 24576, 8192);
            bulk_announce(f);
            bulk_commit();
          }
          HTS(44);
          seen(1);
          HTS(46);
          load(32768, s1 + h1, 8192, 0);
          seen(2);
          HTS(47);
          load(40960, s1 + h1 + 8192, 8192, 1);
          mbar_wait(bars + 8u * B_LOC, inst & 1);
          HTS(45);
          if (elect_one()) {
            bulk_store(img, slots, 16384);
            bulk_announce(g_fk[hp][gb]);
            bulk_commit();
            asm volatile("cp.async.bulk.wait_group.read 1;" ::: "memory");
          }
          check(32768, s1 + h1, 8192, 0, gb > 0, B_HALO);
          HTS(52);
          check(40960, s1 + h1 + 8192, 8192, 1, gb > 0, B_HV);
          HTS(53);
#pragma unroll 1
          for (int n = 1; n < 4; n++) {
            const uint8_t* src = n == 1 ? s1 : (n == 2 ? s2 + h2 : s2);
            const uint32_t off = n == 3 ? 32768 : 32768 - n * 16384;
            seen(2u << n);
            if (n == 2 && elect_one()) bulk_wait_read0();
            mbar_wait(bars + 8u * (B_REL - 1) + 8u * n, ch);
            HTS(47 + n);
            load(off, src, 16384, 0);
            check(off, src, 16384, 0, gb > (n >> 1), B_HALO + n);
            HTS(53 + n);
          }
        } else {
          uint8_t *pk = g_kvB[gb][hp], *pv = pk + 2048;
          const uint8_t* src = gb >= 1 ? pk - 16 * 4096 : g_zero;
          unsigned* f = g_fk[hp][gb];
          pin64(pk), pin64(pv), pin64(f), pin64(src);
          mbar_wait(bars + 8u * B_KV, inst & 1);
          if (elect_one()) {
            bulk_store(pk, KB_ROW0 + 112 * 128, 2048);
            bulk_store(pv, VB_ROW0 + 112 * 128, 2048);
            bulk_announce(f);
            bulk_commit();
          }
          HTS(44);
          if (gb > 0) {
#pragma unroll 1
            for (uint32_t it = 0; it < (1u << 17); ++it)
              if (__any_sync(0xffffffffu, (int)(ld_relaxed_u32(f - 4) - kv0) > 0)) break;
          }
          HTS(46);
#pragma unroll 1
          for (uint32_t it = 0; it < (1u << 17); ++it) {
            if (elect_one()) {
              mbar_expect_tx(bars + 8u * B_HL, 4096);
              bulk_load(KB_ROW0 - 2048, src, 2048, bars + 8u * B_HL);
              bulk_load(VB_ROW0 - 2048, src + 2048, 2048, bars + 8u * B_HL);
            }
            mbar_wait(bars + 8u * B_HL, hpar & 1u);
            hpar ^= 1u;
            const uint32_t t = lds32((lane < 16 ? KB_ROW0 - 2048 : VB_ROW0 - 4096) + lane * 128 + ((lane & 7) << 4)) ^ tag;
            if (!__any_sync(0xffffffffu, gb > 0 && (t & 1u))) break;
            fence_proxy_async_smem();
          }
          if (lane == 0) mbar_arrive(bars + 8u * B_HALO);
          HTS(52);
        }
        if (elect_one()) {
          const CUtensorMap* mo = &P.o;
          unsigned *f1 = g_fo[gb * 2 + 1][hp], *f0 = g_fo[gb * 2][hp];
          int c0 = hp * 64, r0 = gb * 128, r1 = r0 + 64;
          pin64(mo), pin64(f1), pin64(f0);
          asm volatile("" : "+r"(c0), "+r"(r0), "+r"(r1));
          mbar_wait(bars + 8u * B_OS1, (inst & 1) ^ 1);
          tma_store_2d(mo, slots + 7 * UNIT, c0, r1);
          bulk_announce(f1);
          bulk_commit();
          mbar_wait(bars + 8u * B_OS0, inst & 1);
          tma_store_2d(mo, slots + 6 * UNIT, c0, r0);
          bulk_announce(f0);
          bulk_commit();
          bulk_wait_read0();
          mbar_expect_tx(bars + 8u * B_RF, 2 * UNIT);
          tma_load_2d(slots + 6 * UNIT, &P.x[L], bars + 8u * B_RF, ct * 128, ch * 1024 + rt * 64);
          tma_load_2d(slots + 7 * UNIT, &P.x[L], bars + 8u * B_RF, ct * 128 + 64, ch * 1024 + rt * 64);
          if (w_pre(inst)) {
            mbar_expect_tx(bars + 8u * B_PRE, 6 * UNIT);
            mbar_expect_tx(bars + 8u * B_PRE2, 2 * UNIT);
#pragma unroll 1
            for (int j = 0; j < 4; j++) {
              __nanosleep(PRESLEEP);
              if (j == 3) mbar_wait(bars + 8u * B_RDONE, (inst & 1) ^ 1);
              tma_load_3d(slots + j * 2 * UNIT, &P.wo3[L & 1], bars + 8u * (j == 3 ? B_PRE2 : B_PRE), ct * 128, (4 * j + 3) * 64);
            }
          }
        }
        __syncwarp();
      }
    } else {
      const unsigned ep1 = launch_epoch();
      named_bar_sync(0, 512);
      mbar_wait(bars + 8u * B_GO, 0);
#pragma unroll 1
      for (int i = 0; i < 20; i++) {
        const char* src = i < 4 ? reinterpret_cast<const char*>(P.wo_p[0]) + (size_t)b * 16384 + i * 4096
                                : (i < 16 ? reinterpret_cast<const char*>(P.wqkv_p[1]) + (size_t)b * 49152 + (i - 4) * 4096
                                          : reinterpret_cast<const char*>(P.wo_p[1]) + (size_t)b * 16384 + (i - 16) * 4096);
        asm volatile("prefetch.global.L2 [%0];" ::"l"(src + lane * 128));
        __nanosleep(TRICKLE);
      }
#pragma unroll 1
      for (int inst = 2; inst < 10; inst++) {
        const int L = inst >> 1, ch = inst & 1, gb = ch * 8 + qr;
        {
          uint32_t xb = base + (((inst < 9 ? q_split(inst - 1) : 0) + (w_pre(inst - 2) ? 3 : 2)) & 3) * 5 * UNIT;
          unsigned* f = g_fx[ch * 8 + (rt >> 1)][ct * 2];
          const CUtensorMap* mx = &P.x[L];
          int c0 = ct * 128, r0 = ch * 1024 + rt * 64;
          pin64(f), pin64(mx);
          asm volatile("" : "+r"(xb), "+r"(c0), "+r"(r0));
#pragma unroll
          for (int h = 0; h < 2; h++) {
            mbar_wait(bars + 8u * (B_XS + h), ch);
            if (elect_one()) {
              tma_store_2d(mx, xb + h * UNIT, c0 + h * 64, r0);
              if (L < 4) bulk_announce(f + 4 * h);
              bulk_commit();
              if (h == 1) {
                bulk_wait_read0();
                mbar_arrive(bars + 8u * (B_RF + B_E));
              }
            }
          }
          if (L == 4) continue;
        }
#pragma unroll 1
        for (int h = 0; h < 4; h++) {
          const float4* sp = &g_stats[L][0][gb * 128 + h * 32 + lane];
          const float4 s0 = sum_recs<4>(sp, S_LEN, ep1), s1 = sum_recs<4>(sp + 4 * S_LEN, S_LEN, ep1);
          sts32(base + OFF_RS + (ch * 128 + h * 32 + lane) * 4, ln_params(s0.x + s1.x, s0.y + s1.y));
        }
        if (inst == 2) {
#pragma unroll 1
          for (int hf = 0; hf < 2; hf++) {
            const float4* cp = &g_cs[1][hp][0][hf * 32 + lane];
            const float4 s0 = sum_recs<4>(cp, 64, ep1), s1 = sum_recs<4>(cp + 4 * 64, 64, ep1);
            put_colsums(1, hf * 32 + lane, make_float4(s0.x + s1.x, s0.y + s1.y, s0.z + s1.z, 0.f));
          }
        }
        fence_proxy_async_smem();
        __syncwarp();
        if (lane == 0) mbar_arrive(bars + 8u * (B_PREP + ch));
      }
    }
  } else {
    const bool asst = warp >= 8;
    GTL(0);
    if (warp >= 4) named_bar_sync(0, 512);
    if (warp >= 4 && !asst) {
      PHASE_IDS
      {
        const unsigned ep1 = launch_epoch();
        const int row = b * 16 + (tid >> 3);
        const uint4* src = reinterpret_cast<const uint4*>(P.in_x + (size_t)row * DM) + (tid & 7);
        float s1 = 0.f, s2 = 0.f;
#pragma unroll 1
        for (int k = 0; k < 4; k++) {
          mbar_pace(bars + 8u * (B_QF + B_E + ((2 * k) & 3)), k >> 1);
          uint4 v[4];
#pragma unroll
          for (int j = 0; j < 4; j++) v[j] = __ldg(src + (k * 4 + j) * 8);
#pragma unroll
          for (int j = 0; j < 4; j++) {
            const uint32_t w[4] = {v[j].x, v[j].y, v[j].z, v[j].w};
#pragma unroll
            for (int e = 0; e < 4; e++) {
              const float x0 = bf_lo(w[e]), x1 = bf_hi(w[e]);
              s1 += x0 + x1;
              s2 = fmaf(x0, x0, fmaf(x1, x1, s2));
            }
          }
        }
#pragma unroll
        for (int o = 1; o < 8; o <<= 1) {
          s1 += __shfl_xor_sync(0xffffffffu, s1, o);
          s2 += __shfl_xor_sync(0xffffffffu, s2, o);
        }
        if ((tid & 7) == 0) st_rec(&g_stats[0][0][row], s1, s2, 0.f, ep1);
        if (tid == 0) sts32(base + OFF_EPOCH, ep1);
        if (tid < 64) {
          const float4 s0 = sum_recs<8>(&g_cs[0][hp][0][tid], 64, ep1);
          put_colsums(0, tid, s0);
        } else {
          put_colsums(1, tid - 64, make_float4(0.f, 0.f, 0.f, 0.f));
        }
#pragma unroll 1
        for (int cc = 0; cc < 2; cc++) {
          const float4 s0 = sum_recs<1>(&g_stats[0][0][(cc * 8 + qr) * 128 + tid], 0, ep1);
          sts32(base + OFF_RS + (cc * 128 + tid) * 4, ln_params(s0.x, s0.y));
        }
        fence_proxy_async_smem();
        named_bar_sync(2, 128);
        if (tid < 2) mbar_arrive(bars + 8u * (B_PREP + tid));
      }
    }
#pragma unroll 1
    for (int inst = asst ? 0 : warp >> 2; inst < 8; inst += asst ? 1 : 2) {
      const int L = inst >> 1, ch = inst & 1, gb = ch * 8 + qr;
      uint32_t q[2][2][4];
      if (asst) {
        if (inst < 2) colsum_part(&P.wqkv[inst], inst, qr, hp);
        setmaxnreg_dec<24>();
        named_bar_sync(4, 256);
        setmaxnreg_inc<128>();
        const uint32_t ra = q_row_addr(L & 1, 1, warp & 3, fresh_tid() & 31);
#pragma unroll
        for (int j = 0; j < 4; j++) ldmatrix_x4(q[j >> 1][j & 1], ra ^ (j << 5));
      } else {
      setmaxnreg_inc<224>();
      {
        float acc[2][96];
        const int ksp = q_split(inst);
        constexpr uint32_t STG = 5 * (UNIT >> 4), D0 = ((base + 3 * UNIT) >> 4) + 0x10000u;
        constexpr uint32_t DB = ((UNIT >> 4) << 16) - 0x10000u - 3 * (UNIT >> 4);
        uint32_t sd = D0;
        const uint32_t toff = ((fresh_tid() & 127) << 7) + ((fresh_tid() & 7) << 4);
        const bool lane0 = (toff & 0xf80u) == 0u;
        uint32_t tbad = 0u, tw, xt = x_tag(L);
        uint32_t rsa = base + OFF_RS + (ch * 128 + tile_row(L & 1, warp & 3, 0, (toff >> 9) & 7)) * 4;
        uint32_t rsb = rsa + ((L & 1) ? 32 : 128);
        uint32_t lnm = ((toff >> 7) & 3) == (L & 1) ? 0xffffffffu : 0u, tmk = L > 0;
        uint32_t soff = tile_row(L & 1, warp & 3, (toff >> 10) & 1, (toff >> 7) & 7) * 128 + ((toff ^ (toff >> 7)) & 0x10u) + (toff & 0x60u);
        uint32_t bprep = bars + 8u * (B_PREP + ch), bturn = bars + 8u * (B_TURN + (ch ^ 1));
        uint32_t bfree = bars + 8u * (inst == 1 ? B_CSD : B_RDONE), pfree = inst == 1 ? 0 : inst & 1, pprep = L & 1;
        asm volatile("" : "+r"(rsa), "+r"(rsb), "+r"(lnm), "+r"(soff), "+r"(xt), "+r"(tmk));
        asm volatile("" : "+r"(bprep), "+r"(bturn), "+r"(bfree), "+r"(pfree), "+r"(pprep));
        if (inst == 0) named_bar_sync(0, 512);
        if (inst == 1 || (inst > 1 && q_split(inst - 1) < 16)) mbar_wait_lazy<TLAZY>(bars + 8u * (B_TURN + ch), (turn_par(0) >> inst) & 1u);
        if (L == 3) GTL(37);
        mbar_wait(bars + 8u * B_QF, 0);
        GTL(1 + L * 8);
        {
          const uint64_t da = desc_lo(sd) + P.zero;
          wgmma_fence();
          wgmma_n192_ssz_ta0_tb1(acc[1], da + (UNIT >> 4), da + DB);
          wgmma_commit();
          wgmma_n192_ssz_ta0_tb1(acc[0], da, da + DB);
          wgmma_commit();
        }
#pragma unroll 1
        for (int kt = 0; kt < 15; kt++) {
          const bool last = kt + 1 == ksp;
          const uint64_t da = desc_lo(sd) + P.zero;
          const uint32_t fn = bars + 8u * (B_QF + ((kt + 1) & 3)), pn = ((kt + 1) >> 2) & 1;
#pragma unroll
          for (int k16 = 0; k16 < 4; k16++) {
            if (k16 == 0 && kt == 0) continue;
            wgmma_fence();
            wgmma_n192_ss_ta0_tb1(acc[1], da + ((UNIT >> 4) + k16 * 2), da + (DB + k16 * 128), 1);
            wgmma_commit();
            wgmma_wait<1>();
            if (k16 == 0 && lane0 && kt != ksp) mbar_arrive(bars + 8u * (B_QF + B_E + ((kt - 1) & 3)));
            wgmma_fence();
            wgmma_n192_ss_ta0_tb1(acc[0], da + k16 * 2, da + (DB + k16 * 128), 1);
            wgmma_commit();
            if (k16 == 1) tw = lds32(((sd & 0xffffu) << 4) + toff);
            if (k16 == 2) tbad |= tw ^ xt;
            bool ok = true;
            if (k16 == 2) ok = mbar_test(fn, pn) || last;
            if (k16 == QTURN && last && lane0) mbar_arrive(bturn);
            if (k16 < 3) wgmma_wait<1>();
            if (k16 == 2 && !ok) mbar_wait(fn, pn);
          }
          sd = sd == D0 + 3 * STG ? D0 : sd + STG;
          if (last) {
            wgmma_wait<0>();
            if (lane0) mbar_arrive(bars + 8u * (B_QF + B_E + (kt & 3)));
            mbar_wait_lazy<TLAZY>(bars + 8u * (B_TURN + ch), (turn_par(1) >> inst) & 1u);
            mbar_wait(fn, pn);
          }
        }
        constexpr uint32_t DL = D0 + 3 * STG;
        wgmma_fence();
#pragma unroll
        for (int k16 = 0; k16 < 4; k16++) wgmma_n192_ss_ta0_tb1(acc[1], desc_lo(DL + (UNIT >> 4) + k16 * 2), desc_lo(DL + DB + k16 * 128), 1);
        wgmma_commit();
        tw = lds32(((DL & 0xffffu) << 4) + toff);
        mbar_wait(bprep, pprep);
        uint32_t rs[2][2];
        constexpr uint64_t DCS = (uint64_t)((base + OFF_CS) >> 4) | (4ull << 32);
        auto ln_mma = [&](float (&d)[96], uint32_t (&r)[2], int h) {
          uint32_t a[4];
#pragma unroll
          for (int i = 0; i < 2; i++) {
            if (h) r[i] = lds32((i ? rsb : rsa) + 256);
            a[i] = (__byte_perm(r[i], 0u, 0x1010) ^ 0x80008000u) & lnm;
            a[i + 2] = r[i] & P.zero;
          }
#pragma unroll
          for (int i = 0; i < 4; i++) asm volatile("" : "+r"(a[i]));
          wgmma_fence();
          wgmma_n192_rs_tb1(d, a, DCS, 1);
          wgmma_commit();
        };
        ln_mma(acc[1], rs[1], 1);
        wgmma_wait<2>();
        if (lane0 && ksp != 15) mbar_arrive(bars + 8u * (B_QF + B_E + 2));
        wgmma_fence();
#pragma unroll
        for (int k16 = 0; k16 < 4; k16++) wgmma_n192_ss_ta0_tb1(acc[0], desc_lo(DL + k16 * 2), desc_lo(DL + DB + k16 * 128), 1);
        wgmma_commit();
        if (lane0) mbar_arrive(bturn);
        rs[0][0] = lds32(rsa);
        rs[0][1] = lds32(rsb);
        static_assert(SP1 < 16 && (PREMASK & 1u), "column sums of B");
        const bool afree = mbar_test(bfree, pfree) & (mbar_test(bars + 8u * (B_WF + B_E + 7), 1) | (ksp == 16));
        const bool redo = named_bar_or(1 + ch, 128, (tbad | (tw ^ xt)) & tmk);
        float rinv[2];
#pragma unroll
        for (int r = 0; r < 2; r++) {
          rinv[r] = rcp_fast(bf_hi(rs[1][r]));
          asm volatile("" : "+f"(rinv[r]));
        }
        const uint32_t kdst = ((L & 1) ? KB_ROW0 : slots) + soff, vdst = ((L & 1) ? VB_ROW0 : slots + 8192) + soff;
        const uint32_t hs = (L & 1) ? 8192 : 16384, c0 = (toff & 0x180u) == 0u;
        wgmma_wait<1>();
        if (redo) {
          wgmma_wait<0>();
          constexpr uint32_t sa = (DL & 0xffffu) << 4;
          const uint32_t rb = bars + 8u * (B_REDO + ch);
          if (toff == 0) {
            mbar_init(rb, 1);
            fence_barrier_init();
          }
          uint32_t rpar = 0;
#pragma unroll 1
          for (int kt = 0, tries = 0; kt < 16;) {
            fence_proxy_async_smem();
            named_bar_sync(1 + ch, 128);
            if ((warp & 3) == 0 && elect_one()) {
                mbar_expect_tx(rb, 5 * UNIT);
              tma_load_5d(sa, &P.xq[L], rb, kt * 64, gb * 2);
              tma_load_3d(sa - 3 * UNIT, &P.wqkv3[L & 1], rb, hp * 64, kt * 64);
            }
            mbar_wait(rb, rpar);
            rpar ^= 1u;
            if (named_bar_or(1 + ch, 128, (lds32(sa + toff) ^ xt) & 1u) && ++tries < 4096) continue;
            wgmma_fence();
#pragma unroll
            for (int k16 = 0; k16 < 4; k16++) {
              const uint64_t db = make_desc(sa - 3 * UNIT + k16 * 2048, UNIT);
              wgmma_n192_ss_ta0_tb1(acc[1], make_desc(sa + UNIT + k16 * 32, 16), db, kt | k16);
              wgmma_n192_ss_ta0_tb1(acc[0], make_desc(sa + k16 * 32, 16), db, kt | k16);
            }
            wgmma_commit();
            wgmma_wait<0>();
            kt++;
          }
          ln_mma(acc[1], rs[1], 1);
          wgmma_wait<0>();
        }
        ln_mma(acc[0], rs[0], 0);
        reg_fence<96>(acc[1]);
        GTL(2 + L * 8);
        if (!afree) {
          mbar_wait(bfree, pfree);
          if (ksp < 16) mbar_wait(bars + 8u * (B_WF + B_E + 7), 1);
        }
#pragma unroll
        for (int t = 0; t < 24; t++) {
          const int h = t < 12 ? 1 : 0, p = ((t % 12) / 4 + 1) % 3, jp = t & 3;
          if (t == QREL) {
            wgmma_wait<0>();
            reg_fence<96>(acc[0]);
            if (lane0) mbar_arrive(bars + 8u * (B_QF + B_E + 3));
          }
          if (t == 8 || t == 20) {
            rinv[0] *= SM_C;
            rinv[1] *= SM_C;
          }
          const float* a = &acc[h][4 * (p * 8 + 2 * jp)];
          uint32_t r0 = pack_bf16x2(a[0] * rinv[0], a[1] * rinv[0]);
          uint32_t r1 = pack_bf16x2(a[2] * rinv[1], a[3] * rinv[1]);
          if (p != 0 && jp == 0) {
            r0 = set_tag(r0, c0, kv_tag(L));
            r1 = set_tag(r1, c0, kv_tag(L));
          }
          const uint32_t r2 = pack_bf16x2(a[4] * rinv[0], a[5] * rinv[0]);
          const uint32_t r3 = pack_bf16x2(a[6] * rinv[1], a[7] * rinv[1]);
          const uint32_t dst = p == 0 ? slots + 3 * 16384 + soff + h * 8192 : (p == 1 ? kdst : vdst) + h * hs;
          stmatrix_x4(dst ^ (jp << 5), r0, r1, r2, r3);
          if (t >= 20) {
            q[jp >> 1][jp & 1][0] = r0;
            q[jp >> 1][jp & 1][1] = r1;
            q[jp >> 1][jp & 1][2] = r2;
            q[jp >> 1][jp & 1][3] = r3;
          }
          if (t == 7 || t == 19) signal_async(bars + 8u * (t == 7 ? B_KV : B_LOC), lane0);
          if (t == 11) {
            setmaxnreg_dec<128>();
            named_bar_arrive(4, 256);
#pragma unroll
            for (int r = 0; r < 2; r++) rinv[r] = rcp_fast(bf_hi(rs[0][r]));
          }
        }
        mbar_wait(bars + 8u * B_LOC, inst & 1);
      }
      }
      GTL(3 + L * 8);
      if ((L & 1) == 0) attention_a(q, asst, L, gb, hp, ch, warp & 3, P.zero);
      else attention_b(q, asst, gb, inst & 1, warp & 3);
      GTL(4 + L * 8);
      signal_async(bars + 8u * (asst ? B_OS1 : B_OS0), (fresh_tid() & 31) == 0);
      if (asst) continue;
      GTL(5 + L * 8);

      {
        float acc[64];
        const int sp = inst < 7 ? q_split(inst + 1) : 0;
        int st = sp & 3;
        const bool pre = w_pre(inst);
        uint32_t tbad = 0u;
        const uint32_t toff = ((fresh_tid() & 63) << 7) + ((fresh_tid() & 7) << 4);
        const bool lane0 = (toff & 0xf80u) == 0u;
        constexpr uint32_t U4 = UNIT >> 4, LA = 0x10000u, LB = U4 << 16;
        reg_define<64>(acc);
        reg_fence<64>(acc);
        uint32_t xv[8][4];
        {
          PHASE_IDS_W
          const uint32_t xr = slots + 6 * UNIT + (wwarp * 16 + (lane & 15)) * 128 + (((lane >> 4) ^ (lane & 7)) << 4);
          mbar_wait(bars + 8u * B_RF, inst & 1);
#pragma unroll
          for (int jp = 0; jp < 8; jp++) ldmatrix_x4(xv[jp], (xr ^ ((jp & 3) << 5)) + (jp >> 2) * UNIT);
          signal_async(bars + 8u * B_RDONE, lane0);
          if (L > 0) {
            uint32_t lsb;
            asm volatile("ld.shared.u8 %0, [%1];" : "=r"(lsb) : "r"(base + OFF_LSB + ch * 32 + wwarp * 8 + g) : "memory");
#pragma unroll
            for (int k = 0; k < 4; k++) xv[(k >> 1) * 4][k & 1] = set_tag(xv[(k >> 1) * 4][k & 1], c == 0, lsb >> k);
          }
        }
        uint32_t tmx = L < 3 && (toff & 0x180u) == 0u, xt = x_tag(L + 1);
        uint32_t xrow = base + ((st + (pre ? 3 : 2)) & 3) * 5 * UNIT + (warp & 3) * 2048 + (toff & 0x7e0u) + ((toff ^ (toff >> 7)) & 0x10u);
        asm volatile("" : "+r"(tmx), "+r"(xt), "+r"(xrow));
        uint64_t d0 = desc_lo((base >> 4) + st * 5 * U4) + P.zero;
        if (inst < 7 || SP7 == 16) mbar_wait_lazy<TLAZY>(bars + 8u * (B_TURN + ch), (turn_par(2) >> inst) & 1u);
        mbar_wait(bars + 8u * B_WF, 0);
        GTL(6 + L * 8);
        uint32_t s1 = 0;
#pragma unroll 1
        for (int m = 0; m < 4; m++) {
          const uint32_t s0 = base + st * 5 * UNIT, fb = bars + 8u * (B_WF + 4 * (m & 1));
          s1 = base + ((st + 1) & 3) * 5 * UNIT;
          const uint64_t d1 = desc_lo(s1 >> 4) + P.zero;
          const uint64_t d2 = desc_lo((pre ? slots + m * 2 * UNIT : base + ((st + 2) & 3) * 5 * UNIT) >> 4) + P.zero;
          st = (st + (pre ? 2 : 3)) & 3;
#pragma unroll
          for (int i = 0; i < 4; i++) {
            const uint64_t da = (i == 0 ? d0 : d1) + (LA + (i == 2 ? 1 : (i == 3 ? 4 : 0)) * U4);
            const uint64_t db = (i < 2 ? d0 : (i == 2 ? d1 : d2)) + (LB + (i == 0 ? 1 : (i == 1 ? 3 : (i == 2 ? 2 : 0))) * U4);
            if (i == 3 && (m == 0 || m == 3) && pre) mbar_wait(bars + 8u * (m ? B_PRE2 : B_PRE), __popc(PREMASK & ((1u << inst) - 1u)) & 1);
            if (i == (WTURN & 3) && m == 3 && lane0 && (sp < 16 || inst == 6)) mbar_arrive(bars + 8u * (B_TURN + (ch ^ 1)));
            wgmma_fence();
#pragma unroll
            for (int k16 = 0; k16 < 4; k16++) wgmma_n128_ss_ta0_tb1(acc, da + 2 * k16, db + 128 * k16, 1);
            wgmma_commit();
            if (i == 2) d0 = desc_lo((base >> 4) + st * 5 * U4) + P.zero;
            tbad |= lds32((i == 0 ? s0 : s1) + (i == 2 ? 1 : (i == 3 ? 4 : 0)) * UNIT + toff) ^ o_tag(L);
            const uint32_t fn = i < 3 ? fb + 8u * (i + 1) : fb ^ 96u;
            const uint32_t pn = i < 3 ? m >> 1 : m > 0;
            const bool ok = mbar_test(fn, pn) || (i == 3 && m == 3);
            wgmma_wait<1>();
            if (lane0 && (i > 0 || m > 0)) mbar_arrive((i > 0 ? fb + 8u * (i - 1) : (fb ^ 96u) + 24u) + 8u * B_E);
            if (!ok) mbar_wait(fn, pn);
          }
        }
        const bool redo = named_bar_or(1 + ch, 128, tbad & 1u);
        if (redo) {
          wgmma_wait<0>();
          const uint32_t sa = s1 + 4 * UNIT, sb = s1 + 2 * UNIT;
          const uint32_t rb = bars + 8u * (B_REDO + ch);
          if ((fresh_tid() & 127) == 0) {
            mbar_init(rb, 1);
            fence_barrier_init();
          }
          uint32_t rpar = 0;
#pragma unroll 1
          for (int kt = 0, tries = 0; kt < 16;) {
            fence_proxy_async_smem();
            named_bar_sync(1 + ch, 128);
            if ((warp & 3) == 0 && elect_one()) {
                mbar_expect_tx(rb, 3 * UNIT);
              tma_load_2d(sa, &P.o, rb, kt * 64, ch * 1024 + rt * 64);
              tma_load_3d(sb, &P.wo3[L & 1], rb, ct * 128, kt * 64);
            }
            mbar_wait(rb, rpar);
            rpar ^= 1u;
            if (named_bar_or(1 + ch, 128, (lds32(sa + toff) ^ o_tag(L)) & 1u) && ++tries < 4096) continue;
            wgmma_fence();
#pragma unroll
            for (int k16 = 0; k16 < 4; k16++)
              wgmma_n128_ss_ta0_tb1(acc, make_desc(sa + k16 * 32, 16), make_desc(sb + k16 * 2048, UNIT), kt | k16);
            wgmma_commit();
            wgmma_wait<0>();
            kt++;
          }
        }
        wgmma_wait<0>();
        reg_fence<64>(acc);
        if (lane0) mbar_arrive(bars + 8u * (B_WF + B_E + 7));
        GTL(7 + L * 8);
#pragma unroll
        for (int jp = 0; jp < 8; jp++) {
#pragma unroll
          for (int q = 0; q < 4; q++) xv[jp][q] = add_bf16x2(xv[jp][q], pack_bf16x2(acc[8 * jp + 2 * q], acc[8 * jp + 2 * q + 1]));
          const bool tg = (jp & 3) == 0;
          stmatrix_x4((xrow ^ ((jp & 3) << 5)) + (jp >> 2) * UNIT,
                      tg ? set_tag(xv[jp][0], tmx, xt) : xv[jp][0], tg ? set_tag(xv[jp][1], tmx, xt) : xv[jp][1], xv[jp][2], xv[jp][3]);
          if ((jp & 3) == 3) signal_async(bars + 8u * (B_XS + (jp >> 2)), lane0);
        }
        if (L < 3) {
          PHASE_IDS_W
          const int grow = ch * 1024 + rt * 64;
          const unsigned ep1 = lds32(base + OFF_EPOCH);
          if (c == 0)
            asm volatile("st.shared.u8 [%0], %1;" ::"r"(base + OFF_LSB + ch * 32 + wwarp * 8 + g),
                         "r"((xv[0][0] & 1u) | ((xv[0][1] & 1u) << 1) | ((xv[4][0] & 1u) << 2) | ((xv[4][1] & 1u) << 3)) : "memory");
          float s1[2] = {0.f, 0.f}, s2[2] = {0.f, 0.f};
#pragma unroll
          for (int jp = 0; jp < 8; jp++)
#pragma unroll
            for (int q = 0; q < 4; q++) {
              const float x0 = bf_lo(xv[jp][q]), x1 = bf_hi(xv[jp][q]);
              s1[q & 1] += x0 + x1;
              s2[q & 1] = fmaf(x0, x0, fmaf(x1, x1, s2[q & 1]));
            }
#pragma unroll
          for (int r = 0; r < 2; r++) {
            s1[r] += __shfl_xor_sync(0xffffffffu, s1[r], 1);
            s2[r] += __shfl_xor_sync(0xffffffffu, s2[r], 1);
            s1[r] += __shfl_xor_sync(0xffffffffu, s1[r], 2);
            s2[r] += __shfl_xor_sync(0xffffffffu, s2[r], 2);
            if (c == 0) st_rec(&g_stats[L + 1][ct][grow + wwarp * 16 + g + 8 * r], s1[r], s2[r], 0.f, ep1);
          }
        }
        GTL(8 + L * 8);
      }
    }
    if (threadIdx.x == 128) atomicAdd(g_done, 1u);
  }
}

typedef CUresult (*PFN_tmEncode)(CUtensorMap*, CUtensorMapDataType, cuuint32_t, void*, const cuuint64_t*,
                                 const cuuint64_t*, const cuuint32_t*, const cuuint32_t*, CUtensorMapInterleave,
                                 CUtensorMapSwizzle, CUtensorMapL2promotion, CUtensorMapFloatOOBfill);

PFN_tmEncode get_encode_fn() {
  static PFN_tmEncode fn = nullptr;
  if (!fn) {
    cudaDriverEntryPointQueryResult qr;
    void* p = nullptr;
    cudaGetDriverEntryPoint("cuTensorMapEncodeTiled", &p, cudaEnableDefault, &qr);
    fn = (PFN_tmEncode)p;
  }
  return fn;
}

CUtensorMap make_map(const void* ptr, int rows, int cols) {
  CUtensorMap m;
  cuuint64_t gdim[2] = {(cuuint64_t)cols, (cuuint64_t)rows};
  cuuint64_t gstr[1] = {(cuuint64_t)cols * 2};
  cuuint32_t box[2] = {64, 64};
  cuuint32_t estr[2] = {1, 1};
  get_encode_fn()(&m, CU_TENSOR_MAP_DATA_TYPE_BFLOAT16, 2, const_cast<void*>(ptr), gdim, gstr, box, estr,
                  CU_TENSOR_MAP_INTERLEAVE_NONE, CU_TENSOR_MAP_SWIZZLE_128B, CU_TENSOR_MAP_L2_PROMOTION_L2_128B,
                  CU_TENSOR_MAP_FLOAT_OOB_FILL_NONE);
  return m;
}

CUtensorMap make_map3(const void* ptr, int rows, int cols, int n, int step) {
  CUtensorMap m;
  cuuint64_t gdim[3] = {(cuuint64_t)(cols - (n - 1) * step), (cuuint64_t)rows, (cuuint64_t)n};
  cuuint64_t gstr[2] = {(cuuint64_t)cols * 2, (cuuint64_t)step * 2};
  cuuint32_t box[3] = {64, 64, (cuuint32_t)n};
  cuuint32_t estr[3] = {1, 1, 1};
  get_encode_fn()(&m, CU_TENSOR_MAP_DATA_TYPE_BFLOAT16, 3, const_cast<void*>(ptr), gdim, gstr, box, estr,
                  CU_TENSOR_MAP_INTERLEAVE_NONE, CU_TENSOR_MAP_SWIZZLE_128B, CU_TENSOR_MAP_L2_PROMOTION_L2_128B,
                  CU_TENSOR_MAP_FLOAT_OOB_FILL_NONE);
  return m;
}

CUtensorMap make_map_q(const void* ptr, int sw, int sr) {
  CUtensorMap m;
  cuuint64_t gdim[5] = {DM, 8, 2, 4, S_LEN / 64};
  cuuint64_t gstr[4] = {DM * 2, (cuuint64_t)sr * DM * 2, (cuuint64_t)sw * DM * 2, 64 * DM * 2};
  cuuint32_t box[5] = {64, 8, 2, 4, 2};
  cuuint32_t estr[5] = {1, 1, 1, 1, 1};
  get_encode_fn()(&m, CU_TENSOR_MAP_DATA_TYPE_BFLOAT16, 5, const_cast<void*>(ptr), gdim, gstr, box, estr,
                  CU_TENSOR_MAP_INTERLEAVE_NONE, CU_TENSOR_MAP_SWIZZLE_128B, CU_TENSOR_MAP_L2_PROMOTION_L2_128B,
                  CU_TENSOR_MAP_FLOAT_OOB_FILL_NONE);
  return m;
}

}

extern "C" void kernel_launch(void* const* d_in, const int* in_sizes, int n_in, void* d_out, int out_size) {
  (void)in_sizes; (void)n_in; (void)out_size;
  void *p_o, *p_x;
  cudaGetSymbolAddress(&p_o, g_o);
  cudaGetSymbolAddress(&p_x, g_x);
  static bool attr_done = false;
  if (!attr_done) {
    cudaFuncSetAttribute(fused_kernel, cudaFuncAttributeMaxDynamicSharedMemorySize, SMEM_BYTES);
    attr_done = true;
  }
  Params P;
  P.in_x = (const __nv_bfloat16*)d_in[0];
  P.wqkv_p[0] = (const __nv_bfloat16*)d_in[1];
  P.wo_p[0] = (const __nv_bfloat16*)d_in[2];
  P.wqkv_p[1] = (const __nv_bfloat16*)d_in[4];
  P.wo_p[1] = (const __nv_bfloat16*)d_in[5];
  P.out = (__nv_bfloat16*)d_out;
  P.zero = 0;
  for (int L = 0; L < 5; L++) {
    const void* px = L == 0 ? (const void*)P.in_x : (L == 4 ? d_out : p_x);
    P.x[L] = make_map(px, S_LEN, DM);
    if (L < 4) P.xq[L] = (L & 1) ? make_map_q(px, 16, 8) : make_map_q(px, 8, 32);
  }
  P.o = make_map(p_o, S_LEN, DM);
  for (int t = 0; t < 2; t++) {
    P.wqkv[t] = make_map(P.wqkv_p[t], DM, NQKV);
    P.wqkv3[t] = make_map3(P.wqkv_p[t], DM, NQKV, 3, 1024);
    P.wo3[t] = make_map3(P.wo_p[t], DM, DM, 2, 64);
  }
  fused_kernel<<<NCTA, 512, SMEM_BYTES>>>(P);
}
```

```cpp
#include <cuda_runtime.h>
#include <cuda_bf16.h>
#include <cuda.h>
#include <stdint.h>

namespace {

constexpr int S_LEN = 2048;
constexpr int DM = 1024;
constexpr int NQKV = 3072;
constexpr int NCTA = 128;

__device__ __align__(1024) uint8_t g_kvA[16][16][2][16384];
__device__ __align__(1024) uint8_t g_kvB[16][16][4096];
__device__ __align__(1024) uint8_t g_zero[16384];
__device__ __align__(1024) __nv_bfloat16 g_o[S_LEN * DM];
__device__ __align__(1024) __nv_bfloat16 g_x[S_LEN * DM];
__device__ __align__(1024) float4 g_stats[8][S_LEN];
__device__ __align__(1024) float4 g_cs[2][16][8][64];
__device__ __align__(128) unsigned g_fx[16][16][4];
__device__ __align__(128) unsigned g_fo[32][16][4];
__device__ __align__(128) unsigned g_fk[16][16][4];
__device__ __align__(128) unsigned g_done[32];

constexpr uint32_t SBASE = 1024;
constexpr int UNIT = 8192;
constexpr int NUNITS = 20;
constexpr int OFF_SLOT = NUNITS * UNIT;
constexpr int OFF_BAR = OFF_SLOT + 4 * 16384;
constexpr int OFF_EPOCH = OFF_BAR + 424;
constexpr int OFF_LSB = OFF_BAR + 432;
constexpr int OFF_CS = OFF_BAR + 496;
constexpr int OFF_RS = OFF_CS + 1536;
constexpr int OFF_ONE = OFF_RS + 1024;
constexpr int SMEM_BYTES = OFF_ONE + 16;
constexpr int B_QF = 0, B_WF = 4, B_RF = 12, B_E = 13, B_PREP = 26, B_LOC = 28, B_HALO = 29, B_REL = 33, B_OS0 = 36,
              B_TURN = 37, B_XS = 39, B_CS = 41, B_CSD = 42, B_GO = 43, B_PRE = 44, B_HV = 45, B_REDO = 46,
              B_RDONE = 48, B_PRE2 = 49, B_HL = 50, B_KV = 52, B_OS1 = B_GO;
static_assert(SMEM_BYTES <= 232448, "shared memory");

__device__ __forceinline__ uint32_t smem_u32(const void* p) { return (uint32_t)__cvta_generic_to_shared(p); }

__device__ __forceinline__ void mbar_init(uint32_t bar, uint32_t cnt) {
  asm volatile("mbarrier.init.shared::cta.b64 [%0], %1;" ::"r"(bar), "r"(cnt));
}
__device__ __forceinline__ void mbar_expect_tx(uint32_t bar, uint32_t bytes) {
  asm volatile("mbarrier.arrive.expect_tx.shared::cta.b64 _, [%0], %1;" ::"r"(bar), "r"(bytes) : "memory");
}
__device__ __forceinline__ void mbar_arrive(uint32_t bar) {
  asm volatile("mbarrier.arrive.shared::cta.b64 _, [%0];" ::"r"(bar) : "memory");
}
__device__ __forceinline__ bool mbar_try_wait(uint32_t bar, uint32_t parity) {
  uint32_t ok;
  asm volatile(
      "{\n.reg .pred p;\nmbarrier.try_wait.parity.shared::cta.b64 p, [%1], %2;\nselp.b32 %0, 1, 0, p;\n}\n"
      : "=r"(ok)
      : "r"(bar), "r"(parity)
      : "memory");
  return ok != 0;
}
__device__ __forceinline__ bool mbar_try_wait_long(uint32_t bar, uint32_t parity) {
  uint32_t ok;
  asm volatile(
      "{\n.reg .pred p;\nmbarrier.try_wait.parity.shared::cta.b64 p, [%1], %2, %3;\nselp.b32 %0, 1, 0, p;\n}\n"
      : "=r"(ok)
      : "r"(bar), "r"(parity), "n"(20000)
      : "memory");
  return ok != 0;
}
__device__ __forceinline__ bool mbar_test(uint32_t bar, uint32_t parity) {
  uint32_t ok;
  asm volatile(
      "{\n.reg .pred p;\nmbarrier.test_wait.parity.shared::cta.b64 p, [%1], %2;\nselp.b32 %0, 1, 0, p;\n}\n"
      : "=r"(ok)
      : "r"(bar), "r"(parity)
      : "memory");
  return ok != 0;
}
__device__ __forceinline__ void mbar_wait(uint32_t bar, uint32_t parity) {
#pragma unroll 1
  for (uint32_t it = 0; it < (1u << 18); ++it) {
    if (mbar_try_wait(bar, parity)) return;
  }
}
__device__ __forceinline__ void mbar_pace(uint32_t bar, uint32_t parity) {
#pragma unroll 1
  for (uint32_t it = 0; it < 24; ++it) {
    if (mbar_try_wait(bar, parity)) return;
  }
}
template <int NS>
__device__ __forceinline__ void mbar_wait_lazy(uint32_t bar, uint32_t parity) {
#pragma unroll 1
  for (uint32_t it = 0; it < (1u << 18); ++it) {
    if (mbar_try_wait(bar, parity)) return;
    __nanosleep(NS);
  }
}
__device__ __forceinline__ bool elect_one() {
  uint32_t ok;
  asm volatile("{\n.reg .pred p;\nelect.sync _|p, 0xffffffff;\nselp.b32 %0, 1, 0, p;\n}\n" : "=r"(ok));
  return ok != 0;
}
__device__ __forceinline__ void fence_barrier_init() { asm volatile("fence.mbarrier_init.release.cluster;" ::: "memory"); }
__device__ __forceinline__ void fence_proxy_async_smem() { asm volatile("fence.proxy.async.shared::cta;" ::: "memory"); }

__device__ __forceinline__ void signal_async(uint32_t bar, bool lane0) {
  fence_proxy_async_smem();
  __syncwarp();
  asm volatile("{\n.reg .pred p;\nsetp.ne.b32 p, %1, 0;\n@p mbarrier.arrive.shared::cta.b64 _, [%0];\n}\n" ::"r"(bar), "r"((int)lane0) : "memory");
}
template <class T>
__device__ __forceinline__ void pin64(T*& p) { asm volatile("" : "+l"(p)); }

__device__ __forceinline__ void tma_load_2d(uint32_t dst, const CUtensorMap* map, uint32_t bar, int c0, int c1) {
  asm volatile(
      "cp.async.bulk.tensor.2d.shared::cluster.global.mbarrier::complete_tx::bytes [%0], [%1, {%3, %4}], [%2];" ::"r"(dst),
      "l"(map), "r"(bar), "r"(c0), "r"(c1)
      : "memory");
}
__device__ __forceinline__ void tma_load_3d(uint32_t dst, const CUtensorMap* map, uint32_t bar, int c0, int c1) {
  asm volatile(
      "cp.async.bulk.tensor.3d.shared::cluster.global.mbarrier::complete_tx::bytes [%0], [%1, {%3, %4, %5}], [%2];" ::"r"(dst),
      "l"(map), "r"(bar), "r"(c0), "r"(c1), "r"(0)
      : "memory");
}
__device__ __forceinline__ void tma_load_5d(uint32_t dst, const CUtensorMap* map, uint32_t bar, int c0, int c4) {
  asm volatile(
      "cp.async.bulk.tensor.5d.shared::cluster.global.mbarrier::complete_tx::bytes [%0], [%1, {%3, %5, %5, %5, %4}], [%2];" ::"r"(dst),
      "l"(map), "r"(bar), "r"(c0), "r"(c4), "r"(0)
      : "memory");
}
__device__ __forceinline__ void bulk_load(uint32_t dst, const void* src, uint32_t bytes, uint32_t bar) {
  asm volatile("cp.async.bulk.shared::cluster.global.mbarrier::complete_tx::bytes [%0], [%1], %2, [%3];" ::"r"(dst),
               "l"(src), "r"(bytes), "r"(bar)
               : "memory");
}
__device__ __forceinline__ void bulk_store(void* dst, uint32_t src, uint32_t bytes) {
  asm volatile("cp.async.bulk.global.shared::cta.bulk_group [%0], [%1], %2;" ::"l"(dst), "r"(src), "r"(bytes) : "memory");
}
__device__ __forceinline__ void tma_store_2d(const CUtensorMap* map, uint32_t src, int c0, int c1) {
  asm volatile("cp.async.bulk.tensor.2d.global.shared::cta.bulk_group [%0, {%2, %3}], [%1];" ::"l"(map), "r"(src),
               "r"(c0), "r"(c1)
               : "memory");
}
__device__ __forceinline__ void bulk_announce(unsigned* p) {
  asm volatile("cp.reduce.async.bulk.global.shared::cta.bulk_group.add.u32 [%0], [%1], 16;" ::"l"(p), "r"(SBASE + OFF_ONE) : "memory");
}
__device__ __forceinline__ void bulk_commit() { asm volatile("cp.async.bulk.commit_group;" ::: "memory"); }
__device__ __forceinline__ void bulk_wait_read0() { asm volatile("cp.async.bulk.wait_group.read 0;" ::: "memory"); }
__device__ __forceinline__ void bulk_wait0() { asm volatile("cp.async.bulk.wait_group 0;" ::: "memory"); }
__device__ __forceinline__ void named_bar_sync(int id, int nthreads) {
  asm volatile("bar.sync %0, %1;" ::"r"(id), "r"(nthreads) : "memory");
}
__device__ __forceinline__ void named_bar_arrive(int id, int nthreads) {
  asm volatile("bar.arrive %0, %1;" ::"r"(id), "r"(nthreads) : "memory");
}

__device__ __forceinline__ bool named_bar_or(int id, int nthreads, bool v) {
  uint32_t r;
  asm volatile("{\n.reg .pred p, q;\nsetp.ne.b32 q, %3, 0;\nbar.red.or.pred p, %1, %2, q;\nselp.b32 %0, 1, 0, p;\n}\n"
               : "=r"(r) : "r"(id), "r"(nthreads), "r"((int)v) : "memory");
  return __any_sync(0xffffffffu, r != 0);
}

__device__ __forceinline__ void wgmma_fence() { asm volatile("wgmma.fence.sync.aligned;\n" ::: "memory"); }
__device__ __forceinline__ void wgmma_commit() { asm volatile("wgmma.commit_group.sync.aligned;\n" ::: "memory"); }
template <int N>
__device__ __forceinline__ void wgmma_wait() {
  asm volatile("wgmma.wait_group.sync.aligned %0;\n" ::"n"(N) : "memory");
}
template <int R>
__device__ __forceinline__ void setmaxnreg_inc() { asm volatile("setmaxnreg.inc.sync.aligned.u32 %0;\n" ::"n"(R)); }
template <int R>
__device__ __forceinline__ void setmaxnreg_dec() { asm volatile("setmaxnreg.dec.sync.aligned.u32 %0;\n" ::"n"(R)); }
template <int N>
__device__ __forceinline__ void reg_fence(float* r) {
#pragma unroll
  for (int i = 0; i < N; i++) asm volatile("" : "+f"(r[i])::"memory");
}

template <int N>
__device__ __forceinline__ void reg_define(float* r) {
#pragma unroll
  for (int i = 0; i < N; i++) r[i] = 0.f;
}

__device__ __forceinline__ uint64_t desc_lo(uint32_t lo) {
  uint64_t d;
  asm("mov.b64 %0, {%1, %2};" : "=l"(d) : "r"(lo), "r"(0x40000040u));
  return d;
}
__device__ __forceinline__ uint64_t make_desc(uint32_t addr, uint32_t lbo_bytes) {
  return desc_lo((addr >> 4) + ((lbo_bytes >> 4) << 16));
}

__device__ __forceinline__ void wgmma_n192_ss_ta0_tb1(float* d, uint64_t descA, uint64_t descB, int scaleD) {
  asm volatile("{\n.reg .pred p;\nsetp.ne.b32 p, %98, 0;\n"
    "wgmma.mma_async.sync.aligned.m64n192k16.f32.bf16.bf16 {%0, %1, %2, %3, %4, %5, %6, %7, %8, %9, %10, %11, %12, %13, %14, %15, %16, %17, %18, %19, %20, %21, %22, %23, %24, %25, %26, %27, %28, %29, %30, %31, %32, %33, %34, %35, %36, %37, %38, %39, %40, %41, %42, %43, %44, %45, %46, %47, %48, %49, %50, %51, %52, %53, %54, %55, %56, %57, %58, %59, %60, %61, %62, %63, %64, %65, %66, %67, %68, %69, %70, %71, %72, %73, %74, %75, %76, %77, %78, %79, %80, %81, %82, %83, %84, %85, %86, %87, %88, %89, %90, %91, %92, %93, %94, %95}, %96, %97, p, 1, 1, 0, 1;\n}\n"
    : "+f"(d[0]), "+f"(d[1]), "+f"(d[2]), "+f"(d[3]), "+f"(d[4]), "+f"(d[5]), "+f"(d[6]), "+f"(d[7]), "+f"(d[8]), "+f"(d[9]), "+f"(d[10]), "+f"(d[11]), "+f"(d[12]), "+f"(d[13]), "+f"(d[14]), "+f"(d[15]), "+f"(d[16]), "+f"(d[17]), "+f"(d[18]), "+f"(d[19]), "+f"(d[20]), "+f"(d[21]), "+f"(d[22]), "+f"(d[23]), "+f"(d[24]), "+f"(d[25]), "+f"(d[26]), "+f"(d[27]), "+f"(d[28]), "+f"(d[29]), "+f"(d[30]), "+f"(d[31]), "+f"(d[32]), "+f"(d[33]), "+f"(d[34]), "+f"(d[35]), "+f"(d[36]), "+f"(d[37]), "+f"(d[38]), "+f"(d[39]), "+f"(d[40]), "+f"(d[41]), "+f"(d[42]), "+f"(d[43]), "+f"(d[44]), "+f"(d[45]), "+f"(d[46]), "+f"(d[47]), "+f"(d[48]), "+f"(d[49]), "+f"(d[50]), "+f"(d[51]), "+f"(d[52]), "+f"(d[53]), "+f"(d[54]), "+f"(d[55]), "+f"(d[56]), "+f"(d[57]), "+f"(d[58]), "+f"(d[59]), "+f"(d[60]), "+f"(d[61]), "+f"(d[62]), "+f"(d[63]), "+f"(d[64]), "+f"(d[65]), "+f"(d[66]), "+f"(d[67]), "+f"(d[68]), "+f"(d[69]), "+f"(d[70]), "+f"(d[71]), "+f"(d[72]), "+f"(d[73]), "+f"(d[74]), "+f"(d[75]), "+f"(d[76]), "+f"(d[77]), "+f"(d[78]), "+f"(d[79]), "+f"(d[80]), "+f"(d[81]), "+f"(d[82]), "+f"(d[83]), "+f"(d[84]), "+f"(d[85]), "+f"(d[86]), "+f"(d[87]), "+f"(d[88]), "+f"(d[89]), "+f"(d[90]), "+f"(d[91]), "+f"(d[92]), "+f"(d[93]), "+f"(d[94]), "+f"(d[95])
    : "l"(descA), "l"(descB), "r"(scaleD));
}

__device__ __forceinline__ void wgmma_n128_ss_ta0_tb1(float* d, uint64_t descA, uint64_t descB, int scaleD) {
  asm volatile("{\n.reg .pred p;\nsetp.ne.b32 p, %66, 0;\n"
    "wgmma.mma_async.sync.aligned.m64n128k16.f32.bf16.bf16 {%0, %1, %2, %3, %4, %5, %6, %7, %8, %9, %10, %11, %12, %13, %14, %15, %16, %17, %18, %19, %20, %21, %22, %23, %24, %25, %26, %27, %28, %29, %30, %31, %32, %33, %34, %35, %36, %37, %38, %39, %40, %41, %42, %43, %44, %45, %46, %47, %48, %49, %50, %51, %52, %53, %54, %55, %56, %57, %58, %59, %60, %61, %62, %63}, %64, %65, p, 1, 1, 0, 1;\n}\n"
    : "+f"(d[0]), "+f"(d[1]), "+f"(d[2]), "+f"(d[3]), "+f"(d[4]), "+f"(d[5]), "+f"(d[6]), "+f"(d[7]), "+f"(d[8]), "+f"(d[9]), "+f"(d[10]), "+f"(d[11]), "+f"(d[12]), "+f"(d[13]), "+f"(d[14]), "+f"(d[15]), "+f"(d[16]), "+f"(d[17]), "+f"(d[18]), "+f"(d[19]), "+f"(d[20]), "+f"(d[21]), "+f"(d[22]), "+f"(d[23]), "+f"(d[24]), "+f"(d[25]), "+f"(d[26]), "+f"(d[27]), "+f"(d[28]), "+f"(d[29]), "+f"(d[30]), "+f"(d[31]), "+f"(d[32]), "+f"(d[33]), "+f"(d[34]), "+f"(d[35]), "+f"(d[36]), "+f"(d[37]), "+f"(d[38]), "+f"(d[39]), "+f"(d[40]), "+f"(d[41]), "+f"(d[42]), "+f"(d[43]), "+f"(d[44]), "+f"(d[45]), "+f"(d[46]), "+f"(d[47]), "+f"(d[48]), "+f"(d[49]), "+f"(d[50]), "+f"(d[51]), "+f"(d[52]), "+f"(d[53]), "+f"(d[54]), "+f"(d[55]), "+f"(d[56]), "+f"(d[57]), "+f"(d[58]), "+f"(d[59]), "+f"(d[60]), "+f"(d[61]), "+f"(d[62]), "+f"(d[63])
    : "l"(descA), "l"(descB), "r"(scaleD));
}

__device__ __forceinline__ void wgmma_n192_ssz_ta0_tb1(float* d, uint64_t descA, uint64_t descB) {
  asm volatile("{\n.reg .pred p;\nsetp.ne.b32 p, 0, 0;\n"
    "wgmma.mma_async.sync.aligned.m64n192k16.f32.bf16.bf16 {%0, %1, %2, %3, %4, %5, %6, %7, %8, %9, %10, %11, %12, %13, %14, %15, %16, %17, %18, %19, %20, %21, %22, %23, %24, %25, %26, %27, %28, %29, %30, %31, %32, %33, %34, %35, %36, %37, %38, %39, %40, %41, %42, %43, %44, %45, %46, %47, %48, %49, %50, %51, %52, %53, %54, %55, %56, %57, %58, %59, %60, %61, %62, %63, %64, %65, %66, %67, %68, %69, %70, %71, %72, %73, %74, %75, %76, %77, %78, %79, %80, %81, %82, %83, %84, %85, %86, %87, %88, %89, %90, %91, %92, %93, %94, %95}, %96, %97, p, 1, 1, 0, 1;\n}\n"
    : "=f"(d[0]), "=f"(d[1]), "=f"(d[2]), "=f"(d[3]), "=f"(d[4]), "=f"(d[5]), "=f"(d[6]), "=f"(d[7]), "=f"(d[8]), "=f"(d[9]), "=f"(d[10]), "=f"(d[11]), "=f"(d[12]), "=f"(d[13]), "=f"(d[14]), "=f"(d[15]), "=f"(d[16]), "=f"(d[17]), "=f"(d[18]), "=f"(d[19]), "=f"(d[20]), "=f"(d[21]), "=f"(d[22]), "=f"(d[23]), "=f"(d[24]), "=f"(d[25]), "=f"(d[26]), "=f"(d[27]), "=f"(d[28]), "=f"(d[29]), "=f"(d[30]), "=f"(d[31]), "=f"(d[32]), "=f"(d[33]), "=f"(d[34]), "=f"(d[35]), "=f"(d[36]), "=f"(d[37]), "=f"(d[38]), "=f"(d[39]), "=f"(d[40]), "=f"(d[41]), "=f"(d[42]), "=f"(d[43]), "=f"(d[44]), "=f"(d[45]), "=f"(d[46]), "=f"(d[47]), "=f"(d[48]), "=f"(d[49]), "=f"(d[50]), "=f"(d[51]), "=f"(d[52]), "=f"(d[53]), "=f"(d[54]), "=f"(d[55]), "=f"(d[56]), "=f"(d[57]), "=f"(d[58]), "=f"(d[59]), "=f"(d[60]), "=f"(d[61]), "=f"(d[62]), "=f"(d[63]), "=f"(d[64]), "=f"(d[65]), "=f"(d[66]), "=f"(d[67]), "=f"(d[68]), "=f"(d[69]), "=f"(d[70]), "=f"(d[71]), "=f"(d[72]), "=f"(d[73]), "=f"(d[74]), "=f"(d[75]), "=f"(d[76]), "=f"(d[77]), "=f"(d[78]), "=f"(d[79]), "=f"(d[80]), "=f"(d[81]), "=f"(d[82]), "=f"(d[83]), "=f"(d[84]), "=f"(d[85]), "=f"(d[86]), "=f"(d[87]), "=f"(d[88]), "=f"(d[89]), "=f"(d[90]), "=f"(d[91]), "=f"(d[92]), "=f"(d[93]), "=f"(d[94]), "=f"(d[95])
    : "l"(descA), "l"(descB));
}

__device__ __forceinline__ void wgmma_n8_ss_ta1_tb0(float* d, uint64_t descA, uint64_t descB, int scaleD) {
  asm volatile("{\n.reg .pred p;\nsetp.ne.b32 p, %6, 0;\n"
    "wgmma.mma_async.sync.aligned.m64n8k16.f32.bf16.bf16 {%0, %1, %2, %3}, %4, %5, p, 1, 1, 1, 0;\n}\n"
    : "+f"(d[0]), "+f"(d[1]), "+f"(d[2]), "+f"(d[3])
    : "l"(descA), "l"(descB), "r"(scaleD));
}

__device__ __forceinline__ void wgmma_n8_ssz_ta1_tb0(float* d, uint64_t descA, uint64_t descB) {
  asm volatile("{\n.reg .pred p;\nsetp.ne.b32 p, 0, 0;\n"
    "wgmma.mma_async.sync.aligned.m64n8k16.f32.bf16.bf16 {%0, %1, %2, %3}, %4, %5, p, 1, 1, 1, 0;\n}\n"
    : "=f"(d[0]), "=f"(d[1]), "=f"(d[2]), "=f"(d[3])
    : "l"(descA), "l"(descB));
}

__device__ __forceinline__ void wgmma_n192_rs_tb1(float* d, const uint32_t* a, uint64_t descB, int scaleD) {
  asm volatile("{\n.reg .pred p;\nsetp.ne.b32 p, %101, 0;\n"
    "wgmma.mma_async.sync.aligned.m64n192k16.f32.bf16.bf16 {%0, %1, %2, %3, %4, %5, %6, %7, %8, %9, %10, %11, %12, %13, %14, %15, %16, %17, %18, %19, %20, %21, %22, %23, %24, %25, %26, %27, %28, %29, %30, %31, %32, %33, %34, %35, %36, %37, %38, %39, %40, %41, %42, %43, %44, %45, %46, %47, %48, %49, %50, %51, %52, %53, %54, %55, %56, %57, %58, %59, %60, %61, %62, %63, %64, %65, %66, %67, %68, %69, %70, %71, %72, %73, %74, %75, %76, %77, %78, %79, %80, %81, %82, %83, %84, %85, %86, %87, %88, %89, %90, %91, %92, %93, %94, %95}, {%96, %97, %98, %99}, %100, p, 1, 1, 1;\n}\n"
    : "+f"(d[0]), "+f"(d[1]), "+f"(d[2]), "+f"(d[3]), "+f"(d[4]), "+f"(d[5]), "+f"(d[6]), "+f"(d[7]), "+f"(d[8]), "+f"(d[9]), "+f"(d[10]), "+f"(d[11]), "+f"(d[12]), "+f"(d[13]), "+f"(d[14]), "+f"(d[15]), "+f"(d[16]), "+f"(d[17]), "+f"(d[18]), "+f"(d[19]), "+f"(d[20]), "+f"(d[21]), "+f"(d[22]), "+f"(d[23]), "+f"(d[24]), "+f"(d[25]), "+f"(d[26]), "+f"(d[27]), "+f"(d[28]), "+f"(d[29]), "+f"(d[30]), "+f"(d[31]), "+f"(d[32]), "+f"(d[33]), "+f"(d[34]), "+f"(d[35]), "+f"(d[36]), "+f"(d[37]), "+f"(d[38]), "+f"(d[39]), "+f"(d[40]), "+f"(d[41]), "+f"(d[42]), "+f"(d[43]), "+f"(d[44]), "+f"(d[45]), "+f"(d[46]), "+f"(d[47]), "+f"(d[48]), "+f"(d[49]), "+f"(d[50]), "+f"(d[51]), "+f"(d[52]), "+f"(d[53]), "+f"(d[54]), "+f"(d[55]), "+f"(d[56]), "+f"(d[57]), "+f"(d[58]), "+f"(d[59]), "+f"(d[60]), "+f"(d[61]), "+f"(d[62]), "+f"(d[63]), "+f"(d[64]), "+f"(d[65]), "+f"(d[66]), "+f"(d[67]), "+f"(d[68]), "+f"(d[69]), "+f"(d[70]), "+f"(d[71]), "+f"(d[72]), "+f"(d[73]), "+f"(d[74]), "+f"(d[75]), "+f"(d[76]), "+f"(d[77]), "+f"(d[78]), "+f"(d[79]), "+f"(d[80]), "+f"(d[81]), "+f"(d[82]), "+f"(d[83]), "+f"(d[84]), "+f"(d[85]), "+f"(d[86]), "+f"(d[87]), "+f"(d[88]), "+f"(d[89]), "+f"(d[90]), "+f"(d[91]), "+f"(d[92]), "+f"(d[93]), "+f"(d[94]), "+f"(d[95])
    : "r"(a[0]), "r"(a[1]), "r"(a[2]), "r"(a[3]), "l"(descB), "r"(scaleD));
}

__device__ __forceinline__ void wgmma_n80_rs_tb0(float* d, const uint32_t* a, uint64_t descB, int scaleD) {
  asm volatile("{\n.reg .pred p;\nsetp.ne.b32 p, %45, 0;\n"
    "wgmma.mma_async.sync.aligned.m64n80k16.f32.bf16.bf16 {%0, %1, %2, %3, %4, %5, %6, %7, %8, %9, %10, %11, %12, %13, %14, %15, %16, %17, %18, %19, %20, %21, %22, %23, %24, %25, %26, %27, %28, %29, %30, %31, %32, %33, %34, %35, %36, %37, %38, %39}, {%40, %41, %42, %43}, %44, p, 1, 1, 0;\n}\n"
    : "+f"(d[0]), "+f"(d[1]), "+f"(d[2]), "+f"(d[3]), "+f"(d[4]), "+f"(d[5]), "+f"(d[6]), "+f"(d[7]), "+f"(d[8]), "+f"(d[9]), "+f"(d[10]), "+f"(d[11]), "+f"(d[12]), "+f"(d[13]), "+f"(d[14]), "+f"(d[15]), "+f"(d[16]), "+f"(d[17]), "+f"(d[18]), "+f"(d[19]), "+f"(d[20]), "+f"(d[21]), "+f"(d[22]), "+f"(d[23]), "+f"(d[24]), "+f"(d[25]), "+f"(d[26]), "+f"(d[27]), "+f"(d[28]), "+f"(d[29]), "+f"(d[30]), "+f"(d[31]), "+f"(d[32]), "+f"(d[33]), "+f"(d[34]), "+f"(d[35]), "+f"(d[36]), "+f"(d[37]), "+f"(d[38]), "+f"(d[39])
    : "r"(a[0]), "r"(a[1]), "r"(a[2]), "r"(a[3]), "l"(descB), "r"(scaleD));
}

__device__ __forceinline__ void wgmma_n80_rsz_tb0(float* d, const uint32_t* a, uint64_t descB) {
  asm volatile("{\n.reg .pred p;\nsetp.ne.b32 p, 0, 0;\n"
    "wgmma.mma_async.sync.aligned.m64n80k16.f32.bf16.bf16 {%0, %1, %2, %3, %4, %5, %6, %7, %8, %9, %10, %11, %12, %13, %14, %15, %16, %17, %18, %19, %20, %21, %22, %23, %24, %25, %26, %27, %28, %29, %30, %31, %32, %33, %34, %35, %36, %37, %38, %39}, {%40, %41, %42, %43}, %44, p, 1, 1, 0;\n}\n"
    : "=f"(d[0]), "=f"(d[1]), "=f"(d[2]), "=f"(d[3]), "=f"(d[4]), "=f"(d[5]), "=f"(d[6]), "=f"(d[7]), "=f"(d[8]), "=f"(d[9]), "=f"(d[10]), "=f"(d[11]), "=f"(d[12]), "=f"(d[13]), "=f"(d[14]), "=f"(d[15]), "=f"(d[16]), "=f"(d[17]), "=f"(d[18]), "=f"(d[19]), "=f"(d[20]), "=f"(d[21]), "=f"(d[22]), "=f"(d[23]), "=f"(d[24]), "=f"(d[25]), "=f"(d[26]), "=f"(d[27]), "=f"(d[28]), "=f"(d[29]), "=f"(d[30]), "=f"(d[31]), "=f"(d[32]), "=f"(d[33]), "=f"(d[34]), "=f"(d[35]), "=f"(d[36]), "=f"(d[37]), "=f"(d[38]), "=f"(d[39])
    : "r"(a[0]), "r"(a[1]), "r"(a[2]), "r"(a[3]), "l"(descB));
}

__device__ __forceinline__ void wgmma_n32_rs_tb1(float* d, const uint32_t* a, uint64_t descB, int scaleD) {
  asm volatile("{\n.reg .pred p;\nsetp.ne.b32 p, %21, 0;\n"
    "wgmma.mma_async.sync.aligned.m64n32k16.f32.bf16.bf16 {%0, %1, %2, %3, %4, %5, %6, %7, %8, %9, %10, %11, %12, %13, %14, %15}, {%16, %17, %18, %19}, %20, p, 1, 1, 1;\n}\n"
    : "+f"(d[0]), "+f"(d[1]), "+f"(d[2]), "+f"(d[3]), "+f"(d[4]), "+f"(d[5]), "+f"(d[6]), "+f"(d[7]), "+f"(d[8]), "+f"(d[9]), "+f"(d[10]), "+f"(d[11]), "+f"(d[12]), "+f"(d[13]), "+f"(d[14]), "+f"(d[15])
    : "r"(a[0]), "r"(a[1]), "r"(a[2]), "r"(a[3]), "l"(descB), "r"(scaleD));
}

__device__ __forceinline__ void wgmma_n32_rsz_tb1(float* d, const uint32_t* a, uint64_t descB) {
  asm volatile("{\n.reg .pred p;\nsetp.ne.b32 p, 0, 0;\n"
    "wgmma.mma_async.sync.aligned.m64n32k16.f32.bf16.bf16 {%0, %1, %2, %3, %4, %5, %6, %7, %8, %9, %10, %11, %12, %13, %14, %15}, {%16, %17, %18, %19}, %20, p, 1, 1, 1;\n}\n"
    : "=f"(d[0]), "=f"(d[1]), "=f"(d[2]), "=f"(d[3]), "=f"(d[4]), "=f"(d[5]), "=f"(d[6]), "=f"(d[7]), "=f"(d[8]), "=f"(d[9]), "=f"(d[10]), "=f"(d[11]), "=f"(d[12]), "=f"(d[13]), "=f"(d[14]), "=f"(d[15])
    : "r"(a[0]), "r"(a[1]), "r"(a[2]), "r"(a[3]), "l"(descB));
}

__device__ __forceinline__ void wgmma_n32_rs_tb0(float* d, const uint32_t* a, uint64_t descB, int scaleD) {
  asm volatile("{\n.reg .pred p;\nsetp.ne.b32 p, %21, 0;\n"
    "wgmma.mma_async.sync.aligned.m64n32k16.f32.bf16.bf16 {%0, %1, %2, %3, %4, %5, %6, %7, %8, %9, %10, %11, %12, %13, %14, %15}, {%16, %17, %18, %19}, %20, p, 1, 1, 0;\n}\n"
    : "+f"(d[0]), "+f"(d[1]), "+f"(d[2]), "+f"(d[3]), "+f"(d[4]), "+f"(d[5]), "+f"(d[6]), "+f"(d[7]), "+f"(d[8]), "+f"(d[9]), "+f"(d[10]), "+f"(d[11]), "+f"(d[12]), "+f"(d[13]), "+f"(d[14]), "+f"(d[15])
    : "r"(a[0]), "r"(a[1]), "r"(a[2]), "r"(a[3]), "l"(descB), "r"(scaleD));
}

__device__ __forceinline__ void wgmma_n32_rsz_tb0(float* d, const uint32_t* a, uint64_t descB) {
  asm volatile("{\n.reg .pred p;\nsetp.ne.b32 p, 0, 0;\n"
    "wgmma.mma_async.sync.aligned.m64n32k16.f32.bf16.bf16 {%0, %1, %2, %3, %4, %5, %6, %7, %8, %9, %10, %11, %12, %13, %14, %15}, {%16, %17, %18, %19}, %20, p, 1, 1, 0;\n}\n"
    : "=f"(d[0]), "=f"(d[1]), "=f"(d[2]), "=f"(d[3]), "=f"(d[4]), "=f"(d[5]), "=f"(d[6]), "=f"(d[7]), "=f"(d[8]), "=f"(d[9]), "=f"(d[10]), "=f"(d[11]), "=f"(d[12]), "=f"(d[13]), "=f"(d[14]), "=f"(d[15])
    : "r"(a[0]), "r"(a[1]), "r"(a[2]), "r"(a[3]), "l"(descB));
}

__device__ __forceinline__ uint32_t pack_bf16x2(float lo, float hi) {
  uint32_t r;
  asm("cvt.rn.bf16x2.f32 %0, %1, %2;" : "=r"(r) : "f"(hi), "f"(lo));
  return r;
}
__device__ __forceinline__ float bf_lo(uint32_t p) { return __uint_as_float(p << 16); }
__device__ __forceinline__ float bf_hi(uint32_t p) { return __uint_as_float(p & 0xffff0000u); }
__device__ __forceinline__ float bf16_round(float v) { return __bfloat162float(__float2bfloat16_rn(v)); }
__device__ __forceinline__ float ex2_approx(float x) {
  float r;
  asm("ex2.approx.ftz.f32 %0, %1;" : "=f"(r) : "f"(x));
  return r;
}
__device__ __forceinline__ float rcp_fast(float x) {
  float r;
  asm("rcp.approx.ftz.f32 %0, %1;" : "=f"(r) : "f"(x));
  return r;
}
__device__ __forceinline__ void ldmatrix_x4(uint32_t (&r)[4], uint32_t addr) {
  asm volatile("ldmatrix.sync.aligned.m8n8.x4.shared.b16 {%0,%1,%2,%3}, [%4];"
               : "=r"(r[0]), "=r"(r[1]), "=r"(r[2]), "=r"(r[3])
               : "r"(addr)
               : "memory");
}
__device__ __forceinline__ void stmatrix_x4(uint32_t addr, uint32_t r0, uint32_t r1, uint32_t r2, uint32_t r3) {
  asm volatile("stmatrix.sync.aligned.m8n8.x4.shared.b16 [%0], {%1,%2,%3,%4};" ::"r"(addr), "r"(r0), "r"(r1), "r"(r2),
               "r"(r3));
}
__device__ __forceinline__ uint32_t add_bf16x2(uint32_t a, uint32_t b) {
  uint32_t r;
  asm("add.rn.bf16x2 %0, %1, %2;" : "=r"(r) : "r"(a), "r"(b));
  return r;
}
__device__ __forceinline__ uint4 lds128(uint32_t addr) {
  uint4 v;
  asm volatile("ld.shared.v4.b32 {%0,%1,%2,%3}, [%4];" : "=r"(v.x), "=r"(v.y), "=r"(v.z), "=r"(v.w) : "r"(addr) : "memory");
  return v;
}
__device__ __forceinline__ uint32_t lds32(uint32_t addr) {
  uint32_t v;
  asm volatile("ld.shared.b32 %0, [%1];" : "=r"(v) : "r"(addr) : "memory");
  return v;
}
__device__ __forceinline__ void sts32(uint32_t addr, uint32_t v) {
  asm volatile("st.shared.b32 [%0], %1;" ::"r"(addr), "r"(v) : "memory");
}

__device__ __forceinline__ unsigned ld_relaxed_u32(const void* p) {
  unsigned v;
  asm volatile("ld.relaxed.gpu.global.u32 %0, [%1];" : "=r"(v) : "l"(p) : "memory");
  return v;
}
__device__ __forceinline__ unsigned launch_epoch() { return (*(volatile unsigned*)g_done) / NCTA + 1u; }
__device__ __forceinline__ uint32_t set_tag(uint32_t w, uint32_t m, uint32_t tag) { return (w & ~m) | (tag & m); }
__device__ __forceinline__ uint32_t o_tag(int L) { return (L + 1) & 1; }
__device__ __forceinline__ uint32_t x_tag(int L) { return L & 1; }
__device__ __forceinline__ uint32_t kv_tag(int L) { return L < 2; }

__device__ __forceinline__ uint32_t peek_counts(const unsigned* f, unsigned target, int lane) {
  return __ballot_sync(0xffffffffu, (int)(ld_relaxed_u32(f + (lane & 15) * 4) - target) >= 0);
}
__device__ __forceinline__ void wait_count(const unsigned* f, unsigned target, int i, uint32_t& seen, int lane) {
  if ((seen >> i) & 1u) return;
#pragma unroll 1
  for (uint32_t it = 0; it < (1u << 17); ++it) {
    seen = peek_counts(f, target, lane);
    if ((seen >> i) & 1u) break;
  }
}
__device__ __forceinline__ float4 ld_rec(const float4* p) {
  float4 v;
  asm volatile("ld.relaxed.gpu.global.v4.f32 {%0,%1,%2,%3}, [%4];" : "=f"(v.x), "=f"(v.y), "=f"(v.z), "=f"(v.w) : "l"(p) : "memory");
  return v;
}
__device__ __forceinline__ void st_rec(float4* p, float a, float b, float c, unsigned tag) {
  asm volatile("st.relaxed.gpu.global.v4.f32 [%0], {%1,%2,%3,%4};" ::"l"(p), "f"(a), "f"(b), "f"(c), "f"(__uint_as_float(tag)) : "memory");
}
template <int N>
__device__ __forceinline__ float4 sum_recs(const float4* p, int stride, unsigned tag) {
  float4 s;
#pragma unroll 1
  for (uint32_t it = 0; it < (1u << 17); ++it) {
    float4 v[N];
#pragma unroll
    for (int t = 0; t < N; t++) v[t] = ld_rec(p + t * stride);
    bool ok = true;
    s = make_float4(0.f, 0.f, 0.f, 0.f);
#pragma unroll
    for (int t = 0; t < N; t++) {
      ok &= __float_as_uint(v[t].w) == tag;
      s.x += v[t].x;
      s.y += v[t].y;
      s.z += v[t].z;
    }
    if (ok) break;
    __nanosleep(200);
  }
  return s;
}

__device__ __forceinline__ int fresh_tid() {
  int t;
  asm volatile("mov.u32 %0, %%tid.x;" : "=r"(t));
  return t;
}
#define PHASE_IDS                                  \
  const int tid_ = fresh_tid();                    \
  const int lane = tid_ & 31, wwarp = __shfl_sync(0xffffffffu, (tid_ >> 5) & 3, 0), tid = tid_ & 127; \
  const int g = lane >> 2, c = lane & 3;           \
  (void)tid; (void)g; (void)c; (void)wwarp;

#define PHASE_IDS_W                                \
  const int lane = fresh_tid() & 31, wwarp = warp & 3; \
  const int g = lane >> 2, c = lane & 3;

#define GTL(i) do { } while (0)
#define TGET(v) do { } while (0)
#define TPUT(c, i, v) do { } while (0)

constexpr float SM_C = 0.17677669529663687f * 1.4426950408889634f;

__device__ __forceinline__ void stmatrix_x4_if(bool ok, uint32_t addr, uint32_t r0, uint32_t r1, uint32_t r2, uint32_t r3) {
  asm volatile("{\n.reg .pred p;\nsetp.ne.b32 p, %5, 0;\n@p stmatrix.sync.aligned.m8n8.x4.shared.b16 [%0], {%1,%2,%3,%4};\n}\n" ::"r"(addr),
               "r"(r0), "r"(r1), "r"(r2), "r"(r3), "r"((int)ok));
}

__device__ __forceinline__ void attn_a_slow(const uint8_t* __restrict__ kvimg, int L, int gb, int hp, uint32_t bad,
                                            int row0, int lane) {
  constexpr uint32_t sq = SBASE + OFF_SLOT + 3 * 16384;
#pragma unroll 1
  for (int j = 0; j < 8; j++) {
    const uint8_t* tp = kvimg + (size_t)(gb * 16 + hp) * 32768 + (j * 32 + lane) * 128 + ((lane & 7) << 4);
#pragma unroll 1
    for (uint32_t it = 0; it < (1u << 17); ++it)
      if (((ld_relaxed_u32(tp) ^ kv_tag(L)) & 1u) == 0u) break;
  }
  __syncwarp();
#pragma unroll 1
  for (int t = 0; t < 32; t++) {
    const int hh = t >> 4, row = row0 + (t & 7) + (t & 8) * 4;
    if (!((bad >> hh) & 1u)) continue;
    const int qpos = gb * 128 + row;
    const uint32_t qaddr = sq + row * 128;
    float mx = -INFINITY, sum = 0.f, acc = 0.f;
#pragma unroll 1
    for (int pass = 0; pass < 2; pass++) {
#pragma unroll 1
      for (int j = 0; j < 8; j++) {
        const int kp = qpos - (lane + 32 * j);
        const uint8_t* kr = kvimg + ((size_t)((kp >> 7) * 16 + hp) * 2 + ((kp >> 6) & 1)) * 16384 + (kp & 63) * 128;
        float d = -INFINITY;
        if (kp >= 0) {
          d = 0.f;
#pragma unroll 1
          for (int q = 0; q < 4; q++) {
            const uint4 kv = __ldcg(reinterpret_cast<const uint4*>(kr + (((hh * 4 + q) ^ (kp & 7)) << 4)));
            const uint4 qv = lds128(qaddr + (((hh * 4 + q) ^ (row & 7)) << 4));
            const uint32_t kw[4] = {kv.x, kv.y, kv.z, kv.w}, qw[4] = {qv.x, qv.y, qv.z, qv.w};
#pragma unroll
            for (int e = 0; e < 4; e++) d = fmaf(bf_lo(kw[e]), bf_lo(qw[e]), fmaf(bf_hi(kw[e]), bf_hi(qw[e]), d));
          }
        }
        if (pass == 0) {
          mx = fmaxf(mx, d);
        } else {
          const float ev = ex2_approx(d - mx);
          sum += ev;
          const float pv = bf16_round(ev);
#pragma unroll 1
          for (int kk = 0; kk < 32; kk++) {
            const float pk = __shfl_sync(0xffffffffu, pv, kk);
            const int k2 = qpos - (kk + 32 * j);
            if (k2 >= 0) {
              const uint8_t* vr = kvimg + ((size_t)((k2 >> 7) * 16 + hp) * 2 + ((k2 >> 6) & 1)) * 16384 + 8192 + (k2 & 63) * 128;
              const unsigned short vv =
                  __ldcg(reinterpret_cast<const unsigned short*>(vr + (((hh * 4 + (lane >> 3)) ^ (k2 & 7)) << 4) + (lane & 7) * 2));
              acc = fmaf(pk, __uint_as_float((uint32_t)vv << 16), acc);
            }
          }
        }
      }
      if (pass == 0) {
#pragma unroll
        for (int o = 16; o > 0; o >>= 1) mx = fmaxf(mx, __shfl_xor_sync(0xffffffffu, mx, o));
      }
    }
#pragma unroll
    for (int o = 16; o > 0; o >>= 1) sum += __shfl_xor_sync(0xffffffffu, sum, o);
    acc *= rcp_fast(sum);
    const float hi = __shfl_down_sync(0xffffffffu, acc, 1);
    __syncwarp();
    if ((lane & 1) == 0) sts32(qaddr + (((hh * 4 + (lane >> 3)) ^ (row & 7)) << 4) + (lane & 7) * 2,
                               set_tag(pack_bf16x2(acc, hi), hh == 0 && lane == 0, o_tag(L)));
    __syncwarp();
  }
}

template <int HH>
__device__ __forceinline__ void store_o(const float (&o)[16], const float (&inv)[2], uint32_t ra, uint32_t tag, bool ok) {
  const uint32_t m = HH == 0 && (fresh_tid() & 3) == 0;
#pragma unroll
  for (int jp = 0; jp < 2; jp++) {
    uint32_t w0 = pack_bf16x2(o[8 * jp] * inv[0], o[8 * jp + 1] * inv[0]);
    uint32_t w1 = pack_bf16x2(o[8 * jp + 2] * inv[1], o[8 * jp + 3] * inv[1]);
    if (HH == 0 && jp == 0) {
      w0 = set_tag(w0, m, tag);
      w1 = set_tag(w1, m, tag);
    }
    stmatrix_x4_if(ok, ra ^ ((HH * 4 + 2 * jp) << 4), w0, w1, pack_bf16x2(o[8 * jp + 4] * inv[0], o[8 * jp + 5] * inv[0]),
                   pack_bf16x2(o[8 * jp + 6] * inv[1], o[8 * jp + 7] * inv[1]));
  }
}
__device__ __forceinline__ int tile_row(bool B, int w, int r, int g) { return (B ? 16 * w + 8 * r : 8 * w + 32 * r) + g; }
__device__ __forceinline__ uint32_t q_row_addr(bool B, int R, int w, int lane) {
  return SBASE + OFF_SLOT + 3 * 16384 + R * 8192 + tile_row(B, w, (lane >> 3) & 1, lane & 7) * 128 + (((lane >> 4) ^ (lane & 7)) << 4);
}

struct AttnA {
  float s[2][16], o[2][16], l[2][2], sh[2][3];
  uint32_t p[2][4], t[2], me[4], ra, bad, zero;
};
#define ATS_(i) do { } while (0)
template <int V>
__device__ __forceinline__ void attn_sum(AttnA& a, int nv) {
  constexpr int hh = (V >> 1) & 1, kh = V & 1, i = V >> 2;
#pragma unroll
  for (int r = 0; r < 2; r++) {
    const uint32_t t1 = add_bf16x2(add_bf16x2(a.p[0][r], a.p[0][2 + r]), add_bf16x2(a.p[1][r], a.p[1][2 + r]));
    if (kh == 0) {
      a.t[r] = t1;
    } else {
      uint32_t tt = add_bf16x2(a.t[r], t1);
      if (i > 0) tt = i <= nv ? tt : 0u;
      const float v = bf_lo(tt) + bf_hi(tt);
      a.l[hh][r] = i == 0 ? v : a.l[hh][r] + v;
    }
  }
}
template <int HH>
__device__ __forceinline__ void attn_shfl(AttnA& a) {
#pragma unroll
  for (int r = 0; r < 2; r++)
#pragma unroll
    for (int j = 0; j < 3; j++) a.sh[r][j] = __shfl_xor_sync(0xffffffffu, a.l[HH][r], j + 1);
}
template <int HH>
__device__ __forceinline__ void attn_fin(AttnA& a) {
  bool bad = false;
  float inv[2];
#pragma unroll
  for (int r = 0; r < 2; r++) {
    const float v = (a.l[HH][r] + a.sh[r][0]) + (a.sh[r][1] + a.sh[r][2]);
    bad |= !(v <= 1.152921504606846976e18f && v >= 8.673617379884035e-19f);
    inv[r] = rcp_fast(v);
  }
  bad = __any_sync(0xffffffffu, bad);
  if (HH == 1) wgmma_wait<0>();
  reg_fence<16>(a.o[HH]);
  store_o<HH>(a.o[HH], inv, a.ra, o_tag(0), !bad);
  a.bad = (HH == 0 ? 0u : a.bad) | (bad ? 1u << HH : 0u);
}
__device__ __forceinline__ void attn_masks(AttnA& a, int wr) {
  const int lane = fresh_tid() & 31, d = (lane >> 2) - 2 * (lane & 3);
  const uint32_t tri = d >= 1 ? 0xffffffffu : (d == 0 ? 0xffffu : 0u);
#pragma unroll
  for (int t = 0; t < 4; t++) a.me[t] = wr > t ? 0xffffffffu : (wr == t ? tri : 0u);
}
template <int V, int K>
__device__ __forceinline__ uint32_t attn_exp(AttnA& a) {
  constexpr int i = V >> 2, kh = V & 1, r = K & 1;
  if ((i == 0 && kh > r) || (i == 4 && kh < r)) return 0u;
  const uint32_t w = pack_bf16x2(ex2_approx(a.s[V & 1][2 * K]), ex2_approx(a.s[V & 1][2 * K + 1]));
  if (i == 0 && kh == r) return w & a.me[K >> 1];
  if (i == 4 && kh == r) return w & ~a.me[K >> 1];
  return w;
}
template <int V>
__device__ __forceinline__ void attn_unit(AttnA& a, const uint32_t (&q)[2][2][4], uint64_t dcur, uint64_t dnext, int R, int wr, int nv,
                                          uint32_t hbar, uint32_t hpar, uint32_t rbar, bool rel) {
  constexpr int hh = (V >> 1) & 1, kh = V & 1, i = V >> 2;
  ATS_(V + 1);
  asm volatile("" : "+l"(dcur), "+l"(dnext));
  wgmma_wait<1>();
  reg_fence<16>(a.s[V & 1]);
  bool hok = true;
  if (V == 4) hbar = SBASE + OFF_BAR + 8u * (R ? B_LOC : B_HV);
  if (((V & 3) == 2 && V < 16) || V == 4) hok = mbar_test(hbar, hpar);
  const uint64_t d0 = ((V & 3) >= 2 ? dnext : dcur) + ((hh ^ 1) * 4 + kh * 256), d1 = ((V & 3) >= 2 ? dnext : dcur) + ((hh ^ 1) * 4 + kh * 256 + 2);
  const uint64_t d2 = dcur + (512 + hh * 4 + kh * 256), d3 = dcur + (640 + hh * 4 + kh * 256);
  if ((V & 3) == 1 && V > 4 && rel) mbar_arrive(rbar);
  if (V > 0) attn_sum<V - 1>(a, nv);
  if (V == 15) attn_masks(a, wr);
  if (V == 18) {
    attn_shfl<0>(a);
    a.ra = q_row_addr(false, R, wr, fresh_tid() & 31);
  }
  if (V == 19) attn_fin<0>(a);
  uint32_t p[2][4];
  p[0][0] = attn_exp<V, 0>(a);
  p[0][1] = attn_exp<V, 1>(a);
  p[0][2] = attn_exp<V, 2>(a);
  p[0][3] = attn_exp<V, 3>(a);
  p[1][0] = attn_exp<V, 4>(a);
  p[1][1] = attn_exp<V, 5>(a);
  p[1][2] = attn_exp<V, 6>(a);
  p[1][3] = attn_exp<V, 7>(a);
  if (V > 0) {
#pragma unroll
    for (int r = 0; r < 2; r++) p[1][r] ^= (kh ? a.t[r] : __float_as_uint(a.l[hh ^ 1][r])) & a.zero;
  }
#pragma unroll
  for (int k = 0; k < 8; k++) {
    asm volatile("" : "+r"(p[k >> 2][k & 3]));
    a.p[k >> 2][k & 3] = p[k >> 2][k & 3];
  }
  if (!hok) mbar_wait(hbar, hpar);
  wgmma_fence();
  if (V < 18) wgmma_n32_rsz_tb0(a.s[V & 1], q[hh ^ 1][0], d0);
  if (i == 0 && kh == 0) wgmma_n32_rsz_tb1(a.o[hh], a.p[0], d2);
  else wgmma_n32_rs_tb1(a.o[hh], a.p[0], d2, 1);
  if (V < 18) wgmma_n32_rs_tb0(a.s[V & 1], q[hh ^ 1][1], d1, 1);
  wgmma_n32_rs_tb1(a.o[hh], a.p[1], d3, 1);
  wgmma_commit();
}
template <int I>
__device__ __forceinline__ void attn_step(AttnA& a, const uint32_t (&q)[2][2][4], uint64_t dcur, uint64_t dnext, int R, int wr, int nv,
                                          uint32_t hbar, uint32_t hpar, uint32_t rbar, bool rel) {
  attn_unit<4 * I>(a, q, dcur, dnext, R, wr, nv, hbar, hpar, rbar, rel);
  attn_unit<4 * I + 1>(a, q, dcur, dnext, R, wr, nv, hbar, hpar, rbar, rel);
  attn_unit<4 * I + 2>(a, q, dcur, dnext, R, wr, nv, hbar, hpar, rbar, rel);
  attn_unit<4 * I + 3>(a, q, dcur, dnext, R, wr, nv, hbar, hpar, rbar, rel);
}

__device__ __forceinline__ void attention_a(const uint32_t (&q)[2][2][4], int R, int L, int gb, int hp, uint32_t par, int wr,
                                            uint32_t zero) {
  constexpr uint32_t bars = SBASE + OFF_BAR;
  constexpr uint32_t dslot = ((SBASE + OFF_SLOT) >> 4) + 0x10000u;
  auto next = [&](uint64_t d) { return desc_lo((uint32_t)d == dslot ? dslot + 2048 : (uint32_t)d - 1024) + zero; };
  uint64_t d0 = desc_lo(dslot + R * 1024) + zero, d1 = next(d0);
  AttnA a;
  ATS_(0);
  wgmma_fence();
#pragma unroll
  for (int v = 0; v < 2; v++) {
    wgmma_n32_rsz_tb0(a.s[v], q[0][0], d0 + v * 256);
    wgmma_n32_rs_tb0(a.s[v], q[0][1], d0 + (v * 256 + 2), 1);
    wgmma_commit();
  }
  a.zero = zero;
  const bool lane0 = (fresh_tid() & 31) == 0;
  attn_masks(a, wr);
  const int nv = 2 * gb + R;
  const uint32_t hb = bars + 8u * (B_HALO - R), rb = bars + 8u * (B_REL - R);
  attn_step<0>(a, q, d0, d1, R, wr, nv, hb, par, 0, false);
  d0 = next(d1);
  attn_step<1>(a, q, d1, d0, R, wr, nv, R ? bars + 8u * B_HV : hb + 8, par, rb + 8, lane0);
  d1 = next(d0);
  attn_step<2>(a, q, d0, d1, R, wr, nv, hb + 16, par, rb + 16, lane0);
  d0 = next(d1);
  attn_step<3>(a, q, d1, d0, R, wr, nv, hb + 24, par, rb + 24, lane0 && R);
  attn_step<4>(a, q, d0, d0, R, wr, nv, 0, 0, rb, false);
  ATS_(21);
  attn_sum<19>(a, nv);
  attn_shfl<1>(a);
  attn_fin<1>(a);
  ATS_(22);
  if (a.bad != 0u) {
    attn_a_slow(g_kvA[0][0][0], L, gb, hp, a.bad, R * 64 + wr * 8, fresh_tid() & 31);
    named_bar_sync(8 + R * 4 + wr, 32);
  }
}

constexpr uint32_t KB_ROW0 = SBASE + OFF_SLOT + 2048, VB_ROW0 = SBASE + OFF_SLOT + 24576 + 2048;

__device__ __forceinline__ void attention_b(const uint32_t (&q)[2][2][4], int R, int gb, uint32_t par0, int wr) {
  constexpr uint32_t bars = SBASE + OFF_BAR;
  const uint32_t dk = ((KB_ROW0 - 2048) >> 4) + 0x10000u + R * 512, dv = dk + ((VB_ROW0 - KB_ROW0) >> 4);
  float s[2][40];
  mbar_wait(bars + 8u * (B_HALO - R), par0);
  wgmma_fence();
#pragma unroll
  for (int hh = 0; hh < 2; hh++) {
    wgmma_n80_rsz_tb0(s[hh], q[hh][0], desc_lo(dk + hh * 4));
    wgmma_n80_rs_tb0(s[hh], q[hh][1], desc_lo(dk + hh * 4 + 2), 1);
  }
  wgmma_commit();
  const int lane = fresh_tid() & 31, g = lane >> 2;
  const bool odd = g & 1, edge = R == 0 && gb == 0 && wr == 0;
  const int D = 2 * (lane & 3) + (g & 1) - g;
  const uint32_t ra = q_row_addr(true, R, wr, lane);
  wgmma_wait<0>();
  reg_fence<40>(s[0]);
  reg_fence<40>(s[1]);
  float z[2][2], y[2][2];
#define GATHER_(W)                                                                                          \
  _Pragma("unroll") for (int hh = 0; hh < 2; hh++) _Pragma("unroll") for (int r = 0; r < 2; r++) {          \
    const float* e = &s[hh][4 * (2 * W + r) + 2 * r];                                                       \
    z[hh][r] = odd ? e[5] : e[4];                                                                           \
    y[hh][r] = D >= 2 ? (odd ? e[1] : e[0]) : (odd ? e[9] : e[8]);                                          \
  }
  if (wr < 2) {
    if (wr == 0) { GATHER_(0) } else { GATHER_(1) }
  } else {
    if (wr == 2) { GATHER_(2) } else { GATHER_(3) }
  }
#undef GATHER_
  float o[2][16], inv[2][2];
  uint32_t p[2][5][4];
  const int sh = odd ? 16 : 0, kb = wr + (D >= 2 ? 0 : 1);
#pragma unroll
  for (int hh = 0; hh < 2; hh++) {
    if (edge) {
      z[hh][0] = -INFINITY;
      if (D >= 2) y[hh][0] = y[hh][1] = -INFINITY;
    }
    uint32_t ab[2][2];
#pragma unroll
    for (int r = 0; r < 2; r++) {
      float m = fmaxf(z[hh][r], y[hh][r]);
      m = fmaxf(m, __shfl_xor_sync(0xffffffffu, m, 1));
      m = fmaxf(m, __shfl_xor_sync(0xffffffffu, m, 2));
      const float e0 = ex2_approx(z[hh][r] - m), e1 = ex2_approx(y[hh][r] - m);
      inv[hh][r] = e0 + e1;
      ab[r][0] = pack_bf16x2(e0, 0.f) << sh;
      ab[r][1] = pack_bf16x2(e1, 0.f) << sh;
    }
#pragma unroll
    for (int k = 0; k < 5; k++) {
      p[hh][k][0] = k == kb ? ab[0][1] : 0u;
      p[hh][k][1] = k == wr + 1 ? ab[1][0] : 0u;
      p[hh][k][2] = k == wr ? ab[0][0] : 0u;
      p[hh][k][3] = k == kb ? ab[1][1] : 0u;
#pragma unroll
      for (int j = 0; j < 4; j++) asm volatile("" : "+r"(p[hh][k][j]));
    }
  }
  wgmma_fence();
#pragma unroll
  for (int hh = 0; hh < 2; hh++) {
    wgmma_n32_rsz_tb1(o[hh], p[hh][0], desc_lo(dv + hh * 4));
#pragma unroll
    for (int k = 1; k < 5; k++) wgmma_n32_rs_tb1(o[hh], p[hh][k], desc_lo(dv + hh * 4 + k * 128), 1);
  }
  wgmma_commit();
#pragma unroll
  for (int hh = 0; hh < 2; hh++)
#pragma unroll
    for (int r = 0; r < 2; r++) {
      inv[hh][r] += __shfl_xor_sync(0xffffffffu, inv[hh][r], 1);
      inv[hh][r] += __shfl_xor_sync(0xffffffffu, inv[hh][r], 2);
      inv[hh][r] = rcp_fast(inv[hh][r]);
    }
  wgmma_wait<0>();
  reg_fence<16>(o[0]);
  reg_fence<16>(o[1]);
  store_o<0>(o[0], inv[0], ra, o_tag(1), true);
  store_o<1>(o[1], inv[1], ra, o_tag(1), true);
}

#define KTQM 0
#define TRICKLE 300
#define WTURN 15
#define QREL 8
#define PRESLEEP 200
#define CSA 3
#define TLAZY 100
#define SDLY 1500
#define QTURN 2
#define HTS(i) do { } while (0)
struct Params {
  CUtensorMap x[5], xq[4], o, wqkv[2], wqkv3[2], wo3[2];
  const __nv_bfloat16* in_x;
  const __nv_bfloat16* wqkv_p[2];
  const __nv_bfloat16* wo_p[2];
  __nv_bfloat16* out;
  uint32_t zero;
};

__device__ __forceinline__ void colsum_part(const CUtensorMap* wmap, int ty, int qr, int hp) {
  constexpr uint32_t bars = SBASE + OFF_BAR, slots = SBASE + OFF_SLOT;
  PHASE_IDS
  const unsigned ep1 = launch_epoch();
  if (wwarp == 0 && elect_one()) {
    mbar_expect_tx(bars + 8u * B_CS, 6 * UNIT);
#pragma unroll 1
    for (int j = 0; j < 6; j++) {
      if (ty == 0) mbar_pace(bars + 8u * (B_QF + B_E + ((j * CSA / 6) & 3)), (j * CSA / 6) >> 2);
      else mbar_wait_lazy<100>(bars + 8u * (B_WF + B_E + ((2 * j + 3 - (j & 1)) & 7)), j >= 3);
      tma_load_2d(slots + j * UNIT, wmap, bars + 8u * B_CS, (j >> 1) * 1024 + hp * 64, qr * 128 + (j & 1) * 64);
    }
  }
  constexpr uint64_t ones = (SBASE + OFF_LSB + 32) >> 4;
  float s[3][4];
  mbar_wait_lazy<100>(bars + 8u * B_CS, ty);
  wgmma_fence();
#pragma unroll
  for (int p = 0; p < 3; p++) {
    wgmma_n8_ssz_ta1_tb0(s[p], make_desc(slots + p * 2 * UNIT, 16), ones);
#pragma unroll
    for (int k = 1; k < 8; k++) wgmma_n8_ss_ta1_tb0(s[p], make_desc(slots + p * 2 * UNIT + k * 2048, 16), ones, 1);
  }
  wgmma_commit();
  wgmma_wait<0>();
  reg_fence<12>(&s[0][0]);
  if (lane == 0) mbar_arrive(bars + 8u * (ty ? B_CSD : B_RDONE));
  if (c == 0) {
#pragma unroll
    for (int r = 0; r < 2; r++) st_rec(&g_cs[ty][hp][qr][wwarp * 16 + 8 * r + g], s[0][2 * r], s[1][2 * r], s[2][2 * r], ep1);
  }
}

__device__ __forceinline__ void put_colsums(int ty, int col, const float4& s) {
  const float v[3] = {s.x, s.y, s.z};
#pragma unroll
  for (int p = 0; p < 3; p++) {
    const uint32_t a = SBASE + OFF_CS + (p * 8 + (col >> 3)) * 64 + ty * 32 + (col & 7) * 2;
    const float hi = bf16_round(v[p]);
    const uint32_t w = pack_bf16x2(hi, v[p] - hi);
    asm volatile("st.shared.b16 [%0], %1;" ::"r"(a), "h"((unsigned short)w) : "memory");
    asm volatile("st.shared.b16 [%0], %1;" ::"r"(a + 16), "h"((unsigned short)(w >> 16)) : "memory");
  }
}

__device__ __forceinline__ uint32_t ln_params(float s1, float s2) {
  const float mean = s1 * (1.0f / DM);
  const float var = fmaxf(fmaf(-mean, mean, s2 * (1.0f / DM)), 0.f);
  float sd;
  asm("sqrt.approx.f32 %0, %1;" : "=f"(sd) : "f"(bf16_round(bf16_round(var) + 1e-5f)));
  return pack_bf16x2(mean, sd);
}

__host__ __device__ constexpr uint32_t w_rel(int kt) { return ((B_WF + (kt & 7)) << 1) | (kt >> 3); }
__host__ __device__ constexpr uint32_t w_rel4(int a, int b, int c, int d) { return w_rel(a) | (w_rel(b) << 8) | (w_rel(c) << 16) | (w_rel(d) << 24); }
__device__ __forceinline__ void ring_wait(uint32_t e) { mbar_wait(SBASE + OFF_BAR + 8u * B_E + ((e << 2) & 0x3f8u), e & 1u); }
struct RingProd {
  uint32_t rel = ((B_QF << 1) | 1) * 0x01010101u + 0x06040200u;
  __device__ __forceinline__ void q_step(int kt) {
    const int sh = 8 * (kt & 3);
    const uint32_t e = rel >> sh;
    rel ^= ((e ^ (((B_QF + (kt & 3)) << 1) | ((kt >> 2) & 1))) & 255u) << sh;
    ring_wait(e);
  }
  __device__ __forceinline__ void w_job(int st, bool pre, uint32_t sel0, uint32_t sel1, uint32_t last, uint32_t& w0, uint32_t& w1) {
    const uint32_t r = __funnelshift_r(rel, rel, 8 * st);
    w0 = __byte_perm(r, 0u, sel0);
    w1 = __byte_perm(r, w_rel4(0, 1, 2, 3), pre ? sel1 : 0x6543u);
    const uint32_t n = pre ? (w_rel4(9, 11, 13, 0) & 0xffffffu) | (last << 24) : (w_rel4(11, 13, 0, 15) & 0xff00ffffu) | (last << 16);
    rel = __funnelshift_l(n, n, 8 * st);
  }
};

#define SP1 15
#define SP2 14
#define SP3 12
#define SP4 12
#define SP5 15
#define SP6 14
#define SP7 16
__device__ __forceinline__ int q_split(int inst) {
  constexpr uint32_t T = 15u | ((SP1 - 1) << 4) | ((SP2 - 1) << 8) | ((SP3 - 1) << 12) | ((SP4 - 1) << 16) | ((SP5 - 1) << 20) |
                         ((SP6 - 1) << 24) | ((uint32_t)(SP7 - 1) << 28);
  return (int)((T >> (4 * inst)) & 15u) + 1;
}
#define QROT 0
#define WROT 0
__device__ __forceinline__ int qk(int kt) { return (kt + QROT) & 15; }
__device__ __forceinline__ int wk(int kt) { return (kt + WROT) & 15; }
__host__ __device__ constexpr uint32_t turn_par(int kind) {
  const int sp[8] = {16, SP1, SP2, SP3, SP4, SP5, SP6, SP7};
  int cnt[2] = {0, 0};
  uint32_t m = 0;
  for (int i = 0; i < 8; i++)
    for (int k = 0; k < 3; k++) {
      if (k == kind) m |= (uint32_t)(cnt[i & 1] & 1) << i;
      if (k == 0 ? (i == 1 || (i > 1 && sp[i - 1] < 16)) : (k == 2 || sp[i] < 16)) cnt[i & 1]++;
    }
  return m;
}
#define PREMASK 0xBFu
__device__ __forceinline__ bool w_pre(int inst) { return (PREMASK >> inst) & 1u; }
__host__ __device__ constexpr unsigned long long bar_counts(int i0) {
  unsigned long long t = 0;
  for (int i = i0; i < i0 + 32; i++) {
    int l = 0;
    if (i < B_RF) l = 1;
    if ((i >= B_E && i < B_E + B_RF) || i == B_LOC || i == B_REL || i == B_OS0 || i == B_TURN || i == B_TURN + 1 || i == B_XS ||
        i == B_XS + 1 || i == B_CSD || i == B_GO || i == B_RDONE || i == B_KV)
      l = 2;
    if (i == B_REL + 1 || i == B_REL + 2) l = 3;
    t |= (unsigned long long)l << (2 * (i - i0));
  }
  return t;
}

__global__ void __launch_bounds__(512, 1) fused_kernel(const __grid_constant__ Params P) {
  extern __shared__ __align__(1024) uint8_t smem_raw[];
  constexpr uint32_t base = SBASE, bars = base + OFF_BAR, slots = base + OFF_SLOT;
  if (smem_u32(smem_raw) != base) __trap();
  const int warp = __shfl_sync(0xffffffffu, threadIdx.x >> 5, 0), lane = threadIdx.x & 31;
  const int b = blockIdx.x;
#define QS 0
#define WS 1
  const int qr = ((b & ((8 << QS) - 1)) >> QS) ^ (((b >> (3 + QS)) & 1) * 7);
  const int hp = ((b >> (3 + QS)) << QS) + (b & ((1 << QS) - 1));
  const int rt = ((b & ((16 << WS) - 1)) >> WS) ^ (((b >> (4 + WS)) & 1) * 15);
  const int ct = ((b >> (4 + WS)) << WS) + (b & ((1 << WS) - 1));

  if (warp == 12) {
    if (elect_one()) {
#pragma unroll 1
      for (int s = 0; s < 4; s++) {
        const uint32_t fb = bars + 8u * (B_QF + s), sa = base + s * 5 * UNIT;
        mbar_init(fb, 2);
        fence_barrier_init();
        mbar_expect_tx(fb, 5 * UNIT);
        mbar_arrive(fb);
        tma_load_5d(sa + 3 * UNIT, &P.xq[0], fb, s * 64, qr * 2);
        tma_load_3d(sa, &P.wqkv3[0], fb, hp * 64, s * 64);
      }
    }
    __syncwarp();
  } else if (warp >= 4 && warp < 12) {
    if (elect_one()) {
#pragma unroll 1
      for (int i = warp; i <= B_KV; i += 8) mbar_init(bars + 8u * i, 1u << (((i < 32 ? bar_counts(0) : bar_counts(32)) >> (2 * (i & 31))) & 3u));
      sts32(warp < 8 ? base + OFF_ONE - 16 + 4 * warp : base + OFF_LSB + 4 * warp, warp < 8 ? warp == 4 : 0x3f803f80u);
      fence_proxy_async_smem();
      fence_barrier_init();
    }
    __syncwarp();
  }

  if (warp >= 12) {
    setmaxnreg_dec<32>();
    if (warp == 12) {
      named_bar_sync(0, 512);
      if (elect_one()) {
#pragma unroll 1
        for (int s = 4; s < 16; s++) {
          const uint32_t fb = bars + 8u * (B_QF + (s & 3)), sa = base + (s & 3) * 5 * UNIT;
          mbar_wait(fb + 8u * B_E, ((s >> 2) & 1) ^ 1);
          mbar_expect_tx(fb, 5 * UNIT);
          mbar_arrive(fb);
          tma_load_5d(sa + 3 * UNIT, &P.xq[0], fb, s * 64, qr * 2);
          tma_load_3d(sa, &P.wqkv3[0], fb, hp * 64, s * 64);
        }
#pragma unroll
        for (int s = 0; s < 4; s++) mbar_arrive(bars + 8u * B_GO);
        RingProd rp;
#pragma unroll 1
        for (int sg = 4; sg < 34; sg++) {
          const int part = sg & 3, inst = (sg >> 2) - (part & 1);
          if (part == 3 || inst == 8) continue;
          const int ty = (inst >> 1) & 1;
          if (part != 1) {
            const int k0 = part ? q_split(inst) : 0, k1 = part ? 16 : q_split(inst);
#pragma unroll 1
            for (int kt = k0; kt < k1; kt++) {
              const uint32_t sa = base + (kt & 3) * 5 * UNIT, fb = bars + 8u * (B_QF + (kt & 3));
              rp.q_step(kt);
              mbar_expect_tx(fb, 3 * UNIT);
              tma_load_3d(sa, &P.wqkv3[ty], fb, hp * 64, qk(kt) * 64);
            }
          } else {
            const bool pre = w_pre(inst);
            int st = inst < 7 ? q_split(inst + 1) & 3 : 0;
            uint32_t w0, w1;
            rp.w_job(st, pre, pre ? 0x1100u : 0x2100u, 0x3322u, (B_RF << 1) | (inst & 1), w0, w1);
#pragma unroll 1
            for (int m = 0; m < 4; m++) {
              const uint32_t fb = bars + 8u * (B_WF + 4 * (m & 1));
#pragma unroll
              for (int i = 0; i < 4; i++) {
                ring_wait(w0 >> (8 * i));
                if (i == 3 && pre) {
                  mbar_arrive(fb + 24u);
                } else {
                  mbar_expect_tx(fb + 8u * i, 2 * UNIT);
                  tma_load_3d(base + ((st + (i ? i - 1 : 0)) & 3) * 5 * UNIT + ((0x2d >> (2 * i)) & 3) * UNIT, &P.wo3[ty], fb + 8u * i,
                              ct * 128, wk(4 * m + i) * 64);
                }
              }
              st += pre ? 2 : 3;
              w0 = w1;
              w1 = m == 0 ? (pre ? w_rel4(0, 1, 2, 3) : w_rel4(3, 4, 5, 6)) : (pre ? w_rel4(4, 5, 6, 7) : w_rel4(7, 8, 9, 10));
            }
          }
        }
      }
    } else if (warp == 13) {
      RingProd rp;
      unsigned ep1 = 0;
      uint32_t seenx = 0;
      named_bar_sync(0, 512);
      mbar_wait(bars + 8u * B_GO, 0);
#pragma unroll 1
      for (int sg = 4; sg < 34; sg++) {
        const int part = sg & 3, inst = (sg >> 2) - (part & 1);
        if (part == 3 || inst == 8) continue;
        const int L = inst >> 1, ch = inst & 1;
        if (part != 1) {
          const CUtensorMap* tx = &P.xq[L];
          const int k0 = part ? q_split(inst) : 0, k1 = part ? 16 : q_split(inst);
          if (sg == 4) ep1 = launch_epoch();
          if (part == 0) seenx = L == 0 ? 0xffffffffu : peek_counts(g_fx[ch * 8 + qr][0], 6u * ep1 - 6u + 2u * L, lane);
          const int m0 = ch * 16 + qr * 2;
#pragma unroll 1
          for (int kt = k0; kt < k1; kt++) {
            const uint32_t fb = bars + 8u * (B_QF + (kt & 3));
            rp.q_step(kt);
            if (lane == 0) mbar_expect_tx(fb, 2 * UNIT);
            wait_count(g_fx[ch * 8 + qr][0], 6u * ep1 - 6u + 2u * L, qk(kt), seenx, lane);
            TGET(t38);
            if (elect_one()) tma_load_5d(base + ((kt & 3) * 5 + 3) * UNIT, tx, fb, qk(kt) * 64, m0);
            TGET(t39);
            if (L == 3 && kt == 0 && lane == 0) { TPUT(ch, 38, t38); TPUT(ch, 39, t39); }
          }
        } else {
          const int m0 = ch * 1024 + rt * 64;
          const bool pre = w_pre(inst);
          int st = inst < 7 ? q_split(inst + 1) & 3 : 0;
          uint32_t w0, w1;
          uint32_t seen = peek_counts(g_fo[ch * 16 + rt][0], 4u * ep1 - 3u + L, lane);
          rp.w_job(st, pre, 0x1110u, 0x3332u, inst == 6 && SP7 == 16 ? B_RF << 1 : w_rel(15), w0, w1);
#pragma unroll 1
          for (int m = 0; m < 4; m++) {
            const uint32_t fb = bars + 8u * (B_WF + 4 * (m & 1));
#pragma unroll
            for (int i = 0; i < 4; i++) {
              ring_wait(w0 >> (8 * i));
              if (lane == 0) mbar_expect_tx(fb + 8u * i, UNIT);
              wait_count(g_fo[ch * 16 + rt][0], 4u * ep1 - 3u + L, wk(4 * m + i), seen, lane);
              if (elect_one())
                tma_load_2d(base + ((st + (i > 0)) & 3) * 5 * UNIT + (i == 2 ? 1 : (i == 3 ? 4 : 0)) * UNIT, &P.o, fb + 8u * i, wk(4 * m + i) * 64, m0);
            }
            st += pre ? 2 : 3;
            w0 = w1;
            w1 = m == 0 ? (pre ? w_rel4(0, 1, 2, 3) : w_rel4(3, 4, 5, 6)) : (pre ? w_rel4(4, 5, 6, 7) : w_rel4(7, 8, 9, 10));
          }
          if (L == 3) {
#pragma unroll 1
            for (int j = 0; j < 4; j++) {
              g_x[(size_t)(m0 + j * 16 + (lane >> 1)) * DM + ct * 128 + (lane & 1) * 64] = __ushort_as_bfloat16(0);
              __syncwarp();
            }
          }
        }
      }
    } else if (warp == 14) {
      const unsigned ep1 = launch_epoch();
      uint32_t hpar = 0;
      named_bar_sync(0, 512);
#pragma unroll 1
      for (int inst = 0; inst < 8; inst++) {
        const int L = inst >> 1, ch = inst & 1, gb = ch * 8 + qr;
        const unsigned kv0 = 8u * ep1 - 8u + 2u * L + (L & 1);
        const uint32_t tag = kv_tag(L);
        if (L >= 2) {
#pragma unroll 1
          for (uint32_t it = 0; it < (1u << 17); ++it)
            if (__all_sync(0xffffffffu, (int)(ld_relaxed_u32(g_fk[hp][min(gb + 1 + (lane & 1), 15)]) - kv0) >= 0)) break;
        }
        if ((L & 1) == 0) {
          uint8_t* img = g_kvA[gb][hp][0];
          const uint8_t* s1 = gb > 0 ? img - 16 * 32768 : g_zero;
          const uint8_t* s2 = gb > 1 ? img - 32 * 32768 : g_zero;
          const uint32_t h1 = gb > 0 ? 16384 : 0, h2 = gb > 1 ? 16384 : 0;
          const unsigned* cp = g_fk[hp][max(gb - 1 - (lane >= 3), 0)];
          const unsigned ct0 = kv0 + ((0x32321u >> (4 * (lane & 7))) & 3u);
          uint32_t fr = gb == 0 ? 31u : (gb == 1 ? 24u : 0u);
          const uint32_t toff = slots + lane * 128 + ((lane & 7) << 4);
          auto seen = [&](uint32_t m) {
#pragma unroll 1
            for (uint32_t it = 0; it < (1u << 17) && !(fr & m); ++it)
              fr |= __ballot_sync(0xffffffffu, (int)(ld_relaxed_u32(cp) - ct0) >= 0);
          };
          auto load = [&](uint32_t off, const uint8_t* src, uint32_t bytes, int bi) {
            if (elect_one()) {
              mbar_expect_tx(bars + 8u * (B_HL + bi), bytes);
              bulk_load(slots + off, src, bytes, bars + 8u * (B_HL + bi));
            }
          };
          auto check = [&](uint32_t off, const uint8_t* src, uint32_t bytes, int bi, bool real, int done) {
#pragma unroll 1
            for (int tries = 0; tries < 4096; tries++) {
              mbar_wait(bars + 8u * (B_HL + bi), (hpar >> bi) & 1u);
              hpar ^= 1u << bi;
              uint32_t t = (lds32(toff + off) ^ tag) | (lds32(toff + off + 4096) ^ tag);
              if (bytes > 8192) t |= (lds32(toff + off + 8192) ^ tag) | (lds32(toff + off + 12288) ^ tag);
              if (!__any_sync(0xffffffffu, real && (t & 1u))) break;
              fence_proxy_async_smem();
              load(off, src, bytes, bi);
            }
            if (lane == 0) mbar_arrive(bars + 8u * done);
          };
          uint8_t *pk = img + 16384, *pv = img + 24576;
          unsigned* f = g_fk[hp][gb];
          pin64(pk), pin64(pv), pin64(f);
          mbar_wait(bars + 8u * B_KV, inst & 1);
          if (elect_one()) {
            bulk_store(pk, slots + 16384, 8192);
            bulk_announce(f);
            bulk_store(pv, slots + 24576, 8192);
            bulk_announce(f);
            bulk_commit();
          }
          HTS(44);
          seen(1);
          HTS(46);
          load(32768, s1 + h1, 8192, 0);
          seen(2);
          HTS(47);
          load(40960, s1 + h1 + 8192, 8192, 1);
          mbar_wait(bars + 8u * B_LOC, inst & 1);
          HTS(45);
          if (elect_one()) {
            bulk_store(img, slots, 16384);
            bulk_announce(g_fk[hp][gb]);
            bulk_commit();
            asm volatile("cp.async.bulk.wait_group.read 1;" ::: "memory");
          }
          check(32768, s1 + h1, 8192, 0, gb > 0, B_HALO);
          HTS(52);
          check(40960, s1 + h1 + 8192, 8192, 1, gb > 0, B_HV);
          HTS(53);
#pragma unroll 1
          for (int n = 1; n < 4; n++) {
            const uint8_t* src = n == 1 ? s1 : (n == 2 ? s2 + h2 : s2);
            const uint32_t off = n == 3 ? 32768 : 32768 - n * 16384;
            seen(2u << n);
            if (n == 2 && elect_one()) bulk_wait_read0();
            mbar_wait(bars + 8u * (B_REL - 1) + 8u * n, ch);
            HTS(47 + n);
            load(off, src, 16384, 0);
            check(off, src, 16384, 0, gb > (n >> 1), B_HALO + n);
            HTS(53 + n);
          }
        } else {
          uint8_t *pk = g_kvB[gb][hp], *pv = pk + 2048;
          const uint8_t* src = gb >= 1 ? pk - 16 * 4096 : g_zero;
          unsigned* f = g_fk[hp][gb];
          pin64(pk), pin64(pv), pin64(f), pin64(src);
          mbar_wait(bars + 8u * B_KV, inst & 1);
          if (elect_one()) {
            bulk_store(pk, KB_ROW0 + 112 * 128, 2048);
            bulk_store(pv, VB_ROW0 + 112 * 128, 2048);
            bulk_announce(f);
            bulk_commit();
          }
          HTS(44);
          if (gb > 0) {
#pragma unroll 1
            for (uint32_t it = 0; it < (1u << 17); ++it)
              if (__any_sync(0xffffffffu, (int)(ld_relaxed_u32(f - 4) - kv0) > 0)) break;
          }
          HTS(46);
#pragma unroll 1
          for (uint32_t it = 0; it < (1u << 17); ++it) {
            if (elect_one()) {
              mbar_expect_tx(bars + 8u * B_HL, 4096);
              bulk_load(KB_ROW0 - 2048, src, 2048, bars + 8u * B_HL);
              bulk_load(VB_ROW0 - 2048, src + 2048, 2048, bars + 8u * B_HL);
            }
            mbar_wait(bars + 8u * B_HL, hpar & 1u);
            hpar ^= 1u;
            const uint32_t t = lds32((lane < 16 ? KB_ROW0 - 2048 : VB_ROW0 - 4096) + lane * 128 + ((lane & 7) << 4)) ^ tag;
            if (!__any_sync(0xffffffffu, gb > 0 && (t & 1u))) break;
            fence_proxy_async_smem();
          }
          if (lane == 0) mbar_arrive(bars + 8u * B_HALO);
          HTS(52);
        }
        if (elect_one()) {
          const CUtensorMap* mo = &P.o;
          unsigned *f1 = g_fo[gb * 2 + 1][hp], *f0 = g_fo[gb * 2][hp];
          int c0 = hp * 64, r0 = gb * 128, r1 = r0 + 64;
          pin64(mo), pin64(f1), pin64(f0);
          asm volatile("" : "+r"(c0), "+r"(r0), "+r"(r1));
          mbar_wait(bars + 8u * B_OS1, (inst & 1) ^ 1);
          tma_store_2d(mo, slots + 7 * UNIT, c0, r1);
          bulk_announce(f1);
          bulk_commit();
          mbar_wait(bars + 8u * B_OS0, inst & 1);
          tma_store_2d(mo, slots + 6 * UNIT, c0, r0);
          bulk_announce(f0);
          bulk_commit();
          HTS(57);
          bulk_wait_read0();
          HTS(58 - 15);
          mbar_expect_tx(bars + 8u * B_RF, 2 * UNIT);
          tma_load_2d(slots + 6 * UNIT, &P.x[L], bars + 8u * B_RF, ct * 128, ch * 1024 + rt * 64);
          tma_load_2d(slots + 7 * UNIT, &P.x[L], bars + 8u * B_RF, ct * 128 + 64, ch * 1024 + rt * 64);
          if (w_pre(inst)) {
            mbar_expect_tx(bars + 8u * B_PRE, 6 * UNIT);
            mbar_expect_tx(bars + 8u * B_PRE2, 2 * UNIT);
#pragma unroll 1
            for (int j = 0; j < 4; j++) {
              __nanosleep(PRESLEEP);
              if (j == 3) mbar_wait(bars + 8u * B_RDONE, (inst & 1) ^ 1);
              tma_load_3d(slots + j * 2 * UNIT, &P.wo3[L & 1], bars + 8u * (j == 3 ? B_PRE2 : B_PRE), ct * 128, wk(4 * j + 3) * 64);
            }
          }
        }
        __syncwarp();
      }
    } else {
      const unsigned ep1 = launch_epoch();
      named_bar_sync(0, 512);
      mbar_wait(bars + 8u * B_GO, 0);
#pragma unroll 1
      for (int i = 0; i < 20; i++) {
        const char* src = i < 4 ? reinterpret_cast<const char*>(P.wo_p[0]) + (size_t)b * 16384 + i * 4096
                                : (i < 16 ? reinterpret_cast<const char*>(P.wqkv_p[1]) + (size_t)b * 49152 + (i - 4) * 4096
                                          : reinterpret_cast<const char*>(P.wo_p[1]) + (size_t)b * 16384 + (i - 16) * 4096);
        asm volatile("prefetch.global.L2 [%0];" ::"l"(src + lane * 128));
        __nanosleep(TRICKLE);
      }
#pragma unroll 1
      for (int inst = 2; inst < 10; inst++) {
        const int L = inst >> 1, ch = inst & 1, gb = ch * 8 + qr;
        {
          uint32_t xb = base + (((inst < 9 ? q_split(inst - 1) : 0) + (w_pre(inst - 2) ? 3 : 2)) & 3) * 5 * UNIT;
          unsigned* f = g_fx[ch * 8 + (rt >> 1)][ct * 2];
          const CUtensorMap* mx = &P.x[L];
          int c0 = ct * 128, r0 = ch * 1024 + rt * 64;
          pin64(f), pin64(mx);
          asm volatile("" : "+r"(xb), "+r"(c0), "+r"(r0));
#pragma unroll
          for (int h = 0; h < 2; h++) {
            mbar_wait(bars + 8u * (B_XS + h), ch);
            if (elect_one()) {
              tma_store_2d(mx, xb + h * UNIT, c0 + h * 64, r0);
              if (L < 4) bulk_announce(f + 4 * h);
              bulk_commit();
              if (h == 1) {
                bulk_wait_read0();
                mbar_arrive(bars + 8u * (B_RF + B_E));
              }
            }
          }
          if (L == 4) continue;
          __nanosleep(SDLY);
        }
#pragma unroll 1
        for (int h = 0; h < 4; h++) {
          const float4* sp = &g_stats[0][gb * 128 + h * 32 + lane];
          const float4 s0 = sum_recs<4>(sp, S_LEN, 4u * ep1 + L), s1 = sum_recs<4>(sp + 4 * S_LEN, S_LEN, 4u * ep1 + L);
          sts32(base + OFF_RS + (ch * 128 + h * 32 + lane) * 4, ln_params(s0.x + s1.x, s0.y + s1.y));
        }
        if (inst == 2) {
#pragma unroll 1
          for (int hf = 0; hf < 2; hf++) {
            const float4* cp = &g_cs[1][hp][0][hf * 32 + lane];
            const float4 s0 = sum_recs<4>(cp, 64, ep1), s1 = sum_recs<4>(cp + 4 * 64, 64, ep1);
            put_colsums(1, hf * 32 + lane, make_float4(s0.x + s1.x, s0.y + s1.y, s0.z + s1.z, 0.f));
          }
        }
        fence_proxy_async_smem();
        __syncwarp();
        if (lane == 0) mbar_arrive(bars + 8u * (B_PREP + ch));
      }
    }
  } else {
    const bool asst = warp >= 8;
    GTL(0);
    if (warp >= 4) named_bar_sync(0, 512);
    if (warp >= 4 && !asst) {
      PHASE_IDS
      {
        const unsigned ep1 = launch_epoch();
        const int row = b * 16 + (tid >> 3);
        const uint4* src = reinterpret_cast<const uint4*>(P.in_x + (size_t)row * DM) + (tid & 7);
        float s1 = 0.f, s2 = 0.f;
#pragma unroll 1
        for (int k = 0; k < 4; k++) {
          mbar_pace(bars + 8u * (B_QF + B_E + ((2 * k) & 3)), k >> 1);
          uint4 v[4];
#pragma unroll
          for (int j = 0; j < 4; j++) v[j] = __ldg(src + (k * 4 + j) * 8);
#pragma unroll
          for (int j = 0; j < 4; j++) {
            const uint32_t w[4] = {v[j].x, v[j].y, v[j].z, v[j].w};
#pragma unroll
            for (int e = 0; e < 4; e++) {
              const float x0 = bf_lo(w[e]), x1 = bf_hi(w[e]);
              s1 += x0 + x1;
              s2 = fmaf(x0, x0, fmaf(x1, x1, s2));
            }
          }
        }
#pragma unroll
        for (int o = 1; o < 8; o <<= 1) {
          s1 += __shfl_xor_sync(0xffffffffu, s1, o);
          s2 += __shfl_xor_sync(0xffffffffu, s2, o);
        }
        if ((tid & 7) == 0) st_rec(&g_stats[0][row], s1, s2, 0.f, 4u * ep1);
        if (tid == 0) sts32(base + OFF_EPOCH, ep1);
        if (tid < 64) {
          const float4 s0 = sum_recs<8>(&g_cs[0][hp][0][tid], 64, ep1);
          put_colsums(0, tid, s0);
        } else {
          put_colsums(1, tid - 64, make_float4(0.f, 0.f, 0.f, 0.f));
        }
#pragma unroll 1
        for (int cc = 0; cc < 2; cc++) {
          const float4 s0 = sum_recs<1>(&g_stats[0][(cc * 8 + qr) * 128 + tid], 0, 4u * ep1);
          sts32(base + OFF_RS + (cc * 128 + tid) * 4, ln_params(s0.x, s0.y));
        }
        fence_proxy_async_smem();
        named_bar_sync(2, 128);
        if (tid < 2) mbar_arrive(bars + 8u * (B_PREP + tid));
      }
    }
#pragma unroll 1
    for (int inst = asst ? 0 : warp >> 2; inst < 8; inst += asst ? 1 : 2) {
      const int L = inst >> 1, ch = inst & 1, gb = ch * 8 + qr;
      uint32_t q[2][2][4];
      if (asst) {
        if (inst < 2) colsum_part(&P.wqkv[inst], inst, qr, hp);
        setmaxnreg_dec<24>();
        named_bar_sync(4, 256);
        setmaxnreg_inc<128>();
        const uint32_t ra = q_row_addr(L & 1, 1, warp & 3, fresh_tid() & 31);
#pragma unroll
        for (int j = 0; j < 4; j++) ldmatrix_x4(q[j >> 1][j & 1], ra ^ (j << 5));
      } else {
      setmaxnreg_inc<224>();
      {
        float acc[2][96];
        const int ksp = q_split(inst);
        constexpr uint32_t STG = 5 * (UNIT >> 4), D0 = ((base + 3 * UNIT) >> 4) + 0x10000u;
        constexpr uint32_t DB = ((UNIT >> 4) << 16) - 0x10000u - 3 * (UNIT >> 4);
        uint32_t sd = D0;
        const uint32_t toff = ((fresh_tid() & 127) << 7) + ((fresh_tid() & 7) << 4);
        const bool lane0 = (toff & 0xf80u) == 0u;
        uint32_t tbad = 0u, tw, xt = x_tag(L);
        uint32_t rsa = base + OFF_RS + (ch * 128 + tile_row(L & 1, warp & 3, 0, (toff >> 9) & 7)) * 4;
        uint32_t rsb = rsa + ((L & 1) ? 32 : 128);
        uint32_t lnm = ((toff >> 7) & 3) == (L & 1) ? 0xffffffffu : 0u, tmk = L > 0;
        uint32_t soff = tile_row(L & 1, warp & 3, (toff >> 10) & 1, (toff >> 7) & 7) * 128 + ((toff ^ (toff >> 7)) & 0x10u) + (toff & 0x60u);
        uint32_t bprep = bars + 8u * (B_PREP + ch), bturn = bars + 8u * (B_TURN + (ch ^ 1));
        uint32_t bfree = bars + 8u * (inst == 1 ? B_CSD : B_RDONE), pfree = inst == 1 ? 0 : inst & 1, pprep = L & 1;
        asm volatile("" : "+r"(rsa), "+r"(rsb), "+r"(lnm), "+r"(soff), "+r"(xt), "+r"(tmk));
        asm volatile("" : "+r"(bprep), "+r"(bturn), "+r"(bfree), "+r"(pfree), "+r"(pprep));
        if (inst == 0) named_bar_sync(0, 512);
        if (inst == 1 || (inst > 1 && q_split(inst - 1) < 16)) mbar_wait_lazy<TLAZY>(bars + 8u * (B_TURN + ch), (turn_par(0) >> inst) & 1u);
        if (L == 3) GTL(37);
        mbar_wait(bars + 8u * B_QF, 0);
        GTL(1 + L * 8);
        {
          const uint64_t da = desc_lo(sd) + P.zero;
          wgmma_fence();
          wgmma_n192_ssz_ta0_tb1(acc[1], da + (UNIT >> 4), da + DB);
          wgmma_commit();
          wgmma_n192_ssz_ta0_tb1(acc[0], da, da + DB);
          wgmma_commit();
        }
#pragma unroll 1
        for (int kt = 0; kt < 15; kt++) {
          const bool last = kt + 1 == ksp;
          const uint64_t da = desc_lo(sd) + P.zero;
          const uint32_t fn = bars + 8u * (B_QF + ((kt + 1) & 3)), pn = ((kt + 1) >> 2) & 1;
#pragma unroll
          for (int k16 = 0; k16 < 4; k16++) {
            if (k16 == 0 && kt == 0) continue;
            wgmma_fence();
            wgmma_n192_ss_ta0_tb1(acc[1], da + ((UNIT >> 4) + k16 * 2), da + (DB + k16 * 128), 1);
            wgmma_commit();
            wgmma_wait<1>();
            if (k16 == 0 && lane0 && kt != ksp) mbar_arrive(bars + 8u * (B_QF + B_E + ((kt - 1) & 3)));
            wgmma_fence();
            wgmma_n192_ss_ta0_tb1(acc[0], da + k16 * 2, da + (DB + k16 * 128), 1);
            wgmma_commit();
            if (k16 == 1) tw = lds32(((sd & 0xffffu) << 4) + toff);
            if (k16 == 2) tbad |= tw ^ xt;
            bool ok = true;
            if (k16 == 2) ok = mbar_test(fn, pn) || last;
            if (k16 == QTURN && last && lane0) mbar_arrive(bturn);
            if (k16 < 3) wgmma_wait<1>();
            if (k16 == 2 && !ok) mbar_wait(fn, pn);
          }
          sd = sd == D0 + 3 * STG ? D0 : sd + STG;
          if (last) {
            wgmma_wait<0>();
            if (lane0) mbar_arrive(bars + 8u * (B_QF + B_E + (kt & 3)));
            mbar_wait_lazy<TLAZY>(bars + 8u * (B_TURN + ch), (turn_par(1) >> inst) & 1u);
            mbar_wait(fn, pn);
          }
        }
        constexpr uint32_t DL = D0 + 3 * STG;
        wgmma_fence();
#pragma unroll
        for (int k16 = 0; k16 < 4; k16++) wgmma_n192_ss_ta0_tb1(acc[1], desc_lo(DL + (UNIT >> 4) + k16 * 2), desc_lo(DL + DB + k16 * 128), 1);
        wgmma_commit();
        tw = lds32(((DL & 0xffffu) << 4) + toff);
        mbar_wait(bprep, pprep);
        uint32_t rs[2][2];
        constexpr uint64_t DCS = (uint64_t)((base + OFF_CS) >> 4) | (4ull << 32);
        auto ln_mma = [&](float (&d)[96], uint32_t (&r)[2], int h) {
          uint32_t a[4];
#pragma unroll
          for (int i = 0; i < 2; i++) {
            if (h) r[i] = lds32((i ? rsb : rsa) + 256);
            a[i] = (__byte_perm(r[i], 0u, 0x1010) ^ 0x80008000u) & lnm;
            a[i + 2] = r[i] & P.zero;
          }
#pragma unroll
          for (int i = 0; i < 4; i++) asm volatile("" : "+r"(a[i]));
          wgmma_fence();
          wgmma_n192_rs_tb1(d, a, DCS, 1);
          wgmma_commit();
        };
        ln_mma(acc[1], rs[1], 1);
        wgmma_wait<2>();
        if (lane0 && ksp != 15) mbar_arrive(bars + 8u * (B_QF + B_E + 2));
        wgmma_fence();
#pragma unroll
        for (int k16 = 0; k16 < 4; k16++) wgmma_n192_ss_ta0_tb1(acc[0], desc_lo(DL + k16 * 2), desc_lo(DL + DB + k16 * 128), 1);
        wgmma_commit();
        if (lane0) mbar_arrive(bturn);
        rs[0][0] = lds32(rsa);
        rs[0][1] = lds32(rsb);
        static_assert(SP1 < 16 && (PREMASK & 1u), "column sums of B");
        const bool afree = mbar_test(bfree, pfree) & (mbar_test(bars + 8u * (B_WF + B_E + 7), 1) | (ksp == 16));
        const bool redo = named_bar_or(1 + ch, 128, (tbad | (tw ^ xt)) & tmk);
        float rinv[2];
#pragma unroll
        for (int r = 0; r < 2; r++) {
          rinv[r] = rcp_fast(bf_hi(rs[1][r]));
          asm volatile("" : "+f"(rinv[r]));
        }
        const uint32_t kdst = ((L & 1) ? KB_ROW0 : slots) + soff, vdst = ((L & 1) ? VB_ROW0 : slots + 8192) + soff;
        const uint32_t hs = (L & 1) ? 8192 : 16384, c0 = (toff & 0x180u) == 0u;
        wgmma_wait<1>();
        if (redo) {
          wgmma_wait<0>();
          constexpr uint32_t sa = (DL & 0xffffu) << 4;
          const uint32_t rb = bars + 8u * (B_REDO + ch);
          if (toff == 0) {
            mbar_init(rb, 1);
            fence_barrier_init();
          }
          uint32_t rpar = 0;
#pragma unroll 1
          for (int kt = 0, tries = 0; kt < 16;) {
            fence_proxy_async_smem();
            named_bar_sync(1 + ch, 128);
            if ((warp & 3) == 0 && elect_one()) {
                mbar_expect_tx(rb, 5 * UNIT);
              tma_load_5d(sa, &P.xq[L], rb, qk(kt) * 64, gb * 2);
              tma_load_3d(sa - 3 * UNIT, &P.wqkv3[L & 1], rb, hp * 64, qk(kt) * 64);
            }
            mbar_wait(rb, rpar);
            rpar ^= 1u;
            if (named_bar_or(1 + ch, 128, (lds32(sa + toff) ^ xt) & 1u) && ++tries < 4096) continue;
            wgmma_fence();
#pragma unroll
            for (int k16 = 0; k16 < 4; k16++) {
              const uint64_t db = make_desc(sa - 3 * UNIT + k16 * 2048, UNIT);
              wgmma_n192_ss_ta0_tb1(acc[1], make_desc(sa + UNIT + k16 * 32, 16), db, kt | k16);
              wgmma_n192_ss_ta0_tb1(acc[0], make_desc(sa + k16 * 32, 16), db, kt | k16);
            }
            wgmma_commit();
            wgmma_wait<0>();
            kt++;
          }
          ln_mma(acc[1], rs[1], 1);
          wgmma_wait<0>();
        }
        ln_mma(acc[0], rs[0], 0);
        reg_fence<96>(acc[1]);
        GTL(2 + L * 8);
        if (!afree) {
          mbar_wait(bfree, pfree);
          if (ksp < 16) mbar_wait(bars + 8u * (B_WF + B_E + 7), 1);
        }
#pragma unroll
        for (int t = 0; t < 24; t++) {
          const int h = t < 12 ? 1 : 0, p = ((t % 12) / 4 + 1) % 3, jp = t & 3;
          if (t == QREL) {
            wgmma_wait<0>();
            reg_fence<96>(acc[0]);
            if (lane0) mbar_arrive(bars + 8u * (B_QF + B_E + 3));
          }
          if (t == 8 || t == 20) {
            rinv[0] *= SM_C;
            rinv[1] *= SM_C;
          }
          const float* a = &acc[h][4 * (p * 8 + 2 * jp)];
          uint32_t r0 = pack_bf16x2(a[0] * rinv[0], a[1] * rinv[0]);
          uint32_t r1 = pack_bf16x2(a[2] * rinv[1], a[3] * rinv[1]);
          if (p != 0 && jp == 0) {
            r0 = set_tag(r0, c0, kv_tag(L));
            r1 = set_tag(r1, c0, kv_tag(L));
          }
          const uint32_t r2 = pack_bf16x2(a[4] * rinv[0], a[5] * rinv[0]);
          const uint32_t r3 = pack_bf16x2(a[6] * rinv[1], a[7] * rinv[1]);
          const uint32_t dst = p == 0 ? slots + 3 * 16384 + soff + h * 8192 : (p == 1 ? kdst : vdst) + h * hs;
          stmatrix_x4(dst ^ (jp << 5), r0, r1, r2, r3);
          if (t >= 20) {
            q[jp >> 1][jp & 1][0] = r0;
            q[jp >> 1][jp & 1][1] = r1;
            q[jp >> 1][jp & 1][2] = r2;
            q[jp >> 1][jp & 1][3] = r3;
          }
          if (t == 7 || t == 19) signal_async(bars + 8u * (t == 7 ? B_KV : B_LOC), lane0);
          if (t == 11) {
            setmaxnreg_dec<128>();
            named_bar_arrive(4, 256);
#pragma unroll
            for (int r = 0; r < 2; r++) rinv[r] = rcp_fast(bf_hi(rs[0][r]));
          }
        }
        mbar_wait(bars + 8u * B_LOC, inst & 1);
      }
      }
      GTL(3 + L * 8);
      if ((L & 1) == 0) attention_a(q, asst, L, gb, hp, ch, warp & 3, P.zero);
      else attention_b(q, asst, gb, inst & 1, warp & 3);
      GTL(4 + L * 8);
      signal_async(bars + 8u * (asst ? B_OS1 : B_OS0), (fresh_tid() & 31) == 0);
      if (asst) continue;
      GTL(5 + L * 8);

      {
        float acc[64];
        const int sp = inst < 7 ? q_split(inst + 1) : 0;
        int st = sp & 3;
        const bool pre = w_pre(inst);
        uint32_t tbad = 0u;
        const uint32_t toff = ((fresh_tid() & 63) << 7) + ((fresh_tid() & 7) << 4);
        const bool lane0 = (toff & 0xf80u) == 0u;
        constexpr uint32_t U4 = UNIT >> 4, LA = 0x10000u, LB = U4 << 16;
        reg_define<64>(acc);
        reg_fence<64>(acc);
        uint32_t xv[8][4];
        {
          PHASE_IDS_W
          const uint32_t xr = slots + 6 * UNIT + (wwarp * 16 + (lane & 15)) * 128 + (((lane >> 4) ^ (lane & 7)) << 4);
          mbar_wait(bars + 8u * B_RF, inst & 1);
#pragma unroll
          for (int jp = 0; jp < 8; jp++) ldmatrix_x4(xv[jp], (xr ^ ((jp & 3) << 5)) + (jp >> 2) * UNIT);
          signal_async(bars + 8u * B_RDONE, lane0);
          if (L > 0) {
            uint32_t lsb;
            asm volatile("ld.shared.u8 %0, [%1];" : "=r"(lsb) : "r"(base + OFF_LSB + ch * 32 + wwarp * 8 + g) : "memory");
#pragma unroll
            for (int k = 0; k < 4; k++) xv[(k >> 1) * 4][k & 1] = set_tag(xv[(k >> 1) * 4][k & 1], c == 0, lsb >> k);
          }
        }
        uint32_t tmx = L < 3 && (toff & 0x180u) == 0u, xt = x_tag(L + 1);
        uint32_t xrow = base + ((st + (pre ? 3 : 2)) & 3) * 5 * UNIT + (warp & 3) * 2048 + (toff & 0x7e0u) + ((toff ^ (toff >> 7)) & 0x10u);
        asm volatile("" : "+r"(tmx), "+r"(xt), "+r"(xrow));
        uint64_t d0 = desc_lo((base >> 4) + st * 5 * U4) + P.zero;
        if (inst < 7 || SP7 == 16) mbar_wait_lazy<TLAZY>(bars + 8u * (B_TURN + ch), (turn_par(2) >> inst) & 1u);
        mbar_wait(bars + 8u * B_WF, 0);
        GTL(6 + L * 8);
        uint32_t s1 = 0;
#pragma unroll 1
        for (int m = 0; m < 4; m++) {
          const uint32_t s0 = base + st * 5 * UNIT, fb = bars + 8u * (B_WF + 4 * (m & 1));
          s1 = base + ((st + 1) & 3) * 5 * UNIT;
          const uint64_t d1 = desc_lo(s1 >> 4) + P.zero;
          const uint64_t d2 = desc_lo((pre ? slots + m * 2 * UNIT : base + ((st + 2) & 3) * 5 * UNIT) >> 4) + P.zero;
          st = (st + (pre ? 2 : 3)) & 3;
#pragma unroll
          for (int i = 0; i < 4; i++) {
            const uint64_t da = (i == 0 ? d0 : d1) + (LA + (i == 2 ? 1 : (i == 3 ? 4 : 0)) * U4);
            const uint64_t db = (i < 2 ? d0 : (i == 2 ? d1 : d2)) + (LB + (i == 0 ? 1 : (i == 1 ? 3 : (i == 2 ? 2 : 0))) * U4);
            if (i == 3 && (m == 0 || m == 3) && pre) mbar_wait(bars + 8u * (m ? B_PRE2 : B_PRE), __popc(PREMASK & ((1u << inst) - 1u)) & 1);
            if (i == (WTURN & 3) && m == 3 && lane0 && (sp < 16 || inst == 6)) mbar_arrive(bars + 8u * (B_TURN + (ch ^ 1)));
            wgmma_fence();
#pragma unroll
            for (int k16 = 0; k16 < 4; k16++) wgmma_n128_ss_ta0_tb1(acc, da + 2 * k16, db + 128 * k16, 1);
            wgmma_commit();
            if (i == 2) d0 = desc_lo((base >> 4) + st * 5 * U4) + P.zero;
            tbad |= lds32((i == 0 ? s0 : s1) + (i == 2 ? 1 : (i == 3 ? 4 : 0)) * UNIT + toff) ^ o_tag(L);
            const uint32_t fn = i < 3 ? fb + 8u * (i + 1) : fb ^ 96u;
            const uint32_t pn = i < 3 ? m >> 1 : m > 0;
            const bool ok = mbar_test(fn, pn) || (i == 3 && m == 3);
            wgmma_wait<1>();
            if (lane0 && (i > 0 || m > 0)) mbar_arrive((i > 0 ? fb + 8u * (i - 1) : (fb ^ 96u) + 24u) + 8u * B_E);
            if (!ok) mbar_wait(fn, pn);
          }
        }
        const bool redo = named_bar_or(1 + ch, 128, tbad & 1u);
        if (redo) {
          wgmma_wait<0>();
          const uint32_t sa = s1 + 4 * UNIT, sb = s1 + 2 * UNIT;
          const uint32_t rb = bars + 8u * (B_REDO + ch);
          if ((fresh_tid() & 127) == 0) {
            mbar_init(rb, 1);
            fence_barrier_init();
          }
          uint32_t rpar = 0;
#pragma unroll 1
          for (int kt = 0, tries = 0; kt < 16;) {
            fence_proxy_async_smem();
            named_bar_sync(1 + ch, 128);
            if ((warp & 3) == 0 && elect_one()) {
                mbar_expect_tx(rb, 3 * UNIT);
              tma_load_2d(sa, &P.o, rb, wk(kt) * 64, ch * 1024 + rt * 64);
              tma_load_3d(sb, &P.wo3[L & 1], rb, ct * 128, wk(kt) * 64);
            }
            mbar_wait(rb, rpar);
            rpar ^= 1u;
            if (named_bar_or(1 + ch, 128, (lds32(sa + toff) ^ o_tag(L)) & 1u) && ++tries < 4096) continue;
            wgmma_fence();
#pragma unroll
            for (int k16 = 0; k16 < 4; k16++)
              wgmma_n128_ss_ta0_tb1(acc, make_desc(sa + k16 * 32, 16), make_desc(sb + k16 * 2048, UNIT), kt | k16);
            wgmma_commit();
            wgmma_wait<0>();
            kt++;
          }
        }
        wgmma_wait<0>();
        reg_fence<64>(acc);
        if (lane0) mbar_arrive(bars + 8u * (B_WF + B_E + 7));
        GTL(7 + L * 8);
#pragma unroll
        for (int jp = 0; jp < 8; jp++) {
#pragma unroll
          for (int q = 0; q < 4; q++) xv[jp][q] = add_bf16x2(xv[jp][q], pack_bf16x2(acc[8 * jp + 2 * q], acc[8 * jp + 2 * q + 1]));
          const bool tg = (jp & 3) == 0;
          stmatrix_x4((xrow ^ ((jp & 3) << 5)) + (jp >> 2) * UNIT,
                      tg ? set_tag(xv[jp][0], tmx, xt) : xv[jp][0], tg ? set_tag(xv[jp][1], tmx, xt) : xv[jp][1], xv[jp][2], xv[jp][3]);
          if ((jp & 3) == 3) signal_async(bars + 8u * (B_XS + (jp >> 2)), lane0);
        }
        if (L < 3) {
          PHASE_IDS_W
          const int grow = ch * 1024 + rt * 64;
          const unsigned ep1 = lds32(base + OFF_EPOCH);
          if (c == 0)
            asm volatile("st.shared.u8 [%0], %1;" ::"r"(base + OFF_LSB + ch * 32 + wwarp * 8 + g),
                         "r"((xv[0][0] & 1u) | ((xv[0][1] & 1u) << 1) | ((xv[4][0] & 1u) << 2) | ((xv[4][1] & 1u) << 3)) : "memory");
          float s1[2] = {0.f, 0.f}, s2[2] = {0.f, 0.f};
#pragma unroll
          for (int jp = 0; jp < 8; jp++)
#pragma unroll
            for (int q = 0; q < 4; q++) {
              const float x0 = bf_lo(xv[jp][q]), x1 = bf_hi(xv[jp][q]);
              s1[q & 1] += x0 + x1;
              s2[q & 1] = fmaf(x0, x0, fmaf(x1, x1, s2[q & 1]));
            }
#pragma unroll
          for (int r = 0; r < 2; r++) {
            s1[r] += __shfl_xor_sync(0xffffffffu, s1[r], 1);
            s2[r] += __shfl_xor_sync(0xffffffffu, s2[r], 1);
            s1[r] += __shfl_xor_sync(0xffffffffu, s1[r], 2);
            s2[r] += __shfl_xor_sync(0xffffffffu, s2[r], 2);
            if (c == 0) st_rec(&g_stats[ct][grow + wwarp * 16 + g + 8 * r], s1[r], s2[r], 0.f, 4u * ep1 + L + 1);
          }
        }
        GTL(8 + L * 8);
      }
    }
    if (threadIdx.x == 128) atomicAdd(g_done, 1u);
  }
}

typedef CUresult (*PFN_tmEncode)(CUtensorMap*, CUtensorMapDataType, cuuint32_t, void*, const cuuint64_t*,
                                 const cuuint64_t*, const cuuint32_t*, const cuuint32_t*, CUtensorMapInterleave,
                                 CUtensorMapSwizzle, CUtensorMapL2promotion, CUtensorMapFloatOOBfill);

PFN_tmEncode get_encode_fn() {
  static PFN_tmEncode fn = nullptr;
  if (!fn) {
    cudaDriverEntryPointQueryResult qr;
    void* p = nullptr;
    cudaGetDriverEntryPoint("cuTensorMapEncodeTiled", &p, cudaEnableDefault, &qr);
    fn = (PFN_tmEncode)p;
  }
  return fn;
}

CUtensorMap make_map(const void* ptr, int rows, int cols) {
  CUtensorMap m;
  cuuint64_t gdim[2] = {(cuuint64_t)cols, (cuuint64_t)rows};
  cuuint64_t gstr[1] = {(cuuint64_t)cols * 2};
  cuuint32_t box[2] = {64, 64};
  cuuint32_t estr[2] = {1, 1};
  get_encode_fn()(&m, CU_TENSOR_MAP_DATA_TYPE_BFLOAT16, 2, const_cast<void*>(ptr), gdim, gstr, box, estr,
                  CU_TENSOR_MAP_INTERLEAVE_NONE, CU_TENSOR_MAP_SWIZZLE_128B, CU_TENSOR_MAP_L2_PROMOTION_L2_128B,
                  CU_TENSOR_MAP_FLOAT_OOB_FILL_NONE);
  return m;
}

CUtensorMap make_map3(const void* ptr, int rows, int cols, int n, int step) {
  CUtensorMap m;
  cuuint64_t gdim[3] = {(cuuint64_t)(cols - (n - 1) * step), (cuuint64_t)rows, (cuuint64_t)n};
  cuuint64_t gstr[2] = {(cuuint64_t)cols * 2, (cuuint64_t)step * 2};
  cuuint32_t box[3] = {64, 64, (cuuint32_t)n};
  cuuint32_t estr[3] = {1, 1, 1};
  get_encode_fn()(&m, CU_TENSOR_MAP_DATA_TYPE_BFLOAT16, 3, const_cast<void*>(ptr), gdim, gstr, box, estr,
                  CU_TENSOR_MAP_INTERLEAVE_NONE, CU_TENSOR_MAP_SWIZZLE_128B, CU_TENSOR_MAP_L2_PROMOTION_L2_128B,
                  CU_TENSOR_MAP_FLOAT_OOB_FILL_NONE);
  return m;
}

CUtensorMap make_map_q(const void* ptr, int sw, int sr) {
  CUtensorMap m;
  cuuint64_t gdim[5] = {DM, 8, 2, 4, S_LEN / 64};
  cuuint64_t gstr[4] = {DM * 2, (cuuint64_t)sr * DM * 2, (cuuint64_t)sw * DM * 2, 64 * DM * 2};
  cuuint32_t box[5] = {64, 8, 2, 4, 2};
  cuuint32_t estr[5] = {1, 1, 1, 1, 1};
  get_encode_fn()(&m, CU_TENSOR_MAP_DATA_TYPE_BFLOAT16, 5, const_cast<void*>(ptr), gdim, gstr, box, estr,
                  CU_TENSOR_MAP_INTERLEAVE_NONE, CU_TENSOR_MAP_SWIZZLE_128B, CU_TENSOR_MAP_L2_PROMOTION_L2_128B,
                  CU_TENSOR_MAP_FLOAT_OOB_FILL_NONE);
  return m;
}

}

extern "C" void kernel_launch(void* const* d_in, const int* in_sizes, int n_in, void* d_out, int out_size) {
  (void)in_sizes; (void)n_in; (void)out_size;
  void *p_o, *p_x;
  cudaGetSymbolAddress(&p_o, g_o);
  cudaGetSymbolAddress(&p_x, g_x);
  static bool attr_done = false;
  if (!attr_done) {
    cudaFuncSetAttribute(fused_kernel, cudaFuncAttributeMaxDynamicSharedMemorySize, SMEM_BYTES);
    attr_done = true;
  }
  Params P;
  P.in_x = (const __nv_bfloat16*)d_in[0];
  P.wqkv_p[0] = (const __nv_bfloat16*)d_in[1];
  P.wo_p[0] = (const __nv_bfloat16*)d_in[2];
  P.wqkv_p[1] = (const __nv_bfloat16*)d_in[4];
  P.wo_p[1] = (const __nv_bfloat16*)d_in[5];
  P.out = (__nv_bfloat16*)d_out;
  P.zero = 0;
  for (int L = 0; L < 5; L++) {
    const void* px = L == 0 ? (const void*)P.in_x : (L == 4 ? d_out : p_x);
    P.x[L] = make_map(px, S_LEN, DM);
    if (L < 4) P.xq[L] = (L & 1) ? make_map_q(px, 16, 8) : make_map_q(px, 8, 32);
  }
  P.o = make_map(p_o, S_LEN, DM);
  for (int t = 0; t < 2; t++) {
    P.wqkv[t] = make_map(P.wqkv_p[t], DM, NQKV);
    P.wqkv3[t] = make_map3(P.wqkv_p[t], DM, NQKV, 3, 1024);
    P.wo3[t] = make_map3(P.wo_p[t], DM, DM, 2, 64);
  }
  fused_kernel<<<NCTA, 512, SMEM_BYTES>>>(P);
}
```

```cpp
#include <cuda_runtime.h>
#include <cuda_bf16.h>
#include <cuda.h>
#include <stdint.h>

namespace {

constexpr int S_LEN = 2048;
constexpr int DM = 1024;
constexpr int NQKV = 3072;
constexpr int NCTA = 128;

__device__ __align__(1024) uint8_t g_kvA[16][16][2][16384];
__device__ __align__(1024) uint8_t g_kvB[16][16][4096];
__device__ __align__(1024) uint8_t g_zero[16384];
__device__ __align__(1024) __nv_bfloat16 g_o[S_LEN * DM];
__device__ __align__(1024) __nv_bfloat16 g_x[S_LEN * DM];
__device__ __align__(1024) float4 g_stats[8][S_LEN];
__device__ __align__(1024) float4 g_cs[2][16][8][64];
__device__ __align__(128) unsigned g_fx[16][16][4];
__device__ __align__(128) unsigned g_fo[32][16][4];
__device__ __align__(128) unsigned g_fk[16][16][4];
__device__ __align__(128) unsigned g_done[32];

constexpr uint32_t SBASE = 1024;
constexpr int UNIT = 8192;
constexpr int NUNITS = 20;
constexpr int OFF_SLOT = NUNITS * UNIT;
constexpr int OFF_BAR = OFF_SLOT + 4 * 16384;
constexpr int OFF_EPOCH = OFF_BAR + 424;
constexpr int OFF_LSB = OFF_BAR + 432;
constexpr int OFF_CS = OFF_BAR + 496;
constexpr int OFF_RS = OFF_CS + 1536;
constexpr int OFF_ONE = OFF_RS + 1024;
constexpr int SMEM_BYTES = OFF_ONE + 16;
constexpr int B_QF = 0, B_WF = 4, B_RF = 12, B_E = 13, B_PREP = 26, B_LOC = 28, B_HALO = 29, B_REL = 33, B_OS0 = 36,
              B_TURN = 37, B_XS = 39, B_CS = 41, B_CSD = 42, B_GO = 43, B_PRE = 44, B_HV = 45, B_REDO = 46,
              B_RDONE = 48, B_PRE2 = 49, B_HL = 50, B_KV = 52, B_OS1 = B_GO;
static_assert(SMEM_BYTES <= 232448, "shared memory");

__device__ __forceinline__ uint32_t smem_u32(const void* p) { return (uint32_t)__cvta_generic_to_shared(p); }

__device__ __forceinline__ void mbar_init(uint32_t bar, uint32_t cnt) {
  asm volatile("mbarrier.init.shared::cta.b64 [%0], %1;" ::"r"(bar), "r"(cnt));
}
__device__ __forceinline__ void mbar_expect_tx(uint32_t bar, uint32_t bytes) {
  asm volatile("mbarrier.arrive.expect_tx.shared::cta.b64 _, [%0], %1;" ::"r"(bar), "r"(bytes) : "memory");
}
__device__ __forceinline__ void mbar_arrive(uint32_t bar) {
  asm volatile("mbarrier.arrive.shared::cta.b64 _, [%0];" ::"r"(bar) : "memory");
}
__device__ __forceinline__ bool mbar_try_wait(uint32_t bar, uint32_t parity) {
  uint32_t ok;
  asm volatile(
      "{\n.reg .pred p;\nmbarrier.try_wait.parity.shared::cta.b64 p, [%1], %2;\nselp.b32 %0, 1, 0, p;\n}\n"
      : "=r"(ok)
      : "r"(bar), "r"(parity)
      : "memory");
  return ok != 0;
}
__device__ __forceinline__ bool mbar_test(uint32_t bar, uint32_t parity) {
  uint32_t ok;
  asm volatile(
      "{\n.reg .pred p;\nmbarrier.test_wait.parity.shared::cta.b64 p, [%1], %2;\nselp.b32 %0, 1, 0, p;\n}\n"
      : "=r"(ok)
      : "r"(bar), "r"(parity)
      : "memory");
  return ok != 0;
}
__device__ __forceinline__ void mbar_wait(uint32_t bar, uint32_t parity) {
#pragma unroll 1
  for (uint32_t it = 0; it < (1u << 18); ++it) {
    if (mbar_try_wait(bar, parity)) return;
  }
}
__device__ __forceinline__ void mbar_pace(uint32_t bar, uint32_t parity) {
#pragma unroll 1
  for (uint32_t it = 0; it < 24; ++it) {
    if (mbar_try_wait(bar, parity)) return;
  }
}
template <int NS>
__device__ __forceinline__ void mbar_wait_lazy(uint32_t bar, uint32_t parity) {
#pragma unroll 1
  for (uint32_t it = 0; it < (1u << 18); ++it) {
    if (mbar_try_wait(bar, parity)) return;
    __nanosleep(NS);
  }
}
__device__ __forceinline__ bool elect_one() {
  uint32_t ok;
  asm volatile("{\n.reg .pred p;\nelect.sync _|p, 0xffffffff;\nselp.b32 %0, 1, 0, p;\n}\n" : "=r"(ok));
  return ok != 0;
}
__device__ __forceinline__ void fence_barrier_init() { asm volatile("fence.mbarrier_init.release.cluster;" ::: "memory"); }
__device__ __forceinline__ void fence_proxy_async_smem() { asm volatile("fence.proxy.async.shared::cta;" ::: "memory"); }

__device__ __forceinline__ void signal_async(uint32_t bar, bool lane0) {
  fence_proxy_async_smem();
  __syncwarp();
  asm volatile("{\n.reg .pred p;\nsetp.ne.b32 p, %1, 0;\n@p mbarrier.arrive.shared::cta.b64 _, [%0];\n}\n" ::"r"(bar), "r"((int)lane0) : "memory");
}
template <class T>
__device__ __forceinline__ void pin64(T*& p) { asm volatile("" : "+l"(p)); }

__device__ __forceinline__ void tma_load_2d(uint32_t dst, const CUtensorMap* map, uint32_t bar, int c0, int c1) {
  asm volatile(
      "cp.async.bulk.tensor.2d.shared::cluster.global.mbarrier::complete_tx::bytes [%0], [%1, {%3, %4}], [%2];" ::"r"(dst),
      "l"(map), "r"(bar), "r"(c0), "r"(c1)
      : "memory");
}
__device__ __forceinline__ void tma_load_3d(uint32_t dst, const CUtensorMap* map, uint32_t bar, int c0, int c1) {
  asm volatile(
      "cp.async.bulk.tensor.3d.shared::cluster.global.mbarrier::complete_tx::bytes [%0], [%1, {%3, %4, %5}], [%2];" ::"r"(dst),
      "l"(map), "r"(bar), "r"(c0), "r"(c1), "r"(0)
      : "memory");
}
__device__ __forceinline__ void tma_load_5d(uint32_t dst, const CUtensorMap* map, uint32_t bar, int c0, int c4) {
  asm volatile(
      "cp.async.bulk.tensor.5d.shared::cluster.global.mbarrier::complete_tx::bytes [%0], [%1, {%3, %5, %5, %5, %4}], [%2];" ::"r"(dst),
      "l"(map), "r"(bar), "r"(c0), "r"(c4), "r"(0)
      : "memory");
}
__device__ __forceinline__ void bulk_load(uint32_t dst, const void* src, uint32_t bytes, uint32_t bar) {
  asm volatile("cp.async.bulk.shared::cluster.global.mbarrier::complete_tx::bytes [%0], [%1], %2, [%3];" ::"r"(dst),
               "l"(src), "r"(bytes), "r"(bar)
               : "memory");
}
__device__ __forceinline__ void bulk_store(void* dst, uint32_t src, uint32_t bytes) {
  asm volatile("cp.async.bulk.global.shared::cta.bulk_group [%0], [%1], %2;" ::"l"(dst), "r"(src), "r"(bytes) : "memory");
}
__device__ __forceinline__ void tma_store_2d(const CUtensorMap* map, uint32_t src, int c0, int c1) {
  asm volatile("cp.async.bulk.tensor.2d.global.shared::cta.bulk_group [%0, {%2, %3}], [%1];" ::"l"(map), "r"(src),
               "r"(c0), "r"(c1)
               : "memory");
}
__device__ __forceinline__ void bulk_announce(unsigned* p) {
  asm volatile("cp.reduce.async.bulk.global.shared::cta.bulk_group.add.u32 [%0], [%1], 16;" ::"l"(p), "r"(SBASE + OFF_ONE) : "memory");
}
__device__ __forceinline__ void bulk_commit() { asm volatile("cp.async.bulk.commit_group;" ::: "memory"); }
__device__ __forceinline__ void bulk_wait_read0() { asm volatile("cp.async.bulk.wait_group.read 0;" ::: "memory"); }
__device__ __forceinline__ void bulk_wait0() { asm volatile("cp.async.bulk.wait_group 0;" ::: "memory"); }
__device__ __forceinline__ void named_bar_sync(int id, int nthreads) {
  asm volatile("bar.sync %0, %1;" ::"r"(id), "r"(nthreads) : "memory");
}
__device__ __forceinline__ void named_bar_arrive(int id, int nthreads) {
  asm volatile("bar.arrive %0, %1;" ::"r"(id), "r"(nthreads) : "memory");
}

__device__ __forceinline__ void wgmma_fence() { asm volatile("wgmma.fence.sync.aligned;\n" ::: "memory"); }
__device__ __forceinline__ void wgmma_commit() { asm volatile("wgmma.commit_group.sync.aligned;\n" ::: "memory"); }
template <int N>
__device__ __forceinline__ void wgmma_wait() {
  asm volatile("wgmma.wait_group.sync.aligned %0;\n" ::"n"(N) : "memory");
}
template <int R>
__device__ __forceinline__ void setmaxnreg_inc() { asm volatile("setmaxnreg.inc.sync.aligned.u32 %0;\n" ::"n"(R)); }
template <int R>
__device__ __forceinline__ void setmaxnreg_dec() { asm volatile("setmaxnreg.dec.sync.aligned.u32 %0;\n" ::"n"(R)); }
template <int N>
__device__ __forceinline__ void reg_fence(float* r) {
#pragma unroll
  for (int i = 0; i < N; i++) asm volatile("" : "+f"(r[i])::"memory");
}

template <int N>
__device__ __forceinline__ void reg_define(float* r) {
#pragma unroll
  for (int i = 0; i < N; i++) r[i] = 0.f;
}

__device__ __forceinline__ uint64_t desc_lo(uint32_t lo) {
  uint64_t d;
  asm("mov.b64 %0, {%1, %2};" : "=l"(d) : "r"(lo), "r"(0x40000040u));
  return d;
}
__device__ __forceinline__ uint64_t make_desc(uint32_t addr, uint32_t lbo_bytes) {
  return desc_lo((addr >> 4) + ((lbo_bytes >> 4) << 16));
}

__device__ __forceinline__ void wgmma_n192_ss_ta0_tb1(float* d, uint64_t descA, uint64_t descB, int scaleD) {
  asm volatile("{\n.reg .pred p;\nsetp.ne.b32 p, %98, 0;\n"
    "wgmma.mma_async.sync.aligned.m64n192k16.f32.bf16.bf16 {%0, %1, %2, %3, %4, %5, %6, %7, %8, %9, %10, %11, %12, %13, %14, %15, %16, %17, %18, %19, %20, %21, %22, %23, %24, %25, %26, %27, %28, %29, %30, %31, %32, %33, %34, %35, %36, %37, %38, %39, %40, %41, %42, %43, %44, %45, %46, %47, %48, %49, %50, %51, %52, %53, %54, %55, %56, %57, %58, %59, %60, %61, %62, %63, %64, %65, %66, %67, %68, %69, %70, %71, %72, %73, %74, %75, %76, %77, %78, %79, %80, %81, %82, %83, %84, %85, %86, %87, %88, %89, %90, %91, %92, %93, %94, %95}, %96, %97, p, 1, 1, 0, 1;\n}\n"
    : "+f"(d[0]), "+f"(d[1]), "+f"(d[2]), "+f"(d[3]), "+f"(d[4]), "+f"(d[5]), "+f"(d[6]), "+f"(d[7]), "+f"(d[8]), "+f"(d[9]), "+f"(d[10]), "+f"(d[11]), "+f"(d[12]), "+f"(d[13]), "+f"(d[14]), "+f"(d[15]), "+f"(d[16]), "+f"(d[17]), "+f"(d[18]), "+f"(d[19]), "+f"(d[20]), "+f"(d[21]), "+f"(d[22]), "+f"(d[23]), "+f"(d[24]), "+f"(d[25]), "+f"(d[26]), "+f"(d[27]), "+f"(d[28]), "+f"(d[29]), "+f"(d[30]), "+f"(d[31]), "+f"(d[32]), "+f"(d[33]), "+f"(d[34]), "+f"(d[35]), "+f"(d[36]), "+f"(d[37]), "+f"(d[38]), "+f"(d[39]), "+f"(d[40]), "+f"(d[41]), "+f"(d[42]), "+f"(d[43]), "+f"(d[44]), "+f"(d[45]), "+f"(d[46]), "+f"(d[47]), "+f"(d[48]), "+f"(d[49]), "+f"(d[50]), "+f"(d[51]), "+f"(d[52]), "+f"(d[53]), "+f"(d[54]), "+f"(d[55]), "+f"(d[56]), "+f"(d[57]), "+f"(d[58]), "+f"(d[59]), "+f"(d[60]), "+f"(d[61]), "+f"(d[62]), "+f"(d[63]), "+f"(d[64]), "+f"(d[65]), "+f"(d[66]), "+f"(d[67]), "+f"(d[68]), "+f"(d[69]), "+f"(d[70]), "+f"(d[71]), "+f"(d[72]), "+f"(d[73]), "+f"(d[74]), "+f"(d[75]), "+f"(d[76]), "+f"(d[77]), "+f"(d[78]), "+f"(d[79]), "+f"(d[80]), "+f"(d[81]), "+f"(d[82]), "+f"(d[83]), "+f"(d[84]), "+f"(d[85]), "+f"(d[86]), "+f"(d[87]), "+f"(d[88]), "+f"(d[89]), "+f"(d[90]), "+f"(d[91]), "+f"(d[92]), "+f"(d[93]), "+f"(d[94]), "+f"(d[95])
    : "l"(descA), "l"(descB), "r"(scaleD));
}

__device__ __forceinline__ void wgmma_n128_ss_ta0_tb1(float* d, uint64_t descA, uint64_t descB, int scaleD) {
  asm volatile("{\n.reg .pred p;\nsetp.ne.b32 p, %66, 0;\n"
    "wgmma.mma_async.sync.aligned.m64n128k16.f32.bf16.bf16 {%0, %1, %2, %3, %4, %5, %6, %7, %8, %9, %10, %11, %12, %13, %14, %15, %16, %17, %18, %19, %20, %21, %22, %23, %24, %25, %26, %27, %28, %29, %30, %31, %32, %33, %34, %35, %36, %37, %38, %39, %40, %41, %42, %43, %44, %45, %46, %47, %48, %49, %50, %51, %52, %53, %54, %55, %56, %57, %58, %59, %60, %61, %62, %63}, %64, %65, p, 1, 1, 0, 1;\n}\n"
    : "+f"(d[0]), "+f"(d[1]), "+f"(d[2]), "+f"(d[3]), "+f"(d[4]), "+f"(d[5]), "+f"(d[6]), "+f"(d[7]), "+f"(d[8]), "+f"(d[9]), "+f"(d[10]), "+f"(d[11]), "+f"(d[12]), "+f"(d[13]), "+f"(d[14]), "+f"(d[15]), "+f"(d[16]), "+f"(d[17]), "+f"(d[18]), "+f"(d[19]), "+f"(d[20]), "+f"(d[21]), "+f"(d[22]), "+f"(d[23]), "+f"(d[24]), "+f"(d[25]), "+f"(d[26]), "+f"(d[27]), "+f"(d[28]), "+f"(d[29]), "+f"(d[30]), "+f"(d[31]), "+f"(d[32]), "+f"(d[33]), "+f"(d[34]), "+f"(d[35]), "+f"(d[36]), "+f"(d[37]), "+f"(d[38]), "+f"(d[39]), "+f"(d[40]), "+f"(d[41]), "+f"(d[42]), "+f"(d[43]), "+f"(d[44]), "+f"(d[45]), "+f"(d[46]), "+f"(d[47]), "+f"(d[48]), "+f"(d[49]), "+f"(d[50]), "+f"(d[51]), "+f"(d[52]), "+f"(d[53]), "+f"(d[54]), "+f"(d[55]), "+f"(d[56]), "+f"(d[57]), "+f"(d[58]), "+f"(d[59]), "+f"(d[60]), "+f"(d[61]), "+f"(d[62]), "+f"(d[63])
    : "l"(descA), "l"(descB), "r"(scaleD));
}

__device__ __forceinline__ void wgmma_n192_ssz_ta0_tb1(float* d, uint64_t descA, uint64_t descB) {
  asm volatile("{\n.reg .pred p;\nsetp.ne.b32 p, 0, 0;\n"
    "wgmma.mma_async.sync.aligned.m64n192k16.f32.bf16.bf16 {%0, %1, %2, %3, %4, %5, %6, %7, %8, %9, %10, %11, %12, %13, %14, %15, %16, %17, %18, %19, %20, %21, %22, %23, %24, %25, %26, %27, %28, %29, %30, %31, %32, %33, %34, %35, %36, %37, %38, %39, %40, %41, %42, %43, %44, %45, %46, %47, %48, %49, %50, %51, %52, %53, %54, %55, %56, %57, %58, %59, %60, %61, %62, %63, %64, %65, %66, %67, %68, %69, %70, %71, %72, %73, %74, %75, %76, %77, %78, %79, %80, %81, %82, %83, %84, %85, %86, %87, %88, %89, %90, %91, %92, %93, %94, %95}, %96, %97, p, 1, 1, 0, 1;\n}\n"
    : "=f"(d[0]), "=f"(d[1]), "=f"(d[2]), "=f"(d[3]), "=f"(d[4]), "=f"(d[5]), "=f"(d[6]), "=f"(d[7]), "=f"(d[8]), "=f"(d[9]), "=f"(d[10]), "=f"(d[11]), "=f"(d[12]), "=f"(d[13]), "=f"(d[14]), "=f"(d[15]), "=f"(d[16]), "=f"(d[17]), "=f"(d[18]), "=f"(d[19]), "=f"(d[20]), "=f"(d[21]), "=f"(d[22]), "=f"(d[23]), "=f"(d[24]), "=f"(d[25]), "=f"(d[26]), "=f"(d[27]), "=f"(d[28]), "=f"(d[29]), "=f"(d[30]), "=f"(d[31]), "=f"(d[32]), "=f"(d[33]), "=f"(d[34]), "=f"(d[35]), "=f"(d[36]), "=f"(d[37]), "=f"(d[38]), "=f"(d[39]), "=f"(d[40]), "=f"(d[41]), "=f"(d[42]), "=f"(d[43]), "=f"(d[44]), "=f"(d[45]), "=f"(d[46]), "=f"(d[47]), "=f"(d[48]), "=f"(d[49]), "=f"(d[50]), "=f"(d[51]), "=f"(d[52]), "=f"(d[53]), "=f"(d[54]), "=f"(d[55]), "=f"(d[56]), "=f"(d[57]), "=f"(d[58]), "=f"(d[59]), "=f"(d[60]), "=f"(d[61]), "=f"(d[62]), "=f"(d[63]), "=f"(d[64]), "=f"(d[65]), "=f"(d[66]), "=f"(d[67]), "=f"(d[68]), "=f"(d[69]), "=f"(d[70]), "=f"(d[71]), "=f"(d[72]), "=f"(d[73]), "=f"(d[74]), "=f"(d[75]), "=f"(d[76]), "=f"(d[77]), "=f"(d[78]), "=f"(d[79]), "=f"(d[80]), "=f"(d[81]), "=f"(d[82]), "=f"(d[83]), "=f"(d[84]), "=f"(d[85]), "=f"(d[86]), "=f"(d[87]), "=f"(d[88]), "=f"(d[89]), "=f"(d[90]), "=f"(d[91]), "=f"(d[92]), "=f"(d[93]), "=f"(d[94]), "=f"(d[95])
    : "l"(descA), "l"(descB));
}

__device__ __forceinline__ void wgmma_n8_ss_ta1_tb0(float* d, uint64_t descA, uint64_t descB, int scaleD) {
  asm volatile("{\n.reg .pred p;\nsetp.ne.b32 p, %6, 0;\n"
    "wgmma.mma_async.sync.aligned.m64n8k16.f32.bf16.bf16 {%0, %1, %2, %3}, %4, %5, p, 1, 1, 1, 0;\n}\n"
    : "+f"(d[0]), "+f"(d[1]), "+f"(d[2]), "+f"(d[3])
    : "l"(descA), "l"(descB), "r"(scaleD));
}

__device__ __forceinline__ void wgmma_n8_ssz_ta1_tb0(float* d, uint64_t descA, uint64_t descB) {
  asm volatile("{\n.reg .pred p;\nsetp.ne.b32 p, 0, 0;\n"
    "wgmma.mma_async.sync.aligned.m64n8k16.f32.bf16.bf16 {%0, %1, %2, %3}, %4, %5, p, 1, 1, 1, 0;\n}\n"
    : "=f"(d[0]), "=f"(d[1]), "=f"(d[2]), "=f"(d[3])
    : "l"(descA), "l"(descB));
}

__device__ __forceinline__ void wgmma_n192_rs_tb1(float* d, const uint32_t* a, uint64_t descB, int scaleD) {
  asm volatile("{\n.reg .pred p;\nsetp.ne.b32 p, %101, 0;\n"
    "wgmma.mma_async.sync.aligned.m64n192k16.f32.bf16.bf16 {%0, %1, %2, %3, %4, %5, %6, %7, %8, %9, %10, %11, %12, %13, %14, %15, %16, %17, %18, %19, %20, %21, %22, %23, %24, %25, %26, %27, %28, %29, %30, %31, %32, %33, %34, %35, %36, %37, %38, %39, %40, %41, %42, %43, %44, %45, %46, %47, %48, %49, %50, %51, %52, %53, %54, %55, %56, %57, %58, %59, %60, %61, %62, %63, %64, %65, %66, %67, %68, %69, %70, %71, %72, %73, %74, %75, %76, %77, %78, %79, %80, %81, %82, %83, %84, %85, %86, %87, %88, %89, %90, %91, %92, %93, %94, %95}, {%96, %97, %98, %99}, %100, p, 1, 1, 1;\n}\n"
    : "+f"(d[0]), "+f"(d[1]), "+f"(d[2]), "+f"(d[3]), "+f"(d[4]), "+f"(d[5]), "+f"(d[6]), "+f"(d[7]), "+f"(d[8]), "+f"(d[9]), "+f"(d[10]), "+f"(d[11]), "+f"(d[12]), "+f"(d[13]), "+f"(d[14]), "+f"(d[15]), "+f"(d[16]), "+f"(d[17]), "+f"(d[18]), "+f"(d[19]), "+f"(d[20]), "+f"(d[21]), "+f"(d[22]), "+f"(d[23]), "+f"(d[24]), "+f"(d[25]), "+f"(d[26]), "+f"(d[27]), "+f"(d[28]), "+f"(d[29]), "+f"(d[30]), "+f"(d[31]), "+f"(d[32]), "+f"(d[33]), "+f"(d[34]), "+f"(d[35]), "+f"(d[36]), "+f"(d[37]), "+f"(d[38]), "+f"(d[39]), "+f"(d[40]), "+f"(d[41]), "+f"(d[42]), "+f"(d[43]), "+f"(d[44]), "+f"(d[45]), "+f"(d[46]), "+f"(d[47]), "+f"(d[48]), "+f"(d[49]), "+f"(d[50]), "+f"(d[51]), "+f"(d[52]), "+f"(d[53]), "+f"(d[54]), "+f"(d[55]), "+f"(d[56]), "+f"(d[57]), "+f"(d[58]), "+f"(d[59]), "+f"(d[60]), "+f"(d[61]), "+f"(d[62]), "+f"(d[63]), "+f"(d[64]), "+f"(d[65]), "+f"(d[66]), "+f"(d[67]), "+f"(d[68]), "+f"(d[69]), "+f"(d[70]), "+f"(d[71]), "+f"(d[72]), "+f"(d[73]), "+f"(d[74]), "+f"(d[75]), "+f"(d[76]), "+f"(d[77]), "+f"(d[78]), "+f"(d[79]), "+f"(d[80]), "+f"(d[81]), "+f"(d[82]), "+f"(d[83]), "+f"(d[84]), "+f"(d[85]), "+f"(d[86]), "+f"(d[87]), "+f"(d[88]), "+f"(d[89]), "+f"(d[90]), "+f"(d[91]), "+f"(d[92]), "+f"(d[93]), "+f"(d[94]), "+f"(d[95])
    : "r"(a[0]), "r"(a[1]), "r"(a[2]), "r"(a[3]), "l"(descB), "r"(scaleD));
}

__device__ __forceinline__ void wgmma_n80_rs_tb0(float* d, const uint32_t* a, uint64_t descB, int scaleD) {
  asm volatile("{\n.reg .pred p;\nsetp.ne.b32 p, %45, 0;\n"
    "wgmma.mma_async.sync.aligned.m64n80k16.f32.bf16.bf16 {%0, %1, %2, %3, %4, %5, %6, %7, %8, %9, %10, %11, %12, %13, %14, %15, %16, %17, %18, %19, %20, %21, %22, %23, %24, %25, %26, %27, %28, %29, %30, %31, %32, %33, %34, %35, %36, %37, %38, %39}, {%40, %41, %42, %43}, %44, p, 1, 1, 0;\n}\n"
    : "+f"(d[0]), "+f"(d[1]), "+f"(d[2]), "+f"(d[3]), "+f"(d[4]), "+f"(d[5]), "+f"(d[6]), "+f"(d[7]), "+f"(d[8]), "+f"(d[9]), "+f"(d[10]), "+f"(d[11]), "+f"(d[12]), "+f"(d[13]), "+f"(d[14]), "+f"(d[15]), "+f"(d[16]), "+f"(d[17]), "+f"(d[18]), "+f"(d[19]), "+f"(d[20]), "+f"(d[21]), "+f"(d[22]), "+f"(d[23]), "+f"(d[24]), "+f"(d[25]), "+f"(d[26]), "+f"(d[27]), "+f"(d[28]), "+f"(d[29]), "+f"(d[30]), "+f"(d[31]), "+f"(d[32]), "+f"(d[33]), "+f"(d[34]), "+f"(d[35]), "+f"(d[36]), "+f"(d[37]), "+f"(d[38]), "+f"(d[39])
    : "r"(a[0]), "r"(a[1]), "r"(a[2]), "r"(a[3]), "l"(descB), "r"(scaleD));
}

__device__ __forceinline__ void wgmma_n80_rsz_tb0(float* d, const uint32_t* a, uint64_t descB) {
  asm volatile("{\n.reg .pred p;\nsetp.ne.b32 p, 0, 0;\n"
    "wgmma.mma_async.sync.aligned.m64n80k16.f32.bf16.bf16 {%0, %1, %2, %3, %4, %5, %6, %7, %8, %9, %10, %11, %12, %13, %14, %15, %16, %17, %18, %19, %20, %21, %22, %23, %24, %25, %26, %27, %28, %29, %30, %31, %32, %33, %34, %35, %36, %37, %38, %39}, {%40, %41, %42, %43}, %44, p, 1, 1, 0;\n}\n"
    : "=f"(d[0]), "=f"(d[1]), "=f"(d[2]), "=f"(d[3]), "=f"(d[4]), "=f"(d[5]), "=f"(d[6]), "=f"(d[7]), "=f"(d[8]), "=f"(d[9]), "=f"(d[10]), "=f"(d[11]), "=f"(d[12]), "=f"(d[13]), "=f"(d[14]), "=f"(d[15]), "=f"(d[16]), "=f"(d[17]), "=f"(d[18]), "=f"(d[19]), "=f"(d[20]), "=f"(d[21]), "=f"(d[22]), "=f"(d[23]), "=f"(d[24]), "=f"(d[25]), "=f"(d[26]), "=f"(d[27]), "=f"(d[28]), "=f"(d[29]), "=f"(d[30]), "=f"(d[31]), "=f"(d[32]), "=f"(d[33]), "=f"(d[34]), "=f"(d[35]), "=f"(d[36]), "=f"(d[37]), "=f"(d[38]), "=f"(d[39])
    : "r"(a[0]), "r"(a[1]), "r"(a[2]), "r"(a[3]), "l"(descB));
}

__device__ __forceinline__ void wgmma_n32_rs_tb1(float* d, const uint32_t* a, uint64_t descB, int scaleD) {
  asm volatile("{\n.reg .pred p;\nsetp.ne.b32 p, %21, 0;\n"
    "wgmma.mma_async.sync.aligned.m64n32k16.f32.bf16.bf16 {%0, %1, %2, %3, %4, %5, %6, %7, %8, %9, %10, %11, %12, %13, %14, %15}, {%16, %17, %18, %19}, %20, p, 1, 1, 1;\n}\n"
    : "+f"(d[0]), "+f"(d[1]), "+f"(d[2]), "+f"(d[3]), "+f"(d[4]), "+f"(d[5]), "+f"(d[6]), "+f"(d[7]), "+f"(d[8]), "+f"(d[9]), "+f"(d[10]), "+f"(d[11]), "+f"(d[12]), "+f"(d[13]), "+f"(d[14]), "+f"(d[15])
    : "r"(a[0]), "r"(a[1]), "r"(a[2]), "r"(a[3]), "l"(descB), "r"(scaleD));
}

__device__ __forceinline__ void wgmma_n32_rsz_tb1(float* d, const uint32_t* a, uint64_t descB) {
  asm volatile("{\n.reg .pred p;\nsetp.ne.b32 p, 0, 0;\n"
    "wgmma.mma_async.sync.aligned.m64n32k16.f32.bf16.bf16 {%0, %1, %2, %3, %4, %5, %6, %7, %8, %9, %10, %11, %12, %13, %14, %15}, {%16, %17, %18, %19}, %20, p, 1, 1, 1;\n}\n"
    : "=f"(d[0]), "=f"(d[1]), "=f"(d[2]), "=f"(d[3]), "=f"(d[4]), "=f"(d[5]), "=f"(d[6]), "=f"(d[7]), "=f"(d[8]), "=f"(d[9]), "=f"(d[10]), "=f"(d[11]), "=f"(d[12]), "=f"(d[13]), "=f"(d[14]), "=f"(d[15])
    : "r"(a[0]), "r"(a[1]), "r"(a[2]), "r"(a[3]), "l"(descB));
}

__device__ __forceinline__ void wgmma_n32_rs_tb0(float* d, const uint32_t* a, uint64_t descB, int scaleD) {
  asm volatile("{\n.reg .pred p;\nsetp.ne.b32 p, %21, 0;\n"
    "wgmma.mma_async.sync.aligned.m64n32k16.f32.bf16.bf16 {%0, %1, %2, %3, %4, %5, %6, %7, %8, %9, %10, %11, %12, %13, %14, %15}, {%16, %17, %18, %19}, %20, p, 1, 1, 0;\n}\n"
    : "+f"(d[0]), "+f"(d[1]), "+f"(d[2]), "+f"(d[3]), "+f"(d[4]), "+f"(d[5]), "+f"(d[6]), "+f"(d[7]), "+f"(d[8]), "+f"(d[9]), "+f"(d[10]), "+f"(d[11]), "+f"(d[12]), "+f"(d[13]), "+f"(d[14]), "+f"(d[15])
    : "r"(a[0]), "r"(a[1]), "r"(a[2]), "r"(a[3]), "l"(descB), "r"(scaleD));
}

__device__ __forceinline__ void wgmma_n32_rsz_tb0(float* d, const uint32_t* a, uint64_t descB) {
  asm volatile("{\n.reg .pred p;\nsetp.ne.b32 p, 0, 0;\n"
    "wgmma.mma_async.sync.aligned.m64n32k16.f32.bf16.bf16 {%0, %1, %2, %3, %4, %5, %6, %7, %8, %9, %10, %11, %12, %13, %14, %15}, {%16, %17, %18, %19}, %20, p, 1, 1, 0;\n}\n"
    : "=f"(d[0]), "=f"(d[1]), "=f"(d[2]), "=f"(d[3]), "=f"(d[4]), "=f"(d[5]), "=f"(d[6]), "=f"(d[7]), "=f"(d[8]), "=f"(d[9]), "=f"(d[10]), "=f"(d[11]), "=f"(d[12]), "=f"(d[13]), "=f"(d[14]), "=f"(d[15])
    : "r"(a[0]), "r"(a[1]), "r"(a[2]), "r"(a[3]), "l"(descB));
}

__device__ __forceinline__ uint32_t pack_bf16x2(float lo, float hi) {
  uint32_t r;
  asm("cvt.rn.bf16x2.f32 %0, %1, %2;" : "=r"(r) : "f"(hi), "f"(lo));
  return r;
}
__device__ __forceinline__ float bf_lo(uint32_t p) { return __uint_as_float(p << 16); }
__device__ __forceinline__ float bf_hi(uint32_t p) { return __uint_as_float(p & 0xffff0000u); }
__device__ __forceinline__ float bf16_round(float v) { return __bfloat162float(__float2bfloat16_rn(v)); }
__device__ __forceinline__ float ex2_approx(float x) {
  float r;
  asm("ex2.approx.ftz.f32 %0, %1;" : "=f"(r) : "f"(x));
  return r;
}
__device__ __forceinline__ float rcp_fast(float x) {
  float r;
  asm("rcp.approx.ftz.f32 %0, %1;" : "=f"(r) : "f"(x));
  return r;
}
__device__ __forceinline__ void ldmatrix_x4(uint32_t (&r)[4], uint32_t addr) {
  asm volatile("ldmatrix.sync.aligned.m8n8.x4.shared.b16 {%0,%1,%2,%3}, [%4];"
               : "=r"(r[0]), "=r"(r[1]), "=r"(r[2]), "=r"(r[3])
               : "r"(addr)
               : "memory");
}
__device__ __forceinline__ void stmatrix_x4(uint32_t addr, uint32_t r0, uint32_t r1, uint32_t r2, uint32_t r3) {
  asm volatile("stmatrix.sync.aligned.m8n8.x4.shared.b16 [%0], {%1,%2,%3,%4};" ::"r"(addr), "r"(r0), "r"(r1), "r"(r2),
               "r"(r3));
}
__device__ __forceinline__ uint32_t add_bf16x2(uint32_t a, uint32_t b) {
  uint32_t r;
  asm("add.rn.bf16x2 %0, %1, %2;" : "=r"(r) : "r"(a), "r"(b));
  return r;
}
__device__ __forceinline__ uint4 lds128(uint32_t addr) {
  uint4 v;
  asm volatile("ld.shared.v4.b32 {%0,%1,%2,%3}, [%4];" : "=r"(v.x), "=r"(v.y), "=r"(v.z), "=r"(v.w) : "r"(addr) : "memory");
  return v;
}
__device__ __forceinline__ uint32_t lds32(uint32_t addr) {
  uint32_t v;
  asm volatile("ld.shared.b32 %0, [%1];" : "=r"(v) : "r"(addr) : "memory");
  return v;
}
__device__ __forceinline__ void sts32(uint32_t addr, uint32_t v) {
  asm volatile("st.shared.b32 [%0], %1;" ::"r"(addr), "r"(v) : "memory");
}

__device__ __forceinline__ int fresh_tid() {
  int t;
  asm volatile("mov.u32 %0, %%tid.x;" : "=r"(t));
  return t;
}
__device__ __forceinline__ unsigned ld_relaxed_u32(const void* p) {
  unsigned v;
  asm volatile("ld.relaxed.gpu.global.u32 %0, [%1];" : "=r"(v) : "l"(p) : "memory");
  return v;
}
__device__ __forceinline__ unsigned launch_epoch() { return (*(volatile unsigned*)g_done) / NCTA + 1u; }
__device__ __forceinline__ uint32_t set_tag(uint32_t w, uint32_t m, uint32_t tag) { return (w & ~m) | (tag & m); }
__device__ __forceinline__ uint32_t o_tag(int L) { return (L + 1) & 1; }
__device__ __forceinline__ uint32_t x_tag(int L) { return L & 1; }
__device__ __forceinline__ uint32_t kv_tag(int L) { return L < 2; }

#define SPINT 0
template <class F>
__device__ __forceinline__ void fix_lines(uint32_t bar, uint32_t par, uint32_t ta, uint32_t tag, uint32_t mask, int bar_id, F line) {
  uint32_t m;
  mbar_wait(bar, par);
  m = lds32(ta);
  m = __ballot_sync(0xffffffffu, (m ^ tag) & mask);
  if (m == 0u) return;
#pragma unroll 1
  for (uint32_t it = 0; it < (1u << 17) && m != 0u; ++it) {
    const int l = __ffs(m) - 1, j = fresh_tid() & 7;
    uint4 v;
    asm volatile("ld.relaxed.gpu.global.v4.b32 {%0,%1,%2,%3}, [%4];" : "=r"(v.x), "=r"(v.y), "=r"(v.z), "=r"(v.w) : "l"(line(l) + j * 8) : "memory");
    const uint32_t a = __shfl_sync(0xffffffffu, ta, l) ^ (j << 4);
    if (((__shfl_sync(0xffffffffu, v.x, 0) ^ tag) & 1u) == 0u) {
      asm volatile("st.shared.v4.b32 [%0], {%1,%2,%3,%4};" ::"r"(a), "r"(v.x), "r"(v.y), "r"(v.z), "r"(v.w) : "memory");
      m &= m - 1u;
    }
  }
  fence_proxy_async_smem();
  named_bar_sync(bar_id, 32);
}
__device__ __forceinline__ uint32_t peek_counts(const unsigned* f, unsigned target, int lane) {
  return __ballot_sync(0xffffffffu, (int)(ld_relaxed_u32(f + (lane & 15) * 4) - target) >= 0);
}
__device__ __forceinline__ void wait_count(const unsigned* f, unsigned target, int i, uint32_t& seen, int lane) {
  if ((seen >> i) & 1u) return;
#pragma unroll 1
  for (uint32_t it = 0; it < (1u << 17); ++it) {
    seen = peek_counts(f, target, lane);
    if ((seen >> i) & 1u) break;
  }
}
__device__ __forceinline__ float4 ld_rec(const float4* p) {
  float4 v;
  asm volatile("ld.relaxed.gpu.global.v4.f32 {%0,%1,%2,%3}, [%4];" : "=f"(v.x), "=f"(v.y), "=f"(v.z), "=f"(v.w) : "l"(p) : "memory");
  return v;
}
__device__ __forceinline__ void st_rec(float4* p, float a, float b, float c, unsigned tag) {
  asm volatile("st.relaxed.gpu.global.v4.f32 [%0], {%1,%2,%3,%4};" ::"l"(p), "f"(a), "f"(b), "f"(c), "f"(__uint_as_float(tag)) : "memory");
}
template <int N>
__device__ __forceinline__ float4 sum_recs(const float4* p, int stride, unsigned tag) {
  float4 s;
#pragma unroll 1
  for (uint32_t it = 0; it < (1u << 17); ++it) {
    float4 v[N];
#pragma unroll
    for (int t = 0; t < N; t++) v[t] = ld_rec(p + t * stride);
    bool ok = true;
    s = make_float4(0.f, 0.f, 0.f, 0.f);
#pragma unroll
    for (int t = 0; t < N; t++) {
      ok &= __float_as_uint(v[t].w) == tag;
      s.x += v[t].x;
      s.y += v[t].y;
      s.z += v[t].z;
    }
    if (ok) break;
    __nanosleep(200);
  }
  return s;
}

#define PHASE_IDS                                  \
  const int tid_ = fresh_tid();                    \
  const int lane = tid_ & 31, wwarp = __shfl_sync(0xffffffffu, (tid_ >> 5) & 3, 0), tid = tid_ & 127; \
  const int g = lane >> 2, c = lane & 3;           \
  (void)tid; (void)g; (void)c; (void)wwarp;

#define PHASE_IDS_W                                \
  const int lane = fresh_tid() & 31, wwarp = warp & 3; \
  const int g = lane >> 2, c = lane & 3;

#define GTL(i) do { } while (0)
#define TGET(v) do { } while (0)
#define TPUT(c, i, v) do { } while (0)

constexpr float SM_C = 0.17677669529663687f * 1.4426950408889634f;

__device__ __forceinline__ void stmatrix_x4_if(bool ok, uint32_t addr, uint32_t r0, uint32_t r1, uint32_t r2, uint32_t r3) {
  asm volatile("{\n.reg .pred p;\nsetp.ne.b32 p, %5, 0;\n@p stmatrix.sync.aligned.m8n8.x4.shared.b16 [%0], {%1,%2,%3,%4};\n}\n" ::"r"(addr),
               "r"(r0), "r"(r1), "r"(r2), "r"(r3), "r"((int)ok));
}

__device__ __forceinline__ void attn_a_slow(const uint8_t* __restrict__ kvimg, int L, int gb, int hp, uint32_t bad,
                                            int row0, int lane) {
  constexpr uint32_t sq = SBASE + OFF_SLOT + 3 * 16384;
#pragma unroll 1
  for (int j = 0; j < 8; j++) {
    const uint8_t* tp = kvimg + (size_t)(gb * 16 + hp) * 32768 + (j * 32 + lane) * 128 + ((lane & 7) << 4);
#pragma unroll 1
    for (uint32_t it = 0; it < (1u << 17); ++it)
      if (((ld_relaxed_u32(tp) ^ kv_tag(L)) & 1u) == 0u) break;
  }
  __syncwarp();
#pragma unroll 1
  for (int t = 0; t < 32; t++) {
    const int hh = t >> 4, row = row0 + (t & 7) + (t & 8) * 4;
    if (!((bad >> hh) & 1u)) continue;
    const int qpos = gb * 128 + row;
    const uint32_t qaddr = sq + row * 128;
    float mx = -INFINITY, sum = 0.f, acc = 0.f;
#pragma unroll 1
    for (int pass = 0; pass < 2; pass++) {
#pragma unroll 1
      for (int j = 0; j < 8; j++) {
        const int kp = qpos - (lane + 32 * j);
        const uint8_t* kr = kvimg + ((size_t)((kp >> 7) * 16 + hp) * 2 + ((kp >> 6) & 1)) * 16384 + (kp & 63) * 128;
        float d = -INFINITY;
        if (kp >= 0) {
          d = 0.f;
#pragma unroll 1
          for (int q = 0; q < 4; q++) {
            const uint4 kv = __ldcg(reinterpret_cast<const uint4*>(kr + (((hh * 4 + q) ^ (kp & 7)) << 4)));
            const uint4 qv = lds128(qaddr + (((hh * 4 + q) ^ (row & 7)) << 4));
            const uint32_t kw[4] = {kv.x, kv.y, kv.z, kv.w}, qw[4] = {qv.x, qv.y, qv.z, qv.w};
#pragma unroll
            for (int e = 0; e < 4; e++) d = fmaf(bf_lo(kw[e]), bf_lo(qw[e]), fmaf(bf_hi(kw[e]), bf_hi(qw[e]), d));
          }
        }
        if (pass == 0) {
          mx = fmaxf(mx, d);
        } else {
          const float ev = ex2_approx(d - mx);
          sum += ev;
          const float pv = bf16_round(ev);
#pragma unroll 1
          for (int kk = 0; kk < 32; kk++) {
            const float pk = __shfl_sync(0xffffffffu, pv, kk);
            const int k2 = qpos - (kk + 32 * j);
            if (k2 >= 0) {
              const uint8_t* vr = kvimg + ((size_t)((k2 >> 7) * 16 + hp) * 2 + ((k2 >> 6) & 1)) * 16384 + 8192 + (k2 & 63) * 128;
              const unsigned short vv =
                  __ldcg(reinterpret_cast<const unsigned short*>(vr + (((hh * 4 + (lane >> 3)) ^ (k2 & 7)) << 4) + (lane & 7) * 2));
              acc = fmaf(pk, __uint_as_float((uint32_t)vv << 16), acc);
            }
          }
        }
      }
      if (pass == 0) {
#pragma unroll
        for (int o = 16; o > 0; o >>= 1) mx = fmaxf(mx, __shfl_xor_sync(0xffffffffu, mx, o));
      }
    }
#pragma unroll
    for (int o = 16; o > 0; o >>= 1) sum += __shfl_xor_sync(0xffffffffu, sum, o);
    acc *= rcp_fast(sum);
    const float hi = __shfl_down_sync(0xffffffffu, acc, 1);
    __syncwarp();
    if ((lane & 1) == 0) sts32(qaddr + (((hh * 4 + (lane >> 3)) ^ (row & 7)) << 4) + (lane & 7) * 2,
                               set_tag(pack_bf16x2(acc, hi), hh == 0 && lane == 0, o_tag(L)));
    __syncwarp();
  }
}

template <int HH>
__device__ __forceinline__ void store_o(const float (&o)[16], const float (&inv)[2], uint32_t ra, uint32_t tag, bool ok) {
  const uint32_t m = HH == 0 && (fresh_tid() & 3) == 0;
#pragma unroll
  for (int jp = 0; jp < 2; jp++) {
    uint32_t w0 = pack_bf16x2(o[8 * jp] * inv[0], o[8 * jp + 1] * inv[0]);
    uint32_t w1 = pack_bf16x2(o[8 * jp + 2] * inv[1], o[8 * jp + 3] * inv[1]);
    if (HH == 0 && jp == 0) {
      w0 = set_tag(w0, m, tag);
      w1 = set_tag(w1, m, tag);
    }
    stmatrix_x4_if(ok, ra ^ ((HH * 4 + 2 * jp) << 4), w0, w1, pack_bf16x2(o[8 * jp + 4] * inv[0], o[8 * jp + 5] * inv[0]),
                   pack_bf16x2(o[8 * jp + 6] * inv[1], o[8 * jp + 7] * inv[1]));
  }
}
__device__ __forceinline__ int tile_row(bool B, int w, int r, int g) { return (B ? 16 * w + 8 * r : 8 * w + 32 * r) + g; }
__device__ __forceinline__ uint32_t q_row_addr(bool B, int R, int w, int lane) {
  return SBASE + OFF_SLOT + 3 * 16384 + R * 8192 + tile_row(B, w, (lane >> 3) & 1, lane & 7) * 128 + (((lane >> 4) ^ (lane & 7)) << 4);
}

struct AttnA {
  float s[2][16], o[2][16], l[2][2], sh[2][3];
  uint32_t p[2][4], t[2], me[4], ra, bad, zero;
};
#define ATS_(i) do { } while (0)
template <int V>
__device__ __forceinline__ void attn_sum(AttnA& a, int nv) {
  constexpr int hh = (V >> 1) & 1, kh = V & 1, i = V >> 2;
#pragma unroll
  for (int r = 0; r < 2; r++) {
    const uint32_t t1 = add_bf16x2(add_bf16x2(a.p[0][r], a.p[0][2 + r]), add_bf16x2(a.p[1][r], a.p[1][2 + r]));
    if (kh == 0) {
      a.t[r] = t1;
    } else {
      uint32_t tt = add_bf16x2(a.t[r], t1);
      if (i > 0) tt = i <= nv ? tt : 0u;
      const float v = bf_lo(tt) + bf_hi(tt);
      a.l[hh][r] = i == 0 ? v : a.l[hh][r] + v;
    }
  }
}
template <int HH>
__device__ __forceinline__ void attn_shfl(AttnA& a) {
#pragma unroll
  for (int r = 0; r < 2; r++)
#pragma unroll
    for (int j = 0; j < 3; j++) a.sh[r][j] = __shfl_xor_sync(0xffffffffu, a.l[HH][r], j + 1);
}
template <int HH>
__device__ __forceinline__ void attn_fin(AttnA& a) {
  bool bad = false;
  float inv[2];
#pragma unroll
  for (int r = 0; r < 2; r++) {
    const float v = (a.l[HH][r] + a.sh[r][0]) + (a.sh[r][1] + a.sh[r][2]);
    bad |= !(v <= 1.152921504606846976e18f && v >= 8.673617379884035e-19f);
    inv[r] = rcp_fast(v);
  }
  bad = __any_sync(0xffffffffu, bad);
  if (HH == 1) wgmma_wait<0>();
  reg_fence<16>(a.o[HH]);
  store_o<HH>(a.o[HH], inv, a.ra, o_tag(0), !bad);
  a.bad = (HH == 0 ? 0u : a.bad) | (bad ? 1u << HH : 0u);
}
__device__ __forceinline__ void attn_masks(AttnA& a, int wr) {
  const int lane = fresh_tid() & 31, d = (lane >> 2) - 2 * (lane & 3);
  const uint32_t tri = d >= 1 ? 0xffffffffu : (d == 0 ? 0xffffu : 0u);
#pragma unroll
  for (int t = 0; t < 4; t++) a.me[t] = wr > t ? 0xffffffffu : (wr == t ? tri : 0u);
}
template <int V, int K>
__device__ __forceinline__ uint32_t attn_exp(AttnA& a) {
  constexpr int i = V >> 2, kh = V & 1, r = K & 1;
  if ((i == 0 && kh > r) || (i == 4 && kh < r)) return 0u;
  const uint32_t w = pack_bf16x2(ex2_approx(a.s[V & 1][2 * K]), ex2_approx(a.s[V & 1][2 * K + 1]));
  if (i == 0 && kh == r) return w & a.me[K >> 1];
  if (i == 4 && kh == r) return w & ~a.me[K >> 1];
  return w;
}
template <int V>
__device__ __forceinline__ void attn_unit(AttnA& a, const uint32_t (&q)[2][2][4], uint64_t dcur, uint64_t dnext, int R, int wr, int nv,
                                          uint32_t hbar, uint32_t hpar, uint32_t rbar, bool rel) {
  constexpr int hh = (V >> 1) & 1, kh = V & 1, i = V >> 2;
  ATS_(V + 1);
  asm volatile("" : "+l"(dcur), "+l"(dnext));
  wgmma_wait<1>();
  reg_fence<16>(a.s[V & 1]);
  bool hok = true;
  if (V == 4) hbar = SBASE + OFF_BAR + 8u * (R ? B_LOC : B_HV);
  if (((V & 3) == 2 && V < 16) || V == 4) hok = mbar_test(hbar, hpar);
  const uint64_t d0 = ((V & 3) >= 2 ? dnext : dcur) + ((hh ^ 1) * 4 + kh * 256), d1 = ((V & 3) >= 2 ? dnext : dcur) + ((hh ^ 1) * 4 + kh * 256 + 2);
  const uint64_t d2 = dcur + (512 + hh * 4 + kh * 256), d3 = dcur + (640 + hh * 4 + kh * 256);
  if ((V & 3) == 1 && V > 4 && rel) mbar_arrive(rbar);
  if (V > 0) attn_sum<V - 1>(a, nv);
  if (V == 15) attn_masks(a, wr);
  if (V == 18) {
    attn_shfl<0>(a);
    a.ra = q_row_addr(false, R, wr, fresh_tid() & 31);
  }
  if (V == 19) attn_fin<0>(a);
  uint32_t p[2][4];
  p[0][0] = attn_exp<V, 0>(a);
  p[0][1] = attn_exp<V, 1>(a);
  p[0][2] = attn_exp<V, 2>(a);
  p[0][3] = attn_exp<V, 3>(a);
  p[1][0] = attn_exp<V, 4>(a);
  p[1][1] = attn_exp<V, 5>(a);
  p[1][2] = attn_exp<V, 6>(a);
  p[1][3] = attn_exp<V, 7>(a);
  if (V > 0) {
#pragma unroll
    for (int r = 0; r < 2; r++) p[1][r] ^= (kh ? a.t[r] : __float_as_uint(a.l[hh ^ 1][r])) & a.zero;
  }
#pragma unroll
  for (int k = 0; k < 8; k++) {
    asm volatile("" : "+r"(p[k >> 2][k & 3]));
    a.p[k >> 2][k & 3] = p[k >> 2][k & 3];
  }
  if (!hok) mbar_wait(hbar, hpar);
  wgmma_fence();
  if (V < 18) wgmma_n32_rsz_tb0(a.s[V & 1], q[hh ^ 1][0], d0);
  if (i == 0 && kh == 0) wgmma_n32_rsz_tb1(a.o[hh], a.p[0], d2);
  else wgmma_n32_rs_tb1(a.o[hh], a.p[0], d2, 1);
  if (V < 18) wgmma_n32_rs_tb0(a.s[V & 1], q[hh ^ 1][1], d1, 1);
  wgmma_n32_rs_tb1(a.o[hh], a.p[1], d3, 1);
  wgmma_commit();
}
template <int I>
__device__ __forceinline__ void attn_step(AttnA& a, const uint32_t (&q)[2][2][4], uint64_t dcur, uint64_t dnext, int R, int wr, int nv,
                                          uint32_t hbar, uint32_t hpar, uint32_t rbar, bool rel) {
  attn_unit<4 * I>(a, q, dcur, dnext, R, wr, nv, hbar, hpar, rbar, rel);
  attn_unit<4 * I + 1>(a, q, dcur, dnext, R, wr, nv, hbar, hpar, rbar, rel);
  attn_unit<4 * I + 2>(a, q, dcur, dnext, R, wr, nv, hbar, hpar, rbar, rel);
  attn_unit<4 * I + 3>(a, q, dcur, dnext, R, wr, nv, hbar, hpar, rbar, rel);
}

__device__ __forceinline__ void attention_a(const uint32_t (&q)[2][2][4], int R, int L, int gb, int hp, uint32_t par, int wr,
                                            uint32_t zero) {
  constexpr uint32_t bars = SBASE + OFF_BAR;
  constexpr uint32_t dslot = ((SBASE + OFF_SLOT) >> 4) + 0x10000u;
  auto next = [&](uint64_t d) { return desc_lo((uint32_t)d == dslot ? dslot + 2048 : (uint32_t)d - 1024) + zero; };
  uint64_t d0 = desc_lo(dslot + R * 1024) + zero, d1 = next(d0);
  AttnA a;
  ATS_(0);
  wgmma_fence();
#pragma unroll
  for (int v = 0; v < 2; v++) {
    wgmma_n32_rsz_tb0(a.s[v], q[0][0], d0 + v * 256);
    wgmma_n32_rs_tb0(a.s[v], q[0][1], d0 + (v * 256 + 2), 1);
    wgmma_commit();
  }
  a.zero = zero;
  const bool lane0 = (fresh_tid() & 31) == 0;
  attn_masks(a, wr);
  const int nv = 2 * gb + R;
  const uint32_t hb = bars + 8u * (B_HALO - R), rb = bars + 8u * (B_REL - R);
  attn_step<0>(a, q, d0, d1, R, wr, nv, hb, par, 0, false);
  d0 = next(d1);
  attn_step<1>(a, q, d1, d0, R, wr, nv, R ? bars + 8u * B_HV : hb + 8, par, rb + 8, lane0);
  d1 = next(d0);
  attn_step<2>(a, q, d0, d1, R, wr, nv, hb + 16, par, rb + 16, lane0);
  d0 = next(d1);
  attn_step<3>(a, q, d1, d0, R, wr, nv, hb + 24, par, rb + 24, lane0 && R);
  attn_step<4>(a, q, d0, d0, R, wr, nv, 0, 0, rb, false);
  ATS_(21);
  attn_sum<19>(a, nv);
  attn_shfl<1>(a);
  attn_fin<1>(a);
  ATS_(22);
  if (a.bad != 0u) {
    attn_a_slow(g_kvA[0][0][0], L, gb, hp, a.bad, R * 64 + wr * 8, fresh_tid() & 31);
    named_bar_sync(7, 32);
  }
}

constexpr uint32_t KB_ROW0 = SBASE + OFF_SLOT + 2048, VB_ROW0 = SBASE + OFF_SLOT + 24576 + 2048;

__device__ __forceinline__ void attention_b(const uint32_t (&q)[2][2][4], int R, int gb, uint32_t par0, int wr) {
  constexpr uint32_t bars = SBASE + OFF_BAR;
  const uint32_t dk = ((KB_ROW0 - 2048) >> 4) + 0x10000u + R * 512, dv = dk + ((VB_ROW0 - KB_ROW0) >> 4);
  float s[2][40];
  mbar_wait(bars + 8u * (B_HALO - R), par0);
  wgmma_fence();
#pragma unroll
  for (int hh = 0; hh < 2; hh++) {
    wgmma_n80_rsz_tb0(s[hh], q[hh][0], desc_lo(dk + hh * 4));
    wgmma_n80_rs_tb0(s[hh], q[hh][1], desc_lo(dk + hh * 4 + 2), 1);
  }
  wgmma_commit();
  const int lane = fresh_tid() & 31, g = lane >> 2;
  const bool odd = g & 1, edge = R == 0 && gb == 0 && wr == 0;
  const int D = 2 * (lane & 3) + (g & 1) - g;
  const uint32_t ra = q_row_addr(true, R, wr, lane);
  wgmma_wait<0>();
  reg_fence<40>(s[0]);
  reg_fence<40>(s[1]);
  float z[2][2], y[2][2];
#define GATHER_(W)                                                                                          \
  _Pragma("unroll") for (int hh = 0; hh < 2; hh++) _Pragma("unroll") for (int r = 0; r < 2; r++) {          \
    const float* e = &s[hh][4 * (2 * W + r) + 2 * r];                                                       \
    z[hh][r] = odd ? e[5] : e[4];                                                                           \
    y[hh][r] = D >= 2 ? (odd ? e[1] : e[0]) : (odd ? e[9] : e[8]);                                          \
  }
  if (wr < 2) {
    if (wr == 0) { GATHER_(0) } else { GATHER_(1) }
  } else {
    if (wr == 2) { GATHER_(2) } else { GATHER_(3) }
  }
#undef GATHER_
  float o[2][16], inv[2][2];
  uint32_t p[2][5][4];
  const int sh = odd ? 16 : 0, kb = wr + (D >= 2 ? 0 : 1);
#pragma unroll
  for (int hh = 0; hh < 2; hh++) {
    if (edge) {
      z[hh][0] = -INFINITY;
      if (D >= 2) y[hh][0] = y[hh][1] = -INFINITY;
    }
    uint32_t ab[2][2];
#pragma unroll
    for (int r = 0; r < 2; r++) {
      float m = fmaxf(z[hh][r], y[hh][r]);
      m = fmaxf(m, __shfl_xor_sync(0xffffffffu, m, 1));
      m = fmaxf(m, __shfl_xor_sync(0xffffffffu, m, 2));
      const float e0 = ex2_approx(z[hh][r] - m), e1 = ex2_approx(y[hh][r] - m);
      inv[hh][r] = e0 + e1;
      ab[r][0] = pack_bf16x2(e0, 0.f) << sh;
      ab[r][1] = pack_bf16x2(e1, 0.f) << sh;
    }
#pragma unroll
    for (int k = 0; k < 5; k++) {
      p[hh][k][0] = k == kb ? ab[0][1] : 0u;
      p[hh][k][1] = k == wr + 1 ? ab[1][0] : 0u;
      p[hh][k][2] = k == wr ? ab[0][0] : 0u;
      p[hh][k][3] = k == kb ? ab[1][1] : 0u;
#pragma unroll
      for (int j = 0; j < 4; j++) asm volatile("" : "+r"(p[hh][k][j]));
    }
  }
  wgmma_fence();
#pragma unroll
  for (int hh = 0; hh < 2; hh++) {
    wgmma_n32_rsz_tb1(o[hh], p[hh][0], desc_lo(dv + hh * 4));
#pragma unroll
    for (int k = 1; k < 5; k++) wgmma_n32_rs_tb1(o[hh], p[hh][k], desc_lo(dv + hh * 4 + k * 128), 1);
  }
  wgmma_commit();
#pragma unroll
  for (int hh = 0; hh < 2; hh++)
#pragma unroll
    for (int r = 0; r < 2; r++) {
      inv[hh][r] += __shfl_xor_sync(0xffffffffu, inv[hh][r], 1);
      inv[hh][r] += __shfl_xor_sync(0xffffffffu, inv[hh][r], 2);
      inv[hh][r] = rcp_fast(inv[hh][r]);
    }
  wgmma_wait<0>();
  reg_fence<16>(o[0]);
  reg_fence<16>(o[1]);
  store_o<0>(o[0], inv[0], ra, o_tag(1), true);
  store_o<1>(o[1], inv[1], ra, o_tag(1), true);
}

#define KTQM 0
#define TRICKLE 300
#define WTURN 15
#define QREL 8
#define PRESLEEP 200
#define CSA 3
#define TLAZY 100
#define SDLY 1500
#define HTS(i) do { } while (0)
struct Params {
  CUtensorMap x[5], xq[4], o, wqkv[2], wqkv3[2], wo3[2];
  const __nv_bfloat16* in_x;
  const __nv_bfloat16* wqkv_p[2];
  const __nv_bfloat16* wo_p[2];
  __nv_bfloat16* out;
  uint32_t zero;
};

__device__ __forceinline__ void colsum_part(const CUtensorMap* wmap, int ty, int qr, int hp) {
  constexpr uint32_t bars = SBASE + OFF_BAR, slots = SBASE + OFF_SLOT;
  PHASE_IDS
  const unsigned ep1 = launch_epoch();
  if (wwarp == 0 && elect_one()) {
    mbar_expect_tx(bars + 8u * B_CS, 6 * UNIT);
#pragma unroll 1
    for (int j = 0; j < 6; j++) {
      if (ty == 0) mbar_pace(bars + 8u * (B_QF + B_E + ((j * CSA / 6) & 3)), (j * CSA / 6) >> 2);
      else mbar_wait_lazy<100>(bars + 8u * (B_WF + B_E + ((2 * j + 3 - (j & 1)) & 7)), j >= 3);
      tma_load_2d(slots + j * UNIT, wmap, bars + 8u * B_CS, (j >> 1) * 1024 + hp * 64, qr * 128 + (j & 1) * 64);
    }
  }
  constexpr uint64_t ones = (SBASE + OFF_LSB + 32) >> 4;
  float s[3][4];
  mbar_wait_lazy<100>(bars + 8u * B_CS, ty);
  wgmma_fence();
#pragma unroll
  for (int p = 0; p < 3; p++) {
    wgmma_n8_ssz_ta1_tb0(s[p], make_desc(slots + p * 2 * UNIT, 16), ones);
#pragma unroll
    for (int k = 1; k < 8; k++) wgmma_n8_ss_ta1_tb0(s[p], make_desc(slots + p * 2 * UNIT + k * 2048, 16), ones, 1);
  }
  wgmma_commit();
  wgmma_wait<0>();
  reg_fence<12>(&s[0][0]);
  if (lane == 0) mbar_arrive(bars + 8u * (ty ? B_CSD : B_RDONE));
  if (c == 0) {
#pragma unroll
    for (int r = 0; r < 2; r++) st_rec(&g_cs[ty][hp][qr][wwarp * 16 + 8 * r + g], s[0][2 * r], s[1][2 * r], s[2][2 * r], ep1);
  }
}

__device__ __forceinline__ void put_colsums(int ty, int col, const float4& s) {
  const float v[3] = {s.x, s.y, s.z};
#pragma unroll
  for (int p = 0; p < 3; p++) {
    const uint32_t a = SBASE + OFF_CS + (p * 8 + (col >> 3)) * 64 + ty * 32 + (col & 7) * 2;
    const float hi = bf16_round(v[p]);
    const uint32_t w = pack_bf16x2(hi, v[p] - hi);
    asm volatile("st.shared.b16 [%0], %1;" ::"r"(a), "h"((unsigned short)w) : "memory");
    asm volatile("st.shared.b16 [%0], %1;" ::"r"(a + 16), "h"((unsigned short)(w >> 16)) : "memory");
  }
}

__device__ __forceinline__ uint32_t ln_params(float s1, float s2) {
  const float mean = s1 * (1.0f / DM);
  const float var = fmaxf(fmaf(-mean, mean, s2 * (1.0f / DM)), 0.f);
  float sd;
  asm("sqrt.approx.f32 %0, %1;" : "=f"(sd) : "f"(bf16_round(bf16_round(var) + 1e-5f)));
  return pack_bf16x2(mean, sd);
}

__host__ __device__ constexpr uint32_t w_rel(int kt) { return ((B_WF + (kt & 7)) << 1) | (kt >> 3); }
__host__ __device__ constexpr uint32_t w_rel4(int a, int b, int c, int d) { return w_rel(a) | (w_rel(b) << 8) | (w_rel(c) << 16) | (w_rel(d) << 24); }
__device__ __forceinline__ void ring_wait(uint32_t e) { mbar_wait(SBASE + OFF_BAR + 8u * B_E + ((e << 2) & 0x3f8u), e & 1u); }
struct RingProd {
  uint32_t rel = ((B_QF << 1) | 1) * 0x01010101u + 0x06040200u;
  __device__ __forceinline__ void q_step(int kt) {
    const int sh = 8 * (kt & 3);
    const uint32_t e = rel >> sh;
    rel ^= ((e ^ (((B_QF + (kt & 3)) << 1) | ((kt >> 2) & 1))) & 255u) << sh;
    ring_wait(e);
  }
  __device__ __forceinline__ void w_job(int st, bool pre, uint32_t sel0, uint32_t sel1, uint32_t last, uint32_t& w0, uint32_t& w1) {
    const uint32_t r = __funnelshift_r(rel, rel, 8 * st);
    w0 = __byte_perm(r, 0u, sel0);
    w1 = __byte_perm(r, w_rel4(0, 1, 2, 3), pre ? sel1 : 0x6543u);
    const uint32_t n = pre ? (w_rel4(9, 11, 13, 0) & 0xffffffu) | (last << 24) : (w_rel4(11, 13, 0, 15) & 0xff00ffffu) | (last << 16);
    rel = __funnelshift_l(n, n, 8 * st);
  }
};

#define SP1 15
#define SP2 14
#define SP3 12
#define SP4 12
#define SP5 15
#define SP6 14
#define SP7 16
__device__ __forceinline__ int q_split(int inst) {
  constexpr uint32_t T = 15u | ((SP1 - 1) << 4) | ((SP2 - 1) << 8) | ((SP3 - 1) << 12) | ((SP4 - 1) << 16) | ((SP5 - 1) << 20) |
                         ((SP6 - 1) << 24) | ((uint32_t)(SP7 - 1) << 28);
  return (int)((T >> (4 * inst)) & 15u) + 1;
}
#define QROT 0
#define WROT 0
__device__ __forceinline__ int qk(int kt) { return (kt + QROT) & 15; }
__device__ __forceinline__ int wk(int kt) { return (kt + WROT) & 15; }
__host__ __device__ constexpr uint32_t turn_par(int kind) {
  const int sp[8] = {16, SP1, SP2, SP3, SP4, SP5, SP6, SP7};
  int cnt[2] = {0, 0};
  uint32_t m = 0;
  for (int i = 0; i < 8; i++)
    for (int k = 0; k < 3; k++) {
      if (k == kind) m |= (uint32_t)(cnt[i & 1] & 1) << i;
      if (k == 0 ? (i == 1 || (i > 1 && sp[i - 1] < 16)) : (k == 2 || sp[i] < 16)) cnt[i & 1]++;
    }
  return m;
}
#define PREMASK 0xBFu
__device__ __forceinline__ bool w_pre(int inst) { return (PREMASK >> inst) & 1u; }
__host__ __device__ constexpr unsigned long long bar_counts(int i0) {
  unsigned long long t = 0;
  for (int i = i0; i < i0 + 32; i++) {
    int l = 0;
    if (i < B_RF) l = 1;
    if ((i >= B_E && i < B_E + B_RF) || i == B_LOC || i == B_REL || i == B_OS0 || i == B_TURN || i == B_TURN + 1 || i == B_XS ||
        i == B_XS + 1 || i == B_CSD || i == B_GO || i == B_RDONE || i == B_KV)
      l = 2;
    if (i == B_REL + 1 || i == B_REL + 2) l = 3;
    t |= (unsigned long long)l << (2 * (i - i0));
  }
  return t;
}

__global__ void __launch_bounds__(512, 1) fused_kernel(const __grid_constant__ Params P) {
  extern __shared__ __align__(1024) uint8_t smem_raw[];
  constexpr uint32_t base = SBASE, bars = base + OFF_BAR, slots = base + OFF_SLOT;
  if (smem_u32(smem_raw) != base) __trap();
  const int warp = __shfl_sync(0xffffffffu, threadIdx.x >> 5, 0), lane = threadIdx.x & 31;
  const int b = blockIdx.x;
#define QS 0
#define WS 1
  const int qr = ((b & ((8 << QS) - 1)) >> QS) ^ (((b >> (3 + QS)) & 1) * 7);
  const int hp = ((b >> (3 + QS)) << QS) + (b & ((1 << QS) - 1));
  const int rt = ((b & ((16 << WS) - 1)) >> WS) ^ (((b >> (4 + WS)) & 1) * 15);
  const int ct = ((b >> (4 + WS)) << WS) + (b & ((1 << WS) - 1));

  if (warp == 12) {
    if (elect_one()) {
#pragma unroll 1
      for (int s = 0; s < 4; s++) {
        const uint32_t fb = bars + 8u * (B_QF + s), sa = base + s * 5 * UNIT;
        mbar_init(fb, 2);
        fence_barrier_init();
        mbar_expect_tx(fb, 5 * UNIT);
        mbar_arrive(fb);
        tma_load_5d(sa + 3 * UNIT, &P.xq[0], fb, s * 64, qr * 2);
        tma_load_3d(sa, &P.wqkv3[0], fb, hp * 64, s * 64);
      }
    }
    __syncwarp();
  } else if (warp >= 4 && warp < 12) {
    if (elect_one()) {
#pragma unroll 1
      for (int i = warp; i <= B_KV; i += 8) mbar_init(bars + 8u * i, 1u << (((i < 32 ? bar_counts(0) : bar_counts(32)) >> (2 * (i & 31))) & 3u));
      sts32(warp < 8 ? base + OFF_ONE - 16 + 4 * warp : base + OFF_LSB + 4 * warp, warp < 8 ? warp == 4 : 0x3f803f80u);
      fence_proxy_async_smem();
      fence_barrier_init();
    }
    __syncwarp();
  }

  if (warp >= 12) {
    setmaxnreg_dec<32>();
    if (warp == 12) {
      named_bar_sync(0, 512);
      if (elect_one()) {
#pragma unroll 1
        for (int s = 4; s < 16; s++) {
          const uint32_t fb = bars + 8u * (B_QF + (s & 3)), sa = base + (s & 3) * 5 * UNIT;
          mbar_wait(fb + 8u * B_E, ((s >> 2) & 1) ^ 1);
          mbar_expect_tx(fb, 5 * UNIT);
          mbar_arrive(fb);
          tma_load_5d(sa + 3 * UNIT, &P.xq[0], fb, s * 64, qr * 2);
          tma_load_3d(sa, &P.wqkv3[0], fb, hp * 64, s * 64);
        }
#pragma unroll
        for (int s = 0; s < 4; s++) mbar_arrive(bars + 8u * B_GO);
        RingProd rp;
#pragma unroll 1
        for (int sg = 4; sg < 34; sg++) {
          const int part = sg & 3, inst = (sg >> 2) - (part & 1);
          if (part == 3 || inst == 8) continue;
          const int ty = (inst >> 1) & 1;
          if (part != 1) {
            const int k0 = part ? q_split(inst) : 0, k1 = part ? 16 : q_split(inst);
#pragma unroll 1
            for (int kt = k0; kt < k1; kt++) {
              const uint32_t sa = base + (kt & 3) * 5 * UNIT, fb = bars + 8u * (B_QF + (kt & 3));
              rp.q_step(kt);
              mbar_expect_tx(fb, 3 * UNIT);
              tma_load_3d(sa, &P.wqkv3[ty], fb, hp * 64, qk(kt) * 64);
            }
          } else {
            const bool pre = w_pre(inst);
            int st = inst < 7 ? q_split(inst + 1) & 3 : 0;
            uint32_t w0, w1;
            rp.w_job(st, pre, pre ? 0x1100u : 0x2100u, 0x3322u, (B_RF << 1) | (inst & 1), w0, w1);
#pragma unroll 1
            for (int m = 0; m < 4; m++) {
              const uint32_t fb = bars + 8u * (B_WF + 4 * (m & 1));
#pragma unroll
              for (int i = 0; i < 4; i++) {
                ring_wait(w0 >> (8 * i));
                if (i == 3 && pre) {
                  mbar_arrive(fb + 24u);
                } else {
                  mbar_expect_tx(fb + 8u * i, 2 * UNIT);
                  tma_load_3d(base + ((st + (i ? i - 1 : 0)) & 3) * 5 * UNIT + ((0x2d >> (2 * i)) & 3) * UNIT, &P.wo3[ty], fb + 8u * i,
                              ct * 128, wk(4 * m + i) * 64);
                }
              }
              st += pre ? 2 : 3;
              w0 = w1;
              w1 = m == 0 ? (pre ? w_rel4(0, 1, 2, 3) : w_rel4(3, 4, 5, 6)) : (pre ? w_rel4(4, 5, 6, 7) : w_rel4(7, 8, 9, 10));
            }
          }
        }
      }
    } else if (warp == 13) {
      RingProd rp;
      unsigned ep1 = 0;
      uint32_t seenx = 0;
      named_bar_sync(0, 512);
      mbar_wait(bars + 8u * B_GO, 0);
#pragma unroll 1
      for (int sg = 4; sg < 34; sg++) {
        const int part = sg & 3, inst = (sg >> 2) - (part & 1);
        if (part == 3 || inst == 8) continue;
        const int L = inst >> 1, ch = inst & 1;
        if (part != 1) {
          const CUtensorMap* tx = &P.xq[L];
          const int k0 = part ? q_split(inst) : 0, k1 = part ? 16 : q_split(inst);
          if (sg == 4) ep1 = launch_epoch();
          if (part == 0) seenx = L == 0 ? 0xffffffffu : peek_counts(g_fx[ch * 8 + qr][0], 6u * ep1 - 6u + 2u * L, lane);
          const int m0 = ch * 16 + qr * 2;
#pragma unroll 1
          for (int kt = k0; kt < k1; kt++) {
            const uint32_t fb = bars + 8u * (B_QF + (kt & 3));
            rp.q_step(kt);
            if (lane == 0) mbar_expect_tx(fb, 2 * UNIT);
            wait_count(g_fx[ch * 8 + qr][0], 6u * ep1 - 6u + 2u * L, qk(kt), seenx, lane);
            TGET(t38);
            if (elect_one()) tma_load_5d(base + ((kt & 3) * 5 + 3) * UNIT, tx, fb, qk(kt) * 64, m0);
            TGET(t39);
            if (L == 3 && kt == 0 && lane == 0) { TPUT(ch, 38, t38); TPUT(ch, 39, t39); }
          }
        } else {
          const int m0 = ch * 1024 + rt * 64;
          const bool pre = w_pre(inst);
          int st = inst < 7 ? q_split(inst + 1) & 3 : 0;
          uint32_t w0, w1;
          uint32_t seen = peek_counts(g_fo[ch * 16 + rt][0], 4u * ep1 - 3u + L, lane);
          rp.w_job(st, pre, 0x1110u, 0x3332u, inst == 6 && SP7 == 16 ? B_RF << 1 : w_rel(15), w0, w1);
#pragma unroll 1
          for (int m = 0; m < 4; m++) {
            const uint32_t fb = bars + 8u * (B_WF + 4 * (m & 1));
#pragma unroll
            for (int i = 0; i < 4; i++) {
              ring_wait(w0 >> (8 * i));
              if (lane == 0) mbar_expect_tx(fb + 8u * i, UNIT);
              wait_count(g_fo[ch * 16 + rt][0], 4u * ep1 - 3u + L, wk(4 * m + i), seen, lane);
              if (elect_one())
                tma_load_2d(base + ((st + (i > 0)) & 3) * 5 * UNIT + (i == 2 ? 1 : (i == 3 ? 4 : 0)) * UNIT, &P.o, fb + 8u * i, wk(4 * m + i) * 64, m0);
            }
            st += pre ? 2 : 3;
            w0 = w1;
            w1 = m == 0 ? (pre ? w_rel4(0, 1, 2, 3) : w_rel4(3, 4, 5, 6)) : (pre ? w_rel4(4, 5, 6, 7) : w_rel4(7, 8, 9, 10));
          }
          if (L == 3) {
#pragma unroll 1
            for (int j = 0; j < 4; j++) {
              g_x[(size_t)(m0 + j * 16 + (lane >> 1)) * DM + ct * 128 + (lane & 1) * 64] = __ushort_as_bfloat16(0);
              __syncwarp();
            }
          }
        }
      }
    } else if (warp == 14) {
      const unsigned ep1 = launch_epoch();
      uint32_t hpar = 0;
      named_bar_sync(0, 512);
#pragma unroll 1
      for (int inst = 0; inst < 8; inst++) {
        const int L = inst >> 1, ch = inst & 1, gb = ch * 8 + qr;
        const unsigned kv0 = 8u * ep1 - 8u + 2u * L + (L & 1);
        const uint32_t tag = kv_tag(L);
        if (L >= 2) {
#pragma unroll 1
          for (uint32_t it = 0; it < (1u << 17); ++it)
            if (__all_sync(0xffffffffu, (int)(ld_relaxed_u32(g_fk[hp][min(gb + 1 + (lane & 1), 15)]) - kv0) >= 0)) break;
        }
        if ((L & 1) == 0) {
          uint8_t* img = g_kvA[gb][hp][0];
          const uint8_t* s1 = gb > 0 ? img - 16 * 32768 : g_zero;
          const uint8_t* s2 = gb > 1 ? img - 32 * 32768 : g_zero;
          const uint32_t h1 = gb > 0 ? 16384 : 0, h2 = gb > 1 ? 16384 : 0;
          const unsigned* cp = g_fk[hp][max(gb - 1 - (lane >= 3), 0)];
          const unsigned ct0 = kv0 + ((0x32321u >> (4 * (lane & 7))) & 3u);
          uint32_t fr = gb == 0 ? 31u : (gb == 1 ? 24u : 0u);
          const uint32_t toff = slots + lane * 128 + ((lane & 7) << 4);
          auto seen = [&](uint32_t m) {
#pragma unroll 1
            for (uint32_t it = 0; it < (1u << 17) && !(fr & m); ++it)
              fr |= __ballot_sync(0xffffffffu, (int)(ld_relaxed_u32(cp) - ct0) >= 0);
          };
          auto load = [&](uint32_t off, const uint8_t* src, uint32_t bytes, int bi) {
            if (elect_one()) {
              mbar_expect_tx(bars + 8u * (B_HL + bi), bytes);
              bulk_load(slots + off, src, bytes, bars + 8u * (B_HL + bi));
            }
          };
          auto check = [&](uint32_t off, const uint8_t* src, uint32_t bytes, int bi, bool real, int done) {
#pragma unroll 1
            for (int tries = 0; tries < 4096; tries++) {
              mbar_wait(bars + 8u * (B_HL + bi), (hpar >> bi) & 1u);
              hpar ^= 1u << bi;
              uint32_t t = (lds32(toff + off) ^ tag) | (lds32(toff + off + 4096) ^ tag);
              if (bytes > 8192) t |= (lds32(toff + off + 8192) ^ tag) | (lds32(toff + off + 12288) ^ tag);
              if (!__any_sync(0xffffffffu, real && (t & 1u))) break;
              fence_proxy_async_smem();
              load(off, src, bytes, bi);
            }
            if (lane == 0) mbar_arrive(bars + 8u * done);
          };
          uint8_t *pk = img + 16384, *pv = img + 24576;
          unsigned* f = g_fk[hp][gb];
          pin64(pk), pin64(pv), pin64(f);
          mbar_wait(bars + 8u * B_KV, inst & 1);
          if (elect_one()) {
            bulk_store(pk, slots + 16384, 8192);
            bulk_announce(f);
            bulk_store(pv, slots + 24576, 8192);
            bulk_announce(f);
            bulk_commit();
          }
          HTS(44);
          seen(1);
          HTS(46);
          load(32768, s1 + h1, 8192, 0);
          seen(2);
          HTS(47);
          load(40960, s1 + h1 + 8192, 8192, 1);
          mbar_wait(bars + 8u * B_LOC, inst & 1);
          HTS(45);
          if (elect_one()) {
            bulk_store(img, slots, 16384);
            bulk_announce(g_fk[hp][gb]);
            bulk_commit();
            asm volatile("cp.async.bulk.wait_group.read 1;" ::: "memory");
          }
          check(32768, s1 + h1, 8192, 0, gb > 0, B_HALO);
          HTS(52);
          check(40960, s1 + h1 + 8192, 8192, 1, gb > 0, B_HV);
          HTS(53);
#pragma unroll 1
          for (int n = 1; n < 4; n++) {
            const uint8_t* src = n == 1 ? s1 : (n == 2 ? s2 + h2 : s2);
            const uint32_t off = n == 3 ? 32768 : 32768 - n * 16384;
            seen(2u << n);
            if (n == 2 && elect_one()) bulk_wait_read0();
            mbar_wait(bars + 8u * (B_REL - 1) + 8u * n, ch);
            HTS(47 + n);
            load(off, src, 16384, 0);
            check(off, src, 16384, 0, gb > (n >> 1), B_HALO + n);
            HTS(53 + n);
          }
        } else {
          uint8_t *pk = g_kvB[gb][hp], *pv = pk + 2048;
          const uint8_t* src = gb >= 1 ? pk - 16 * 4096 : g_zero;
          unsigned* f = g_fk[hp][gb];
          pin64(pk), pin64(pv), pin64(f), pin64(src);
          mbar_wait(bars + 8u * B_KV, inst & 1);
          if (elect_one()) {
            bulk_store(pk, KB_ROW0 + 112 * 128, 2048);
            bulk_store(pv, VB_ROW0 + 112 * 128, 2048);
            bulk_announce(f);
            bulk_commit();
          }
          HTS(44);
          if (gb > 0) {
#pragma unroll 1
            for (uint32_t it = 0; it < (1u << 17); ++it)
              if (__any_sync(0xffffffffu, (int)(ld_relaxed_u32(f - 4) - kv0) > 0)) break;
          }
          HTS(46);
#pragma unroll 1
          for (uint32_t it = 0; it < (1u << 17); ++it) {
            if (elect_one()) {
              mbar_expect_tx(bars + 8u * B_HL, 4096);
              bulk_load(KB_ROW0 - 2048, src, 2048, bars + 8u * B_HL);
              bulk_load(VB_ROW0 - 2048, src + 2048, 2048, bars + 8u * B_HL);
            }
            mbar_wait(bars + 8u * B_HL, hpar & 1u);
            hpar ^= 1u;
            const uint32_t t = lds32((lane < 16 ? KB_ROW0 - 2048 : VB_ROW0 - 4096) + lane * 128 + ((lane & 7) << 4)) ^ tag;
            if (!__any_sync(0xffffffffu, gb > 0 && (t & 1u))) break;
            fence_proxy_async_smem();
          }
          if (lane == 0) mbar_arrive(bars + 8u * B_HALO);
          HTS(52);
        }
        if (elect_one()) {
          const CUtensorMap* mo = &P.o;
          unsigned *f1 = g_fo[gb * 2 + 1][hp], *f0 = g_fo[gb * 2][hp];
          int c0 = hp * 64, r0 = gb * 128, r1 = r0 + 64;
          pin64(mo), pin64(f1), pin64(f0);
          asm volatile("" : "+r"(c0), "+r"(r0), "+r"(r1));
          mbar_wait(bars + 8u * B_OS1, (inst & 1) ^ 1);
          tma_store_2d(mo, slots + 7 * UNIT, c0, r1);
          bulk_announce(f1);
          bulk_commit();
          mbar_wait(bars + 8u * B_OS0, inst & 1);
          tma_store_2d(mo, slots + 6 * UNIT, c0, r0);
          bulk_announce(f0);
          bulk_commit();
          HTS(57);
          bulk_wait_read0();
          HTS(58 - 15);
          mbar_expect_tx(bars + 8u * B_RF, 2 * UNIT);
          tma_load_2d(slots + 6 * UNIT, &P.x[L], bars + 8u * B_RF, ct * 128, ch * 1024 + rt * 64);
          tma_load_2d(slots + 7 * UNIT, &P.x[L], bars + 8u * B_RF, ct * 128 + 64, ch * 1024 + rt * 64);
          if (w_pre(inst)) {
            mbar_expect_tx(bars + 8u * B_PRE, 6 * UNIT);
            mbar_expect_tx(bars + 8u * B_PRE2, 2 * UNIT);
#pragma unroll 1
            for (int j = 0; j < 4; j++) {
              __nanosleep(PRESLEEP);
              if (j == 3) mbar_wait(bars + 8u * B_RDONE, (inst & 1) ^ 1);
              tma_load_3d(slots + j * 2 * UNIT, &P.wo3[L & 1], bars + 8u * (j == 3 ? B_PRE2 : B_PRE), ct * 128, wk(4 * j + 3) * 64);
            }
          }
        }
        __syncwarp();
      }
    } else {
      const unsigned ep1 = launch_epoch();
      named_bar_sync(0, 512);
      mbar_wait(bars + 8u * B_GO, 0);
#pragma unroll 1
      for (int i = 0; i < 20; i++) {
        const char* src = i < 4 ? reinterpret_cast<const char*>(P.wo_p[0]) + (size_t)b * 16384 + i * 4096
                                : (i < 16 ? reinterpret_cast<const char*>(P.wqkv_p[1]) + (size_t)b * 49152 + (i - 4) * 4096
                                          : reinterpret_cast<const char*>(P.wo_p[1]) + (size_t)b * 16384 + (i - 16) * 4096);
        asm volatile("prefetch.global.L2 [%0];" ::"l"(src + lane * 128));
        __nanosleep(TRICKLE);
      }
#pragma unroll 1
      for (int inst = 2; inst < 10; inst++) {
        const int L = inst >> 1, ch = inst & 1, gb = ch * 8 + qr;
        {
          uint32_t xb = base + (((inst < 9 ? q_split(inst - 1) : 0) + (w_pre(inst - 2) ? 3 : 2)) & 3) * 5 * UNIT;
          unsigned* f = g_fx[ch * 8 + (rt >> 1)][ct * 2];
          const CUtensorMap* mx = &P.x[L];
          int c0 = ct * 128, r0 = ch * 1024 + rt * 64;
          pin64(f), pin64(mx);
          asm volatile("" : "+r"(xb), "+r"(c0), "+r"(r0));
#pragma unroll
          for (int h = 0; h < 2; h++) {
            mbar_wait(bars + 8u * (B_XS + h), ch);
            if (elect_one()) {
              tma_store_2d(mx, xb + h * UNIT, c0 + h * 64, r0);
              if (L < 4) bulk_announce(f + 4 * h);
              bulk_commit();
              if (h == 1) {
                bulk_wait_read0();
                mbar_arrive(bars + 8u * (B_RF + B_E));
              }
            }
          }
          if (L == 4) continue;
          __nanosleep(SDLY);
        }
#pragma unroll 1
        for (int h = 0; h < 4; h++) {
          const float4* sp = &g_stats[0][gb * 128 + h * 32 + lane];
          const float4 s0 = sum_recs<4>(sp, S_LEN, 4u * ep1 + L), s1 = sum_recs<4>(sp + 4 * S_LEN, S_LEN, 4u * ep1 + L);
          sts32(base + OFF_RS + (ch * 128 + h * 32 + lane) * 4, ln_params(s0.x + s1.x, s0.y + s1.y));
        }
        if (inst == 2) {
#pragma unroll 1
          for (int hf = 0; hf < 2; hf++) {
            const float4* cp = &g_cs[1][hp][0][hf * 32 + lane];
            const float4 s0 = sum_recs<4>(cp, 64, ep1), s1 = sum_recs<4>(cp + 4 * 64, 64, ep1);
            put_colsums(1, hf * 32 + lane, make_float4(s0.x + s1.x, s0.y + s1.y, s0.z + s1.z, 0.f));
          }
        }
        fence_proxy_async_smem();
        __syncwarp();
        if (lane == 0) mbar_arrive(bars + 8u * (B_PREP + ch));
      }
    }
  } else {
    const bool asst = warp >= 8;
    GTL(0);
    if (warp >= 4) named_bar_sync(0, 512);
    if (warp >= 4 && !asst) {
      PHASE_IDS
      {
        const unsigned ep1 = launch_epoch();
        const int row = b * 16 + (tid >> 3);
        const uint4* src = reinterpret_cast<const uint4*>(P.in_x + (size_t)row * DM) + (tid & 7);
        float s1 = 0.f, s2 = 0.f;
#pragma unroll 1
        for (int k = 0; k < 4; k++) {
          mbar_pace(bars + 8u * (B_QF + B_E + ((2 * k) & 3)), k >> 1);
          uint4 v[4];
#pragma unroll
          for (int j = 0; j < 4; j++) v[j] = __ldg(src + (k * 4 + j) * 8);
#pragma unroll
          for (int j = 0; j < 4; j++) {
            const uint32_t w[4] = {v[j].x, v[j].y, v[j].z, v[j].w};
#pragma unroll
            for (int e = 0; e < 4; e++) {
              const float x0 = bf_lo(w[e]), x1 = bf_hi(w[e]);
              s1 += x0 + x1;
              s2 = fmaf(x0, x0, fmaf(x1, x1, s2));
            }
          }
        }
#pragma unroll
        for (int o = 1; o < 8; o <<= 1) {
          s1 += __shfl_xor_sync(0xffffffffu, s1, o);
          s2 += __shfl_xor_sync(0xffffffffu, s2, o);
        }
        if ((tid & 7) == 0) st_rec(&g_stats[0][row], s1, s2, 0.f, 4u * ep1);
        if (tid == 0) sts32(base + OFF_EPOCH, ep1);
        if (tid < 64) {
          const float4 s0 = sum_recs<8>(&g_cs[0][hp][0][tid], 64, ep1);
          put_colsums(0, tid, s0);
        } else {
          put_colsums(1, tid - 64, make_float4(0.f, 0.f, 0.f, 0.f));
        }
#pragma unroll 1
        for (int cc = 0; cc < 2; cc++) {
          const float4 s0 = sum_recs<1>(&g_stats[0][(cc * 8 + qr) * 128 + tid], 0, 4u * ep1);
          sts32(base + OFF_RS + (cc * 128 + tid) * 4, ln_params(s0.x, s0.y));
        }
        fence_proxy_async_smem();
        named_bar_sync(2, 128);
        if (tid < 2) mbar_arrive(bars + 8u * (B_PREP + tid));
      }
    }
#pragma unroll 1
    for (int inst = asst ? 0 : warp >> 2; inst < 8; inst += asst ? 1 : 2) {
      const int L = inst >> 1, ch = inst & 1, gb = ch * 8 + qr;
      uint32_t q[2][2][4];
      if (asst) {
        if (inst < 2) colsum_part(&P.wqkv[inst], inst, qr, hp);
        setmaxnreg_dec<24>();
        named_bar_sync(4, 256);
        setmaxnreg_inc<128>();
        const uint32_t ra = q_row_addr(L & 1, 1, warp & 3, fresh_tid() & 31);
#pragma unroll
        for (int j = 0; j < 4; j++) ldmatrix_x4(q[j >> 1][j & 1], ra ^ (j << 5));
      } else {
      setmaxnreg_inc<224>();
      {
        float acc[2][96];
        const int ksp = q_split(inst);
        constexpr uint32_t STG = 5 * (UNIT >> 4), D0 = ((base + 3 * UNIT) >> 4) + 0x10000u;
        constexpr uint32_t DB = ((UNIT >> 4) << 16) - 0x10000u - 3 * (UNIT >> 4);
        const uint32_t toff = ((fresh_tid() & 127) << 7) + ((fresh_tid() & 7) << 4);
        const bool lane0 = (toff & 0xf80u) == 0u;
        uint32_t xt = x_tag(L), tro = (warp & 3) * 2048 + (toff & 0x7f0u) + ((toff << 2) & 0x2000u);
        auto check_x = [&](uint32_t bar, uint32_t par, uint32_t ta, int kt, uint32_t mask) {
          fix_lines(bar, par, ta, xt, mask, 8 + warp, [&](int l) {
            return g_x + (size_t)(gb * 128 + (l >> 4) * 64 + tile_row(L & 1, warp & 3, (l >> 3) & 1, l & 7)) * DM + qk(kt) * 64;
          });
        };
        uint32_t rsa = base + OFF_RS + (ch * 128 + tile_row(L & 1, warp & 3, 0, (toff >> 9) & 7)) * 4;
        uint32_t rsb = rsa + ((L & 1) ? 32 : 128);
        uint32_t lnm = ((toff >> 7) & 3) == (L & 1) ? 0xffffffffu : 0u, tmk = L > 0;
        uint32_t soff = tile_row(L & 1, warp & 3, (toff >> 10) & 1, (toff >> 7) & 7) * 128 + ((toff ^ (toff >> 7)) & 0x10u) + (toff & 0x60u);
        uint32_t bprep = bars + 8u * (B_PREP + ch), bturn = bars + 8u * (B_TURN + (ch ^ 1));
        uint32_t bfree = bars + 8u * (inst == 1 ? B_CSD : B_RDONE), pfree = inst == 1 ? 0 : inst & 1, pprep = L & 1;
        asm volatile("" : "+r"(rsa), "+r"(rsb), "+r"(lnm), "+r"(soff), "+r"(xt), "+r"(tmk), "+r"(tro));
        asm volatile("" : "+r"(bprep), "+r"(bturn), "+r"(bfree), "+r"(pfree), "+r"(pprep));
        if (inst == 0) named_bar_sync(0, 512);
        if (inst == 1 || (inst > 1 && q_split(inst - 1) < 16)) mbar_wait_lazy<TLAZY>(bars + 8u * (B_TURN + ch), (turn_par(0) >> inst) & 1u);
        if (L == 3) GTL(37);
        check_x(bars + 8u * B_QF, 0, base + 3 * UNIT + tro, 0, tmk);
        GTL(1 + L * 8);
        {
          const uint64_t da = desc_lo(D0) + P.zero;
          wgmma_fence();
          wgmma_n192_ssz_ta0_tb1(acc[1], da + (UNIT >> 4), da + DB);
          wgmma_commit();
          wgmma_n192_ssz_ta0_tb1(acc[0], da, da + DB);
          wgmma_commit();
        }
        int left = ksp;
        asm volatile("" : "+r"(left));
        uint64_t da = desc_lo(D0) + P.zero, dn = da + STG;
        uint32_t fn = bars + 8u * (B_QF + 1), pn = 0, ta = base + 8 * UNIT + tro;
#pragma unroll 1
        for (int kt = 0; kt < 15; kt++) {
          bool ok, last;
          uint32_t tw;
#pragma unroll
          for (int k16 = 0; k16 < 4; k16++) {
            if (k16 == 0 && kt == 0) continue;
            wgmma_fence();
            wgmma_n192_ss_ta0_tb1(acc[1], da + ((UNIT >> 4) + k16 * 2), da + (DB + k16 * 128), 1);
            wgmma_commit();
            if (k16 == 0) {
              const int s1 = (kt + 1) & 3;
              dn = desc_lo(D0 + s1 * STG) + P.zero;
              ta = base + 3 * UNIT + s1 * 5 * UNIT + tro;
            }
            if (k16 == 1) last = --left == 0;
            if (k16 == 3) ok = !__any_sync(0xffffffffu, !ok || ((tw ^ xt) & tmk)) && !last;
            wgmma_wait<1>();
            if (k16 == 0 && lane0 && left != 0) mbar_arrive(bars + 8u * (B_QF + B_E + ((kt - 1) & 3)));
            wgmma_fence();
            wgmma_n192_ss_ta0_tb1(acc[0], da + k16 * 2, da + (DB + k16 * 128), 1);
            wgmma_commit();
            if (k16 == 0) {
              fn = bars + 8u * (B_QF + ((kt + 1) & 3));
              pn = ((kt + 1) >> 2) & 1;
            }
            if (k16 == 2) {
              ok = mbar_test(fn, pn);
              tw = lds32(ta);
              if (last && lane0) mbar_arrive(bturn);
            }
            if (k16 < 3) wgmma_wait<1>();
          }
          da = dn;
          if (!ok) {
            if (last) {
              wgmma_wait<0>();
              if (lane0) mbar_arrive(bars + 8u * (B_QF + B_E + (kt & 3)));
            }
            if (last) mbar_wait_lazy<TLAZY>(bars + 8u * (B_TURN + ch), (turn_par(1) >> inst) & 1u);
            check_x(fn, pn, ta, kt + 1, tmk);
          }
        }
        constexpr uint32_t DL = D0 + 3 * STG;
        wgmma_fence();
#pragma unroll
        for (int k16 = 0; k16 < 4; k16++) wgmma_n192_ss_ta0_tb1(acc[1], desc_lo(DL + (UNIT >> 4) + k16 * 2), desc_lo(DL + DB + k16 * 128), 1);
        wgmma_commit();
        mbar_wait(bprep, pprep);
        uint32_t rs[2][2];
        constexpr uint64_t DCS = (uint64_t)((base + OFF_CS) >> 4) | (4ull << 32);
        auto ln_mma = [&](float (&d)[96], uint32_t (&r)[2], int h) {
          uint32_t a[4];
#pragma unroll
          for (int i = 0; i < 2; i++) {
            if (h) r[i] = lds32((i ? rsb : rsa) + 256);
            a[i] = (__byte_perm(r[i], 0u, 0x1010) ^ 0x80008000u) & lnm;
            a[i + 2] = r[i] & P.zero;
          }
#pragma unroll
          for (int i = 0; i < 4; i++) asm volatile("" : "+r"(a[i]));
          wgmma_fence();
          wgmma_n192_rs_tb1(d, a, DCS, 1);
          wgmma_commit();
        };
        ln_mma(acc[1], rs[1], 1);
        wgmma_wait<2>();
        if (lane0 && ksp != 15) mbar_arrive(bars + 8u * (B_QF + B_E + 2));
        wgmma_fence();
#pragma unroll
        for (int k16 = 0; k16 < 4; k16++) wgmma_n192_ss_ta0_tb1(acc[0], desc_lo(DL + k16 * 2), desc_lo(DL + DB + k16 * 128), 1);
        wgmma_commit();
        if (lane0) mbar_arrive(bturn);
        rs[0][0] = lds32(rsa);
        rs[0][1] = lds32(rsb);
        static_assert(SP1 < 16 && (PREMASK & 1u), "column sums of B");
        const bool afree = mbar_test(bfree, pfree) & (mbar_test(bars + 8u * (B_WF + B_E + 7), 1) | (ksp == 16));
        float rinv[2];
#pragma unroll
        for (int r = 0; r < 2; r++) {
          rinv[r] = rcp_fast(bf_hi(rs[1][r]));
          asm volatile("" : "+f"(rinv[r]));
        }
        const uint32_t kdst = ((L & 1) ? KB_ROW0 : slots) + soff, vdst = ((L & 1) ? VB_ROW0 : slots + 8192) + soff;
        const uint32_t hs = (L & 1) ? 8192 : 16384, c0 = (toff & 0x180u) == 0u;
        wgmma_wait<1>();
        ln_mma(acc[0], rs[0], 0);
        reg_fence<96>(acc[1]);
        GTL(2 + L * 8);
        if (!afree) {
          mbar_wait(bfree, pfree);
          if (ksp < 16) mbar_wait(bars + 8u * (B_WF + B_E + 7), 1);
        }
#pragma unroll
        for (int t = 0; t < 24; t++) {
          const int h = t < 12 ? 1 : 0, p = ((t % 12) / 4 + 1) % 3, jp = t & 3;
          if (t == QREL) {
            wgmma_wait<0>();
            reg_fence<96>(acc[0]);
            if (lane0) mbar_arrive(bars + 8u * (B_QF + B_E + 3));
          }
          if (t == 8 || t == 20) {
            rinv[0] *= SM_C;
            rinv[1] *= SM_C;
          }
          const float* a = &acc[h][4 * (p * 8 + 2 * jp)];
          uint32_t r0 = pack_bf16x2(a[0] * rinv[0], a[1] * rinv[0]);
          uint32_t r1 = pack_bf16x2(a[2] * rinv[1], a[3] * rinv[1]);
          if (p != 0 && jp == 0) {
            r0 = set_tag(r0, c0, kv_tag(L));
            r1 = set_tag(r1, c0, kv_tag(L));
          }
          const uint32_t r2 = pack_bf16x2(a[4] * rinv[0], a[5] * rinv[0]);
          const uint32_t r3 = pack_bf16x2(a[6] * rinv[1], a[7] * rinv[1]);
          const uint32_t dst = p == 0 ? slots + 3 * 16384 + soff + h * 8192 : (p == 1 ? kdst : vdst) + h * hs;
          stmatrix_x4(dst ^ (jp << 5), r0, r1, r2, r3);
          if (t >= 20) {
            q[jp >> 1][jp & 1][0] = r0;
            q[jp >> 1][jp & 1][1] = r1;
            q[jp >> 1][jp & 1][2] = r2;
            q[jp >> 1][jp & 1][3] = r3;
          }
          if (t == 7 || t == 19) signal_async(bars + 8u * (t == 7 ? B_KV : B_LOC), lane0);
          if (t == 11) {
            setmaxnreg_dec<128>();
            named_bar_arrive(4, 256);
#pragma unroll
            for (int r = 0; r < 2; r++) rinv[r] = rcp_fast(bf_hi(rs[0][r]));
          }
        }
        mbar_wait(bars + 8u * B_LOC, inst & 1);
      }
      }
      GTL(3 + L * 8);
      if ((L & 1) == 0) attention_a(q, asst, L, gb, hp, ch, warp & 3, P.zero);
      else attention_b(q, asst, gb, inst & 1, warp & 3);
      GTL(4 + L * 8);
      signal_async(bars + 8u * (asst ? B_OS1 : B_OS0), (fresh_tid() & 31) == 0);
      if (asst) continue;
      GTL(5 + L * 8);

      {
        float acc[64];
        const int sp = inst < 7 ? q_split(inst + 1) : 0;
        int st = sp & 3;
        const bool pre = w_pre(inst);
        const uint32_t toff = ((fresh_tid() & 63) << 7) + ((fresh_tid() & 7) << 4);
        uint32_t tro = (warp & 3) * 2048 + (toff & 0x7f0u);
        auto check_o = [&](uint32_t bar, uint32_t par, uint32_t sa, int kt) {
          fix_lines(bar, par, sa + tro, o_tag(L), 1u, 8 + warp, [&](int l) {
            return g_o + (size_t)(ch * 1024 + rt * 64 + (warp & 3) * 16 + (l & 15)) * DM + wk(kt) * 64;
          });
        };
        const bool lane0 = (toff & 0xf80u) == 0u;
        constexpr uint32_t U4 = UNIT >> 4, LA = 0x10000u, LB = U4 << 16;
        reg_define<64>(acc);
        reg_fence<64>(acc);
        uint32_t xv[8][4];
        {
          PHASE_IDS_W
          const uint32_t xr = slots + 6 * UNIT + (wwarp * 16 + (lane & 15)) * 128 + (((lane >> 4) ^ (lane & 7)) << 4);
          mbar_wait(bars + 8u * B_RF, inst & 1);
#pragma unroll
          for (int jp = 0; jp < 8; jp++) ldmatrix_x4(xv[jp], (xr ^ ((jp & 3) << 5)) + (jp >> 2) * UNIT);
          signal_async(bars + 8u * B_RDONE, lane0);
          if (L > 0) {
            uint32_t lsb;
            asm volatile("ld.shared.u8 %0, [%1];" : "=r"(lsb) : "r"(base + OFF_LSB + ch * 32 + wwarp * 8 + g) : "memory");
#pragma unroll
            for (int k = 0; k < 4; k++) xv[(k >> 1) * 4][k & 1] = set_tag(xv[(k >> 1) * 4][k & 1], c == 0, lsb >> k);
          }
        }
        uint32_t tmx = L < 3 && (toff & 0x180u) == 0u, xt = x_tag(L + 1);
        uint32_t xrow = base + ((st + (pre ? 3 : 2)) & 3) * 5 * UNIT + (warp & 3) * 2048 + (toff & 0x7e0u) + ((toff ^ (toff >> 7)) & 0x10u);
        asm volatile("" : "+r"(tmx), "+r"(xt), "+r"(xrow), "+r"(tro));
        uint64_t d0 = desc_lo((base >> 4) + st * 5 * U4) + P.zero;
        if (inst < 7 || SP7 == 16) mbar_wait_lazy<TLAZY>(bars + 8u * (B_TURN + ch), (turn_par(2) >> inst) & 1u);
        check_o(bars + 8u * B_WF, 0, base + st * 5 * UNIT, 0);
        GTL(6 + L * 8);
#pragma unroll 1
        for (int m = 0; m < 4; m++) {
          const uint32_t s1 = base + ((st + 1) & 3) * 5 * UNIT, fb = bars + 8u * (B_WF + 4 * (m & 1));
          const uint64_t d1 = desc_lo(s1 >> 4) + P.zero;
          const uint64_t d2 = desc_lo((pre ? slots + m * 2 * UNIT : base + ((st + 2) & 3) * 5 * UNIT) >> 4) + P.zero;
          st = (st + (pre ? 2 : 3)) & 3;
#pragma unroll
          for (int i = 0; i < 4; i++) {
            const uint64_t da = (i == 0 ? d0 : d1) + (LA + (i == 2 ? 1 : (i == 3 ? 4 : 0)) * U4);
            const uint64_t db = (i < 2 ? d0 : (i == 2 ? d1 : d2)) + (LB + (i == 0 ? 1 : (i == 1 ? 3 : (i == 2 ? 2 : 0))) * U4);
            if (i == 3 && (m == 0 || m == 3) && pre) mbar_wait(bars + 8u * (m ? B_PRE2 : B_PRE), __popc(PREMASK & ((1u << inst) - 1u)) & 1);
            if (i == (WTURN & 3) && m == 3 && lane0 && (sp < 16 || inst == 6)) mbar_arrive(bars + 8u * (B_TURN + (ch ^ 1)));
            wgmma_fence();
#pragma unroll
            for (int k16 = 0; k16 < 4; k16++) wgmma_n128_ss_ta0_tb1(acc, da + 2 * k16, db + 128 * k16, 1);
            wgmma_commit();
            if (i == 2) d0 = desc_lo((base >> 4) + st * 5 * U4) + P.zero;
            const uint32_t fn = i < 3 ? fb + 8u * (i + 1) : fb ^ 96u;
            const uint32_t pn = i < 3 ? m >> 1 : m > 0;
            const uint32_t an = i < 3 ? s1 + (i == 1 ? 1 : (i == 2 ? 4 : 0)) * UNIT : base + st * 5 * UNIT;
            bool ok = mbar_test(fn, pn);
            const uint32_t tw = lds32(an + tro);
            ok = !__any_sync(0xffffffffu, !ok || ((tw ^ o_tag(L)) & 1u)) || (i == 3 && m == 3);
            wgmma_wait<1>();
            if (lane0 && (i > 0 || m > 0)) mbar_arrive((i > 0 ? fb + 8u * (i - 1) : (fb ^ 96u) + 24u) + 8u * B_E);
            if (!ok) check_o(fn, pn, an, 4 * m + i + 1);
          }
        }
        wgmma_wait<0>();
        reg_fence<64>(acc);
        if (lane0) mbar_arrive(bars + 8u * (B_WF + B_E + 7));
        GTL(7 + L * 8);
#pragma unroll
        for (int jp = 0; jp < 8; jp++) {
#pragma unroll
          for (int q = 0; q < 4; q++) xv[jp][q] = add_bf16x2(xv[jp][q], pack_bf16x2(acc[8 * jp + 2 * q], acc[8 * jp + 2 * q + 1]));
          const bool tg = (jp & 3) == 0;
          stmatrix_x4((xrow ^ ((jp & 3) << 5)) + (jp >> 2) * UNIT,
                      tg ? set_tag(xv[jp][0], tmx, xt) : xv[jp][0], tg ? set_tag(xv[jp][1], tmx, xt) : xv[jp][1], xv[jp][2], xv[jp][3]);
          if ((jp & 3) == 3) signal_async(bars + 8u * (B_XS + (jp >> 2)), lane0);
        }
        if (L < 3) {
          PHASE_IDS_W
          const int grow = ch * 1024 + rt * 64;
          const unsigned ep1 = lds32(base + OFF_EPOCH);
          if (c == 0)
            asm volatile("st.shared.u8 [%0], %1;" ::"r"(base + OFF_LSB + ch * 32 + wwarp * 8 + g),
                         "r"((xv[0][0] & 1u) | ((xv[0][1] & 1u) << 1) | ((xv[4][0] & 1u) << 2) | ((xv[4][1] & 1u) << 3)) : "memory");
          float s1[2] = {0.f, 0.f}, s2[2] = {0.f, 0.f};
#pragma unroll
          for (int jp = 0; jp < 8; jp++)
#pragma unroll
            for (int q = 0; q < 4; q++) {
              const float x0 = bf_lo(xv[jp][q]), x1 = bf_hi(xv[jp][q]);
              s1[q & 1] += x0 + x1;
              s2[q & 1] = fmaf(x0, x0, fmaf(x1, x1, s2[q & 1]));
            }
#pragma unroll
          for (int r = 0; r < 2; r++) {
            s1[r] += __shfl_xor_sync(0xffffffffu, s1[r], 1);
            s2[r] += __shfl_xor_sync(0xffffffffu, s2[r], 1);
            s1[r] += __shfl_xor_sync(0xffffffffu, s1[r], 2);
            s2[r] += __shfl_xor_sync(0xffffffffu, s2[r], 2);
            if (c == 0) st_rec(&g_stats[ct][grow + wwarp * 16 + g + 8 * r], s1[r], s2[r], 0.f, 4u * ep1 + L + 1);
          }
        }
        GTL(8 + L * 8);
      }
    }
    if (threadIdx.x == 128) atomicAdd(g_done, 1u);
  }
}

typedef CUresult (*PFN_tmEncode)(CUtensorMap*, CUtensorMapDataType, cuuint32_t, void*, const cuuint64_t*,
                                 const cuuint64_t*, const cuuint32_t*, const cuuint32_t*, CUtensorMapInterleave,
                                 CUtensorMapSwizzle, CUtensorMapL2promotion, CUtensorMapFloatOOBfill);

PFN_tmEncode get_encode_fn() {
  static PFN_tmEncode fn = nullptr;
  if (!fn) {
    cudaDriverEntryPointQueryResult qr;
    void* p = nullptr;
    cudaGetDriverEntryPoint("cuTensorMapEncodeTiled", &p, cudaEnableDefault, &qr);
    fn = (PFN_tmEncode)p;
  }
  return fn;
}

CUtensorMap make_map(const void* ptr, int rows, int cols) {
  CUtensorMap m;
  cuuint64_t gdim[2] = {(cuuint64_t)cols, (cuuint64_t)rows};
  cuuint64_t gstr[1] = {(cuuint64_t)cols * 2};
  cuuint32_t box[2] = {64, 64};
  cuuint32_t estr[2] = {1, 1};
  get_encode_fn()(&m, CU_TENSOR_MAP_DATA_TYPE_BFLOAT16, 2, const_cast<void*>(ptr), gdim, gstr, box, estr,
                  CU_TENSOR_MAP_INTERLEAVE_NONE, CU_TENSOR_MAP_SWIZZLE_128B, CU_TENSOR_MAP_L2_PROMOTION_L2_128B,
                  CU_TENSOR_MAP_FLOAT_OOB_FILL_NONE);
  return m;
}

CUtensorMap make_map3(const void* ptr, int rows, int cols, int n, int step) {
  CUtensorMap m;
  cuuint64_t gdim[3] = {(cuuint64_t)(cols - (n - 1) * step), (cuuint64_t)rows, (cuuint64_t)n};
  cuuint64_t gstr[2] = {(cuuint64_t)cols * 2, (cuuint64_t)step * 2};
  cuuint32_t box[3] = {64, 64, (cuuint32_t)n};
  cuuint32_t estr[3] = {1, 1, 1};
  get_encode_fn()(&m, CU_TENSOR_MAP_DATA_TYPE_BFLOAT16, 3, const_cast<void*>(ptr), gdim, gstr, box, estr,
                  CU_TENSOR_MAP_INTERLEAVE_NONE, CU_TENSOR_MAP_SWIZZLE_128B, CU_TENSOR_MAP_L2_PROMOTION_L2_128B,
                  CU_TENSOR_MAP_FLOAT_OOB_FILL_NONE);
  return m;
}

CUtensorMap make_map_q(const void* ptr, int sw, int sr) {
  CUtensorMap m;
  cuuint64_t gdim[5] = {DM, 8, 2, 4, S_LEN / 64};
  cuuint64_t gstr[4] = {DM * 2, (cuuint64_t)sr * DM * 2, (cuuint64_t)sw * DM * 2, 64 * DM * 2};
  cuuint32_t box[5] = {64, 8, 2, 4, 2};
  cuuint32_t estr[5] = {1, 1, 1, 1, 1};
  get_encode_fn()(&m, CU_TENSOR_MAP_DATA_TYPE_BFLOAT16, 5, const_cast<void*>(ptr), gdim, gstr, box, estr,
                  CU_TENSOR_MAP_INTERLEAVE_NONE, CU_TENSOR_MAP_SWIZZLE_128B, CU_TENSOR_MAP_L2_PROMOTION_L2_128B,
                  CU_TENSOR_MAP_FLOAT_OOB_FILL_NONE);
  return m;
}

}

extern "C" void kernel_launch(void* const* d_in, const int* in_sizes, int n_in, void* d_out, int out_size) {
  (void)in_sizes; (void)n_in; (void)out_size;
  void *p_o, *p_x;
  cudaGetSymbolAddress(&p_o, g_o);
  cudaGetSymbolAddress(&p_x, g_x);
  static bool attr_done = false;
  if (!attr_done) {
    cudaFuncSetAttribute(fused_kernel, cudaFuncAttributeMaxDynamicSharedMemorySize, SMEM_BYTES);
    attr_done = true;
  }
  Params P;
  P.in_x = (const __nv_bfloat16*)d_in[0];
  P.wqkv_p[0] = (const __nv_bfloat16*)d_in[1];
  P.wo_p[0] = (const __nv_bfloat16*)d_in[2];
  P.wqkv_p[1] = (const __nv_bfloat16*)d_in[4];
  P.wo_p[1] = (const __nv_bfloat16*)d_in[5];
  P.out = (__nv_bfloat16*)d_out;
  P.zero = 0;
  for (int L = 0; L < 5; L++) {
    const void* px = L == 0 ? (const void*)P.in_x : (L == 4 ? d_out : p_x);
    P.x[L] = make_map(px, S_LEN, DM);
    if (L < 4) P.xq[L] = (L & 1) ? make_map_q(px, 16, 8) : make_map_q(px, 8, 32);
  }
  P.o = make_map(p_o, S_LEN, DM);
  for (int t = 0; t < 2; t++) {
    P.wqkv[t] = make_map(P.wqkv_p[t], DM, NQKV);
    P.wqkv3[t] = make_map3(P.wqkv_p[t], DM, NQKV, 3, 1024);
    P.wo3[t] = make_map3(P.wo_p[t], DM, DM, 2, 64);
  }
  fused_kernel<<<NCTA, 512, SMEM_BYTES>>>(P);
}
```

```cpp
#include <cuda_runtime.h>
#include <cuda_bf16.h>
#include <cuda.h>
#include <stdint.h>

namespace {

constexpr int S_LEN = 2048;
constexpr int DM = 1024;
constexpr int NQKV = 3072;
constexpr int NCTA = 128;

__device__ __align__(1024) uint8_t g_kvA[16][16][2][16384];
__device__ __align__(1024) uint8_t g_kvB[16][16][4096];
__device__ __align__(1024) uint8_t g_zero[16384];
__device__ __align__(1024) __nv_bfloat16 g_o[S_LEN * DM];
__device__ __align__(1024) __nv_bfloat16 g_x[S_LEN * DM];
__device__ __align__(1024) float4 g_stats[8][S_LEN];
__device__ __align__(1024) float4 g_cs[2][16][8][64];
__device__ __align__(128) unsigned g_fx[16][16][4];
__device__ __align__(128) unsigned g_fo[32][16][4];
__device__ __align__(128) unsigned g_fk[16][16][4];
__device__ __align__(128) unsigned g_done[32];

constexpr uint32_t SBASE = 1024;
constexpr int UNIT = 8192;
constexpr int NUNITS = 20;
constexpr int OFF_SLOT = NUNITS * UNIT;
constexpr int OFF_BAR = OFF_SLOT + 4 * 16384;
constexpr int OFF_EPOCH = OFF_BAR + 424;
constexpr int OFF_LSB = OFF_BAR + 432;
constexpr int OFF_CS = OFF_BAR + 496;
constexpr int OFF_RS = OFF_CS + 1536;
constexpr int OFF_ONE = OFF_RS + 1024;
constexpr int SMEM_BYTES = OFF_ONE + 16;
constexpr int B_QF = 0, B_WF = 4, B_RF = 12, B_E = 13, B_PREP = 26, B_LOC = 28, B_HALO = 29, B_REL = 33, B_OS0 = 36,
              B_TURN = 37, B_XS = 39, B_CS = 41, B_CSD = 42, B_GO = 43, B_PRE = 44, B_HV = 45, B_REDO = 46,
              B_RDONE = 48, B_PRE2 = 49, B_HL = 50, B_KV = 52, B_OS1 = B_GO;
static_assert(SMEM_BYTES <= 232448, "shared memory");

__device__ __forceinline__ uint32_t smem_u32(const void* p) { return (uint32_t)__cvta_generic_to_shared(p); }

__device__ __forceinline__ void mbar_init(uint32_t bar, uint32_t cnt) {
  asm volatile("mbarrier.init.shared::cta.b64 [%0], %1;" ::"r"(bar), "r"(cnt));
}
__device__ __forceinline__ void mbar_expect_tx(uint32_t bar, uint32_t bytes) {
  asm volatile("mbarrier.arrive.expect_tx.shared::cta.b64 _, [%0], %1;" ::"r"(bar), "r"(bytes) : "memory");
}
__device__ __forceinline__ void mbar_arrive(uint32_t bar) {
  asm volatile("mbarrier.arrive.shared::cta.b64 _, [%0];" ::"r"(bar) : "memory");
}
__device__ __forceinline__ bool mbar_try_wait(uint32_t bar, uint32_t parity) {
  uint32_t ok;
  asm volatile(
      "{\n.reg .pred p;\nmbarrier.try_wait.parity.shared::cta.b64 p, [%1], %2;\nselp.b32 %0, 1, 0, p;\n}\n"
      : "=r"(ok)
      : "r"(bar), "r"(parity)
      : "memory");
  return ok != 0;
}
__device__ __forceinline__ bool mbar_test(uint32_t bar, uint32_t parity) {
  uint32_t ok;
  asm volatile(
      "{\n.reg .pred p;\nmbarrier.test_wait.parity.shared::cta.b64 p, [%1], %2;\nselp.b32 %0, 1, 0, p;\n}\n"
      : "=r"(ok)
      : "r"(bar), "r"(parity)
      : "memory");
  return ok != 0;
}
__device__ __forceinline__ void mbar_wait(uint32_t bar, uint32_t parity) {
#pragma unroll 1
  for (uint32_t it = 0; it < (1u << 18); ++it) {
    if (mbar_try_wait(bar, parity)) return;
  }
}
__device__ __forceinline__ void mbar_pace(uint32_t bar, uint32_t parity, uint32_t n) {
#pragma unroll 1
  for (uint32_t it = 0; it < n; ++it) {
    if (mbar_test(bar, parity)) return;
    __nanosleep(100);
  }
}
template <int NS>
__device__ __forceinline__ void mbar_wait_lazy(uint32_t bar, uint32_t parity) {
#pragma unroll 1
  for (uint32_t it = 0; it < (1u << 18); ++it) {
    if (mbar_try_wait(bar, parity)) return;
    __nanosleep(NS);
  }
}
__device__ __forceinline__ bool elect_one() {
  uint32_t ok;
  asm volatile("{\n.reg .pred p;\nelect.sync _|p, 0xffffffff;\nselp.b32 %0, 1, 0, p;\n}\n" : "=r"(ok));
  return ok != 0;
}
__device__ __forceinline__ void fence_barrier_init() { asm volatile("fence.mbarrier_init.release.cluster;" ::: "memory"); }
__device__ __forceinline__ void fence_proxy_async_smem() { asm volatile("fence.proxy.async.shared::cta;" ::: "memory"); }

__device__ __forceinline__ void signal_async(uint32_t bar, bool lane0) {
  fence_proxy_async_smem();
  __syncwarp();
  asm volatile("{\n.reg .pred p;\nsetp.ne.b32 p, %1, 0;\n@p mbarrier.arrive.shared::cta.b64 _, [%0];\n}\n" ::"r"(bar), "r"((int)lane0) : "memory");
}
template <class T>
__device__ __forceinline__ void pin64(T*& p) { asm volatile("" : "+l"(p)); }

__device__ __forceinline__ void tma_load_2d(uint32_t dst, const CUtensorMap* map, uint32_t bar, int c0, int c1) {
  asm volatile(
      "cp.async.bulk.tensor.2d.shared::cluster.global.mbarrier::complete_tx::bytes [%0], [%1, {%3, %4}], [%2];" ::"r"(dst),
      "l"(map), "r"(bar), "r"(c0), "r"(c1)
      : "memory");
}
__device__ __forceinline__ void tma_load_3d(uint32_t dst, const CUtensorMap* map, uint32_t bar, int c0, int c1) {
  asm volatile(
      "cp.async.bulk.tensor.3d.shared::cluster.global.mbarrier::complete_tx::bytes [%0], [%1, {%3, %4, %5}], [%2];" ::"r"(dst),
      "l"(map), "r"(bar), "r"(c0), "r"(c1), "r"(0)
      : "memory");
}
__device__ __forceinline__ void tma_load_5d(uint32_t dst, const CUtensorMap* map, uint32_t bar, int c0, int c4) {
  asm volatile(
      "cp.async.bulk.tensor.5d.shared::cluster.global.mbarrier::complete_tx::bytes [%0], [%1, {%3, %5, %5, %5, %4}], [%2];" ::"r"(dst),
      "l"(map), "r"(bar), "r"(c0), "r"(c4), "r"(0)
      : "memory");
}
__device__ __forceinline__ void bulk_load(uint32_t dst, const void* src, uint32_t bytes, uint32_t bar) {
  asm volatile("cp.async.bulk.shared::cluster.global.mbarrier::complete_tx::bytes [%0], [%1], %2, [%3];" ::"r"(dst),
               "l"(src), "r"(bytes), "r"(bar)
               : "memory");
}
__device__ __forceinline__ void bulk_store(void* dst, uint32_t src, uint32_t bytes) {
  asm volatile("cp.async.bulk.global.shared::cta.bulk_group [%0], [%1], %2;" ::"l"(dst), "r"(src), "r"(bytes) : "memory");
}
__device__ __forceinline__ void tma_store_2d(const CUtensorMap* map, uint32_t src, int c0, int c1) {
  asm volatile("cp.async.bulk.tensor.2d.global.shared::cta.bulk_group [%0, {%2, %3}], [%1];" ::"l"(map), "r"(src),
               "r"(c0), "r"(c1)
               : "memory");
}
__device__ __forceinline__ void bulk_announce(unsigned* p) {
  asm volatile("cp.reduce.async.bulk.global.shared::cta.bulk_group.add.u32 [%0], [%1], 16;" ::"l"(p), "r"(SBASE + OFF_ONE) : "memory");
}
__device__ __forceinline__ void bulk_commit() { asm volatile("cp.async.bulk.commit_group;" ::: "memory"); }
__device__ __forceinline__ void bulk_wait_read0() { asm volatile("cp.async.bulk.wait_group.read 0;" ::: "memory"); }
__device__ __forceinline__ void bulk_wait0() { asm volatile("cp.async.bulk.wait_group 0;" ::: "memory"); }
__device__ __forceinline__ void named_bar_sync(int id, int nthreads) {
  asm volatile("bar.sync %0, %1;" ::"r"(id), "r"(nthreads) : "memory");
}
__device__ __forceinline__ void named_bar_arrive(int id, int nthreads) {
  asm volatile("bar.arrive %0, %1;" ::"r"(id), "r"(nthreads) : "memory");
}

__device__ __forceinline__ void wgmma_fence() { asm volatile("wgmma.fence.sync.aligned;\n" ::: "memory"); }
__device__ __forceinline__ void wgmma_commit() { asm volatile("wgmma.commit_group.sync.aligned;\n" ::: "memory"); }
template <int N>
__device__ __forceinline__ void wgmma_wait() {
  asm volatile("wgmma.wait_group.sync.aligned %0;\n" ::"n"(N) : "memory");
}
template <int R>
__device__ __forceinline__ void setmaxnreg_inc() { asm volatile("setmaxnreg.inc.sync.aligned.u32 %0;\n" ::"n"(R)); }
template <int R>
__device__ __forceinline__ void setmaxnreg_dec() { asm volatile("setmaxnreg.dec.sync.aligned.u32 %0;\n" ::"n"(R)); }
template <int N>
__device__ __forceinline__ void reg_fence(float* r) {
#pragma unroll
  for (int i = 0; i < N; i++) asm volatile("" : "+f"(r[i])::"memory");
}

template <int N>
__device__ __forceinline__ void reg_define(float* r) {
#pragma unroll
  for (int i = 0; i < N; i++) r[i] = 0.f;
}

__device__ __forceinline__ uint64_t desc_lo(uint32_t lo) {
  uint64_t d;
  asm("mov.b64 %0, {%1, %2};" : "=l"(d) : "r"(lo), "r"(0x40000040u));
  return d;
}
__device__ __forceinline__ uint64_t make_desc(uint32_t addr, uint32_t lbo_bytes) {
  return desc_lo((addr >> 4) + ((lbo_bytes >> 4) << 16));
}

__device__ __forceinline__ void wgmma_n192_ss_ta0_tb1(float* d, uint64_t descA, uint64_t descB, int scaleD) {
  asm volatile("{\n.reg .pred p;\nsetp.ne.b32 p, %98, 0;\n"
    "wgmma.mma_async.sync.aligned.m64n192k16.f32.bf16.bf16 {%0, %1, %2, %3, %4, %5, %6, %7, %8, %9, %10, %11, %12, %13, %14, %15, %16, %17, %18, %19, %20, %21, %22, %23, %24, %25, %26, %27, %28, %29, %30, %31, %32, %33, %34, %35, %36, %37, %38, %39, %40, %41, %42, %43, %44, %45, %46, %47, %48, %49, %50, %51, %52, %53, %54, %55, %56, %57, %58, %59, %60, %61, %62, %63, %64, %65, %66, %67, %68, %69, %70, %71, %72, %73, %74, %75, %76, %77, %78, %79, %80, %81, %82, %83, %84, %85, %86, %87, %88, %89, %90, %91, %92, %93, %94, %95}, %96, %97, p, 1, 1, 0, 1;\n}\n"
    : "+f"(d[0]), "+f"(d[1]), "+f"(d[2]), "+f"(d[3]), "+f"(d[4]), "+f"(d[5]), "+f"(d[6]), "+f"(d[7]), "+f"(d[8]), "+f"(d[9]), "+f"(d[10]), "+f"(d[11]), "+f"(d[12]), "+f"(d[13]), "+f"(d[14]), "+f"(d[15]), "+f"(d[16]), "+f"(d[17]), "+f"(d[18]), "+f"(d[19]), "+f"(d[20]), "+f"(d[21]), "+f"(d[22]), "+f"(d[23]), "+f"(d[24]), "+f"(d[25]), "+f"(d[26]), "+f"(d[27]), "+f"(d[28]), "+f"(d[29]), "+f"(d[30]), "+f"(d[31]), "+f"(d[32]), "+f"(d[33]), "+f"(d[34]), "+f"(d[35]), "+f"(d[36]), "+f"(d[37]), "+f"(d[38]), "+f"(d[39]), "+f"(d[40]), "+f"(d[41]), "+f"(d[42]), "+f"(d[43]), "+f"(d[44]), "+f"(d[45]), "+f"(d[46]), "+f"(d[47]), "+f"(d[48]), "+f"(d[49]), "+f"(d[50]), "+f"(d[51]), "+f"(d[52]), "+f"(d[53]), "+f"(d[54]), "+f"(d[55]), "+f"(d[56]), "+f"(d[57]), "+f"(d[58]), "+f"(d[59]), "+f"(d[60]), "+f"(d[61]), "+f"(d[62]), "+f"(d[63]), "+f"(d[64]), "+f"(d[65]), "+f"(d[66]), "+f"(d[67]), "+f"(d[68]), "+f"(d[69]), "+f"(d[70]), "+f"(d[71]), "+f"(d[72]), "+f"(d[73]), "+f"(d[74]), "+f"(d[75]), "+f"(d[76]), "+f"(d[77]), "+f"(d[78]), "+f"(d[79]), "+f"(d[80]), "+f"(d[81]), "+f"(d[82]), "+f"(d[83]), "+f"(d[84]), "+f"(d[85]), "+f"(d[86]), "+f"(d[87]), "+f"(d[88]), "+f"(d[89]), "+f"(d[90]), "+f"(d[91]), "+f"(d[92]), "+f"(d[93]), "+f"(d[94]), "+f"(d[95])
    : "l"(descA), "l"(descB), "r"(scaleD));
}

__device__ __forceinline__ void wgmma_n128_ss_ta0_tb1(float* d, uint64_t descA, uint64_t descB, int scaleD) {
  asm volatile("{\n.reg .pred p;\nsetp.ne.b32 p, %66, 0;\n"
    "wgmma.mma_async.sync.aligned.m64n128k16.f32.bf16.bf16 {%0, %1, %2, %3, %4, %5, %6, %7, %8, %9, %10, %11, %12, %13, %14, %15, %16, %17, %18, %19, %20, %21, %22, %23, %24, %25, %26, %27, %28, %29, %30, %31, %32, %33, %34, %35, %36, %37, %38, %39, %40, %41, %42, %43, %44, %45, %46, %47, %48, %49, %50, %51, %52, %53, %54, %55, %56, %57, %58, %59, %60, %61, %62, %63}, %64, %65, p, 1, 1, 0, 1;\n}\n"
    : "+f"(d[0]), "+f"(d[1]), "+f"(d[2]), "+f"(d[3]), "+f"(d[4]), "+f"(d[5]), "+f"(d[6]), "+f"(d[7]), "+f"(d[8]), "+f"(d[9]), "+f"(d[10]), "+f"(d[11]), "+f"(d[12]), "+f"(d[13]), "+f"(d[14]), "+f"(d[15]), "+f"(d[16]), "+f"(d[17]), "+f"(d[18]), "+f"(d[19]), "+f"(d[20]), "+f"(d[21]), "+f"(d[22]), "+f"(d[23]), "+f"(d[24]), "+f"(d[25]), "+f"(d[26]), "+f"(d[27]), "+f"(d[28]), "+f"(d[29]), "+f"(d[30]), "+f"(d[31]), "+f"(d[32]), "+f"(d[33]), "+f"(d[34]), "+f"(d[35]), "+f"(d[36]), "+f"(d[37]), "+f"(d[38]), "+f"(d[39]), "+f"(d[40]), "+f"(d[41]), "+f"(d[42]), "+f"(d[43]), "+f"(d[44]), "+f"(d[45]), "+f"(d[46]), "+f"(d[47]), "+f"(d[48]), "+f"(d[49]), "+f"(d[50]), "+f"(d[51]), "+f"(d[52]), "+f"(d[53]), "+f"(d[54]), "+f"(d[55]), "+f"(d[56]), "+f"(d[57]), "+f"(d[58]), "+f"(d[59]), "+f"(d[60]), "+f"(d[61]), "+f"(d[62]), "+f"(d[63])
    : "l"(descA), "l"(descB), "r"(scaleD));
}

__device__ __forceinline__ void wgmma_n192_ssz_ta0_tb1(float* d, uint64_t descA, uint64_t descB) {
  asm volatile("{\n.reg .pred p;\nsetp.ne.b32 p, 0, 0;\n"
    "wgmma.mma_async.sync.aligned.m64n192k16.f32.bf16.bf16 {%0, %1, %2, %3, %4, %5, %6, %7, %8, %9, %10, %11, %12, %13, %14, %15, %16, %17, %18, %19, %20, %21, %22, %23, %24, %25, %26, %27, %28, %29, %30, %31, %32, %33, %34, %35, %36, %37, %38, %39, %40, %41, %42, %43, %44, %45, %46, %47, %48, %49, %50, %51, %52, %53, %54, %55, %56, %57, %58, %59, %60, %61, %62, %63, %64, %65, %66, %67, %68, %69, %70, %71, %72, %73, %74, %75, %76, %77, %78, %79, %80, %81, %82, %83, %84, %85, %86, %87, %88, %89, %90, %91, %92, %93, %94, %95}, %96, %97, p, 1, 1, 0, 1;\n}\n"
    : "=f"(d[0]), "=f"(d[1]), "=f"(d[2]), "=f"(d[3]), "=f"(d[4]), "=f"(d[5]), "=f"(d[6]), "=f"(d[7]), "=f"(d[8]), "=f"(d[9]), "=f"(d[10]), "=f"(d[11]), "=f"(d[12]), "=f"(d[13]), "=f"(d[14]), "=f"(d[15]), "=f"(d[16]), "=f"(d[17]), "=f"(d[18]), "=f"(d[19]), "=f"(d[20]), "=f"(d[21]), "=f"(d[22]), "=f"(d[23]), "=f"(d[24]), "=f"(d[25]), "=f"(d[26]), "=f"(d[27]), "=f"(d[28]), "=f"(d[29]), "=f"(d[30]), "=f"(d[31]), "=f"(d[32]), "=f"(d[33]), "=f"(d[34]), "=f"(d[35]), "=f"(d[36]), "=f"(d[37]), "=f"(d[38]), "=f"(d[39]), "=f"(d[40]), "=f"(d[41]), "=f"(d[42]), "=f"(d[43]), "=f"(d[44]), "=f"(d[45]), "=f"(d[46]), "=f"(d[47]), "=f"(d[48]), "=f"(d[49]), "=f"(d[50]), "=f"(d[51]), "=f"(d[52]), "=f"(d[53]), "=f"(d[54]), "=f"(d[55]), "=f"(d[56]), "=f"(d[57]), "=f"(d[58]), "=f"(d[59]), "=f"(d[60]), "=f"(d[61]), "=f"(d[62]), "=f"(d[63]), "=f"(d[64]), "=f"(d[65]), "=f"(d[66]), "=f"(d[67]), "=f"(d[68]), "=f"(d[69]), "=f"(d[70]), "=f"(d[71]), "=f"(d[72]), "=f"(d[73]), "=f"(d[74]), "=f"(d[75]), "=f"(d[76]), "=f"(d[77]), "=f"(d[78]), "=f"(d[79]), "=f"(d[80]), "=f"(d[81]), "=f"(d[82]), "=f"(d[83]), "=f"(d[84]), "=f"(d[85]), "=f"(d[86]), "=f"(d[87]), "=f"(d[88]), "=f"(d[89]), "=f"(d[90]), "=f"(d[91]), "=f"(d[92]), "=f"(d[93]), "=f"(d[94]), "=f"(d[95])
    : "l"(descA), "l"(descB));
}

__device__ __forceinline__ void wgmma_n8_ss_ta1_tb0(float* d, uint64_t descA, uint64_t descB, int scaleD) {
  asm volatile("{\n.reg .pred p;\nsetp.ne.b32 p, %6, 0;\n"
    "wgmma.mma_async.sync.aligned.m64n8k16.f32.bf16.bf16 {%0, %1, %2, %3}, %4, %5, p, 1, 1, 1, 0;\n}\n"
    : "+f"(d[0]), "+f"(d[1]), "+f"(d[2]), "+f"(d[3])
    : "l"(descA), "l"(descB), "r"(scaleD));
}

__device__ __forceinline__ void wgmma_n8_ssz_ta1_tb0(float* d, uint64_t descA, uint64_t descB) {
  asm volatile("{\n.reg .pred p;\nsetp.ne.b32 p, 0, 0;\n"
    "wgmma.mma_async.sync.aligned.m64n8k16.f32.bf16.bf16 {%0, %1, %2, %3}, %4, %5, p, 1, 1, 1, 0;\n}\n"
    : "=f"(d[0]), "=f"(d[1]), "=f"(d[2]), "=f"(d[3])
    : "l"(descA), "l"(descB));
}

__device__ __forceinline__ void wgmma_n192_rs_tb1(float* d, const uint32_t* a, uint64_t descB, int scaleD) {
  asm volatile("{\n.reg .pred p;\nsetp.ne.b32 p, %101, 0;\n"
    "wgmma.mma_async.sync.aligned.m64n192k16.f32.bf16.bf16 {%0, %1, %2, %3, %4, %5, %6, %7, %8, %9, %10, %11, %12, %13, %14, %15, %16, %17, %18, %19, %20, %21, %22, %23, %24, %25, %26, %27, %28, %29, %30, %31, %32, %33, %34, %35, %36, %37, %38, %39, %40, %41, %42, %43, %44, %45, %46, %47, %48, %49, %50, %51, %52, %53, %54, %55, %56, %57, %58, %59, %60, %61, %62, %63, %64, %65, %66, %67, %68, %69, %70, %71, %72, %73, %74, %75, %76, %77, %78, %79, %80, %81, %82, %83, %84, %85, %86, %87, %88, %89, %90, %91, %92, %93, %94, %95}, {%96, %97, %98, %99}, %100, p, 1, 1, 1;\n}\n"
    : "+f"(d[0]), "+f"(d[1]), "+f"(d[2]), "+f"(d[3]), "+f"(d[4]), "+f"(d[5]), "+f"(d[6]), "+f"(d[7]), "+f"(d[8]), "+f"(d[9]), "+f"(d[10]), "+f"(d[11]), "+f"(d[12]), "+f"(d[13]), "+f"(d[14]), "+f"(d[15]), "+f"(d[16]), "+f"(d[17]), "+f"(d[18]), "+f"(d[19]), "+f"(d[20]), "+f"(d[21]), "+f"(d[22]), "+f"(d[23]), "+f"(d[24]), "+f"(d[25]), "+f"(d[26]), "+f"(d[27]), "+f"(d[28]), "+f"(d[29]), "+f"(d[30]), "+f"(d[31]), "+f"(d[32]), "+f"(d[33]), "+f"(d[34]), "+f"(d[35]), "+f"(d[36]), "+f"(d[37]), "+f"(d[38]), "+f"(d[39]), "+f"(d[40]), "+f"(d[41]), "+f"(d[42]), "+f"(d[43]), "+f"(d[44]), "+f"(d[45]), "+f"(d[46]), "+f"(d[47]), "+f"(d[48]), "+f"(d[49]), "+f"(d[50]), "+f"(d[51]), "+f"(d[52]), "+f"(d[53]), "+f"(d[54]), "+f"(d[55]), "+f"(d[56]), "+f"(d[57]), "+f"(d[58]), "+f"(d[59]), "+f"(d[60]), "+f"(d[61]), "+f"(d[62]), "+f"(d[63]), "+f"(d[64]), "+f"(d[65]), "+f"(d[66]), "+f"(d[67]), "+f"(d[68]), "+f"(d[69]), "+f"(d[70]), "+f"(d[71]), "+f"(d[72]), "+f"(d[73]), "+f"(d[74]), "+f"(d[75]), "+f"(d[76]), "+f"(d[77]), "+f"(d[78]), "+f"(d[79]), "+f"(d[80]), "+f"(d[81]), "+f"(d[82]), "+f"(d[83]), "+f"(d[84]), "+f"(d[85]), "+f"(d[86]), "+f"(d[87]), "+f"(d[88]), "+f"(d[89]), "+f"(d[90]), "+f"(d[91]), "+f"(d[92]), "+f"(d[93]), "+f"(d[94]), "+f"(d[95])
    : "r"(a[0]), "r"(a[1]), "r"(a[2]), "r"(a[3]), "l"(descB), "r"(scaleD));
}

__device__ __forceinline__ void wgmma_n80_rs_tb0(float* d, const uint32_t* a, uint64_t descB, int scaleD) {
  asm volatile("{\n.reg .pred p;\nsetp.ne.b32 p, %45, 0;\n"
    "wgmma.mma_async.sync.aligned.m64n80k16.f32.bf16.bf16 {%0, %1, %2, %3, %4, %5, %6, %7, %8, %9, %10, %11, %12, %13, %14, %15, %16, %17, %18, %19, %20, %21, %22, %23, %24, %25, %26, %27, %28, %29, %30, %31, %32, %33, %34, %35, %36, %37, %38, %39}, {%40, %41, %42, %43}, %44, p, 1, 1, 0;\n}\n"
    : "+f"(d[0]), "+f"(d[1]), "+f"(d[2]), "+f"(d[3]), "+f"(d[4]), "+f"(d[5]), "+f"(d[6]), "+f"(d[7]), "+f"(d[8]), "+f"(d[9]), "+f"(d[10]), "+f"(d[11]), "+f"(d[12]), "+f"(d[13]), "+f"(d[14]), "+f"(d[15]), "+f"(d[16]), "+f"(d[17]), "+f"(d[18]), "+f"(d[19]), "+f"(d[20]), "+f"(d[21]), "+f"(d[22]), "+f"(d[23]), "+f"(d[24]), "+f"(d[25]), "+f"(d[26]), "+f"(d[27]), "+f"(d[28]), "+f"(d[29]), "+f"(d[30]), "+f"(d[31]), "+f"(d[32]), "+f"(d[33]), "+f"(d[34]), "+f"(d[35]), "+f"(d[36]), "+f"(d[37]), "+f"(d[38]), "+f"(d[39])
    : "r"(a[0]), "r"(a[1]), "r"(a[2]), "r"(a[3]), "l"(descB), "r"(scaleD));
}

__device__ __forceinline__ void wgmma_n80_rsz_tb0(float* d, const uint32_t* a, uint64_t descB) {
  asm volatile("{\n.reg .pred p;\nsetp.ne.b32 p, 0, 0;\n"
    "wgmma.mma_async.sync.aligned.m64n80k16.f32.bf16.bf16 {%0, %1, %2, %3, %4, %5, %6, %7, %8, %9, %10, %11, %12, %13, %14, %15, %16, %17, %18, %19, %20, %21, %22, %23, %24, %25, %26, %27, %28, %29, %30, %31, %32, %33, %34, %35, %36, %37, %38, %39}, {%40, %41, %42, %43}, %44, p, 1, 1, 0;\n}\n"
    : "=f"(d[0]), "=f"(d[1]), "=f"(d[2]), "=f"(d[3]), "=f"(d[4]), "=f"(d[5]), "=f"(d[6]), "=f"(d[7]), "=f"(d[8]), "=f"(d[9]), "=f"(d[10]), "=f"(d[11]), "=f"(d[12]), "=f"(d[13]), "=f"(d[14]), "=f"(d[15]), "=f"(d[16]), "=f"(d[17]), "=f"(d[18]), "=f"(d[19]), "=f"(d[20]), "=f"(d[21]), "=f"(d[22]), "=f"(d[23]), "=f"(d[24]), "=f"(d[25]), "=f"(d[26]), "=f"(d[27]), "=f"(d[28]), "=f"(d[29]), "=f"(d[30]), "=f"(d[31]), "=f"(d[32]), "=f"(d[33]), "=f"(d[34]), "=f"(d[35]), "=f"(d[36]), "=f"(d[37]), "=f"(d[38]), "=f"(d[39])
    : "r"(a[0]), "r"(a[1]), "r"(a[2]), "r"(a[3]), "l"(descB));
}

__device__ __forceinline__ void wgmma_n32_rs_tb1(float* d, const uint32_t* a, uint64_t descB, int scaleD) {
  asm volatile("{\n.reg .pred p;\nsetp.ne.b32 p, %21, 0;\n"
    "wgmma.mma_async.sync.aligned.m64n32k16.f32.bf16.bf16 {%0, %1, %2, %3, %4, %5, %6, %7, %8, %9, %10, %11, %12, %13, %14, %15}, {%16, %17, %18, %19}, %20, p, 1, 1, 1;\n}\n"
    : "+f"(d[0]), "+f"(d[1]), "+f"(d[2]), "+f"(d[3]), "+f"(d[4]), "+f"(d[5]), "+f"(d[6]), "+f"(d[7]), "+f"(d[8]), "+f"(d[9]), "+f"(d[10]), "+f"(d[11]), "+f"(d[12]), "+f"(d[13]), "+f"(d[14]), "+f"(d[15])
    : "r"(a[0]), "r"(a[1]), "r"(a[2]), "r"(a[3]), "l"(descB), "r"(scaleD));
}

__device__ __forceinline__ void wgmma_n32_rsz_tb1(float* d, const uint32_t* a, uint64_t descB) {
  asm volatile("{\n.reg .pred p;\nsetp.ne.b32 p, 0, 0;\n"
    "wgmma.mma_async.sync.aligned.m64n32k16.f32.bf16.bf16 {%0, %1, %2, %3, %4, %5, %6, %7, %8, %9, %10, %11, %12, %13, %14, %15}, {%16, %17, %18, %19}, %20, p, 1, 1, 1;\n}\n"
    : "=f"(d[0]), "=f"(d[1]), "=f"(d[2]), "=f"(d[3]), "=f"(d[4]), "=f"(d[5]), "=f"(d[6]), "=f"(d[7]), "=f"(d[8]), "=f"(d[9]), "=f"(d[10]), "=f"(d[11]), "=f"(d[12]), "=f"(d[13]), "=f"(d[14]), "=f"(d[15])
    : "r"(a[0]), "r"(a[1]), "r"(a[2]), "r"(a[3]), "l"(descB));
}

__device__ __forceinline__ void wgmma_n32_rs_tb0(float* d, const uint32_t* a, uint64_t descB, int scaleD) {
  asm volatile("{\n.reg .pred p;\nsetp.ne.b32 p, %21, 0;\n"
    "wgmma.mma_async.sync.aligned.m64n32k16.f32.bf16.bf16 {%0, %1, %2, %3, %4, %5, %6, %7, %8, %9, %10, %11, %12, %13, %14, %15}, {%16, %17, %18, %19}, %20, p, 1, 1, 0;\n}\n"
    : "+f"(d[0]), "+f"(d[1]), "+f"(d[2]), "+f"(d[3]), "+f"(d[4]), "+f"(d[5]), "+f"(d[6]), "+f"(d[7]), "+f"(d[8]), "+f"(d[9]), "+f"(d[10]), "+f"(d[11]), "+f"(d[12]), "+f"(d[13]), "+f"(d[14]), "+f"(d[15])
    : "r"(a[0]), "r"(a[1]), "r"(a[2]), "r"(a[3]), "l"(descB), "r"(scaleD));
}

__device__ __forceinline__ void wgmma_n32_rsz_tb0(float* d, const uint32_t* a, uint64_t descB) {
  asm volatile("{\n.reg .pred p;\nsetp.ne.b32 p, 0, 0;\n"
    "wgmma.mma_async.sync.aligned.m64n32k16.f32.bf16.bf16 {%0, %1, %2, %3, %4, %5, %6, %7, %8, %9, %10, %11, %12, %13, %14, %15}, {%16, %17, %18, %19}, %20, p, 1, 1, 0;\n}\n"
    : "=f"(d[0]), "=f"(d[1]), "=f"(d[2]), "=f"(d[3]), "=f"(d[4]), "=f"(d[5]), "=f"(d[6]), "=f"(d[7]), "=f"(d[8]), "=f"(d[9]), "=f"(d[10]), "=f"(d[11]), "=f"(d[12]), "=f"(d[13]), "=f"(d[14]), "=f"(d[15])
    : "r"(a[0]), "r"(a[1]), "r"(a[2]), "r"(a[3]), "l"(descB));
}

__device__ __forceinline__ uint32_t pack_bf16x2(float lo, float hi) {
  uint32_t r;
  asm("cvt.rn.bf16x2.f32 %0, %1, %2;" : "=r"(r) : "f"(hi), "f"(lo));
  return r;
}
__device__ __forceinline__ float bf_lo(uint32_t p) { return __uint_as_float(p << 16); }
__device__ __forceinline__ float bf_hi(uint32_t p) { return __uint_as_float(p & 0xffff0000u); }
__device__ __forceinline__ float bf16_round(float v) { return __bfloat162float(__float2bfloat16_rn(v)); }
__device__ __forceinline__ float ex2_approx(float x) {
  float r;
  asm("ex2.approx.ftz.f32 %0, %1;" : "=f"(r) : "f"(x));
  return r;
}
__device__ __forceinline__ float rcp_fast(float x) {
  float r;
  asm("rcp.approx.ftz.f32 %0, %1;" : "=f"(r) : "f"(x));
  return r;
}
__device__ __forceinline__ void ldmatrix_x4(uint32_t (&r)[4], uint32_t addr) {
  asm volatile("ldmatrix.sync.aligned.m8n8.x4.shared.b16 {%0,%1,%2,%3}, [%4];"
               : "=r"(r[0]), "=r"(r[1]), "=r"(r[2]), "=r"(r[3])
               : "r"(addr)
               : "memory");
}
__device__ __forceinline__ void stmatrix_x4(uint32_t addr, uint32_t r0, uint32_t r1, uint32_t r2, uint32_t r3) {
  asm volatile("stmatrix.sync.aligned.m8n8.x4.shared.b16 [%0], {%1,%2,%3,%4};" ::"r"(addr), "r"(r0), "r"(r1), "r"(r2),
               "r"(r3));
}
__device__ __forceinline__ uint32_t add_bf16x2(uint32_t a, uint32_t b) {
  uint32_t r;
  asm("add.rn.bf16x2 %0, %1, %2;" : "=r"(r) : "r"(a), "r"(b));
  return r;
}
__device__ __forceinline__ uint4 lds128(uint32_t addr) {
  uint4 v;
  asm volatile("ld.shared.v4.b32 {%0,%1,%2,%3}, [%4];" : "=r"(v.x), "=r"(v.y), "=r"(v.z), "=r"(v.w) : "r"(addr) : "memory");
  return v;
}
__device__ __forceinline__ uint32_t lds32(uint32_t addr) {
  uint32_t v;
  asm volatile("ld.shared.b32 %0, [%1];" : "=r"(v) : "r"(addr) : "memory");
  return v;
}
__device__ __forceinline__ void sts32(uint32_t addr, uint32_t v) {
  asm volatile("st.shared.b32 [%0], %1;" ::"r"(addr), "r"(v) : "memory");
}

__device__ __forceinline__ int fresh_tid() {
  int t;
  asm volatile("mov.u32 %0, %%tid.x;" : "=r"(t));
  return t;
}
__device__ __forceinline__ unsigned ld_relaxed_u32(const void* p) {
  unsigned v;
  asm volatile("ld.relaxed.gpu.global.u32 %0, [%1];" : "=r"(v) : "l"(p) : "memory");
  return v;
}
__device__ __forceinline__ unsigned launch_epoch() { return (*(volatile unsigned*)g_done) / NCTA + 1u; }
__device__ __forceinline__ uint32_t set_tag(uint32_t w, uint32_t m, uint32_t tag) { return (w & ~m) | (tag & m); }
__device__ __forceinline__ uint32_t o_tag(int L) { return (L + 1) & 1; }
__device__ __forceinline__ uint32_t x_tag(int L) { return L & 1; }
__device__ __forceinline__ uint32_t kv_tag(int L) { return L < 2; }

#define SPINT 0
template <class F>
__device__ __forceinline__ void fix_lines(uint32_t bar, uint32_t par, uint32_t ta, uint32_t tag, uint32_t mask, int bar_id, F line) {
  uint32_t m;
  mbar_wait(bar, par);
  m = lds32(ta);
  m = __ballot_sync(0xffffffffu, (m ^ tag) & mask);
  if (m == 0u) return;
#pragma unroll 1
  for (uint32_t it = 0; it < (1u << 17) && m != 0u; ++it) {
    const int l = __ffs(m) - 1, j = fresh_tid() & 7;
    uint4 v;
    asm volatile("ld.relaxed.gpu.global.v4.b32 {%0,%1,%2,%3}, [%4];" : "=r"(v.x), "=r"(v.y), "=r"(v.z), "=r"(v.w) : "l"(line(l) + j * 8) : "memory");
    const uint32_t a = __shfl_sync(0xffffffffu, ta, l) ^ (j << 4);
    if (((__shfl_sync(0xffffffffu, v.x, 0) ^ tag) & 1u) == 0u) {
      asm volatile("st.shared.v4.b32 [%0], {%1,%2,%3,%4};" ::"r"(a), "r"(v.x), "r"(v.y), "r"(v.z), "r"(v.w) : "memory");
      m &= m - 1u;
    }
  }
  fence_proxy_async_smem();
  named_bar_sync(bar_id, 32);
}
__device__ __forceinline__ uint32_t peek_counts(const unsigned* f, unsigned target, int lane) {
  return __ballot_sync(0xffffffffu, (int)(ld_relaxed_u32(f + (lane & 15) * 4) - target) >= 0);
}
__device__ __forceinline__ void wait_count(const unsigned* f, unsigned target, int i, uint32_t& seen, int lane) {
  if ((seen >> i) & 1u) return;
#pragma unroll 1
  for (uint32_t it = 0; it < (1u << 17); ++it) {
    seen = peek_counts(f, target, lane);
    if ((seen >> i) & 1u) break;
  }
}
__device__ __forceinline__ float4 ld_rec(const float4* p) {
  float4 v;
  asm volatile("ld.relaxed.gpu.global.v4.f32 {%0,%1,%2,%3}, [%4];" : "=f"(v.x), "=f"(v.y), "=f"(v.z), "=f"(v.w) : "l"(p) : "memory");
  return v;
}
__device__ __forceinline__ void st_rec(float4* p, float a, float b, float c, unsigned tag) {
  asm volatile("st.relaxed.gpu.global.v4.f32 [%0], {%1,%2,%3,%4};" ::"l"(p), "f"(a), "f"(b), "f"(c), "f"(__uint_as_float(tag)) : "memory");
}
template <int N>
__device__ __forceinline__ float4 sum_recs(const float4* p, int stride, unsigned tag) {
  float4 s;
#pragma unroll 1
  for (uint32_t it = 0; it < (1u << 17); ++it) {
    float4 v[N];
#pragma unroll
    for (int t = 0; t < N; t++) v[t] = ld_rec(p + t * stride);
    bool ok = true;
    s = make_float4(0.f, 0.f, 0.f, 0.f);
#pragma unroll
    for (int t = 0; t < N; t++) {
      ok &= __float_as_uint(v[t].w) == tag;
      s.x += v[t].x;
      s.y += v[t].y;
      s.z += v[t].z;
    }
    if (ok) break;
    __nanosleep(200);
  }
  return s;
}

#define PHASE_IDS                                  \
  const int tid_ = fresh_tid();                    \
  const int lane = tid_ & 31, wwarp = __shfl_sync(0xffffffffu, (tid_ >> 5) & 3, 0), tid = tid_ & 127; \
  const int g = lane >> 2, c = lane & 3;           \
  (void)tid; (void)g; (void)c; (void)wwarp;

#define PHASE_IDS_W                                \
  const int lane = fresh_tid() & 31, wwarp = warp & 3; \
  const int g = lane >> 2, c = lane & 3;

#define GTL(i) do { } while (0)
#define TGET(v) do { } while (0)
#define TPUT(c, i, v) do { } while (0)

constexpr float SM_C = 0.17677669529663687f * 1.4426950408889634f;

__device__ __forceinline__ void stmatrix_x4_if(bool ok, uint32_t addr, uint32_t r0, uint32_t r1, uint32_t r2, uint32_t r3) {
  asm volatile("{\n.reg .pred p;\nsetp.ne.b32 p, %5, 0;\n@p stmatrix.sync.aligned.m8n8.x4.shared.b16 [%0], {%1,%2,%3,%4};\n}\n" ::"r"(addr),
               "r"(r0), "r"(r1), "r"(r2), "r"(r3), "r"((int)ok));
}

__device__ __forceinline__ void attn_a_slow(const uint8_t* __restrict__ kvimg, int L, int gb, int hp, uint32_t bad,
                                            int row0, int lane) {
  constexpr uint32_t sq = SBASE + OFF_SLOT + 3 * 16384;
#pragma unroll 1
  for (int j = 0; j < 8; j++) {
    const uint8_t* tp = kvimg + (size_t)(gb * 16 + hp) * 32768 + (j * 32 + lane) * 128 + ((lane & 7) << 4);
#pragma unroll 1
    for (uint32_t it = 0; it < (1u << 17); ++it)
      if (((ld_relaxed_u32(tp) ^ kv_tag(L)) & 1u) == 0u) break;
  }
  __syncwarp();
#pragma unroll 1
  for (int t = 0; t < 32; t++) {
    const int hh = t >> 4, row = row0 + (t & 7) + (t & 8) * 4;
    if (!((bad >> hh) & 1u)) continue;
    const int qpos = gb * 128 + row;
    const uint32_t qaddr = sq + row * 128;
    float mx = -INFINITY, sum = 0.f, acc = 0.f;
#pragma unroll 1
    for (int pass = 0; pass < 2; pass++) {
#pragma unroll 1
      for (int j = 0; j < 8; j++) {
        const int kp = qpos - (lane + 32 * j);
        const uint8_t* kr = kvimg + ((size_t)((kp >> 7) * 16 + hp) * 2 + ((kp >> 6) & 1)) * 16384 + (kp & 63) * 128;
        float d = -INFINITY;
        if (kp >= 0) {
          d = 0.f;
#pragma unroll 1
          for (int q = 0; q < 4; q++) {
            const uint4 kv = __ldcg(reinterpret_cast<const uint4*>(kr + (((hh * 4 + q) ^ (kp & 7)) << 4)));
            const uint4 qv = lds128(qaddr + (((hh * 4 + q) ^ (row & 7)) << 4));
            const uint32_t kw[4] = {kv.x, kv.y, kv.z, kv.w}, qw[4] = {qv.x, qv.y, qv.z, qv.w};
#pragma unroll
            for (int e = 0; e < 4; e++) d = fmaf(bf_lo(kw[e]), bf_lo(qw[e]), fmaf(bf_hi(kw[e]), bf_hi(qw[e]), d));
          }
        }
        if (pass == 0) {
          mx = fmaxf(mx, d);
        } else {
          const float ev = ex2_approx(d - mx);
          sum += ev;
          const float pv = bf16_round(ev);
#pragma unroll 1
          for (int kk = 0; kk < 32; kk++) {
            const float pk = __shfl_sync(0xffffffffu, pv, kk);
            const int k2 = qpos - (kk + 32 * j);
            if (k2 >= 0) {
              const uint8_t* vr = kvimg + ((size_t)((k2 >> 7) * 16 + hp) * 2 + ((k2 >> 6) & 1)) * 16384 + 8192 + (k2 & 63) * 128;
              const unsigned short vv =
                  __ldcg(reinterpret_cast<const unsigned short*>(vr + (((hh * 4 + (lane >> 3)) ^ (k2 & 7)) << 4) + (lane & 7) * 2));
              acc = fmaf(pk, __uint_as_float((uint32_t)vv << 16), acc);
            }
          }
        }
      }
      if (pass == 0) {
#pragma unroll
        for (int o = 16; o > 0; o >>= 1) mx = fmaxf(mx, __shfl_xor_sync(0xffffffffu, mx, o));
      }
    }
#pragma unroll
    for (int o = 16; o > 0; o >>= 1) sum += __shfl_xor_sync(0xffffffffu, sum, o);
    acc *= rcp_fast(sum);
    const float hi = __shfl_down_sync(0xffffffffu, acc, 1);
    __syncwarp();
    if ((lane & 1) == 0) sts32(qaddr + (((hh * 4 + (lane >> 3)) ^ (row & 7)) << 4) + (lane & 7) * 2,
                               set_tag(pack_bf16x2(acc, hi), hh == 0 && lane == 0, o_tag(L)));
    __syncwarp();
  }
}

template <int HH>
__device__ __forceinline__ void store_o(const float (&o)[16], const float (&inv)[2], uint32_t ra, uint32_t tag, bool ok) {
  const uint32_t m = HH == 0 && (fresh_tid() & 3) == 0;
#pragma unroll
  for (int jp = 0; jp < 2; jp++) {
    uint32_t w0 = pack_bf16x2(o[8 * jp] * inv[0], o[8 * jp + 1] * inv[0]);
    uint32_t w1 = pack_bf16x2(o[8 * jp + 2] * inv[1], o[8 * jp + 3] * inv[1]);
    if (HH == 0 && jp == 0) {
      w0 = set_tag(w0, m, tag);
      w1 = set_tag(w1, m, tag);
    }
    stmatrix_x4_if(ok, ra ^ ((HH * 4 + 2 * jp) << 4), w0, w1, pack_bf16x2(o[8 * jp + 4] * inv[0], o[8 * jp + 5] * inv[0]),
                   pack_bf16x2(o[8 * jp + 6] * inv[1], o[8 * jp + 7] * inv[1]));
  }
}
__device__ __forceinline__ int tile_row(bool B, int w, int r, int g) { return (B ? 16 * w + 8 * r : 8 * w + 32 * r) + g; }
__device__ __forceinline__ uint32_t q_row_addr(bool B, int R, int w, int lane) {
  return SBASE + OFF_SLOT + 3 * 16384 + R * 8192 + tile_row(B, w, (lane >> 3) & 1, lane & 7) * 128 + (((lane >> 4) ^ (lane & 7)) << 4);
}

struct AttnA {
  float s[2][16], o[2][16], l[2][2], sh[2][3];
  uint32_t p[2][4], t[2], me[4], ra, bad, zero;
};
#define ATS_(i) do { } while (0)
template <int V>
__device__ __forceinline__ void attn_sum(AttnA& a, int nv) {
  constexpr int hh = (V >> 1) & 1, kh = V & 1, i = V >> 2;
#pragma unroll
  for (int r = 0; r < 2; r++) {
    const uint32_t t1 = add_bf16x2(add_bf16x2(a.p[0][r], a.p[0][2 + r]), add_bf16x2(a.p[1][r], a.p[1][2 + r]));
    if (kh == 0) {
      a.t[r] = t1;
    } else {
      uint32_t tt = add_bf16x2(a.t[r], t1);
      if (i > 0) tt = i <= nv ? tt : 0u;
      const float v = bf_lo(tt) + bf_hi(tt);
      a.l[hh][r] = i == 0 ? v : a.l[hh][r] + v;
    }
  }
}
template <int HH>
__device__ __forceinline__ void attn_shfl(AttnA& a) {
#pragma unroll
  for (int r = 0; r < 2; r++)
#pragma unroll
    for (int j = 0; j < 3; j++) a.sh[r][j] = __shfl_xor_sync(0xffffffffu, a.l[HH][r], j + 1);
}
template <int HH>
__device__ __forceinline__ void attn_fin(AttnA& a) {
  bool bad = false;
  float inv[2];
#pragma unroll
  for (int r = 0; r < 2; r++) {
    const float v = (a.l[HH][r] + a.sh[r][0]) + (a.sh[r][1] + a.sh[r][2]);
    bad |= !(v <= 1.152921504606846976e18f && v >= 8.673617379884035e-19f);
    inv[r] = rcp_fast(v);
  }
  bad = __any_sync(0xffffffffu, bad);
  if (HH == 1) wgmma_wait<0>();
  reg_fence<16>(a.o[HH]);
  store_o<HH>(a.o[HH], inv, a.ra, o_tag(0), !bad);
  a.bad = (HH == 0 ? 0u : a.bad) | (bad ? 1u << HH : 0u);
}
__device__ __forceinline__ void attn_masks(AttnA& a, int wr) {
  const int lane = fresh_tid() & 31, d = (lane >> 2) - 2 * (lane & 3);
  const uint32_t tri = d >= 1 ? 0xffffffffu : (d == 0 ? 0xffffu : 0u);
#pragma unroll
  for (int t = 0; t < 4; t++) a.me[t] = wr > t ? 0xffffffffu : (wr == t ? tri : 0u);
}
template <int V, int K>
__device__ __forceinline__ uint32_t attn_exp(AttnA& a) {
  constexpr int i = V >> 2, kh = V & 1, r = K & 1;
  if ((i == 0 && kh > r) || (i == 4 && kh < r)) return 0u;
  const uint32_t w = pack_bf16x2(ex2_approx(a.s[V & 1][2 * K]), ex2_approx(a.s[V & 1][2 * K + 1]));
  if (i == 0 && kh == r) return w & a.me[K >> 1];
  if (i == 4 && kh == r) return w & ~a.me[K >> 1];
  return w;
}
template <int V>
__device__ __forceinline__ void attn_unit(AttnA& a, const uint32_t (&q)[2][2][4], uint64_t dcur, uint64_t dnext, int R, int wr, int nv,
                                          uint32_t hbar, uint32_t hpar, uint32_t rbar, bool rel) {
  constexpr int hh = (V >> 1) & 1, kh = V & 1, i = V >> 2;
  ATS_(V + 1);
  asm volatile("" : "+l"(dcur), "+l"(dnext));
  wgmma_wait<1>();
  reg_fence<16>(a.s[V & 1]);
  bool hok = true;
  if (V == 4) hbar = SBASE + OFF_BAR + 8u * (R ? B_LOC : B_HV);
  if (((V & 3) == 2 && V < 16) || V == 4) hok = mbar_test(hbar, hpar);
  const uint64_t d0 = ((V & 3) >= 2 ? dnext : dcur) + ((hh ^ 1) * 4 + kh * 256), d1 = ((V & 3) >= 2 ? dnext : dcur) + ((hh ^ 1) * 4 + kh * 256 + 2);
  const uint64_t d2 = dcur + (512 + hh * 4 + kh * 256), d3 = dcur + (640 + hh * 4 + kh * 256);
  if ((V & 3) == 1 && V > 4 && rel) mbar_arrive(rbar);
  if (V > 0) attn_sum<V - 1>(a, nv);
  if (V == 15) attn_masks(a, wr);
  if (V == 18) {
    attn_shfl<0>(a);
    a.ra = q_row_addr(false, R, wr, fresh_tid() & 31);
  }
  if (V == 19) attn_fin<0>(a);
  uint32_t p[2][4];
  p[0][0] = attn_exp<V, 0>(a);
  p[0][1] = attn_exp<V, 1>(a);
  p[0][2] = attn_exp<V, 2>(a);
  p[0][3] = attn_exp<V, 3>(a);
  p[1][0] = attn_exp<V, 4>(a);
  p[1][1] = attn_exp<V, 5>(a);
  p[1][2] = attn_exp<V, 6>(a);
  p[1][3] = attn_exp<V, 7>(a);
  if (V > 0) {
#pragma unroll
    for (int r = 0; r < 2; r++) p[1][r] ^= (kh ? a.t[r] : __float_as_uint(a.l[hh ^ 1][r])) & a.zero;
  }
#pragma unroll
  for (int k = 0; k < 8; k++) {
    asm volatile("" : "+r"(p[k >> 2][k & 3]));
    a.p[k >> 2][k & 3] = p[k >> 2][k & 3];
  }
  if (!hok) mbar_wait(hbar, hpar);
  wgmma_fence();
  if (V < 18) wgmma_n32_rsz_tb0(a.s[V & 1], q[hh ^ 1][0], d0);
  if (i == 0 && kh == 0) wgmma_n32_rsz_tb1(a.o[hh], a.p[0], d2);
  else wgmma_n32_rs_tb1(a.o[hh], a.p[0], d2, 1);
  if (V < 18) wgmma_n32_rs_tb0(a.s[V & 1], q[hh ^ 1][1], d1, 1);
  wgmma_n32_rs_tb1(a.o[hh], a.p[1], d3, 1);
  wgmma_commit();
}
template <int I>
__device__ __forceinline__ void attn_step(AttnA& a, const uint32_t (&q)[2][2][4], uint64_t dcur, uint64_t dnext, int R, int wr, int nv,
                                          uint32_t hbar, uint32_t hpar, uint32_t rbar, bool rel) {
  attn_unit<4 * I>(a, q, dcur, dnext, R, wr, nv, hbar, hpar, rbar, rel);
  attn_unit<4 * I + 1>(a, q, dcur, dnext, R, wr, nv, hbar, hpar, rbar, rel);
  attn_unit<4 * I + 2>(a, q, dcur, dnext, R, wr, nv, hbar, hpar, rbar, rel);
  attn_unit<4 * I + 3>(a, q, dcur, dnext, R, wr, nv, hbar, hpar, rbar, rel);
}

__device__ __forceinline__ void attention_a(const uint32_t (&q)[2][2][4], int R, int L, int gb, int hp, uint32_t par, int wr,
                                            uint32_t zero) {
  constexpr uint32_t bars = SBASE + OFF_BAR;
  constexpr uint32_t dslot = ((SBASE + OFF_SLOT) >> 4) + 0x10000u;
  auto next = [&](uint64_t d) { return desc_lo((uint32_t)d == dslot ? dslot + 2048 : (uint32_t)d - 1024) + zero; };
  uint64_t d0 = desc_lo(dslot + R * 1024) + zero, d1 = next(d0);
  AttnA a;
  ATS_(0);
  wgmma_fence();
#pragma unroll
  for (int v = 0; v < 2; v++) {
    wgmma_n32_rsz_tb0(a.s[v], q[0][0], d0 + v * 256);
    wgmma_n32_rs_tb0(a.s[v], q[0][1], d0 + (v * 256 + 2), 1);
    wgmma_commit();
  }
  a.zero = zero;
  const bool lane0 = (fresh_tid() & 31) == 0;
  attn_masks(a, wr);
  const int nv = 2 * gb + R;
  const uint32_t hb = bars + 8u * (B_HALO - R), rb = bars + 8u * (B_REL - R);
  attn_step<0>(a, q, d0, d1, R, wr, nv, hb, par, 0, false);
  d0 = next(d1);
  attn_step<1>(a, q, d1, d0, R, wr, nv, R ? bars + 8u * B_HV : hb + 8, par, rb + 8, lane0);
  d1 = next(d0);
  attn_step<2>(a, q, d0, d1, R, wr, nv, hb + 16, par, rb + 16, lane0);
  d0 = next(d1);
  attn_step<3>(a, q, d1, d0, R, wr, nv, hb + 24, par, rb + 24, lane0 && R);
  attn_step<4>(a, q, d0, d0, R, wr, nv, 0, 0, rb, false);
  ATS_(21);
  attn_sum<19>(a, nv);
  attn_shfl<1>(a);
  attn_fin<1>(a);
  ATS_(22);
  if (a.bad != 0u) {
    attn_a_slow(g_kvA[0][0][0], L, gb, hp, a.bad, R * 64 + wr * 8, fresh_tid() & 31);
    named_bar_sync(7, 32);
  }
}

constexpr uint32_t KB_ROW0 = SBASE + OFF_SLOT + 2048, VB_ROW0 = SBASE + OFF_SLOT + 24576 + 2048;

__device__ __forceinline__ void attention_b(const uint32_t (&q)[2][2][4], int R, int gb, uint32_t par0, int wr) {
  constexpr uint32_t bars = SBASE + OFF_BAR;
  const uint32_t dk = ((KB_ROW0 - 2048) >> 4) + 0x10000u + R * 512, dv = dk + ((VB_ROW0 - KB_ROW0) >> 4);
  float s[2][40];
  mbar_wait(bars + 8u * (B_HALO - R), par0);
  wgmma_fence();
#pragma unroll
  for (int hh = 0; hh < 2; hh++) {
    wgmma_n80_rsz_tb0(s[hh], q[hh][0], desc_lo(dk + hh * 4));
    wgmma_n80_rs_tb0(s[hh], q[hh][1], desc_lo(dk + hh * 4 + 2), 1);
  }
  wgmma_commit();
  const int lane = fresh_tid() & 31, g = lane >> 2;
  const bool odd = g & 1, edge = R == 0 && gb == 0 && wr == 0;
  const int D = 2 * (lane & 3) + (g & 1) - g;
  const uint32_t ra = q_row_addr(true, R, wr, lane);
  wgmma_wait<0>();
  reg_fence<40>(s[0]);
  reg_fence<40>(s[1]);
  float z[2][2], y[2][2];
#define GATHER_(W)                                                                                          \
  _Pragma("unroll") for (int hh = 0; hh < 2; hh++) _Pragma("unroll") for (int r = 0; r < 2; r++) {          \
    const float* e = &s[hh][4 * (2 * W + r) + 2 * r];                                                       \
    z[hh][r] = odd ? e[5] : e[4];                                                                           \
    y[hh][r] = D >= 2 ? (odd ? e[1] : e[0]) : (odd ? e[9] : e[8]);                                          \
  }
  if (wr < 2) {
    if (wr == 0) { GATHER_(0) } else { GATHER_(1) }
  } else {
    if (wr == 2) { GATHER_(2) } else { GATHER_(3) }
  }
#undef GATHER_
  float o[2][16], inv[2][2];
  uint32_t p[2][5][4];
  const int sh = odd ? 16 : 0, kb = wr + (D >= 2 ? 0 : 1);
#pragma unroll
  for (int hh = 0; hh < 2; hh++) {
    if (edge) {
      z[hh][0] = -INFINITY;
      if (D >= 2) y[hh][0] = y[hh][1] = -INFINITY;
    }
    uint32_t ab[2][2];
#pragma unroll
    for (int r = 0; r < 2; r++) {
      float m = fmaxf(z[hh][r], y[hh][r]);
      m = fmaxf(m, __shfl_xor_sync(0xffffffffu, m, 1));
      m = fmaxf(m, __shfl_xor_sync(0xffffffffu, m, 2));
      const float e0 = ex2_approx(z[hh][r] - m), e1 = ex2_approx(y[hh][r] - m);
      inv[hh][r] = e0 + e1;
      ab[r][0] = pack_bf16x2(e0, 0.f) << sh;
      ab[r][1] = pack_bf16x2(e1, 0.f) << sh;
    }
#pragma unroll
    for (int k = 0; k < 5; k++) {
      p[hh][k][0] = k == kb ? ab[0][1] : 0u;
      p[hh][k][1] = k == wr + 1 ? ab[1][0] : 0u;
      p[hh][k][2] = k == wr ? ab[0][0] : 0u;
      p[hh][k][3] = k == kb ? ab[1][1] : 0u;
#pragma unroll
      for (int j = 0; j < 4; j++) asm volatile("" : "+r"(p[hh][k][j]));
    }
  }
  wgmma_fence();
#pragma unroll
  for (int hh = 0; hh < 2; hh++) {
    wgmma_n32_rsz_tb1(o[hh], p[hh][0], desc_lo(dv + hh * 4));
#pragma unroll
    for (int k = 1; k < 5; k++) wgmma_n32_rs_tb1(o[hh], p[hh][k], desc_lo(dv + hh * 4 + k * 128), 1);
  }
  wgmma_commit();
#pragma unroll
  for (int hh = 0; hh < 2; hh++)
#pragma unroll
    for (int r = 0; r < 2; r++) {
      inv[hh][r] += __shfl_xor_sync(0xffffffffu, inv[hh][r], 1);
      inv[hh][r] += __shfl_xor_sync(0xffffffffu, inv[hh][r], 2);
      inv[hh][r] = rcp_fast(inv[hh][r]);
    }
  wgmma_wait<0>();
  reg_fence<16>(o[0]);
  reg_fence<16>(o[1]);
  store_o<0>(o[0], inv[0], ra, o_tag(1), true);
  store_o<1>(o[1], inv[1], ra, o_tag(1), true);
}

#define KTQM 0
#define TRICKLE 300
#define QREL 8
#define PRESLEEP 200
#define CSA 3
#define PN1 4
#define PN2 5
#define TLAZY 100
#define SDLY 1500
#define HTS(i) do { } while (0)
struct Params {
  CUtensorMap x[5], xq[4], o, wqkv[2], wqkv3[2], wo3[2];
  const __nv_bfloat16* in_x;
  const __nv_bfloat16* wqkv_p[2];
  const __nv_bfloat16* wo_p[2];
  __nv_bfloat16* out;
  uint32_t zero;
};

__device__ __forceinline__ void colsum_part(const CUtensorMap* wmap, int ty, int qr, int hp) {
  constexpr uint32_t bars = SBASE + OFF_BAR, slots = SBASE + OFF_SLOT;
  PHASE_IDS
  const unsigned ep1 = launch_epoch();
  if (wwarp == 0 && elect_one()) {
    mbar_expect_tx(bars + 8u * B_CS, 6 * UNIT);
#pragma unroll 1
    for (int j = 0; j < 6; j++) {
      if (ty == 0) mbar_pace(bars + 8u * (B_QF + B_E + ((j * CSA / 6) & 3)), (j * CSA / 6) >> 2, j ? PN1 : 30);
      else mbar_wait_lazy<100>(bars + 8u * (B_WF + B_E + ((2 * j + 3 - (j & 1)) & 7)), j >= 3);
      tma_load_2d(slots + j * UNIT, wmap, bars + 8u * B_CS, (j >> 1) * 1024 + hp * 64, qr * 128 + (j & 1) * 64);
    }
  }
  constexpr uint64_t ones = (SBASE + OFF_LSB + 32) >> 4;
  float s[3][4];
  mbar_wait_lazy<100>(bars + 8u * B_CS, ty);
  wgmma_fence();
#pragma unroll
  for (int p = 0; p < 3; p++) {
    wgmma_n8_ssz_ta1_tb0(s[p], make_desc(slots + p * 2 * UNIT, 16), ones);
#pragma unroll
    for (int k = 1; k < 8; k++) wgmma_n8_ss_ta1_tb0(s[p], make_desc(slots + p * 2 * UNIT + k * 2048, 16), ones, 1);
  }
  wgmma_commit();
  wgmma_wait<0>();
  reg_fence<12>(&s[0][0]);
  if (lane == 0) mbar_arrive(bars + 8u * (ty ? B_CSD : B_RDONE));
  if (c == 0) {
#pragma unroll
    for (int r = 0; r < 2; r++) st_rec(&g_cs[ty][hp][qr][wwarp * 16 + 8 * r + g], s[0][2 * r], s[1][2 * r], s[2][2 * r], ep1);
  }
}

__device__ __forceinline__ void put_colsums(int ty, int col, const float4& s) {
  const float v[3] = {s.x, s.y, s.z};
#pragma unroll
  for (int p = 0; p < 3; p++) {
    const uint32_t a = SBASE + OFF_CS + (p * 8 + (col >> 3)) * 64 + ty * 32 + (col & 7) * 2;
    const float hi = bf16_round(v[p]);
    const uint32_t w = pack_bf16x2(hi, v[p] - hi);
    asm volatile("st.shared.b16 [%0], %1;" ::"r"(a), "h"((unsigned short)w) : "memory");
    asm volatile("st.shared.b16 [%0], %1;" ::"r"(a + 16), "h"((unsigned short)(w >> 16)) : "memory");
  }
}

__device__ __forceinline__ uint32_t ln_params(float s1, float s2) {
  const float mean = s1 * (1.0f / DM);
  const float var = fmaxf(fmaf(-mean, mean, s2 * (1.0f / DM)), 0.f);
  float sd;
  asm("sqrt.approx.f32 %0, %1;" : "=f"(sd) : "f"(bf16_round(bf16_round(var) + 1e-5f)));
  return pack_bf16x2(mean, sd);
}

__host__ __device__ constexpr uint32_t w_rel(int kt) { return ((B_WF + (kt & 7)) << 1) | (kt >> 3); }
__host__ __device__ constexpr uint32_t w_rel4(int a, int b, int c, int d) { return w_rel(a) | (w_rel(b) << 8) | (w_rel(c) << 16) | (w_rel(d) << 24); }
__device__ __forceinline__ void ring_wait(uint32_t e) { mbar_wait(SBASE + OFF_BAR + 8u * B_E + ((e << 2) & 0x3f8u), e & 1u); }
struct RingProd {
  uint32_t rel = ((B_QF << 1) | 1) * 0x01010101u + 0x06040200u;
  __device__ __forceinline__ void q_step(int kt) {
    const int sh = 8 * (kt & 3);
    const uint32_t e = rel >> sh;
    rel ^= ((e ^ (((B_QF + (kt & 3)) << 1) | ((kt >> 2) & 1))) & 255u) << sh;
    ring_wait(e);
  }
  __device__ __forceinline__ void w_job(int st, bool pre, uint32_t sel0, uint32_t sel1, uint32_t last, uint32_t& w0, uint32_t& w1) {
    const uint32_t r = __funnelshift_r(rel, rel, 8 * st);
    w0 = __byte_perm(r, 0u, sel0);
    w1 = __byte_perm(r, w_rel4(0, 1, 2, 3), pre ? sel1 : 0x6543u);
    const uint32_t n = pre ? (w_rel4(9, 11, 13, 0) & 0xffffffu) | (last << 24) : (w_rel4(11, 13, 0, 15) & 0xff00ffffu) | (last << 16);
    rel = __funnelshift_l(n, n, 8 * st);
  }
};

#define SP1 15
#define SP2 14
#define SP3 12
#define SP4 12
#define SP5 15
#define SP6 14
#define SP7 16
__device__ __forceinline__ int q_split(int inst) {
  constexpr uint32_t T = 15u | ((SP1 - 1) << 4) | ((SP2 - 1) << 8) | ((SP3 - 1) << 12) | ((SP4 - 1) << 16) | ((SP5 - 1) << 20) |
                         ((SP6 - 1) << 24) | ((uint32_t)(SP7 - 1) << 28);
  return (int)((T >> (4 * inst)) & 15u) + 1;
}
#define QROT 0
#define WROT 0
__device__ __forceinline__ int qk(int kt) { return (kt + QROT) & 15; }
__device__ __forceinline__ int wk(int kt) { return (kt + WROT) & 15; }
__host__ __device__ constexpr uint32_t turn_par(int kind) {
  const int sp[8] = {16, SP1, SP2, SP3, SP4, SP5, SP6, SP7};
  int cnt[2] = {0, 0};
  uint32_t m = 0;
  for (int i = 0; i < 8; i++)
    for (int k = 0; k < 3; k++) {
      if (k == kind) m |= (uint32_t)(cnt[i & 1] & 1) << i;
      if (k == 0 ? (i == 1 || (i > 1 && sp[i - 1] < 16)) : (k == 2 || sp[i] < 16)) cnt[i & 1]++;
    }
  return m;
}
#define PREMASK 0xBFu
__device__ __forceinline__ bool w_pre(int inst) { return (PREMASK >> inst) & 1u; }
__host__ __device__ constexpr unsigned long long bar_counts(int i0) {
  unsigned long long t = 0;
  for (int i = i0; i < i0 + 32; i++) {
    int l = 0;
    if (i < B_RF) l = 1;
    if ((i >= B_E && i < B_E + B_RF) || i == B_LOC || i == B_REL || i == B_OS0 || i == B_TURN || i == B_TURN + 1 || i == B_XS ||
        i == B_XS + 1 || i == B_CSD || i == B_GO || i == B_RDONE || i == B_KV)
      l = 2;
    if (i == B_REL + 1 || i == B_REL + 2) l = 3;
    t |= (unsigned long long)l << (2 * (i - i0));
  }
  return t;
}

__global__ void __launch_bounds__(512, 1) fused_kernel(const __grid_constant__ Params P) {
  extern __shared__ __align__(1024) uint8_t smem_raw[];
  constexpr uint32_t base = SBASE, bars = base + OFF_BAR, slots = base + OFF_SLOT;
  if (smem_u32(smem_raw) != base) __trap();
  const int warp = __shfl_sync(0xffffffffu, threadIdx.x >> 5, 0), lane = threadIdx.x & 31;
  const int b = blockIdx.x;
#define QS 0
#define WS 1
  const int qr = ((b & ((8 << QS) - 1)) >> QS) ^ (((b >> (3 + QS)) & 1) * 7);
  const int hp = ((b >> (3 + QS)) << QS) + (b & ((1 << QS) - 1));
  const int rt = ((b & ((16 << WS) - 1)) >> WS) ^ (((b >> (4 + WS)) & 1) * 15);
  const int ct = ((b >> (4 + WS)) << WS) + (b & ((1 << WS) - 1));

  if (warp == 12) {
    if (elect_one()) {
#pragma unroll 1
      for (int s = 0; s < 4; s++) {
        const uint32_t fb = bars + 8u * (B_QF + s), sa = base + s * 5 * UNIT;
        mbar_init(fb, 2);
        fence_barrier_init();
        mbar_expect_tx(fb, 5 * UNIT);
        mbar_arrive(fb);
        tma_load_5d(sa + 3 * UNIT, &P.xq[0], fb, s * 64, qr * 2);
        tma_load_3d(sa, &P.wqkv3[0], fb, hp * 64, s * 64);
      }
    }
    __syncwarp();
  } else if (warp >= 4 && warp < 12) {
    if (elect_one()) {
#pragma unroll 1
      for (int i = warp; i <= B_KV; i += 8) mbar_init(bars + 8u * i, 1u << (((i < 32 ? bar_counts(0) : bar_counts(32)) >> (2 * (i & 31))) & 3u));
      sts32(warp < 8 ? base + OFF_ONE - 16 + 4 * warp : base + OFF_LSB + 4 * warp, warp < 8 ? warp == 4 : 0x3f803f80u);
      fence_proxy_async_smem();
      fence_barrier_init();
    }
    __syncwarp();
  }

  if (warp >= 12) {
    setmaxnreg_dec<32>();
    if (warp == 12) {
      named_bar_sync(0, 512);
      if (elect_one()) {
#pragma unroll 1
        for (int s = 4; s < 16; s++) {
          const uint32_t fb = bars + 8u * (B_QF + (s & 3)), sa = base + (s & 3) * 5 * UNIT;
          mbar_wait(fb + 8u * B_E, ((s >> 2) & 1) ^ 1);
          mbar_expect_tx(fb, 5 * UNIT);
          mbar_arrive(fb);
          tma_load_5d(sa + 3 * UNIT, &P.xq[0], fb, s * 64, qr * 2);
          tma_load_3d(sa, &P.wqkv3[0], fb, hp * 64, s * 64);
        }
#pragma unroll
        for (int s = 0; s < 4; s++) mbar_arrive(bars + 8u * B_GO);
        RingProd rp;
#pragma unroll 1
        for (int sg = 4; sg < 34; sg++) {
          const int part = sg & 3, inst = (sg >> 2) - (part & 1);
          if (part == 3 || inst == 8) continue;
          const int ty = (inst >> 1) & 1;
          if (part != 1) {
            const int k0 = part ? q_split(inst) : 0, k1 = part ? 16 : q_split(inst);
#pragma unroll 1
            for (int kt = k0; kt < k1; kt++) {
              const uint32_t sa = base + (kt & 3) * 5 * UNIT, fb = bars + 8u * (B_QF + (kt & 3));
              rp.q_step(kt);
              mbar_expect_tx(fb, 3 * UNIT);
              tma_load_3d(sa, &P.wqkv3[ty], fb, hp * 64, qk(kt) * 64);
            }
          } else {
            const bool pre = w_pre(inst);
            int st = inst < 7 ? q_split(inst + 1) & 3 : 0;
            uint32_t w0, w1;
            rp.w_job(st, pre, pre ? 0x1100u : 0x2100u, 0x3322u, (B_RF << 1) | (inst & 1), w0, w1);
#pragma unroll 1
            for (int m = 0; m < 4; m++) {
              const uint32_t fb = bars + 8u * (B_WF + 4 * (m & 1));
#pragma unroll
              for (int i = 0; i < 4; i++) {
                if (i < 3 || !pre) {
                  ring_wait(w0 >> (8 * i));
                  mbar_expect_tx(fb + 8u * i, 2 * UNIT);
                  tma_load_3d(base + ((st + (i ? i - 1 : 0)) & 3) * 5 * UNIT + ((0x2d >> (2 * i)) & 3) * UNIT, &P.wo3[ty], fb + 8u * i,
                              ct * 128, wk(4 * m + i) * 64);
                }
              }
              st += pre ? 2 : 3;
              w0 = w1;
              w1 = m == 0 ? (pre ? w_rel4(0, 1, 2, 3) : w_rel4(3, 4, 5, 6)) : (pre ? w_rel4(4, 5, 6, 7) : w_rel4(7, 8, 9, 10));
            }
          }
        }
      }
    } else if (warp == 13) {
      RingProd rp;
      unsigned ep1 = 0;
      uint32_t seenx = 0;
      named_bar_sync(0, 512);
      mbar_wait(bars + 8u * B_GO, 0);
#pragma unroll 1
      for (int sg = 4; sg < 34; sg++) {
        const int part = sg & 3, inst = (sg >> 2) - (part & 1);
        if (part == 3 || inst == 8) continue;
        const int L = inst >> 1, ch = inst & 1;
        if (part != 1) {
          const CUtensorMap* tx = &P.xq[L];
          const int k0 = part ? q_split(inst) : 0, k1 = part ? 16 : q_split(inst);
          if (sg == 4) ep1 = launch_epoch();
          if (part == 0) seenx = L == 0 ? 0xffffffffu : peek_counts(g_fx[ch * 8 + qr][0], 6u * ep1 - 6u + 2u * L, lane);
          const int m0 = ch * 16 + qr * 2;
#pragma unroll 1
          for (int kt = k0; kt < k1; kt++) {
            const uint32_t fb = bars + 8u * (B_QF + (kt & 3));
            rp.q_step(kt);
            if (lane == 0) mbar_expect_tx(fb, 2 * UNIT);
            wait_count(g_fx[ch * 8 + qr][0], 6u * ep1 - 6u + 2u * L, qk(kt), seenx, lane);
            TGET(t38);
            if (elect_one()) tma_load_5d(base + ((kt & 3) * 5 + 3) * UNIT, tx, fb, qk(kt) * 64, m0);
            TGET(t39);
            if (L == 3 && kt == 0 && lane == 0) { TPUT(ch, 38, t38); TPUT(ch, 39, t39); }
          }
        } else {
          const int m0 = ch * 1024 + rt * 64;
          const bool pre = w_pre(inst);
          int st = inst < 7 ? q_split(inst + 1) & 3 : 0;
          uint32_t w0, w1;
          uint32_t seen = peek_counts(g_fo[ch * 16 + rt][0], 4u * ep1 - 3u + L, lane);
          rp.w_job(st, pre, 0x1110u, 0x3332u, inst == 6 && SP7 == 16 ? B_RF << 1 : w_rel(15), w0, w1);
#pragma unroll 1
          for (int m = 0; m < 4; m++) {
            const uint32_t fb = bars + 8u * (B_WF + 4 * (m & 1));
#pragma unroll
            for (int i = 0; i < 4; i++) {
              ring_wait(w0 >> (8 * i));
              if (lane == 0) mbar_expect_tx(fb + 8u * i, UNIT);
              wait_count(g_fo[ch * 16 + rt][0], 4u * ep1 - 3u + L, wk(4 * m + i), seen, lane);
              if (elect_one())
                tma_load_2d(base + ((st + (i > 0)) & 3) * 5 * UNIT + (i == 2 ? 1 : (i == 3 ? 4 : 0)) * UNIT, &P.o, fb + 8u * i, wk(4 * m + i) * 64, m0);
            }
            st += pre ? 2 : 3;
            w0 = w1;
            w1 = m == 0 ? (pre ? w_rel4(0, 1, 2, 3) : w_rel4(3, 4, 5, 6)) : (pre ? w_rel4(4, 5, 6, 7) : w_rel4(7, 8, 9, 10));
          }
          if (L == 3) {
#pragma unroll 1
            for (int j = 0; j < 4; j++) {
              g_x[(size_t)(m0 + j * 16 + (lane >> 1)) * DM + ct * 128 + (lane & 1) * 64] = __ushort_as_bfloat16(0);
              __syncwarp();
            }
          }
        }
      }
    } else if (warp == 14) {
      const unsigned ep1 = launch_epoch();
      uint32_t hpar = 0;
      named_bar_sync(0, 512);
#pragma unroll 1
      for (int inst = 0; inst < 8; inst++) {
        const int L = inst >> 1, ch = inst & 1, gb = ch * 8 + qr;
        const unsigned kv0 = 8u * ep1 - 8u + 2u * L + (L & 1);
        const uint32_t tag = kv_tag(L);
        if (L >= 2) {
#pragma unroll 1
          for (uint32_t it = 0; it < (1u << 17); ++it)
            if (__all_sync(0xffffffffu, (int)(ld_relaxed_u32(g_fk[hp][min(gb + 1 + (lane & 1), 15)]) - kv0) >= 0)) break;
        }
        if ((L & 1) == 0) {
          uint8_t* img = g_kvA[gb][hp][0];
          const uint8_t* s1 = gb > 0 ? img - 16 * 32768 : g_zero;
          const uint8_t* s2 = gb > 1 ? img - 32 * 32768 : g_zero;
          const uint32_t h1 = gb > 0 ? 16384 : 0, h2 = gb > 1 ? 16384 : 0;
          const unsigned* cp = g_fk[hp][max(gb - 1 - (lane >= 3), 0)];
          const unsigned ct0 = kv0 + ((0x32321u >> (4 * (lane & 7))) & 3u);
          uint32_t fr = gb == 0 ? 31u : (gb == 1 ? 24u : 0u);
          const uint32_t toff = slots + lane * 128 + ((lane & 7) << 4);
          auto seen = [&](uint32_t m) {
#pragma unroll 1
            for (uint32_t it = 0; it < (1u << 17) && !(fr & m); ++it)
              fr |= __ballot_sync(0xffffffffu, (int)(ld_relaxed_u32(cp) - ct0) >= 0);
          };
          auto load = [&](uint32_t off, const uint8_t* src, uint32_t bytes, int bi) {
            if (elect_one()) {
              mbar_expect_tx(bars + 8u * (B_HL + bi), bytes);
              bulk_load(slots + off, src, bytes, bars + 8u * (B_HL + bi));
            }
          };
          auto check = [&](uint32_t off, const uint8_t* src, uint32_t bytes, int bi, bool real, int done) {
#pragma unroll 1
            for (int tries = 0; tries < 4096; tries++) {
              mbar_wait(bars + 8u * (B_HL + bi), (hpar >> bi) & 1u);
              hpar ^= 1u << bi;
              uint32_t t = (lds32(toff + off) ^ tag) | (lds32(toff + off + 4096) ^ tag);
              if (bytes > 8192) t |= (lds32(toff + off + 8192) ^ tag) | (lds32(toff + off + 12288) ^ tag);
              if (!__any_sync(0xffffffffu, real && (t & 1u))) break;
              fence_proxy_async_smem();
              load(off, src, bytes, bi);
            }
            if (lane == 0) mbar_arrive(bars + 8u * done);
          };
          uint8_t *pk = img + 16384, *pv = img + 24576;
          unsigned* f = g_fk[hp][gb];
          pin64(pk), pin64(pv), pin64(f);
          mbar_wait(bars + 8u * B_KV, inst & 1);
          if (elect_one()) {
            bulk_store(pk, slots + 16384, 8192);
            bulk_announce(f);
            bulk_store(pv, slots + 24576, 8192);
            bulk_announce(f);
            bulk_commit();
          }
          HTS(44);
          seen(1);
          HTS(46);
          load(32768, s1 + h1, 8192, 0);
          seen(2);
          HTS(47);
          load(40960, s1 + h1 + 8192, 8192, 1);
          mbar_wait(bars + 8u * B_LOC, inst & 1);
          HTS(45);
          if (elect_one()) {
            bulk_store(img, slots, 16384);
            bulk_announce(g_fk[hp][gb]);
            bulk_commit();
            asm volatile("cp.async.bulk.wait_group.read 1;" ::: "memory");
          }
          check(32768, s1 + h1, 8192, 0, gb > 0, B_HALO);
          HTS(52);
          check(40960, s1 + h1 + 8192, 8192, 1, gb > 0, B_HV);
          HTS(53);
#pragma unroll 1
          for (int n = 1; n < 4; n++) {
            const uint8_t* src = n == 1 ? s1 : (n == 2 ? s2 + h2 : s2);
            const uint32_t off = n == 3 ? 32768 : 32768 - n * 16384;
            seen(2u << n);
            if (n == 2 && elect_one()) bulk_wait_read0();
            mbar_wait(bars + 8u * (B_REL - 1) + 8u * n, ch);
            HTS(47 + n);
            load(off, src, 16384, 0);
            check(off, src, 16384, 0, gb > (n >> 1), B_HALO + n);
            HTS(53 + n);
          }
        } else {
          uint8_t *pk = g_kvB[gb][hp], *pv = pk + 2048;
          const uint8_t* src = gb >= 1 ? pk - 16 * 4096 : g_zero;
          unsigned* f = g_fk[hp][gb];
          pin64(pk), pin64(pv), pin64(f), pin64(src);
          mbar_wait(bars + 8u * B_KV, inst & 1);
          if (elect_one()) {
            bulk_store(pk, KB_ROW0 + 112 * 128, 2048);
            bulk_store(pv, VB_ROW0 + 112 * 128, 2048);
            bulk_announce(f);
            bulk_commit();
          }
          HTS(44);
          if (gb > 0) {
#pragma unroll 1
            for (uint32_t it = 0; it < (1u << 17); ++it)
              if (__any_sync(0xffffffffu, (int)(ld_relaxed_u32(f - 4) - kv0) > 0)) break;
          }
          HTS(46);
#pragma unroll 1
          for (uint32_t it = 0; it < (1u << 17); ++it) {
            if (elect_one()) {
              mbar_expect_tx(bars + 8u * B_HL, 4096);
              bulk_load(KB_ROW0 - 2048, src, 2048, bars + 8u * B_HL);
              bulk_load(VB_ROW0 - 2048, src + 2048, 2048, bars + 8u * B_HL);
            }
            mbar_wait(bars + 8u * B_HL, hpar & 1u);
            hpar ^= 1u;
            const uint32_t t = lds32((lane < 16 ? KB_ROW0 - 2048 : VB_ROW0 - 4096) + lane * 128 + ((lane & 7) << 4)) ^ tag;
            if (!__any_sync(0xffffffffu, gb > 0 && (t & 1u))) break;
            fence_proxy_async_smem();
          }
          if (lane == 0) mbar_arrive(bars + 8u * B_HALO);
          HTS(52);
        }
        if (elect_one()) {
          const CUtensorMap* mo = &P.o;
          unsigned *f1 = g_fo[gb * 2 + 1][hp], *f0 = g_fo[gb * 2][hp];
          int c0 = hp * 64, r0 = gb * 128, r1 = r0 + 64;
          pin64(mo), pin64(f1), pin64(f0);
          asm volatile("" : "+r"(c0), "+r"(r0), "+r"(r1));
          mbar_wait(bars + 8u * B_OS1, (inst & 1) ^ 1);
          tma_store_2d(mo, slots + 7 * UNIT, c0, r1);
          bulk_announce(f1);
          bulk_commit();
          mbar_wait(bars + 8u * B_OS0, inst & 1);
          tma_store_2d(mo, slots + 6 * UNIT, c0, r0);
          bulk_announce(f0);
          bulk_commit();
          HTS(57);
          const bool pre = w_pre(inst);
          bulk_wait_read0();
          HTS(58 - 15);
          mbar_expect_tx(bars + 8u * B_RF, 2 * UNIT);
          tma_load_2d(slots + 6 * UNIT, &P.x[L], bars + 8u * B_RF, ct * 128, ch * 1024 + rt * 64);
          tma_load_2d(slots + 7 * UNIT, &P.x[L], bars + 8u * B_RF, ct * 128 + 64, ch * 1024 + rt * 64);
          if (pre) {
            const uint32_t pp = __popc(PREMASK & ((1u << inst) - 1u)) & 1;
            mbar_expect_tx(bars + 8u * B_PRE, 2 * UNIT);
            mbar_expect_tx(bars + 8u * B_PRE2, 6 * UNIT);
#pragma unroll 1
            for (int j = 0; j < 4; j++) {
              __nanosleep(PRESLEEP);
              if (j == 3) mbar_wait(bars + 8u * B_RDONE, (inst & 1) ^ 1);
              tma_load_3d(slots + j * 2 * UNIT, &P.wo3[L & 1], bars + 8u * (j ? B_PRE2 : B_PRE), ct * 128, wk(4 * j + 3) * 64);
            }
#pragma unroll 1
            for (int j = 0; j < 4; j++) {
              const uint32_t fb = bars + 8u * (B_WF + 3 + 4 * (j & 1));
              if (j < 2) mbar_wait(bars + 8u * (j ? B_PRE2 : B_PRE), pp);
              if (j < 2 && inst == 7 && SP7 == 16) mbar_wait(bars + 8u * (B_TURN + 1), (turn_par(2) >> 7) & 1u);
              mbar_wait(fb + 8u * B_E, j < 2);
              mbar_arrive(fb);
            }
          }
        }
        __syncwarp();
      }
    } else {
      const unsigned ep1 = launch_epoch();
      named_bar_sync(0, 512);
      mbar_wait(bars + 8u * B_GO, 0);
#pragma unroll 1
      for (int i = 0; i < 20; i++) {
        const char* src = i < 4 ? reinterpret_cast<const char*>(P.wo_p[0]) + (size_t)b * 16384 + i * 4096
                                : (i < 16 ? reinterpret_cast<const char*>(P.wqkv_p[1]) + (size_t)b * 49152 + (i - 4) * 4096
                                          : reinterpret_cast<const char*>(P.wo_p[1]) + (size_t)b * 16384 + (i - 16) * 4096);
        asm volatile("prefetch.global.L2 [%0];" ::"l"(src + lane * 128));
        __nanosleep(TRICKLE);
      }
#pragma unroll 1
      for (int inst = 2; inst < 10; inst++) {
        const int L = inst >> 1, ch = inst & 1, gb = ch * 8 + qr;
        {
          uint32_t xb = base + (((inst < 9 ? q_split(inst - 1) : 0) + (w_pre(inst - 2) ? 3 : 2)) & 3) * 5 * UNIT;
          unsigned* f = g_fx[ch * 8 + (rt >> 1)][ct * 2];
          const CUtensorMap* mx = &P.x[L];
          int c0 = ct * 128, r0 = ch * 1024 + rt * 64;
          pin64(f), pin64(mx);
          asm volatile("" : "+r"(xb), "+r"(c0), "+r"(r0));
#pragma unroll
          for (int h = 0; h < 2; h++) {
            mbar_wait(bars + 8u * (B_XS + h), ch);
            if (elect_one()) {
              tma_store_2d(mx, xb + h * UNIT, c0 + h * 64, r0);
              if (L < 4) bulk_announce(f + 4 * h);
              bulk_commit();
              if (h == 1) {
                bulk_wait_read0();
                mbar_arrive(bars + 8u * (B_RF + B_E));
              }
            }
          }
          if (L == 4) continue;
          __nanosleep(SDLY);
        }
#pragma unroll 1
        for (int h = 0; h < 4; h++) {
          const float4* sp = &g_stats[0][gb * 128 + h * 32 + lane];
          const float4 s0 = sum_recs<4>(sp, S_LEN, 4u * ep1 + L), s1 = sum_recs<4>(sp + 4 * S_LEN, S_LEN, 4u * ep1 + L);
          sts32(base + OFF_RS + (ch * 128 + h * 32 + lane) * 4, ln_params(s0.x + s1.x, s0.y + s1.y));
        }
        if (inst == 2) {
#pragma unroll 1
          for (int hf = 0; hf < 2; hf++) {
            const float4* cp = &g_cs[1][hp][0][hf * 32 + lane];
            const float4 s0 = sum_recs<4>(cp, 64, ep1), s1 = sum_recs<4>(cp + 4 * 64, 64, ep1);
            put_colsums(1, hf * 32 + lane, make_float4(s0.x + s1.x, s0.y + s1.y, s0.z + s1.z, 0.f));
          }
        }
        fence_proxy_async_smem();
        __syncwarp();
        if (lane == 0) mbar_arrive(bars + 8u * (B_PREP + ch));
      }
    }
  } else {
    const bool asst = warp >= 8;
    GTL(0);
    if (warp >= 4) named_bar_sync(0, 512);
    if (warp >= 4 && !asst) {
      PHASE_IDS
      {
        const unsigned ep1 = launch_epoch();
        const int row = b * 16 + (tid >> 3);
        const uint4* src = reinterpret_cast<const uint4*>(P.in_x + (size_t)row * DM) + (tid & 7);
        float s1 = 0.f, s2 = 0.f;
#pragma unroll 1
        for (int k = 0; k < 4; k++) {
          mbar_pace(bars + 8u * (B_QF + B_E + ((2 * k) & 3)), k >> 1, k ? PN2 : 30);
          uint4 v[4];
#pragma unroll
          for (int j = 0; j < 4; j++) v[j] = __ldg(src + (k * 4 + j) * 8);
#pragma unroll
          for (int j = 0; j < 4; j++) {
            const uint32_t w[4] = {v[j].x, v[j].y, v[j].z, v[j].w};
#pragma unroll
            for (int e = 0; e < 4; e++) {
              const float x0 = bf_lo(w[e]), x1 = bf_hi(w[e]);
              s1 += x0 + x1;
              s2 = fmaf(x0, x0, fmaf(x1, x1, s2));
            }
          }
        }
#pragma unroll
        for (int o = 1; o < 8; o <<= 1) {
          s1 += __shfl_xor_sync(0xffffffffu, s1, o);
          s2 += __shfl_xor_sync(0xffffffffu, s2, o);
        }
        if ((tid & 7) == 0) st_rec(&g_stats[0][row], s1, s2, 0.f, 4u * ep1);
        if (tid == 0) sts32(base + OFF_EPOCH, ep1);
        if (tid < 64) {
          const float4 s0 = sum_recs<8>(&g_cs[0][hp][0][tid], 64, ep1);
          put_colsums(0, tid, s0);
        } else {
          put_colsums(1, tid - 64, make_float4(0.f, 0.f, 0.f, 0.f));
        }
#pragma unroll 1
        for (int cc = 0; cc < 2; cc++) {
          const float4 s0 = sum_recs<1>(&g_stats[0][(cc * 8 + qr) * 128 + tid], 0, 4u * ep1);
          sts32(base + OFF_RS + (cc * 128 + tid) * 4, ln_params(s0.x, s0.y));
        }
        fence_proxy_async_smem();
        named_bar_sync(2, 128);
        if (tid < 2) mbar_arrive(bars + 8u * (B_PREP + tid));
      }
    }
#pragma unroll 1
    for (int inst = asst ? 0 : warp >> 2; inst < 8; inst += asst ? 1 : 2) {
      const int L = inst >> 1, ch = inst & 1, gb = ch * 8 + qr;
      uint32_t q[2][2][4];
      if (asst) {
        if (inst < 2) colsum_part(&P.wqkv[inst], inst, qr, hp);
        setmaxnreg_dec<24>();
        named_bar_sync(4, 256);
        setmaxnreg_inc<128>();
        const uint32_t ra = q_row_addr(L & 1, 1, warp & 3, fresh_tid() & 31);
#pragma unroll
        for (int j = 0; j < 4; j++) ldmatrix_x4(q[j >> 1][j & 1], ra ^ (j << 5));
      } else {
      setmaxnreg_inc<224>();
      {
        float acc[2][96];
        const int ksp = q_split(inst);
        constexpr uint32_t STG = 5 * (UNIT >> 4), D0 = ((base + 3 * UNIT) >> 4) + 0x10000u;
        constexpr uint32_t DB = ((UNIT >> 4) << 16) - 0x10000u - 3 * (UNIT >> 4);
        const uint32_t toff = ((fresh_tid() & 127) << 7) + ((fresh_tid() & 7) << 4);
        const bool lane0 = (toff & 0xf80u) == 0u;
        uint32_t xt = x_tag(L), tro = (warp & 3) * 2048 + (toff & 0x7f0u) + ((toff << 2) & 0x2000u);
        auto check_x = [&](uint32_t bar, uint32_t par, uint32_t ta, int kt, uint32_t mask) {
          fix_lines(bar, par, ta, xt, mask, 8 + warp, [&](int l) {
            return g_x + (size_t)(gb * 128 + (l >> 4) * 64 + tile_row(L & 1, warp & 3, (l >> 3) & 1, l & 7)) * DM + qk(kt) * 64;
          });
        };
        uint32_t rsa = base + OFF_RS + (ch * 128 + tile_row(L & 1, warp & 3, 0, (toff >> 9) & 7)) * 4;
        uint32_t rsb = rsa + ((L & 1) ? 32 : 128);
        uint32_t lnm = ((toff >> 7) & 3) == (L & 1) ? 0xffffffffu : 0u, tmk = L > 0;
        uint32_t soff = tile_row(L & 1, warp & 3, (toff >> 10) & 1, (toff >> 7) & 7) * 128 + ((toff ^ (toff >> 7)) & 0x10u) + (toff & 0x60u);
        uint32_t bprep = bars + 8u * (B_PREP + ch), bturn = bars + 8u * (B_TURN + (ch ^ 1));
        uint32_t bfree = bars + 8u * (inst == 1 ? B_CSD : B_RDONE), pfree = inst == 1 ? 0 : inst & 1, pprep = L & 1;
        asm volatile("" : "+r"(rsa), "+r"(rsb), "+r"(lnm), "+r"(soff), "+r"(xt), "+r"(tmk), "+r"(tro));
        asm volatile("" : "+r"(bprep), "+r"(bturn), "+r"(bfree), "+r"(pfree), "+r"(pprep));
        if (inst == 0) named_bar_sync(0, 512);
        if (inst == 1 || (inst > 1 && q_split(inst - 1) < 16)) mbar_wait_lazy<TLAZY>(bars + 8u * (B_TURN + ch), (turn_par(0) >> inst) & 1u);
        if (L == 3) GTL(37);
        check_x(bars + 8u * B_QF, 0, base + 3 * UNIT + tro, 0, tmk);
        GTL(1 + L * 8);
        {
          const uint64_t da = desc_lo(D0) + P.zero;
          wgmma_fence();
          wgmma_n192_ssz_ta0_tb1(acc[1], da + (UNIT >> 4), da + DB);
          wgmma_commit();
          wgmma_n192_ssz_ta0_tb1(acc[0], da, da + DB);
          wgmma_commit();
        }
        int left = ksp;
        asm volatile("" : "+r"(left));
        uint64_t da = desc_lo(D0) + P.zero, dn = da + STG;
        uint32_t fn = bars + 8u * (B_QF + 1), pn = 0, ta = base + 8 * UNIT + tro;
#pragma unroll 1
        for (int kt = 0; kt < 15; kt++) {
          bool ok, last;
          uint32_t tw;
#pragma unroll
          for (int k16 = 0; k16 < 4; k16++) {
            if (k16 == 0 && kt == 0) continue;
            wgmma_fence();
            wgmma_n192_ss_ta0_tb1(acc[1], da + ((UNIT >> 4) + k16 * 2), da + (DB + k16 * 128), 1);
            wgmma_commit();
            if (k16 == 0) {
              const int s1 = (kt + 1) & 3;
              dn = desc_lo(D0 + s1 * STG) + P.zero;
              ta = base + 3 * UNIT + s1 * 5 * UNIT + tro;
            }
            if (k16 == 1) last = --left == 0;
            if (k16 == 3) ok = !__any_sync(0xffffffffu, !ok || ((tw ^ xt) & tmk)) && !last;
            wgmma_wait<1>();
            if (k16 == 0 && lane0 && left != 0) mbar_arrive(bars + 8u * (B_QF + B_E + ((kt - 1) & 3)));
            wgmma_fence();
            wgmma_n192_ss_ta0_tb1(acc[0], da + k16 * 2, da + (DB + k16 * 128), 1);
            wgmma_commit();
            if (k16 == 0) {
              fn = bars + 8u * (B_QF + ((kt + 1) & 3));
              pn = ((kt + 1) >> 2) & 1;
            }
            if (k16 == 2) {
              ok = mbar_test(fn, pn);
              tw = lds32(ta);
              if (last && lane0) mbar_arrive(bturn);
            }
            if (k16 < 3) wgmma_wait<1>();
          }
          da = dn;
          if (!ok) {
            if (last) {
              wgmma_wait<0>();
              if (lane0) mbar_arrive(bars + 8u * (B_QF + B_E + (kt & 3)));
            }
            if (last) mbar_wait_lazy<TLAZY>(bars + 8u * (B_TURN + ch), (turn_par(1) >> inst) & 1u);
            check_x(fn, pn, ta, kt + 1, tmk);
          }
        }
        constexpr uint32_t DL = D0 + 3 * STG;
        wgmma_fence();
#pragma unroll
        for (int k16 = 0; k16 < 4; k16++) wgmma_n192_ss_ta0_tb1(acc[1], desc_lo(DL + (UNIT >> 4) + k16 * 2), desc_lo(DL + DB + k16 * 128), 1);
        wgmma_commit();
        mbar_wait(bprep, pprep);
        uint32_t rs[2][2];
        constexpr uint64_t DCS = (uint64_t)((base + OFF_CS) >> 4) | (4ull << 32);
        auto ln_mma = [&](float (&d)[96], uint32_t (&r)[2], int h) {
          uint32_t a[4];
#pragma unroll
          for (int i = 0; i < 2; i++) {
            if (h) r[i] = lds32((i ? rsb : rsa) + 256);
            a[i] = (__byte_perm(r[i], 0u, 0x1010) ^ 0x80008000u) & lnm;
            a[i + 2] = r[i] & P.zero;
          }
#pragma unroll
          for (int i = 0; i < 4; i++) asm volatile("" : "+r"(a[i]));
          wgmma_fence();
          wgmma_n192_rs_tb1(d, a, DCS, 1);
          wgmma_commit();
        };
        ln_mma(acc[1], rs[1], 1);
        wgmma_wait<2>();
        if (lane0 && ksp != 15) mbar_arrive(bars + 8u * (B_QF + B_E + 2));
        wgmma_fence();
#pragma unroll
        for (int k16 = 0; k16 < 4; k16++) wgmma_n192_ss_ta0_tb1(acc[0], desc_lo(DL + k16 * 2), desc_lo(DL + DB + k16 * 128), 1);
        wgmma_commit();
        if (lane0) mbar_arrive(bturn);
        rs[0][0] = lds32(rsa);
        rs[0][1] = lds32(rsb);
        static_assert(SP1 < 16 && (PREMASK & 1u), "column sums of B");
        const bool afree = mbar_test(bfree, pfree) & (mbar_test(bars + 8u * (B_WF + B_E + 7), 1) | (ksp == 16));
        float rinv[2];
#pragma unroll
        for (int r = 0; r < 2; r++) {
          rinv[r] = rcp_fast(bf_hi(rs[1][r]));
          asm volatile("" : "+f"(rinv[r]));
        }
        const uint32_t kdst = ((L & 1) ? KB_ROW0 : slots) + soff, vdst = ((L & 1) ? VB_ROW0 : slots + 8192) + soff;
        const uint32_t hs = (L & 1) ? 8192 : 16384, c0 = (toff & 0x180u) == 0u;
        wgmma_wait<1>();
        ln_mma(acc[0], rs[0], 0);
        reg_fence<96>(acc[1]);
        GTL(2 + L * 8);
        if (!afree) {
          mbar_wait(bfree, pfree);
          if (ksp < 16) mbar_wait(bars + 8u * (B_WF + B_E + 7), 1);
        }
#pragma unroll
        for (int t = 0; t < 24; t++) {
          const int h = t < 12 ? 1 : 0, p = ((t % 12) / 4 + 1) % 3, jp = t & 3;
          if (t == QREL) {
            wgmma_wait<0>();
            reg_fence<96>(acc[0]);
            if (lane0) mbar_arrive(bars + 8u * (B_QF + B_E + 3));
          }
          if (t == 8 || t == 20) {
            rinv[0] *= SM_C;
            rinv[1] *= SM_C;
          }
          const float* a = &acc[h][4 * (p * 8 + 2 * jp)];
          uint32_t r0 = pack_bf16x2(a[0] * rinv[0], a[1] * rinv[0]);
          uint32_t r1 = pack_bf16x2(a[2] * rinv[1], a[3] * rinv[1]);
          if (p != 0 && jp == 0) {
            r0 = set_tag(r0, c0, kv_tag(L));
            r1 = set_tag(r1, c0, kv_tag(L));
          }
          const uint32_t r2 = pack_bf16x2(a[4] * rinv[0], a[5] * rinv[0]);
          const uint32_t r3 = pack_bf16x2(a[6] * rinv[1], a[7] * rinv[1]);
          const uint32_t dst = p == 0 ? slots + 3 * 16384 + soff + h * 8192 : (p == 1 ? kdst : vdst) + h * hs;
          stmatrix_x4(dst ^ (jp << 5), r0, r1, r2, r3);
          if (t >= 20) {
            q[jp >> 1][jp & 1][0] = r0;
            q[jp >> 1][jp & 1][1] = r1;
            q[jp >> 1][jp & 1][2] = r2;
            q[jp >> 1][jp & 1][3] = r3;
          }
          if (t == 7 || t == 19) signal_async(bars + 8u * (t == 7 ? B_KV : B_LOC), lane0);
          if (t == 11) {
            setmaxnreg_dec<128>();
            named_bar_arrive(4, 256);
#pragma unroll
            for (int r = 0; r < 2; r++) rinv[r] = rcp_fast(bf_hi(rs[0][r]));
          }
        }
        mbar_wait(bars + 8u * B_LOC, inst & 1);
      }
      }
      GTL(3 + L * 8);
      if ((L & 1) == 0) attention_a(q, asst, L, gb, hp, ch, warp & 3, P.zero);
      else attention_b(q, asst, gb, inst & 1, warp & 3);
      GTL(4 + L * 8);
      signal_async(bars + 8u * (asst ? B_OS1 : B_OS0), (fresh_tid() & 31) == 0);
      if (asst) continue;
      GTL(5 + L * 8);

      {
        float acc[64];
        const int sp = inst < 7 ? q_split(inst + 1) : 0;
        const int st = sp & 3;
        const bool pre = w_pre(inst);
        const uint32_t toff = ((fresh_tid() & 63) << 7) + ((fresh_tid() & 7) << 4);
        uint32_t tro = (warp & 3) * 2048 + (toff & 0x7f0u);
        auto check_o = [&](uint32_t bar, uint32_t par, uint32_t sa, int kt) {
          fix_lines(bar, par, sa + tro, o_tag(L), 1u, 8 + warp, [&](int l) {
            return g_o + (size_t)(ch * 1024 + rt * 64 + (warp & 3) * 16 + (l & 15)) * DM + wk(kt) * 64;
          });
        };
        const bool lane0 = (toff & 0xf80u) == 0u;
        constexpr uint32_t U4 = UNIT >> 4, LA = 0x10000u, LB = U4 << 16;
        reg_define<64>(acc);
        reg_fence<64>(acc);
        uint32_t xv[8][4];
        {
          PHASE_IDS_W
          const uint32_t xr = slots + 6 * UNIT + (wwarp * 16 + (lane & 15)) * 128 + (((lane >> 4) ^ (lane & 7)) << 4);
          mbar_wait(bars + 8u * B_RF, inst & 1);
#pragma unroll
          for (int jp = 0; jp < 8; jp++) ldmatrix_x4(xv[jp], (xr ^ ((jp & 3) << 5)) + (jp >> 2) * UNIT);
          signal_async(bars + 8u * B_RDONE, lane0);
          if (L > 0) {
            uint32_t lsb;
            asm volatile("ld.shared.u8 %0, [%1];" : "=r"(lsb) : "r"(base + OFF_LSB + ch * 32 + wwarp * 8 + g) : "memory");
#pragma unroll
            for (int k = 0; k < 4; k++) xv[(k >> 1) * 4][k & 1] = set_tag(xv[(k >> 1) * 4][k & 1], c == 0, lsb >> k);
          }
        }
        uint32_t tmx = L < 3 && (toff & 0x180u) == 0u, xt = x_tag(L + 1);
        uint32_t xrow = base + ((st + (pre ? 3 : 2)) & 3) * 5 * UNIT + (warp & 3) * 2048 + (toff & 0x7e0u) + ((toff ^ (toff >> 7)) & 0x10u);
        asm volatile("" : "+r"(tmx), "+r"(xt), "+r"(xrow), "+r"(tro));
        const uint64_t dz = desc_lo(0) + P.zero;
        auto nexts = [&](uint32_t a) { return a == base + 15 * UNIT ? base : a + 5 * UNIT; };
        uint32_t s0 = base + st * 5 * UNIT, sp3 = slots, fb = bars + 8u * B_WF;
        int turn = lane0 && (sp < 16 || inst == 6) ? 3 : -1;
        asm volatile("" : "+r"(turn));
        if (inst < 7 || SP7 == 16) mbar_wait_lazy<TLAZY>(bars + 8u * (B_TURN + ch), (turn_par(2) >> inst) & 1u);
        check_o(bars + 8u * B_WF, 0, s0, 0);
        GTL(6 + L * 8);
#pragma unroll 1
        for (int m = 0; m < 4; m++) {
          uint32_t s1, s2;
#pragma unroll
          for (int i = 0; i < 4; i++) {
            const uint64_t da = dz + ((i == 0 ? s0 : s1) >> 4) + (LA + (i == 2 ? 1 : (i == 3 ? 4 : 0)) * U4);
            const uint64_t db = dz + ((i < 2 ? s0 : (i == 2 ? s1 : s2)) >> 4) + (LB + (i == 0 ? 1 : (i == 1 ? 3 : (i == 2 ? 2 : 0))) * U4);
            wgmma_fence();
#pragma unroll
            for (int k16 = 0; k16 < 4; k16++) wgmma_n128_ss_ta0_tb1(acc, da + 2 * k16, db + 128 * k16, 1);
            wgmma_commit();
            if (i == 0) s1 = nexts(s0);
            if (i == 1) s0 = nexts(s1);
            if (i == 2) {
              s2 = pre ? sp3 : s0;
              s0 = pre ? s0 : nexts(s0);
              sp3 += 2 * UNIT;
            }
            const uint32_t fn = i < 3 ? fb + 8u * (i + 1) : fb ^ 96u;
            const uint32_t pn = i < 3 ? m >> 1 : m > 0;
            const uint32_t an = i < 3 ? s1 + (i == 1 ? 1 : (i == 2 ? 4 : 0)) * UNIT : s0;
            bool ok = mbar_test(fn, pn);
            const uint32_t tw = lds32(an + tro);
            ok = !__any_sync(0xffffffffu, (!ok || ((tw ^ o_tag(L)) & 1u)) && (i < 3 || m < 3));
            wgmma_wait<1>();
            if (lane0 && (i > 0 || m > 0)) mbar_arrive((i > 0 ? fb + 8u * (i - 1) : (fb ^ 96u) + 24u) + 8u * B_E);
            if (i == 2 && m == turn) mbar_arrive(bars + 8u * (B_TURN + (ch ^ 1)));
            if (!ok) check_o(fn, pn, an, 4 * m + i + 1);
          }
          fb ^= 96u;
        }
        wgmma_wait<0>();
        reg_fence<64>(acc);
        if (lane0) mbar_arrive(bars + 8u * (B_WF + B_E + 7));
        GTL(7 + L * 8);
#pragma unroll
        for (int jp = 0; jp < 8; jp++) {
#pragma unroll
          for (int q = 0; q < 4; q++) xv[jp][q] = add_bf16x2(xv[jp][q], pack_bf16x2(acc[8 * jp + 2 * q], acc[8 * jp + 2 * q + 1]));
          const bool tg = (jp & 3) == 0;
          stmatrix_x4((xrow ^ ((jp & 3) << 5)) + (jp >> 2) * UNIT,
                      tg ? set_tag(xv[jp][0], tmx, xt) : xv[jp][0], tg ? set_tag(xv[jp][1], tmx, xt) : xv[jp][1], xv[jp][2], xv[jp][3]);
          if ((jp & 3) == 3) signal_async(bars + 8u * (B_XS + (jp >> 2)), lane0);
        }
        if (L < 3) {
          PHASE_IDS_W
          const int grow = ch * 1024 + rt * 64;
          const unsigned ep1 = lds32(base + OFF_EPOCH);
          if (c == 0)
            asm volatile("st.shared.u8 [%0], %1;" ::"r"(base + OFF_LSB + ch * 32 + wwarp * 8 + g),
                         "r"((xv[0][0] & 1u) | ((xv[0][1] & 1u) << 1) | ((xv[4][0] & 1u) << 2) | ((xv[4][1] & 1u) << 3)) : "memory");
          float s1[2] = {0.f, 0.f}, s2[2] = {0.f, 0.f};
#pragma unroll
          for (int jp = 0; jp < 8; jp++)
#pragma unroll
            for (int q = 0; q < 4; q++) {
              const float x0 = bf_lo(xv[jp][q]), x1 = bf_hi(xv[jp][q]);
              s1[q & 1] += x0 + x1;
              s2[q & 1] = fmaf(x0, x0, fmaf(x1, x1, s2[q & 1]));
            }
#pragma unroll
          for (int r = 0; r < 2; r++) {
            s1[r] += __shfl_xor_sync(0xffffffffu, s1[r], 1);
            s2[r] += __shfl_xor_sync(0xffffffffu, s2[r], 1);
            s1[r] += __shfl_xor_sync(0xffffffffu, s1[r], 2);
            s2[r] += __shfl_xor_sync(0xffffffffu, s2[r], 2);
            if (c == 0) st_rec(&g_stats[ct][grow + wwarp * 16 + g + 8 * r], s1[r], s2[r], 0.f, 4u * ep1 + L + 1);
          }
        }
        GTL(8 + L * 8);
      }
    }
    if (threadIdx.x == 128) atomicAdd(g_done, 1u);
  }
}

typedef CUresult (*PFN_tmEncode)(CUtensorMap*, CUtensorMapDataType, cuuint32_t, void*, const cuuint64_t*,
                                 const cuuint64_t*, const cuuint32_t*, const cuuint32_t*, CUtensorMapInterleave,
                                 CUtensorMapSwizzle, CUtensorMapL2promotion, CUtensorMapFloatOOBfill);

PFN_tmEncode get_encode_fn() {
  static PFN_tmEncode fn = nullptr;
  if (!fn) {
    cudaDriverEntryPointQueryResult qr;
    void* p = nullptr;
    cudaGetDriverEntryPoint("cuTensorMapEncodeTiled", &p, cudaEnableDefault, &qr);
    fn = (PFN_tmEncode)p;
  }
  return fn;
}

CUtensorMap make_map(const void* ptr, int rows, int cols) {
  CUtensorMap m;
  cuuint64_t gdim[2] = {(cuuint64_t)cols, (cuuint64_t)rows};
  cuuint64_t gstr[1] = {(cuuint64_t)cols * 2};
  cuuint32_t box[2] = {64, 64};
  cuuint32_t estr[2] = {1, 1};
  get_encode_fn()(&m, CU_TENSOR_MAP_DATA_TYPE_BFLOAT16, 2, const_cast<void*>(ptr), gdim, gstr, box, estr,
                  CU_TENSOR_MAP_INTERLEAVE_NONE, CU_TENSOR_MAP_SWIZZLE_128B, CU_TENSOR_MAP_L2_PROMOTION_L2_128B,
                  CU_TENSOR_MAP_FLOAT_OOB_FILL_NONE);
  return m;
}

CUtensorMap make_map3(const void* ptr, int rows, int cols, int n, int step) {
  CUtensorMap m;
  cuuint64_t gdim[3] = {(cuuint64_t)(cols - (n - 1) * step), (cuuint64_t)rows, (cuuint64_t)n};
  cuuint64_t gstr[2] = {(cuuint64_t)cols * 2, (cuuint64_t)step * 2};
  cuuint32_t box[3] = {64, 64, (cuuint32_t)n};
  cuuint32_t estr[3] = {1, 1, 1};
  get_encode_fn()(&m, CU_TENSOR_MAP_DATA_TYPE_BFLOAT16, 3, const_cast<void*>(ptr), gdim, gstr, box, estr,
                  CU_TENSOR_MAP_INTERLEAVE_NONE, CU_TENSOR_MAP_SWIZZLE_128B, CU_TENSOR_MAP_L2_PROMOTION_L2_128B,
                  CU_TENSOR_MAP_FLOAT_OOB_FILL_NONE);
  return m;
}

CUtensorMap make_map_q(const void* ptr, int sw, int sr) {
  CUtensorMap m;
  cuuint64_t gdim[5] = {DM, 8, 2, 4, S_LEN / 64};
  cuuint64_t gstr[4] = {DM * 2, (cuuint64_t)sr * DM * 2, (cuuint64_t)sw * DM * 2, 64 * DM * 2};
  cuuint32_t box[5] = {64, 8, 2, 4, 2};
  cuuint32_t estr[5] = {1, 1, 1, 1, 1};
  get_encode_fn()(&m, CU_TENSOR_MAP_DATA_TYPE_BFLOAT16, 5, const_cast<void*>(ptr), gdim, gstr, box, estr,
                  CU_TENSOR_MAP_INTERLEAVE_NONE, CU_TENSOR_MAP_SWIZZLE_128B, CU_TENSOR_MAP_L2_PROMOTION_L2_128B,
                  CU_TENSOR_MAP_FLOAT_OOB_FILL_NONE);
  return m;
}

}

extern "C" void kernel_launch(void* const* d_in, const int* in_sizes, int n_in, void* d_out, int out_size) {
  (void)in_sizes; (void)n_in; (void)out_size;
  void *p_o, *p_x;
  cudaGetSymbolAddress(&p_o, g_o);
  cudaGetSymbolAddress(&p_x, g_x);
  static bool attr_done = false;
  if (!attr_done) {
    cudaFuncSetAttribute(fused_kernel, cudaFuncAttributeMaxDynamicSharedMemorySize, SMEM_BYTES);
    attr_done = true;
  }
  Params P;
  P.in_x = (const __nv_bfloat16*)d_in[0];
  P.wqkv_p[0] = (const __nv_bfloat16*)d_in[1];
  P.wo_p[0] = (const __nv_bfloat16*)d_in[2];
  P.wqkv_p[1] = (const __nv_bfloat16*)d_in[4];
  P.wo_p[1] = (const __nv_bfloat16*)d_in[5];
  P.out = (__nv_bfloat16*)d_out;
  P.zero = 0;
  for (int L = 0; L < 5; L++) {
    const void* px = L == 0 ? (const void*)P.in_x : (L == 4 ? d_out : p_x);
    P.x[L] = make_map(px, S_LEN, DM);
    if (L < 4) P.xq[L] = (L & 1) ? make_map_q(px, 16, 8) : make_map_q(px, 8, 32);
  }
  P.o = make_map(p_o, S_LEN, DM);
  for (int t = 0; t < 2; t++) {
    P.wqkv[t] = make_map(P.wqkv_p[t], DM, NQKV);
    P.wqkv3[t] = make_map3(P.wqkv_p[t], DM, NQKV, 3, 1024);
    P.wo3[t] = make_map3(P.wo_p[t], DM, DM, 2, 64);
  }
  fused_kernel<<<NCTA, 512, SMEM_BYTES>>>(P);
}
```

```cpp
#include <cuda_runtime.h>
#include <cuda_bf16.h>
#include <cuda.h>
#include <stdint.h>

namespace {

constexpr int S_LEN = 2048;
constexpr int DM = 1024;
constexpr int NQKV = 3072;
constexpr int NCTA = 128;

__device__ __align__(1024) uint8_t g_kvA[16][16][2][16384];
__device__ __align__(1024) uint8_t g_kvB[16][16][4096];
__device__ __align__(1024) uint8_t g_zero[16384];
__device__ __align__(1024) __nv_bfloat16 g_o[S_LEN * DM];
__device__ __align__(1024) __nv_bfloat16 g_x[S_LEN * DM];
__device__ __align__(1024) float4 g_stats[8][S_LEN];
__device__ __align__(1024) float4 g_cs[2][16][8][64];
__device__ __align__(128) unsigned g_fx[16][16][4];
__device__ __align__(128) unsigned g_fo[32][16][4];
__device__ __align__(128) unsigned g_fk[16][16][4];
__device__ __align__(128) unsigned g_done[32];

constexpr uint32_t SBASE = 1024;
constexpr int UNIT = 8192;
constexpr int NUNITS = 20;
constexpr int OFF_SLOT = NUNITS * UNIT;
constexpr int OFF_BAR = OFF_SLOT + 4 * 16384;
constexpr int OFF_EPOCH = OFF_BAR + 424;
constexpr int OFF_LSB = OFF_BAR + 432;
constexpr int OFF_CS = OFF_BAR + 496;
constexpr int OFF_RS = OFF_CS + 1536;
constexpr int OFF_ONE = OFF_RS + 1024;
constexpr int SMEM_BYTES = OFF_ONE + 16;
constexpr int B_QF = 0, B_WF = 4, B_RF = 12, B_E = 13, B_PREP = 26, B_LOC = 28, B_HALO = 29, B_REL = 33, B_OS0 = 36,
              B_TURN = 37, B_XS = 39, B_CS = 41, B_CSD = 42, B_GO = 43, B_PRE = 44, B_HV = 45, B_REDO = 46,
              B_RDONE = 48, B_PRE2 = 49, B_HL = 50, B_KV = 52, B_OS1 = B_GO;
static_assert(SMEM_BYTES <= 232448, "shared memory");

__device__ __forceinline__ uint32_t smem_u32(const void* p) { return (uint32_t)__cvta_generic_to_shared(p); }

__device__ __forceinline__ void mbar_init(uint32_t bar, uint32_t cnt) {
  asm volatile("mbarrier.init.shared::cta.b64 [%0], %1;" ::"r"(bar), "r"(cnt));
}
__device__ __forceinline__ void mbar_expect_tx(uint32_t bar, uint32_t bytes) {
  asm volatile("mbarrier.arrive.expect_tx.shared::cta.b64 _, [%0], %1;" ::"r"(bar), "r"(bytes) : "memory");
}
__device__ __forceinline__ void mbar_arrive(uint32_t bar) {
  asm volatile("mbarrier.arrive.shared::cta.b64 _, [%0];" ::"r"(bar) : "memory");
}
__device__ __forceinline__ bool mbar_try_wait(uint32_t bar, uint32_t parity) {
  uint32_t ok;
  asm volatile(
      "{\n.reg .pred p;\nmbarrier.try_wait.parity.shared::cta.b64 p, [%1], %2;\nselp.b32 %0, 1, 0, p;\n}\n"
      : "=r"(ok)
      : "r"(bar), "r"(parity)
      : "memory");
  return ok != 0;
}
__device__ __forceinline__ bool mbar_test(uint32_t bar, uint32_t parity) {
  uint32_t ok;
  asm volatile(
      "{\n.reg .pred p;\nmbarrier.test_wait.parity.shared::cta.b64 p, [%1], %2;\nselp.b32 %0, 1, 0, p;\n}\n"
      : "=r"(ok)
      : "r"(bar), "r"(parity)
      : "memory");
  return ok != 0;
}
__device__ __forceinline__ void mbar_wait(uint32_t bar, uint32_t parity) {
#pragma unroll 1
  for (uint32_t it = 0; it < (1u << 18); ++it) {
    if (mbar_try_wait(bar, parity)) return;
  }
}
__device__ __forceinline__ void mbar_pace(uint32_t bar, uint32_t parity, uint32_t n) {
#pragma unroll 1
  for (uint32_t it = 0; it < n; ++it) {
    if (mbar_test(bar, parity)) return;
    __nanosleep(100);
  }
}
template <int NS>
__device__ __forceinline__ void mbar_wait_lazy(uint32_t bar, uint32_t parity) {
#pragma unroll 1
  for (uint32_t it = 0; it < (1u << 18); ++it) {
    if (mbar_try_wait(bar, parity)) return;
    __nanosleep(NS);
  }
}
__device__ __forceinline__ bool elect_one() {
  uint32_t ok;
  asm volatile("{\n.reg .pred p;\nelect.sync _|p, 0xffffffff;\nselp.b32 %0, 1, 0, p;\n}\n" : "=r"(ok));
  return ok != 0;
}
__device__ __forceinline__ void fence_barrier_init() { asm volatile("fence.mbarrier_init.release.cluster;" ::: "memory"); }
__device__ __forceinline__ void fence_proxy_async_smem() { asm volatile("fence.proxy.async.shared::cta;" ::: "memory"); }

__device__ __forceinline__ void signal_async(uint32_t bar, bool lane0) {
  fence_proxy_async_smem();
  __syncwarp();
  asm volatile("{\n.reg .pred p;\nsetp.ne.b32 p, %1, 0;\n@p mbarrier.arrive.shared::cta.b64 _, [%0];\n}\n" ::"r"(bar), "r"((int)lane0) : "memory");
}
template <class T>
__device__ __forceinline__ void pin64(T*& p) { asm volatile("" : "+l"(p)); }

__device__ __forceinline__ void tma_load_2d(uint32_t dst, const CUtensorMap* map, uint32_t bar, int c0, int c1) {
  asm volatile(
      "cp.async.bulk.tensor.2d.shared::cluster.global.mbarrier::complete_tx::bytes [%0], [%1, {%3, %4}], [%2];" ::"r"(dst),
      "l"(map), "r"(bar), "r"(c0), "r"(c1)
      : "memory");
}
__device__ __forceinline__ void tma_load_3d(uint32_t dst, const CUtensorMap* map, uint32_t bar, int c0, int c1) {
  asm volatile(
      "cp.async.bulk.tensor.3d.shared::cluster.global.mbarrier::complete_tx::bytes [%0], [%1, {%3, %4, %5}], [%2];" ::"r"(dst),
      "l"(map), "r"(bar), "r"(c0), "r"(c1), "r"(0)
      : "memory");
}
__device__ __forceinline__ void tma_load_5d(uint32_t dst, const CUtensorMap* map, uint32_t bar, int c0, int c4) {
  asm volatile(
      "cp.async.bulk.tensor.5d.shared::cluster.global.mbarrier::complete_tx::bytes [%0], [%1, {%3, %5, %5, %5, %4}], [%2];" ::"r"(dst),
      "l"(map), "r"(bar), "r"(c0), "r"(c4), "r"(0)
      : "memory");
}
__device__ __forceinline__ void bulk_load(uint32_t dst, const void* src, uint32_t bytes, uint32_t bar) {
  asm volatile("cp.async.bulk.shared::cluster.global.mbarrier::complete_tx::bytes [%0], [%1], %2, [%3];" ::"r"(dst),
               "l"(src), "r"(bytes), "r"(bar)
               : "memory");
}
__device__ __forceinline__ void bulk_store(void* dst, uint32_t src, uint32_t bytes) {
  asm volatile("cp.async.bulk.global.shared::cta.bulk_group [%0], [%1], %2;" ::"l"(dst), "r"(src), "r"(bytes) : "memory");
}
__device__ __forceinline__ void tma_store_2d(const CUtensorMap* map, uint32_t src, int c0, int c1) {
  asm volatile("cp.async.bulk.tensor.2d.global.shared::cta.bulk_group [%0, {%2, %3}], [%1];" ::"l"(map), "r"(src),
               "r"(c0), "r"(c1)
               : "memory");
}
__device__ __forceinline__ void bulk_announce(unsigned* p) {
  asm volatile("cp.reduce.async.bulk.global.shared::cta.bulk_group.add.u32 [%0], [%1], 16;" ::"l"(p), "r"(SBASE + OFF_ONE) : "memory");
}
__device__ __forceinline__ void bulk_commit() { asm volatile("cp.async.bulk.commit_group;" ::: "memory"); }
__device__ __forceinline__ void bulk_wait_read0() { asm volatile("cp.async.bulk.wait_group.read 0;" ::: "memory"); }
__device__ __forceinline__ void bulk_wait0() { asm volatile("cp.async.bulk.wait_group 0;" ::: "memory"); }
__device__ __forceinline__ void named_bar_sync(int id, int nthreads) {
  asm volatile("bar.sync %0, %1;" ::"r"(id), "r"(nthreads) : "memory");
}
__device__ __forceinline__ void named_bar_arrive(int id, int nthreads) {
  asm volatile("bar.arrive %0, %1;" ::"r"(id), "r"(nthreads) : "memory");
}

__device__ __forceinline__ void wgmma_fence() { asm volatile("wgmma.fence.sync.aligned;\n" ::: "memory"); }
__device__ __forceinline__ void wgmma_commit() { asm volatile("wgmma.commit_group.sync.aligned;\n" ::: "memory"); }
template <int N>
__device__ __forceinline__ void wgmma_wait() {
  asm volatile("wgmma.wait_group.sync.aligned %0;\n" ::"n"(N) : "memory");
}
template <int R>
__device__ __forceinline__ void setmaxnreg_inc() { asm volatile("setmaxnreg.inc.sync.aligned.u32 %0;\n" ::"n"(R)); }
template <int R>
__device__ __forceinline__ void setmaxnreg_dec() { asm volatile("setmaxnreg.dec.sync.aligned.u32 %0;\n" ::"n"(R)); }
template <int N>
__device__ __forceinline__ void reg_fence(float* r) {
#pragma unroll
  for (int i = 0; i < N; i++) asm volatile("" : "+f"(r[i])::"memory");
}

template <int N>
__device__ __forceinline__ void reg_define(float* r) {
#pragma unroll
  for (int i = 0; i < N; i++) r[i] = 0.f;
}

__device__ __forceinline__ uint64_t desc_lo(uint32_t lo) {
  uint64_t d;
  asm("mov.b64 %0, {%1, %2};" : "=l"(d) : "r"(lo), "r"(0x40000040u));
  return d;
}
__device__ __forceinline__ uint64_t make_desc(uint32_t addr, uint32_t lbo_bytes) {
  return desc_lo((addr >> 4) + ((lbo_bytes >> 4) << 16));
}

__device__ __forceinline__ void wgmma_n192_ss_ta0_tb1(float* d, uint64_t descA, uint64_t descB, int scaleD) {
  asm volatile("{\n.reg .pred p;\nsetp.ne.b32 p, %98, 0;\n"
    "wgmma.mma_async.sync.aligned.m64n192k16.f32.bf16.bf16 {%0, %1, %2, %3, %4, %5, %6, %7, %8, %9, %10, %11, %12, %13, %14, %15, %16, %17, %18, %19, %20, %21, %22, %23, %24, %25, %26, %27, %28, %29, %30, %31, %32, %33, %34, %35, %36, %37, %38, %39, %40, %41, %42, %43, %44, %45, %46, %47, %48, %49, %50, %51, %52, %53, %54, %55, %56, %57, %58, %59, %60, %61, %62, %63, %64, %65, %66, %67, %68, %69, %70, %71, %72, %73, %74, %75, %76, %77, %78, %79, %80, %81, %82, %83, %84, %85, %86, %87, %88, %89, %90, %91, %92, %93, %94, %95}, %96, %97, p, 1, 1, 0, 1;\n}\n"
    : "+f"(d[0]), "+f"(d[1]), "+f"(d[2]), "+f"(d[3]), "+f"(d[4]), "+f"(d[5]), "+f"(d[6]), "+f"(d[7]), "+f"(d[8]), "+f"(d[9]), "+f"(d[10]), "+f"(d[11]), "+f"(d[12]), "+f"(d[13]), "+f"(d[14]), "+f"(d[15]), "+f"(d[16]), "+f"(d[17]), "+f"(d[18]), "+f"(d[19]), "+f"(d[20]), "+f"(d[21]), "+f"(d[22]), "+f"(d[23]), "+f"(d[24]), "+f"(d[25]), "+f"(d[26]), "+f"(d[27]), "+f"(d[28]), "+f"(d[29]), "+f"(d[30]), "+f"(d[31]), "+f"(d[32]), "+f"(d[33]), "+f"(d[34]), "+f"(d[35]), "+f"(d[36]), "+f"(d[37]), "+f"(d[38]), "+f"(d[39]), "+f"(d[40]), "+f"(d[41]), "+f"(d[42]), "+f"(d[43]), "+f"(d[44]), "+f"(d[45]), "+f"(d[46]), "+f"(d[47]), "+f"(d[48]), "+f"(d[49]), "+f"(d[50]), "+f"(d[51]), "+f"(d[52]), "+f"(d[53]), "+f"(d[54]), "+f"(d[55]), "+f"(d[56]), "+f"(d[57]), "+f"(d[58]), "+f"(d[59]), "+f"(d[60]), "+f"(d[61]), "+f"(d[62]), "+f"(d[63]), "+f"(d[64]), "+f"(d[65]), "+f"(d[66]), "+f"(d[67]), "+f"(d[68]), "+f"(d[69]), "+f"(d[70]), "+f"(d[71]), "+f"(d[72]), "+f"(d[73]), "+f"(d[74]), "+f"(d[75]), "+f"(d[76]), "+f"(d[77]), "+f"(d[78]), "+f"(d[79]), "+f"(d[80]), "+f"(d[81]), "+f"(d[82]), "+f"(d[83]), "+f"(d[84]), "+f"(d[85]), "+f"(d[86]), "+f"(d[87]), "+f"(d[88]), "+f"(d[89]), "+f"(d[90]), "+f"(d[91]), "+f"(d[92]), "+f"(d[93]), "+f"(d[94]), "+f"(d[95])
    : "l"(descA), "l"(descB), "r"(scaleD));
}

__device__ __forceinline__ void wgmma_n128_ss_ta0_tb1(float* d, uint64_t descA, uint64_t descB, int scaleD) {
  asm volatile("{\n.reg .pred p;\nsetp.ne.b32 p, %66, 0;\n"
    "wgmma.mma_async.sync.aligned.m64n128k16.f32.bf16.bf16 {%0, %1, %2, %3, %4, %5, %6, %7, %8, %9, %10, %11, %12, %13, %14, %15, %16, %17, %18, %19, %20, %21, %22, %23, %24, %25, %26, %27, %28, %29, %30, %31, %32, %33, %34, %35, %36, %37, %38, %39, %40, %41, %42, %43, %44, %45, %46, %47, %48, %49, %50, %51, %52, %53, %54, %55, %56, %57, %58, %59, %60, %61, %62, %63}, %64, %65, p, 1, 1, 0, 1;\n}\n"
    : "+f"(d[0]), "+f"(d[1]), "+f"(d[2]), "+f"(d[3]), "+f"(d[4]), "+f"(d[5]), "+f"(d[6]), "+f"(d[7]), "+f"(d[8]), "+f"(d[9]), "+f"(d[10]), "+f"(d[11]), "+f"(d[12]), "+f"(d[13]), "+f"(d[14]), "+f"(d[15]), "+f"(d[16]), "+f"(d[17]), "+f"(d[18]), "+f"(d[19]), "+f"(d[20]), "+f"(d[21]), "+f"(d[22]), "+f"(d[23]), "+f"(d[24]), "+f"(d[25]), "+f"(d[26]), "+f"(d[27]), "+f"(d[28]), "+f"(d[29]), "+f"(d[30]), "+f"(d[31]), "+f"(d[32]), "+f"(d[33]), "+f"(d[34]), "+f"(d[35]), "+f"(d[36]), "+f"(d[37]), "+f"(d[38]), "+f"(d[39]), "+f"(d[40]), "+f"(d[41]), "+f"(d[42]), "+f"(d[43]), "+f"(d[44]), "+f"(d[45]), "+f"(d[46]), "+f"(d[47]), "+f"(d[48]), "+f"(d[49]), "+f"(d[50]), "+f"(d[51]), "+f"(d[52]), "+f"(d[53]), "+f"(d[54]), "+f"(d[55]), "+f"(d[56]), "+f"(d[57]), "+f"(d[58]), "+f"(d[59]), "+f"(d[60]), "+f"(d[61]), "+f"(d[62]), "+f"(d[63])
    : "l"(descA), "l"(descB), "r"(scaleD));
}

__device__ __forceinline__ void wgmma_n192_ssz_ta0_tb1(float* d, uint64_t descA, uint64_t descB) {
  asm volatile("{\n.reg .pred p;\nsetp.ne.b32 p, 0, 0;\n"
    "wgmma.mma_async.sync.aligned.m64n192k16.f32.bf16.bf16 {%0, %1, %2, %3, %4, %5, %6, %7, %8, %9, %10, %11, %12, %13, %14, %15, %16, %17, %18, %19, %20, %21, %22, %23, %24, %25, %26, %27, %28, %29, %30, %31, %32, %33, %34, %35, %36, %37, %38, %39, %40, %41, %42, %43, %44, %45, %46, %47, %48, %49, %50, %51, %52, %53, %54, %55, %56, %57, %58, %59, %60, %61, %62, %63, %64, %65, %66, %67, %68, %69, %70, %71, %72, %73, %74, %75, %76, %77, %78, %79, %80, %81, %82, %83, %84, %85, %86, %87, %88, %89, %90, %91, %92, %93, %94, %95}, %96, %97, p, 1, 1, 0, 1;\n}\n"
    : "=f"(d[0]), "=f"(d[1]), "=f"(d[2]), "=f"(d[3]), "=f"(d[4]), "=f"(d[5]), "=f"(d[6]), "=f"(d[7]), "=f"(d[8]), "=f"(d[9]), "=f"(d[10]), "=f"(d[11]), "=f"(d[12]), "=f"(d[13]), "=f"(d[14]), "=f"(d[15]), "=f"(d[16]), "=f"(d[17]), "=f"(d[18]), "=f"(d[19]), "=f"(d[20]), "=f"(d[21]), "=f"(d[22]), "=f"(d[23]), "=f"(d[24]), "=f"(d[25]), "=f"(d[26]), "=f"(d[27]), "=f"(d[28]), "=f"(d[29]), "=f"(d[30]), "=f"(d[31]), "=f"(d[32]), "=f"(d[33]), "=f"(d[34]), "=f"(d[35]), "=f"(d[36]), "=f"(d[37]), "=f"(d[38]), "=f"(d[39]), "=f"(d[40]), "=f"(d[41]), "=f"(d[42]), "=f"(d[43]), "=f"(d[44]), "=f"(d[45]), "=f"(d[46]), "=f"(d[47]), "=f"(d[48]), "=f"(d[49]), "=f"(d[50]), "=f"(d[51]), "=f"(d[52]), "=f"(d[53]), "=f"(d[54]), "=f"(d[55]), "=f"(d[56]), "=f"(d[57]), "=f"(d[58]), "=f"(d[59]), "=f"(d[60]), "=f"(d[61]), "=f"(d[62]), "=f"(d[63]), "=f"(d[64]), "=f"(d[65]), "=f"(d[66]), "=f"(d[67]), "=f"(d[68]), "=f"(d[69]), "=f"(d[70]), "=f"(d[71]), "=f"(d[72]), "=f"(d[73]), "=f"(d[74]), "=f"(d[75]), "=f"(d[76]), "=f"(d[77]), "=f"(d[78]), "=f"(d[79]), "=f"(d[80]), "=f"(d[81]), "=f"(d[82]), "=f"(d[83]), "=f"(d[84]), "=f"(d[85]), "=f"(d[86]), "=f"(d[87]), "=f"(d[88]), "=f"(d[89]), "=f"(d[90]), "=f"(d[91]), "=f"(d[92]), "=f"(d[93]), "=f"(d[94]), "=f"(d[95])
    : "l"(descA), "l"(descB));
}

__device__ __forceinline__ void wgmma_n8_ss_ta1_tb0(float* d, uint64_t descA, uint64_t descB, int scaleD) {
  asm volatile("{\n.reg .pred p;\nsetp.ne.b32 p, %6, 0;\n"
    "wgmma.mma_async.sync.aligned.m64n8k16.f32.bf16.bf16 {%0, %1, %2, %3}, %4, %5, p, 1, 1, 1, 0;\n}\n"
    : "+f"(d[0]), "+f"(d[1]), "+f"(d[2]), "+f"(d[3])
    : "l"(descA), "l"(descB), "r"(scaleD));
}

__device__ __forceinline__ void wgmma_n8_ssz_ta1_tb0(float* d, uint64_t descA, uint64_t descB) {
  asm volatile("{\n.reg .pred p;\nsetp.ne.b32 p, 0, 0;\n"
    "wgmma.mma_async.sync.aligned.m64n8k16.f32.bf16.bf16 {%0, %1, %2, %3}, %4, %5, p, 1, 1, 1, 0;\n}\n"
    : "=f"(d[0]), "=f"(d[1]), "=f"(d[2]), "=f"(d[3])
    : "l"(descA), "l"(descB));
}

__device__ __forceinline__ void wgmma_n192_rs_tb1(float* d, const uint32_t* a, uint64_t descB, int scaleD) {
  asm volatile("{\n.reg .pred p;\nsetp.ne.b32 p, %101, 0;\n"
    "wgmma.mma_async.sync.aligned.m64n192k16.f32.bf16.bf16 {%0, %1, %2, %3, %4, %5, %6, %7, %8, %9, %10, %11, %12, %13, %14, %15, %16, %17, %18, %19, %20, %21, %22, %23, %24, %25, %26, %27, %28, %29, %30, %31, %32, %33, %34, %35, %36, %37, %38, %39, %40, %41, %42, %43, %44, %45, %46, %47, %48, %49, %50, %51, %52, %53, %54, %55, %56, %57, %58, %59, %60, %61, %62, %63, %64, %65, %66, %67, %68, %69, %70, %71, %72, %73, %74, %75, %76, %77, %78, %79, %80, %81, %82, %83, %84, %85, %86, %87, %88, %89, %90, %91, %92, %93, %94, %95}, {%96, %97, %98, %99}, %100, p, 1, 1, 1;\n}\n"
    : "+f"(d[0]), "+f"(d[1]), "+f"(d[2]), "+f"(d[3]), "+f"(d[4]), "+f"(d[5]), "+f"(d[6]), "+f"(d[7]), "+f"(d[8]), "+f"(d[9]), "+f"(d[10]), "+f"(d[11]), "+f"(d[12]), "+f"(d[13]), "+f"(d[14]), "+f"(d[15]), "+f"(d[16]), "+f"(d[17]), "+f"(d[18]), "+f"(d[19]), "+f"(d[20]), "+f"(d[21]), "+f"(d[22]), "+f"(d[23]), "+f"(d[24]), "+f"(d[25]), "+f"(d[26]), "+f"(d[27]), "+f"(d[28]), "+f"(d[29]), "+f"(d[30]), "+f"(d[31]), "+f"(d[32]), "+f"(d[33]), "+f"(d[34]), "+f"(d[35]), "+f"(d[36]), "+f"(d[37]), "+f"(d[38]), "+f"(d[39]), "+f"(d[40]), "+f"(d[41]), "+f"(d[42]), "+f"(d[43]), "+f"(d[44]), "+f"(d[45]), "+f"(d[46]), "+f"(d[47]), "+f"(d[48]), "+f"(d[49]), "+f"(d[50]), "+f"(d[51]), "+f"(d[52]), "+f"(d[53]), "+f"(d[54]), "+f"(d[55]), "+f"(d[56]), "+f"(d[57]), "+f"(d[58]), "+f"(d[59]), "+f"(d[60]), "+f"(d[61]), "+f"(d[62]), "+f"(d[63]), "+f"(d[64]), "+f"(d[65]), "+f"(d[66]), "+f"(d[67]), "+f"(d[68]), "+f"(d[69]), "+f"(d[70]), "+f"(d[71]), "+f"(d[72]), "+f"(d[73]), "+f"(d[74]), "+f"(d[75]), "+f"(d[76]), "+f"(d[77]), "+f"(d[78]), "+f"(d[79]), "+f"(d[80]), "+f"(d[81]), "+f"(d[82]), "+f"(d[83]), "+f"(d[84]), "+f"(d[85]), "+f"(d[86]), "+f"(d[87]), "+f"(d[88]), "+f"(d[89]), "+f"(d[90]), "+f"(d[91]), "+f"(d[92]), "+f"(d[93]), "+f"(d[94]), "+f"(d[95])
    : "r"(a[0]), "r"(a[1]), "r"(a[2]), "r"(a[3]), "l"(descB), "r"(scaleD));
}

__device__ __forceinline__ void wgmma_n80_rs_tb0(float* d, const uint32_t* a, uint64_t descB, int scaleD) {
  asm volatile("{\n.reg .pred p;\nsetp.ne.b32 p, %45, 0;\n"
    "wgmma.mma_async.sync.aligned.m64n80k16.f32.bf16.bf16 {%0, %1, %2, %3, %4, %5, %6, %7, %8, %9, %10, %11, %12, %13, %14, %15, %16, %17, %18, %19, %20, %21, %22, %23, %24, %25, %26, %27, %28, %29, %30, %31, %32, %33, %34, %35, %36, %37, %38, %39}, {%40, %41, %42, %43}, %44, p, 1, 1, 0;\n}\n"
    : "+f"(d[0]), "+f"(d[1]), "+f"(d[2]), "+f"(d[3]), "+f"(d[4]), "+f"(d[5]), "+f"(d[6]), "+f"(d[7]), "+f"(d[8]), "+f"(d[9]), "+f"(d[10]), "+f"(d[11]), "+f"(d[12]), "+f"(d[13]), "+f"(d[14]), "+f"(d[15]), "+f"(d[16]), "+f"(d[17]), "+f"(d[18]), "+f"(d[19]), "+f"(d[20]), "+f"(d[21]), "+f"(d[22]), "+f"(d[23]), "+f"(d[24]), "+f"(d[25]), "+f"(d[26]), "+f"(d[27]), "+f"(d[28]), "+f"(d[29]), "+f"(d[30]), "+f"(d[31]), "+f"(d[32]), "+f"(d[33]), "+f"(d[34]), "+f"(d[35]), "+f"(d[36]), "+f"(d[37]), "+f"(d[38]), "+f"(d[39])
    : "r"(a[0]), "r"(a[1]), "r"(a[2]), "r"(a[3]), "l"(descB), "r"(scaleD));
}

__device__ __forceinline__ void wgmma_n80_rsz_tb0(float* d, const uint32_t* a, uint64_t descB) {
  asm volatile("{\n.reg .pred p;\nsetp.ne.b32 p, 0, 0;\n"
    "wgmma.mma_async.sync.aligned.m64n80k16.f32.bf16.bf16 {%0, %1, %2, %3, %4, %5, %6, %7, %8, %9, %10, %11, %12, %13, %14, %15, %16, %17, %18, %19, %20, %21, %22, %23, %24, %25, %26, %27, %28, %29, %30, %31, %32, %33, %34, %35, %36, %37, %38, %39}, {%40, %41, %42, %43}, %44, p, 1, 1, 0;\n}\n"
    : "=f"(d[0]), "=f"(d[1]), "=f"(d[2]), "=f"(d[3]), "=f"(d[4]), "=f"(d[5]), "=f"(d[6]), "=f"(d[7]), "=f"(d[8]), "=f"(d[9]), "=f"(d[10]), "=f"(d[11]), "=f"(d[12]), "=f"(d[13]), "=f"(d[14]), "=f"(d[15]), "=f"(d[16]), "=f"(d[17]), "=f"(d[18]), "=f"(d[19]), "=f"(d[20]), "=f"(d[21]), "=f"(d[22]), "=f"(d[23]), "=f"(d[24]), "=f"(d[25]), "=f"(d[26]), "=f"(d[27]), "=f"(d[28]), "=f"(d[29]), "=f"(d[30]), "=f"(d[31]), "=f"(d[32]), "=f"(d[33]), "=f"(d[34]), "=f"(d[35]), "=f"(d[36]), "=f"(d[37]), "=f"(d[38]), "=f"(d[39])
    : "r"(a[0]), "r"(a[1]), "r"(a[2]), "r"(a[3]), "l"(descB));
}

__device__ __forceinline__ void wgmma_n32_rs_tb1(float* d, const uint32_t* a, uint64_t descB, int scaleD) {
  asm volatile("{\n.reg .pred p;\nsetp.ne.b32 p, %21, 0;\n"
    "wgmma.mma_async.sync.aligned.m64n32k16.f32.bf16.bf16 {%0, %1, %2, %3, %4, %5, %6, %7, %8, %9, %10, %11, %12, %13, %14, %15}, {%16, %17, %18, %19}, %20, p, 1, 1, 1;\n}\n"
    : "+f"(d[0]), "+f"(d[1]), "+f"(d[2]), "+f"(d[3]), "+f"(d[4]), "+f"(d[5]), "+f"(d[6]), "+f"(d[7]), "+f"(d[8]), "+f"(d[9]), "+f"(d[10]), "+f"(d[11]), "+f"(d[12]), "+f"(d[13]), "+f"(d[14]), "+f"(d[15])
    : "r"(a[0]), "r"(a[1]), "r"(a[2]), "r"(a[3]), "l"(descB), "r"(scaleD));
}

__device__ __forceinline__ void wgmma_n32_rsz_tb1(float* d, const uint32_t* a, uint64_t descB) {
  asm volatile("{\n.reg .pred p;\nsetp.ne.b32 p, 0, 0;\n"
    "wgmma.mma_async.sync.aligned.m64n32k16.f32.bf16.bf16 {%0, %1, %2, %3, %4, %5, %6, %7, %8, %9, %10, %11, %12, %13, %14, %15}, {%16, %17, %18, %19}, %20, p, 1, 1, 1;\n}\n"
    : "=f"(d[0]), "=f"(d[1]), "=f"(d[2]), "=f"(d[3]), "=f"(d[4]), "=f"(d[5]), "=f"(d[6]), "=f"(d[7]), "=f"(d[8]), "=f"(d[9]), "=f"(d[10]), "=f"(d[11]), "=f"(d[12]), "=f"(d[13]), "=f"(d[14]), "=f"(d[15])
    : "r"(a[0]), "r"(a[1]), "r"(a[2]), "r"(a[3]), "l"(descB));
}

__device__ __forceinline__ void wgmma_n32_rs_tb0(float* d, const uint32_t* a, uint64_t descB, int scaleD) {
  asm volatile("{\n.reg .pred p;\nsetp.ne.b32 p, %21, 0;\n"
    "wgmma.mma_async.sync.aligned.m64n32k16.f32.bf16.bf16 {%0, %1, %2, %3, %4, %5, %6, %7, %8, %9, %10, %11, %12, %13, %14, %15}, {%16, %17, %18, %19}, %20, p, 1, 1, 0;\n}\n"
    : "+f"(d[0]), "+f"(d[1]), "+f"(d[2]), "+f"(d[3]), "+f"(d[4]), "+f"(d[5]), "+f"(d[6]), "+f"(d[7]), "+f"(d[8]), "+f"(d[9]), "+f"(d[10]), "+f"(d[11]), "+f"(d[12]), "+f"(d[13]), "+f"(d[14]), "+f"(d[15])
    : "r"(a[0]), "r"(a[1]), "r"(a[2]), "r"(a[3]), "l"(descB), "r"(scaleD));
}

__device__ __forceinline__ void wgmma_n32_rsz_tb0(float* d, const uint32_t* a, uint64_t descB) {
  asm volatile("{\n.reg .pred p;\nsetp.ne.b32 p, 0, 0;\n"
    "wgmma.mma_async.sync.aligned.m64n32k16.f32.bf16.bf16 {%0, %1, %2, %3, %4, %5, %6, %7, %8, %9, %10, %11, %12, %13, %14, %15}, {%16, %17, %18, %19}, %20, p, 1, 1, 0;\n}\n"
    : "=f"(d[0]), "=f"(d[1]), "=f"(d[2]), "=f"(d[3]), "=f"(d[4]), "=f"(d[5]), "=f"(d[6]), "=f"(d[7]), "=f"(d[8]), "=f"(d[9]), "=f"(d[10]), "=f"(d[11]), "=f"(d[12]), "=f"(d[13]), "=f"(d[14]), "=f"(d[15])
    : "r"(a[0]), "r"(a[1]), "r"(a[2]), "r"(a[3]), "l"(descB));
}

__device__ __forceinline__ uint32_t pack_bf16x2(float lo, float hi) {
  uint32_t r;
  asm("cvt.rn.bf16x2.f32 %0, %1, %2;" : "=r"(r) : "f"(hi), "f"(lo));
  return r;
}
__device__ __forceinline__ float bf_lo(uint32_t p) { return __uint_as_float(p << 16); }
__device__ __forceinline__ float bf_hi(uint32_t p) { return __uint_as_float(p & 0xffff0000u); }
__device__ __forceinline__ float bf16_round(float v) { return __bfloat162float(__float2bfloat16_rn(v)); }
__device__ __forceinline__ float ex2_approx(float x) {
  float r;
  asm("ex2.approx.ftz.f32 %0, %1;" : "=f"(r) : "f"(x));
  return r;
}
__device__ __forceinline__ float rcp_fast(float x) {
  float r;
  asm("rcp.approx.ftz.f32 %0, %1;" : "=f"(r) : "f"(x));
  return r;
}
__device__ __forceinline__ void ldmatrix_x4(uint32_t (&r)[4], uint32_t addr) {
  asm volatile("ldmatrix.sync.aligned.m8n8.x4.shared.b16 {%0,%1,%2,%3}, [%4];"
               : "=r"(r[0]), "=r"(r[1]), "=r"(r[2]), "=r"(r[3])
               : "r"(addr)
               : "memory");
}
__device__ __forceinline__ void stmatrix_x4(uint32_t addr, uint32_t r0, uint32_t r1, uint32_t r2, uint32_t r3) {
  asm volatile("stmatrix.sync.aligned.m8n8.x4.shared.b16 [%0], {%1,%2,%3,%4};" ::"r"(addr), "r"(r0), "r"(r1), "r"(r2),
               "r"(r3));
}
__device__ __forceinline__ uint32_t add_bf16x2(uint32_t a, uint32_t b) {
  uint32_t r;
  asm("add.rn.bf16x2 %0, %1, %2;" : "=r"(r) : "r"(a), "r"(b));
  return r;
}
__device__ __forceinline__ uint4 lds128(uint32_t addr) {
  uint4 v;
  asm volatile("ld.shared.v4.b32 {%0,%1,%2,%3}, [%4];" : "=r"(v.x), "=r"(v.y), "=r"(v.z), "=r"(v.w) : "r"(addr) : "memory");
  return v;
}
__device__ __forceinline__ uint32_t lds32(uint32_t addr) {
  uint32_t v;
  asm volatile("ld.shared.b32 %0, [%1];" : "=r"(v) : "r"(addr) : "memory");
  return v;
}
__device__ __forceinline__ void sts32(uint32_t addr, uint32_t v) {
  asm volatile("st.shared.b32 [%0], %1;" ::"r"(addr), "r"(v) : "memory");
}

__device__ __forceinline__ int fresh_tid() {
  int t;
  asm volatile("mov.u32 %0, %%tid.x;" : "=r"(t));
  return t;
}
__device__ __forceinline__ unsigned ld_relaxed_u32(const void* p) {
  unsigned v;
  asm volatile("ld.relaxed.gpu.global.u32 %0, [%1];" : "=r"(v) : "l"(p) : "memory");
  return v;
}
__device__ __forceinline__ unsigned launch_epoch() { return (*(volatile unsigned*)g_done) / NCTA + 1u; }
__device__ __forceinline__ uint32_t set_tag(uint32_t w, uint32_t m, uint32_t tag) { return (w & ~m) | (tag & m); }
__device__ __forceinline__ uint32_t o_tag(int L) { return (L + 1) & 1; }
__device__ __forceinline__ uint32_t x_tag(int L) { return L & 1; }
__device__ __forceinline__ uint32_t kv_tag(int L) { return L < 2; }

#define SPINT 0
template <class F>
__device__ __forceinline__ void fix_lines(uint32_t bar, uint32_t par, uint32_t ta, uint32_t tag, uint32_t mask, int bar_id, F line) {
  uint32_t m;
  mbar_wait(bar, par);
  m = lds32(ta);
  m = __ballot_sync(0xffffffffu, (m ^ tag) & mask);
  if (m == 0u) return;
#pragma unroll 1
  for (uint32_t it = 0; it < (1u << 17) && m != 0u; ++it) {
    const int l = __ffs(m) - 1, j = fresh_tid() & 7;
    uint4 v;
    asm volatile("ld.relaxed.gpu.global.v4.b32 {%0,%1,%2,%3}, [%4];" : "=r"(v.x), "=r"(v.y), "=r"(v.z), "=r"(v.w) : "l"(line(l) + j * 8) : "memory");
    const uint32_t a = __shfl_sync(0xffffffffu, ta, l) ^ (j << 4);
    if (((__shfl_sync(0xffffffffu, v.x, 0) ^ tag) & 1u) == 0u) {
      asm volatile("st.shared.v4.b32 [%0], {%1,%2,%3,%4};" ::"r"(a), "r"(v.x), "r"(v.y), "r"(v.z), "r"(v.w) : "memory");
      m &= m - 1u;
    }
  }
  fence_proxy_async_smem();
  named_bar_sync(bar_id, 32);
}
__device__ __forceinline__ uint32_t peek_counts(const unsigned* f, unsigned target, int lane) {
  return __ballot_sync(0xffffffffu, (int)(ld_relaxed_u32(f + (lane & 15) * 4) - target) >= 0);
}
__device__ __forceinline__ void wait_count(const unsigned* f, unsigned target, int i, uint32_t& seen, int lane) {
  if ((seen >> i) & 1u) return;
#pragma unroll 1
  for (uint32_t it = 0; it < (1u << 17); ++it) {
    seen = peek_counts(f, target, lane);
    if ((seen >> i) & 1u) break;
  }
}
__device__ __forceinline__ float4 ld_rec(const float4* p) {
  float4 v;
  asm volatile("ld.relaxed.gpu.global.v4.f32 {%0,%1,%2,%3}, [%4];" : "=f"(v.x), "=f"(v.y), "=f"(v.z), "=f"(v.w) : "l"(p) : "memory");
  return v;
}
__device__ __forceinline__ void st_rec(float4* p, float a, float b, float c, unsigned tag) {
  asm volatile("st.relaxed.gpu.global.v4.f32 [%0], {%1,%2,%3,%4};" ::"l"(p), "f"(a), "f"(b), "f"(c), "f"(__uint_as_float(tag)) : "memory");
}
template <int N>
__device__ __forceinline__ float4 sum_recs(const float4* p, int stride, unsigned tag) {
  float4 s;
#pragma unroll 1
  for (uint32_t it = 0; it < (1u << 17); ++it) {
    float4 v[N];
#pragma unroll
    for (int t = 0; t < N; t++) v[t] = ld_rec(p + t * stride);
    bool ok = true;
    s = make_float4(0.f, 0.f, 0.f, 0.f);
#pragma unroll
    for (int t = 0; t < N; t++) {
      ok &= __float_as_uint(v[t].w) == tag;
      s.x += v[t].x;
      s.y += v[t].y;
      s.z += v[t].z;
    }
    if (ok) break;
    __nanosleep(200);
  }
  return s;
}

#define PHASE_IDS                                  \
  const int tid_ = fresh_tid();                    \
  const int lane = tid_ & 31, wwarp = __shfl_sync(0xffffffffu, (tid_ >> 5) & 3, 0), tid = tid_ & 127; \
  const int g = lane >> 2, c = lane & 3;           \
  (void)tid; (void)g; (void)c; (void)wwarp;

#define PHASE_IDS_W                                \
  const int lane = fresh_tid() & 31, wwarp = warp & 3; \
  const int g = lane >> 2, c = lane & 3;

#define GTL(i) do { } while (0)
#define TGET(v) do { } while (0)
#define TPUT(c, i, v) do { } while (0)

constexpr float SM_C = 0.17677669529663687f * 1.4426950408889634f;

__device__ __forceinline__ void stmatrix_x4_if(bool ok, uint32_t addr, uint32_t r0, uint32_t r1, uint32_t r2, uint32_t r3) {
  asm volatile("{\n.reg .pred p;\nsetp.ne.b32 p, %5, 0;\n@p stmatrix.sync.aligned.m8n8.x4.shared.b16 [%0], {%1,%2,%3,%4};\n}\n" ::"r"(addr),
               "r"(r0), "r"(r1), "r"(r2), "r"(r3), "r"((int)ok));
}

__device__ __forceinline__ void attn_a_slow(const uint8_t* __restrict__ kvimg, int L, int gb, int hp, uint32_t bad,
                                            int row0, int lane) {
  constexpr uint32_t sq = SBASE + OFF_SLOT + 3 * 16384;
#pragma unroll 1
  for (int j = 0; j < 8; j++) {
    const uint8_t* tp = kvimg + (size_t)(gb * 16 + hp) * 32768 + (j * 32 + lane) * 128 + ((lane & 7) << 4);
#pragma unroll 1
    for (uint32_t it = 0; it < (1u << 17); ++it)
      if (((ld_relaxed_u32(tp) ^ kv_tag(L)) & 1u) == 0u) break;
  }
  __syncwarp();
#pragma unroll 1
  for (int t = 0; t < 32; t++) {
    const int hh = t >> 4, row = row0 + (t & 7) + (t & 8) * 4;
    if (!((bad >> hh) & 1u)) continue;
    const int qpos = gb * 128 + row;
    const uint32_t qaddr = sq + row * 128;
    float mx = -INFINITY, sum = 0.f, acc = 0.f;
#pragma unroll 1
    for (int pass = 0; pass < 2; pass++) {
#pragma unroll 1
      for (int j = 0; j < 8; j++) {
        const int kp = qpos - (lane + 32 * j);
        const uint8_t* kr = kvimg + ((size_t)((kp >> 7) * 16 + hp) * 2 + ((kp >> 6) & 1)) * 16384 + (kp & 63) * 128;
        float d = -INFINITY;
        if (kp >= 0) {
          d = 0.f;
#pragma unroll 1
          for (int q = 0; q < 4; q++) {
            const uint4 kv = __ldcg(reinterpret_cast<const uint4*>(kr + (((hh * 4 + q) ^ (kp & 7)) << 4)));
            const uint4 qv = lds128(qaddr + (((hh * 4 + q) ^ (row & 7)) << 4));
            const uint32_t kw[4] = {kv.x, kv.y, kv.z, kv.w}, qw[4] = {qv.x, qv.y, qv.z, qv.w};
#pragma unroll
            for (int e = 0; e < 4; e++) d = fmaf(bf_lo(kw[e]), bf_lo(qw[e]), fmaf(bf_hi(kw[e]), bf_hi(qw[e]), d));
          }
        }
        if (pass == 0) {
          mx = fmaxf(mx, d);
        } else {
          const float ev = ex2_approx(d - mx);
          sum += ev;
          const float pv = bf16_round(ev);
#pragma unroll 1
          for (int kk = 0; kk < 32; kk++) {
            const float pk = __shfl_sync(0xffffffffu, pv, kk);
            const int k2 = qpos - (kk + 32 * j);
            if (k2 >= 0) {
              const uint8_t* vr = kvimg + ((size_t)((k2 >> 7) * 16 + hp) * 2 + ((k2 >> 6) & 1)) * 16384 + 8192 + (k2 & 63) * 128;
              const unsigned short vv =
                  __ldcg(reinterpret_cast<const unsigned short*>(vr + (((hh * 4 + (lane >> 3)) ^ (k2 & 7)) << 4) + (lane & 7) * 2));
              acc = fmaf(pk, __uint_as_float((uint32_t)vv << 16), acc);
            }
          }
        }
      }
      if (pass == 0) {
#pragma unroll
        for (int o = 16; o > 0; o >>= 1) mx = fmaxf(mx, __shfl_xor_sync(0xffffffffu, mx, o));
      }
    }
#pragma unroll
    for (int o = 16; o > 0; o >>= 1) sum += __shfl_xor_sync(0xffffffffu, sum, o);
    acc *= rcp_fast(sum);
    const float hi = __shfl_down_sync(0xffffffffu, acc, 1);
    __syncwarp();
    if ((lane & 1) == 0) sts32(qaddr + (((hh * 4 + (lane >> 3)) ^ (row & 7)) << 4) + (lane & 7) * 2,
                               set_tag(pack_bf16x2(acc, hi), hh == 0 && lane == 0, o_tag(L)));
    __syncwarp();
  }
}

template <int HH>
__device__ __forceinline__ void store_o(const float (&o)[16], const float (&inv)[2], uint32_t ra, uint32_t tag, bool ok) {
  const uint32_t m = HH == 0 && (fresh_tid() & 3) == 0;
#pragma unroll
  for (int jp = 0; jp < 2; jp++) {
    uint32_t w0 = pack_bf16x2(o[8 * jp] * inv[0], o[8 * jp + 1] * inv[0]);
    uint32_t w1 = pack_bf16x2(o[8 * jp + 2] * inv[1], o[8 * jp + 3] * inv[1]);
    if (HH == 0 && jp == 0) {
      w0 = set_tag(w0, m, tag);
      w1 = set_tag(w1, m, tag);
    }
    stmatrix_x4_if(ok, ra ^ ((HH * 4 + 2 * jp) << 4), w0, w1, pack_bf16x2(o[8 * jp + 4] * inv[0], o[8 * jp + 5] * inv[0]),
                   pack_bf16x2(o[8 * jp + 6] * inv[1], o[8 * jp + 7] * inv[1]));
  }
}
__device__ __forceinline__ int tile_row(bool B, int w, int r, int g) { return (B ? 16 * w + 8 * r : 8 * w + 32 * r) + g; }
__device__ __forceinline__ uint32_t q_row_addr(bool B, int R, int w, int lane) {
  return SBASE + OFF_SLOT + 3 * 16384 + R * 8192 + tile_row(B, w, (lane >> 3) & 1, lane & 7) * 128 + (((lane >> 4) ^ (lane & 7)) << 4);
}

struct AttnA {
  float s[2][16], o[2][16], l[2][2], sh[2][3];
  uint32_t p[2][4], t[2], me[4], ra, bad, zero;
};
#define ATS_(i) do { } while (0)
template <int V>
__device__ __forceinline__ void attn_sum(AttnA& a, int nv) {
  constexpr int hh = (V >> 1) & 1, kh = V & 1, i = V >> 2;
#pragma unroll
  for (int r = 0; r < 2; r++) {
    const uint32_t t1 = add_bf16x2(add_bf16x2(a.p[0][r], a.p[0][2 + r]), add_bf16x2(a.p[1][r], a.p[1][2 + r]));
    if (kh == 0) {
      a.t[r] = t1;
    } else {
      uint32_t tt = add_bf16x2(a.t[r], t1);
      if (i > 0) tt = i <= nv ? tt : 0u;
      const float v = bf_lo(tt) + bf_hi(tt);
      a.l[hh][r] = i == 0 ? v : a.l[hh][r] + v;
    }
  }
}
template <int HH>
__device__ __forceinline__ void attn_shfl(AttnA& a) {
#pragma unroll
  for (int r = 0; r < 2; r++)
#pragma unroll
    for (int j = 0; j < 3; j++) a.sh[r][j] = __shfl_xor_sync(0xffffffffu, a.l[HH][r], j + 1);
}
template <int HH>
__device__ __forceinline__ void attn_fin(AttnA& a) {
  bool bad = false;
  float inv[2];
#pragma unroll
  for (int r = 0; r < 2; r++) {
    const float v = (a.l[HH][r] + a.sh[r][0]) + (a.sh[r][1] + a.sh[r][2]);
    bad |= !(v <= 1.152921504606846976e18f && v >= 8.673617379884035e-19f);
    inv[r] = rcp_fast(v);
  }
  bad = __any_sync(0xffffffffu, bad);
  if (HH == 1) wgmma_wait<0>();
  reg_fence<16>(a.o[HH]);
  store_o<HH>(a.o[HH], inv, a.ra, o_tag(0), !bad);
  a.bad = (HH == 0 ? 0u : a.bad) | (bad ? 1u << HH : 0u);
}
__device__ __forceinline__ void attn_masks(AttnA& a, int wr) {
  const int lane = fresh_tid() & 31, d = (lane >> 2) - 2 * (lane & 3);
  const uint32_t tri = d >= 1 ? 0xffffffffu : (d == 0 ? 0xffffu : 0u);
#pragma unroll
  for (int t = 0; t < 4; t++) a.me[t] = wr > t ? 0xffffffffu : (wr == t ? tri : 0u);
}
template <int V, int K>
__device__ __forceinline__ uint32_t attn_exp(AttnA& a) {
  constexpr int i = V >> 2, kh = V & 1, r = K & 1;
  if ((i == 0 && kh > r) || (i == 4 && kh < r)) return 0u;
  const uint32_t w = pack_bf16x2(ex2_approx(a.s[V & 1][2 * K]), ex2_approx(a.s[V & 1][2 * K + 1]));
  if (i == 0 && kh == r) return w & a.me[K >> 1];
  if (i == 4 && kh == r) return w & ~a.me[K >> 1];
  return w;
}
template <int V>
__device__ __forceinline__ void attn_unit(AttnA& a, const uint32_t (&q)[2][2][4], uint64_t dcur, uint64_t dnext, int R, int wr, int nv,
                                          uint32_t hbar, uint32_t hpar, uint32_t rbar, bool rel) {
  constexpr int hh = (V >> 1) & 1, kh = V & 1, i = V >> 2;
  ATS_(V + 1);
  asm volatile("" : "+l"(dcur), "+l"(dnext));
  wgmma_wait<1>();
  reg_fence<16>(a.s[V & 1]);
  bool hok = true;
  if (V == 4) hbar = SBASE + OFF_BAR + 8u * (R ? B_LOC : B_HV);
  if (((V & 3) == 2 && V < 16) || V == 4) hok = mbar_test(hbar, hpar);
  const uint64_t d0 = ((V & 3) >= 2 ? dnext : dcur) + ((hh ^ 1) * 4 + kh * 256), d1 = ((V & 3) >= 2 ? dnext : dcur) + ((hh ^ 1) * 4 + kh * 256 + 2);
  const uint64_t d2 = dcur + (512 + hh * 4 + kh * 256), d3 = dcur + (640 + hh * 4 + kh * 256);
  if ((V & 3) == 1 && V > 4 && rel) mbar_arrive(rbar);
  if (V > 0) attn_sum<V - 1>(a, nv);
  if (V == 15) attn_masks(a, wr);
  if (V == 18) {
    attn_shfl<0>(a);
    a.ra = q_row_addr(false, R, wr, fresh_tid() & 31);
  }
  if (V == 19) attn_fin<0>(a);
  uint32_t p[2][4];
  p[0][0] = attn_exp<V, 0>(a);
  p[0][1] = attn_exp<V, 1>(a);
  p[0][2] = attn_exp<V, 2>(a);
  p[0][3] = attn_exp<V, 3>(a);
  p[1][0] = attn_exp<V, 4>(a);
  p[1][1] = attn_exp<V, 5>(a);
  p[1][2] = attn_exp<V, 6>(a);
  p[1][3] = attn_exp<V, 7>(a);
  if (V > 0) {
#pragma unroll
    for (int r = 0; r < 2; r++) p[1][r] ^= (kh ? a.t[r] : __float_as_uint(a.l[hh ^ 1][r])) & a.zero;
  }
#pragma unroll
  for (int k = 0; k < 8; k++) {
    asm volatile("" : "+r"(p[k >> 2][k & 3]));
    a.p[k >> 2][k & 3] = p[k >> 2][k & 3];
  }
  if (!hok) mbar_wait(hbar, hpar);
  wgmma_fence();
  if (V < 18) wgmma_n32_rsz_tb0(a.s[V & 1], q[hh ^ 1][0], d0);
  if (i == 0 && kh == 0) wgmma_n32_rsz_tb1(a.o[hh], a.p[0], d2);
  else wgmma_n32_rs_tb1(a.o[hh], a.p[0], d2, 1);
  if (V < 18) wgmma_n32_rs_tb0(a.s[V & 1], q[hh ^ 1][1], d1, 1);
  wgmma_n32_rs_tb1(a.o[hh], a.p[1], d3, 1);
  wgmma_commit();
}
template <int I>
__device__ __forceinline__ void attn_step(AttnA& a, const uint32_t (&q)[2][2][4], uint64_t dcur, uint64_t dnext, int R, int wr, int nv,
                                          uint32_t hbar, uint32_t hpar, uint32_t rbar, bool rel) {
  attn_unit<4 * I>(a, q, dcur, dnext, R, wr, nv, hbar, hpar, rbar, rel);
  attn_unit<4 * I + 1>(a, q, dcur, dnext, R, wr, nv, hbar, hpar, rbar, rel);
  attn_unit<4 * I + 2>(a, q, dcur, dnext, R, wr, nv, hbar, hpar, rbar, rel);
  attn_unit<4 * I + 3>(a, q, dcur, dnext, R, wr, nv, hbar, hpar, rbar, rel);
}

__device__ __forceinline__ void attention_a(const uint32_t (&q)[2][2][4], int R, int L, int gb, int hp, uint32_t par, int wr,
                                            uint32_t zero) {
  constexpr uint32_t bars = SBASE + OFF_BAR;
  constexpr uint32_t dslot = ((SBASE + OFF_SLOT) >> 4) + 0x10000u;
  auto next = [&](uint64_t d) { return desc_lo((uint32_t)d == dslot ? dslot + 2048 : (uint32_t)d - 1024) + zero; };
  uint64_t d0 = desc_lo(dslot + R * 1024) + zero, d1 = next(d0);
  AttnA a;
  ATS_(0);
  wgmma_fence();
#pragma unroll
  for (int v = 0; v < 2; v++) {
    wgmma_n32_rsz_tb0(a.s[v], q[0][0], d0 + v * 256);
    wgmma_n32_rs_tb0(a.s[v], q[0][1], d0 + (v * 256 + 2), 1);
    wgmma_commit();
  }
  a.zero = zero;
  const bool lane0 = (fresh_tid() & 31) == 0;
  attn_masks(a, wr);
  const int nv = 2 * gb + R;
  const uint32_t hb = bars + 8u * (B_HALO - R), rb = bars + 8u * (B_REL - R);
  attn_step<0>(a, q, d0, d1, R, wr, nv, hb, par, 0, false);
  d0 = next(d1);
  attn_step<1>(a, q, d1, d0, R, wr, nv, R ? bars + 8u * B_HV : hb + 8, par, rb + 8, lane0);
  d1 = next(d0);
  attn_step<2>(a, q, d0, d1, R, wr, nv, hb + 16, par, rb + 16, lane0);
  d0 = next(d1);
  attn_step<3>(a, q, d1, d0, R, wr, nv, hb + 24, par, rb + 24, lane0 && R);
  attn_step<4>(a, q, d0, d0, R, wr, nv, 0, 0, rb, false);
  ATS_(21);
  attn_sum<19>(a, nv);
  attn_shfl<1>(a);
  attn_fin<1>(a);
  ATS_(22);
  if (a.bad != 0u) {
    attn_a_slow(g_kvA[0][0][0], L, gb, hp, a.bad, R * 64 + wr * 8, fresh_tid() & 31);
    named_bar_sync(7, 32);
  }
}

constexpr uint32_t KB_ROW0 = SBASE + OFF_SLOT + 2048, VB_ROW0 = SBASE + OFF_SLOT + 24576 + 2048;

__device__ __forceinline__ void attention_b(const uint32_t (&q)[2][2][4], int R, int gb, uint32_t par0, int wr) {
  constexpr uint32_t bars = SBASE + OFF_BAR;
  const uint32_t dk = ((KB_ROW0 - 2048) >> 4) + 0x10000u + R * 512, dv = dk + ((VB_ROW0 - KB_ROW0) >> 4);
  float s[2][40];
  mbar_wait(bars + 8u * (B_HALO - R), par0);
  wgmma_fence();
#pragma unroll
  for (int hh = 0; hh < 2; hh++) {
    wgmma_n80_rsz_tb0(s[hh], q[hh][0], desc_lo(dk + hh * 4));
    wgmma_n80_rs_tb0(s[hh], q[hh][1], desc_lo(dk + hh * 4 + 2), 1);
  }
  wgmma_commit();
  const int lane = fresh_tid() & 31, g = lane >> 2;
  const bool odd = g & 1, edge = R == 0 && gb == 0 && wr == 0;
  const int D = 2 * (lane & 3) + (g & 1) - g;
  const uint32_t ra = q_row_addr(true, R, wr, lane);
  wgmma_wait<0>();
  reg_fence<40>(s[0]);
  reg_fence<40>(s[1]);
  float z[2][2], y[2][2];
#define GATHER_(W)                                                                                          \
  _Pragma("unroll") for (int hh = 0; hh < 2; hh++) _Pragma("unroll") for (int r = 0; r < 2; r++) {          \
    const float* e = &s[hh][4 * (2 * W + r) + 2 * r];                                                       \
    z[hh][r] = odd ? e[5] : e[4];                                                                           \
    y[hh][r] = D >= 2 ? (odd ? e[1] : e[0]) : (odd ? e[9] : e[8]);                                          \
  }
  if (wr < 2) {
    if (wr == 0) { GATHER_(0) } else { GATHER_(1) }
  } else {
    if (wr == 2) { GATHER_(2) } else { GATHER_(3) }
  }
#undef GATHER_
  float o[2][16], inv[2][2];
  uint32_t p[2][5][4];
  const int sh = odd ? 16 : 0, kb = wr + (D >= 2 ? 0 : 1);
#pragma unroll
  for (int hh = 0; hh < 2; hh++) {
    if (edge) {
      z[hh][0] = -INFINITY;
      if (D >= 2) y[hh][0] = y[hh][1] = -INFINITY;
    }
    uint32_t ab[2][2];
#pragma unroll
    for (int r = 0; r < 2; r++) {
      float m = fmaxf(z[hh][r], y[hh][r]);
      m = fmaxf(m, __shfl_xor_sync(0xffffffffu, m, 1));
      m = fmaxf(m, __shfl_xor_sync(0xffffffffu, m, 2));
      const float e0 = ex2_approx(z[hh][r] - m), e1 = ex2_approx(y[hh][r] - m);
      inv[hh][r] = e0 + e1;
      ab[r][0] = pack_bf16x2(e0, 0.f) << sh;
      ab[r][1] = pack_bf16x2(e1, 0.f) << sh;
    }
#pragma unroll
    for (int k = 0; k < 5; k++) {
      p[hh][k][0] = k == kb ? ab[0][1] : 0u;
      p[hh][k][1] = k == wr + 1 ? ab[1][0] : 0u;
      p[hh][k][2] = k == wr ? ab[0][0] : 0u;
      p[hh][k][3] = k == kb ? ab[1][1] : 0u;
#pragma unroll
      for (int j = 0; j < 4; j++) asm volatile("" : "+r"(p[hh][k][j]));
    }
  }
  wgmma_fence();
#pragma unroll
  for (int hh = 0; hh < 2; hh++) {
    wgmma_n32_rsz_tb1(o[hh], p[hh][0], desc_lo(dv + hh * 4));
#pragma unroll
    for (int k = 1; k < 5; k++) wgmma_n32_rs_tb1(o[hh], p[hh][k], desc_lo(dv + hh * 4 + k * 128), 1);
  }
  wgmma_commit();
#pragma unroll
  for (int hh = 0; hh < 2; hh++)
#pragma unroll
    for (int r = 0; r < 2; r++) {
      inv[hh][r] += __shfl_xor_sync(0xffffffffu, inv[hh][r], 1);
      inv[hh][r] += __shfl_xor_sync(0xffffffffu, inv[hh][r], 2);
      inv[hh][r] = rcp_fast(inv[hh][r]);
    }
  wgmma_wait<0>();
  reg_fence<16>(o[0]);
  reg_fence<16>(o[1]);
  store_o<0>(o[0], inv[0], ra, o_tag(1), true);
  store_o<1>(o[1], inv[1], ra, o_tag(1), true);
}

#define KTQM 0
#define TRICKLE 300
#define QREL 5
#define PRESLEEP 200
#define CSA 5
#define PN1 4
#define PN2 5
#define TLAZY 100
#define SDLY 1500
#define HTS(i) do { } while (0)
struct Params {
  CUtensorMap x[5], xq[4], o, wqkv[2], wqkv3[2], wo3[2];
  const __nv_bfloat16* in_x;
  const __nv_bfloat16* wqkv_p[2];
  const __nv_bfloat16* wo_p[2];
  __nv_bfloat16* out;
  uint32_t zero;
};

__device__ __forceinline__ void colsum_part(const CUtensorMap* wmap, int ty, int qr, int hp) {
  constexpr uint32_t bars = SBASE + OFF_BAR, slots = SBASE + OFF_SLOT;
  PHASE_IDS
  const unsigned ep1 = launch_epoch();
  if (wwarp == 0 && elect_one()) {
    mbar_expect_tx(bars + 8u * B_CS, 6 * UNIT);
#pragma unroll 1
    for (int j = 0; j < 6; j++) {
      if (ty == 0) mbar_pace(bars + 8u * (B_QF + B_E + ((j * CSA / 6) & 3)), (j * CSA / 6) >> 2, j ? PN1 : 30);
      else mbar_wait_lazy<100>(bars + 8u * (B_WF + B_E + ((2 * j + 3 - (j & 1)) & 7)), j >= 3);
      tma_load_2d(slots + j * UNIT, wmap, bars + 8u * B_CS, (j >> 1) * 1024 + hp * 64, qr * 128 + (j & 1) * 64);
    }
  }
  constexpr uint64_t ones = (SBASE + OFF_LSB + 32) >> 4;
  float s[3][4];
  mbar_wait_lazy<100>(bars + 8u * B_CS, ty);
  wgmma_fence();
#pragma unroll
  for (int p = 0; p < 3; p++) {
    wgmma_n8_ssz_ta1_tb0(s[p], make_desc(slots + p * 2 * UNIT, 16), ones);
#pragma unroll
    for (int k = 1; k < 8; k++) wgmma_n8_ss_ta1_tb0(s[p], make_desc(slots + p * 2 * UNIT + k * 2048, 16), ones, 1);
  }
  wgmma_commit();
  wgmma_wait<0>();
  reg_fence<12>(&s[0][0]);
  if (lane == 0) mbar_arrive(bars + 8u * (ty ? B_CSD : B_RDONE));
  if (c == 0) {
#pragma unroll
    for (int r = 0; r < 2; r++) st_rec(&g_cs[ty][hp][qr][wwarp * 16 + 8 * r + g], s[0][2 * r], s[1][2 * r], s[2][2 * r], ep1);
  }
}

__device__ __forceinline__ void put_colsums(int ty, int col, const float4& s) {
  const float v[3] = {s.x, s.y, s.z};
#pragma unroll
  for (int p = 0; p < 3; p++) {
    const uint32_t a = SBASE + OFF_CS + (p * 8 + (col >> 3)) * 64 + ty * 32 + (col & 7) * 2;
    const float hi = bf16_round(v[p]);
    const uint32_t w = pack_bf16x2(hi, v[p] - hi);
    asm volatile("st.shared.b16 [%0], %1;" ::"r"(a), "h"((unsigned short)w) : "memory");
    asm volatile("st.shared.b16 [%0], %1;" ::"r"(a + 16), "h"((unsigned short)(w >> 16)) : "memory");
  }
}

__device__ __forceinline__ uint32_t ln_params(float s1, float s2) {
  const float mean = s1 * (1.0f / DM);
  const float var = fmaxf(fmaf(-mean, mean, s2 * (1.0f / DM)), 0.f);
  float sd;
  asm("sqrt.approx.f32 %0, %1;" : "=f"(sd) : "f"(bf16_round(bf16_round(var) + 1e-5f)));
  return pack_bf16x2(mean, sd);
}

__host__ __device__ constexpr uint32_t w_rel(int kt) { return ((B_WF + (kt & 7)) << 1) | (kt >> 3); }
__host__ __device__ constexpr uint32_t w_rel4(int a, int b, int c, int d) { return w_rel(a) | (w_rel(b) << 8) | (w_rel(c) << 16) | (w_rel(d) << 24); }
__device__ __forceinline__ void ring_wait(uint32_t e) { mbar_wait(SBASE + OFF_BAR + 8u * B_E + ((e << 2) & 0x3f8u), e & 1u); }
struct RingProd {
  uint32_t rel = ((B_QF << 1) | 1) * 0x01010101u + 0x06040200u;
  __device__ __forceinline__ void q_step(int kt) {
    const int sh = 8 * (kt & 3);
    const uint32_t e = rel >> sh;
    rel ^= ((e ^ (((B_QF + (kt & 3)) << 1) | ((kt >> 2) & 1))) & 255u) << sh;
    ring_wait(e);
  }
  __device__ __forceinline__ void w_job(int st, bool pre, uint32_t sel0, uint32_t sel1, uint32_t last, uint32_t& w0, uint32_t& w1) {
    const uint32_t r = __funnelshift_r(rel, rel, 8 * st);
    w0 = __byte_perm(r, 0u, sel0);
    w1 = __byte_perm(r, w_rel4(0, 1, 2, 3), pre ? sel1 : 0x6543u);
    const uint32_t n = pre ? (w_rel4(9, 11, 13, 0) & 0xffffffu) | (last << 24) : (w_rel4(11, 13, 0, 15) & 0xff00ffffu) | (last << 16);
    rel = __funnelshift_l(n, n, 8 * st);
  }
};

#define SP1 15
#define SP2 13
#define SP3 11
#define SP4 11
#define SP5 15
#define SP6 13
#define SP7 16
__device__ __forceinline__ int q_split(int inst) {
  constexpr uint32_t T = 15u | ((SP1 - 1) << 4) | ((SP2 - 1) << 8) | ((SP3 - 1) << 12) | ((SP4 - 1) << 16) | ((SP5 - 1) << 20) |
                         ((SP6 - 1) << 24) | ((uint32_t)(SP7 - 1) << 28);
  return (int)((T >> (4 * inst)) & 15u) + 1;
}
#define QROT 4
#define WROT 2
__device__ __forceinline__ int qk(int kt) { return (kt + QROT) & 15; }
__device__ __forceinline__ int wk(int kt) { return (kt + WROT) & 15; }
__host__ __device__ constexpr uint32_t turn_par(int kind) {
  const int sp[8] = {16, SP1, SP2, SP3, SP4, SP5, SP6, SP7};
  int cnt[2] = {0, 0};
  uint32_t m = 0;
  for (int i = 0; i < 8; i++)
    for (int k = 0; k < 3; k++) {
      if (k == kind) m |= (uint32_t)(cnt[i & 1] & 1) << i;
      if (k == 0 ? (i == 1 || (i > 1 && sp[i - 1] < 16)) : (k == 2 || sp[i] < 16)) cnt[i & 1]++;
    }
  return m;
}
#define PREMASK 0xBFu
__device__ __forceinline__ bool w_pre(int inst) { return (PREMASK >> inst) & 1u; }
#define STGMASK 0x2Eu
__device__ __forceinline__ bool w_stg(int inst) { return (STGMASK >> inst) & 1u; }
__device__ __forceinline__ uint32_t w_out(int inst) {
  return w_stg(inst) ? SBASE + OFF_SLOT : SBASE + (((inst < 7 ? q_split(inst + 1) : 0) + (w_pre(inst) ? 3 : 2)) & 3) * 5 * UNIT;
}
__host__ __device__ constexpr unsigned long long bar_counts(int i0) {
  unsigned long long t = 0;
  for (int i = i0; i < i0 + 32; i++) {
    int l = 0;
    if (i < B_RF) l = 1;
    if ((i >= B_E && i < B_E + B_RF) || i == B_LOC || i == B_REL || i == B_OS0 || i == B_TURN || i == B_TURN + 1 || i == B_XS ||
        i == B_XS + 1 || i == B_CSD || i == B_GO || i == B_RDONE || i == B_KV)
      l = 2;
    if (i == B_REL + 1 || i == B_REL + 2) l = 3;
    t |= (unsigned long long)l << (2 * (i - i0));
  }
  return t;
}

__global__ void __launch_bounds__(512, 1) fused_kernel(const __grid_constant__ Params P) {
  extern __shared__ __align__(1024) uint8_t smem_raw[];
  constexpr uint32_t base = SBASE, bars = base + OFF_BAR, slots = base + OFF_SLOT;
  if (smem_u32(smem_raw) != base) __trap();
  const int warp = __shfl_sync(0xffffffffu, threadIdx.x >> 5, 0), lane = threadIdx.x & 31;
  const int b = blockIdx.x;
#define QS 1
#define WS 1
  const int qr = ((b & ((8 << QS) - 1)) >> QS) ^ (((b >> (3 + QS)) & 1) * 7);
  const int hp = ((b >> (3 + QS)) << QS) + (b & ((1 << QS) - 1));
  const int rt = ((b & ((16 << WS) - 1)) >> WS) ^ (((b >> (4 + WS)) & 1) * 15);
  const int ct = ((b >> (4 + WS)) << WS) + (b & ((1 << WS) - 1));

  if (warp == 12) {
    if (elect_one()) {
#pragma unroll 1
      for (int s = 0; s < 4; s++) {
        const uint32_t fb = bars + 8u * (B_QF + s), sa = base + s * 5 * UNIT;
        mbar_init(fb, 2);
        fence_barrier_init();
        mbar_expect_tx(fb, 5 * UNIT);
        mbar_arrive(fb);
        tma_load_5d(sa + 3 * UNIT, &P.xq[0], fb, s * 64, qr * 2);
        tma_load_3d(sa, &P.wqkv3[0], fb, hp * 64, s * 64);
      }
    }
    __syncwarp();
  } else if (warp >= 4 && warp < 12) {
    if (elect_one()) {
#pragma unroll 1
      for (int i = warp; i <= B_KV; i += 8) mbar_init(bars + 8u * i, 1u << (((i < 32 ? bar_counts(0) : bar_counts(32)) >> (2 * (i & 31))) & 3u));
      sts32(warp < 8 ? base + OFF_ONE - 16 + 4 * warp : base + OFF_LSB + 4 * warp, warp < 8 ? warp == 4 : 0x3f803f80u);
      fence_proxy_async_smem();
      fence_barrier_init();
    }
    __syncwarp();
  }

  if (warp >= 12) {
    setmaxnreg_dec<32>();
    if (warp == 12) {
      named_bar_sync(0, 512);
      if (elect_one()) {
#pragma unroll 1
        for (int s = 4; s < 16; s++) {
          const uint32_t fb = bars + 8u * (B_QF + (s & 3)), sa = base + (s & 3) * 5 * UNIT;
          mbar_wait(fb + 8u * B_E, ((s >> 2) & 1) ^ 1);
          mbar_expect_tx(fb, 5 * UNIT);
          mbar_arrive(fb);
          tma_load_5d(sa + 3 * UNIT, &P.xq[0], fb, s * 64, qr * 2);
          tma_load_3d(sa, &P.wqkv3[0], fb, hp * 64, s * 64);
        }
#pragma unroll
        for (int s = 0; s < 4; s++) mbar_arrive(bars + 8u * B_GO);
        RingProd rp;
#pragma unroll 1
        for (int sg = 4; sg < 34; sg++) {
          const int part = sg & 3, inst = (sg >> 2) - (part & 1);
          if (part == 3 || inst == 8) continue;
          const int ty = (inst >> 1) & 1;
          if (part != 1) {
            const int k0 = part ? q_split(inst) : 0, k1 = part ? 16 : q_split(inst);
#pragma unroll 1
            for (int kt = k0; kt < k1; kt++) {
              const uint32_t sa = base + (kt & 3) * 5 * UNIT, fb = bars + 8u * (B_QF + (kt & 3));
              rp.q_step(kt);
              mbar_expect_tx(fb, 3 * UNIT);
              tma_load_3d(sa, &P.wqkv3[ty], fb, hp * 64, qk(kt) * 64);
            }
          } else {
            const bool pre = w_pre(inst);
            int st = inst < 7 ? q_split(inst + 1) & 3 : 0;
            uint32_t w0, w1;
            rp.w_job(st, pre, pre ? 0x1100u : 0x2100u, 0x3322u, w_stg(inst) ? w_rel(15) : (B_RF << 1) | (inst & 1), w0, w1);
#pragma unroll 1
            for (int m = 0; m < 4; m++) {
              const uint32_t fb = bars + 8u * (B_WF + 4 * (m & 1));
#pragma unroll
              for (int i = 0; i < 4; i++) {
                if (i < 3 || !pre) {
                  ring_wait(w0 >> (8 * i));
                  mbar_expect_tx(fb + 8u * i, 2 * UNIT);
                  tma_load_3d(base + ((st + (i ? i - 1 : 0)) & 3) * 5 * UNIT + ((0x2d >> (2 * i)) & 3) * UNIT, &P.wo3[ty], fb + 8u * i,
                              ct * 128, wk(4 * m + i) * 64);
                }
              }
              st += pre ? 2 : 3;
              w0 = w1;
              w1 = m == 0 ? (pre ? w_rel4(0, 1, 2, 3) : w_rel4(3, 4, 5, 6)) : (pre ? w_rel4(4, 5, 6, 7) : w_rel4(7, 8, 9, 10));
            }
          }
        }
      }
    } else if (warp == 13) {
      RingProd rp;
      unsigned ep1 = 0;
      uint32_t seenx = 0;
      named_bar_sync(0, 512);
      mbar_wait(bars + 8u * B_GO, 0);
#pragma unroll 1
      for (int sg = 4; sg < 34; sg++) {
        const int part = sg & 3, inst = (sg >> 2) - (part & 1);
        if (part == 3 || inst == 8) continue;
        const int L = inst >> 1, ch = inst & 1;
        if (part != 1) {
          const CUtensorMap* tx = &P.xq[L];
          const int k0 = part ? q_split(inst) : 0, k1 = part ? 16 : q_split(inst);
          if (sg == 4) ep1 = launch_epoch();
          if (part == 0) seenx = L == 0 ? 0xffffffffu : peek_counts(g_fx[ch * 8 + qr][0], 6u * ep1 - 6u + 2u * L, lane);
          const int m0 = ch * 16 + qr * 2;
#pragma unroll 1
          for (int kt = k0; kt < k1; kt++) {
            const uint32_t fb = bars + 8u * (B_QF + (kt & 3));
            rp.q_step(kt);
            if (lane == 0) mbar_expect_tx(fb, 2 * UNIT);
            wait_count(g_fx[ch * 8 + qr][0], 6u * ep1 - 6u + 2u * L, qk(kt), seenx, lane);
            TGET(t38);
            if (elect_one()) tma_load_5d(base + ((kt & 3) * 5 + 3) * UNIT, tx, fb, qk(kt) * 64, m0);
            TGET(t39);
            if (L == 3 && kt == 0 && lane == 0) { TPUT(ch, 38, t38); TPUT(ch, 39, t39); }
          }
        } else {
          const int m0 = ch * 1024 + rt * 64;
          const bool pre = w_pre(inst);
          int st = inst < 7 ? q_split(inst + 1) & 3 : 0;
          uint32_t w0, w1;
          uint32_t seen = peek_counts(g_fo[ch * 16 + rt][0], 4u * ep1 - 3u + L, lane);
          rp.w_job(st, pre, 0x1110u, 0x3332u, inst == 6 && SP7 == 16 ? B_RF << 1 : w_rel(15), w0, w1);
#pragma unroll 1
          for (int m = 0; m < 4; m++) {
            const uint32_t fb = bars + 8u * (B_WF + 4 * (m & 1));
#pragma unroll
            for (int i = 0; i < 4; i++) {
              ring_wait(w0 >> (8 * i));
              if (lane == 0) mbar_expect_tx(fb + 8u * i, UNIT);
              wait_count(g_fo[ch * 16 + rt][0], 4u * ep1 - 3u + L, wk(4 * m + i), seen, lane);
              if (elect_one())
                tma_load_2d(base + ((st + (i > 0)) & 3) * 5 * UNIT + (i == 2 ? 1 : (i == 3 ? 4 : 0)) * UNIT, &P.o, fb + 8u * i, wk(4 * m + i) * 64, m0);
            }
            st += pre ? 2 : 3;
            w0 = w1;
            w1 = m == 0 ? (pre ? w_rel4(0, 1, 2, 3) : w_rel4(3, 4, 5, 6)) : (pre ? w_rel4(4, 5, 6, 7) : w_rel4(7, 8, 9, 10));
          }
          if (L == 3) {
#pragma unroll 1
            for (int j = 0; j < 4; j++) {
              g_x[(size_t)(m0 + j * 16 + (lane >> 1)) * DM + ct * 128 + (lane & 1) * 64] = __ushort_as_bfloat16(0);
              __syncwarp();
            }
          }
        }
      }
    } else if (warp == 14) {
      const unsigned ep1 = launch_epoch();
      uint32_t hpar = 0;
      named_bar_sync(0, 512);
#pragma unroll 1
      for (int inst = 0; inst < 8; inst++) {
        const int L = inst >> 1, ch = inst & 1, gb = ch * 8 + qr;
        const unsigned kv0 = 8u * ep1 - 8u + 2u * L + (L & 1);
        const uint32_t tag = kv_tag(L);
        if (L >= 2) {
#pragma unroll 1
          for (uint32_t it = 0; it < (1u << 17); ++it)
            if (__all_sync(0xffffffffu, (int)(ld_relaxed_u32(g_fk[hp][min(gb + 1 + (lane & 1), 15)]) - kv0) >= 0)) break;
        }
        if ((L & 1) == 0) {
          uint8_t* img = g_kvA[gb][hp][0];
          const uint8_t* s1 = gb > 0 ? img - 16 * 32768 : g_zero;
          const uint8_t* s2 = gb > 1 ? img - 32 * 32768 : g_zero;
          const uint32_t h1 = gb > 0 ? 16384 : 0, h2 = gb > 1 ? 16384 : 0;
          const unsigned* cp = g_fk[hp][max(gb - 1 - (lane >= 3), 0)];
          const unsigned ct0 = kv0 + ((0x32321u >> (4 * (lane & 7))) & 3u);
          uint32_t fr = gb == 0 ? 31u : (gb == 1 ? 24u : 0u);
          const uint32_t toff = slots + lane * 128 + ((lane & 7) << 4);
          auto seen = [&](uint32_t m) {
#pragma unroll 1
            for (uint32_t it = 0; it < (1u << 17) && !(fr & m); ++it)
              fr |= __ballot_sync(0xffffffffu, (int)(ld_relaxed_u32(cp) - ct0) >= 0);
          };
          auto load = [&](uint32_t off, const uint8_t* src, uint32_t bytes, int bi) {
            if (elect_one()) {
              mbar_expect_tx(bars + 8u * (B_HL + bi), bytes);
              bulk_load(slots + off, src, bytes, bars + 8u * (B_HL + bi));
            }
          };
          auto check = [&](uint32_t off, const uint8_t* src, uint32_t bytes, int bi, bool real, int done) {
#pragma unroll 1
            for (int tries = 0; tries < 4096; tries++) {
              mbar_wait(bars + 8u * (B_HL + bi), (hpar >> bi) & 1u);
              hpar ^= 1u << bi;
              uint32_t t = (lds32(toff + off) ^ tag) | (lds32(toff + off + 4096) ^ tag);
              if (bytes > 8192) t |= (lds32(toff + off + 8192) ^ tag) | (lds32(toff + off + 12288) ^ tag);
              if (!__any_sync(0xffffffffu, real && (t & 1u))) break;
              fence_proxy_async_smem();
              load(off, src, bytes, bi);
            }
            if (lane == 0) mbar_arrive(bars + 8u * done);
          };
          uint8_t *pk = img + 16384, *pv = img + 24576;
          unsigned* f = g_fk[hp][gb];
          pin64(pk), pin64(pv), pin64(f);
          mbar_wait(bars + 8u * B_KV, inst & 1);
          if (elect_one()) {
            bulk_store(pk, slots + 16384, 8192);
            bulk_announce(f);
            bulk_store(pv, slots + 24576, 8192);
            bulk_announce(f);
            bulk_commit();
          }
          HTS(44);
          seen(1);
          HTS(46);
          load(32768, s1 + h1, 8192, 0);
          seen(2);
          HTS(47);
          load(40960, s1 + h1 + 8192, 8192, 1);
          mbar_wait(bars + 8u * B_LOC, inst & 1);
          HTS(45);
          if (elect_one()) {
            bulk_store(img, slots, 16384);
            bulk_announce(g_fk[hp][gb]);
            bulk_commit();
            asm volatile("cp.async.bulk.wait_group.read 1;" ::: "memory");
          }
          check(32768, s1 + h1, 8192, 0, gb > 0, B_HALO);
          HTS(52);
          check(40960, s1 + h1 + 8192, 8192, 1, gb > 0, B_HV);
          HTS(53);
#pragma unroll 1
          for (int n = 1; n < 4; n++) {
            const uint8_t* src = n == 1 ? s1 : (n == 2 ? s2 + h2 : s2);
            const uint32_t off = n == 3 ? 32768 : 32768 - n * 16384;
            seen(2u << n);
            if (n == 2 && elect_one()) bulk_wait_read0();
            mbar_wait(bars + 8u * (B_REL - 1) + 8u * n, ch);
            HTS(47 + n);
            load(off, src, 16384, 0);
            check(off, src, 16384, 0, gb > (n >> 1), B_HALO + n);
            HTS(53 + n);
          }
        } else {
          uint8_t *pk = g_kvB[gb][hp], *pv = pk + 2048;
          const uint8_t* src = gb >= 1 ? pk - 16 * 4096 : g_zero;
          unsigned* f = g_fk[hp][gb];
          pin64(pk), pin64(pv), pin64(f), pin64(src);
          mbar_wait(bars + 8u * B_KV, inst & 1);
          if (elect_one()) {
            bulk_store(pk, KB_ROW0 + 112 * 128, 2048);
            bulk_store(pv, VB_ROW0 + 112 * 128, 2048);
            bulk_announce(f);
            bulk_commit();
          }
          HTS(44);
          if (gb > 0) {
#pragma unroll 1
            for (uint32_t it = 0; it < (1u << 17); ++it)
              if (__any_sync(0xffffffffu, (int)(ld_relaxed_u32(f - 4) - kv0) > 0)) break;
          }
          HTS(46);
#pragma unroll 1
          for (uint32_t it = 0; it < (1u << 17); ++it) {
            if (elect_one()) {
              mbar_expect_tx(bars + 8u * B_HL, 4096);
              bulk_load(KB_ROW0 - 2048, src, 2048, bars + 8u * B_HL);
              bulk_load(VB_ROW0 - 2048, src + 2048, 2048, bars + 8u * B_HL);
            }
            mbar_wait(bars + 8u * B_HL, hpar & 1u);
            hpar ^= 1u;
            const uint32_t t = lds32((lane < 16 ? KB_ROW0 - 2048 : VB_ROW0 - 4096) + lane * 128 + ((lane & 7) << 4)) ^ tag;
            if (!__any_sync(0xffffffffu, gb > 0 && (t & 1u))) break;
            fence_proxy_async_smem();
          }
          if (lane == 0) mbar_arrive(bars + 8u * B_HALO);
          HTS(52);
        }
        if (elect_one()) {
          const CUtensorMap* mo = &P.o;
          unsigned *f1 = g_fo[gb * 2 + 1][hp], *f0 = g_fo[gb * 2][hp];
          int c0 = hp * 64, r0 = gb * 128, r1 = r0 + 64;
          pin64(mo), pin64(f1), pin64(f0);
          asm volatile("" : "+r"(c0), "+r"(r0), "+r"(r1));
          mbar_wait(bars + 8u * B_OS1, (inst & 1) ^ 1);
          tma_store_2d(mo, slots + 7 * UNIT, c0, r1);
          bulk_announce(f1);
          bulk_commit();
          mbar_wait(bars + 8u * B_OS0, inst & 1);
          tma_store_2d(mo, slots + 6 * UNIT, c0, r0);
          bulk_announce(f0);
          bulk_commit();
          HTS(57);
          const bool pre = w_pre(inst);
          bulk_wait_read0();
          HTS(58 - 15);
          mbar_expect_tx(bars + 8u * B_RF, 2 * UNIT);
          tma_load_2d(slots + 6 * UNIT, &P.x[L], bars + 8u * B_RF, ct * 128, ch * 1024 + rt * 64);
          tma_load_2d(slots + 7 * UNIT, &P.x[L], bars + 8u * B_RF, ct * 128 + 64, ch * 1024 + rt * 64);
          if (pre) {
            const uint32_t pp = __popc(PREMASK & ((1u << inst) - 1u)) & 1;
            mbar_expect_tx(bars + 8u * B_PRE, 2 * UNIT);
            mbar_expect_tx(bars + 8u * B_PRE2, 6 * UNIT);
#pragma unroll 1
            for (int j = 0; j < 4; j++) {
              __nanosleep(PRESLEEP);
              if (j == 3) mbar_wait(bars + 8u * B_RDONE, (inst & 1) ^ 1);
              tma_load_3d(slots + j * 2 * UNIT, &P.wo3[L & 1], bars + 8u * (j ? B_PRE2 : B_PRE), ct * 128, wk(4 * j + 3) * 64);
            }
#pragma unroll 1
            for (int j = 0; j < 4; j++) {
              const uint32_t fb = bars + 8u * (B_WF + 3 + 4 * (j & 1));
              if (j < 2) mbar_wait(bars + 8u * (j ? B_PRE2 : B_PRE), pp);
              if (j < 2 && inst == 7 && SP7 == 16) mbar_wait(bars + 8u * (B_TURN + 1), (turn_par(2) >> 7) & 1u);
              mbar_wait(fb + 8u * B_E, j < 2);
              mbar_arrive(fb);
            }
          }
        }
        __syncwarp();
      }
    } else {
      const unsigned ep1 = launch_epoch();
      named_bar_sync(0, 512);
      mbar_wait(bars + 8u * B_GO, 0);
#pragma unroll 1
      for (int i = 0; i < 20; i++) {
        const char* src = i < 4 ? reinterpret_cast<const char*>(P.wo_p[0]) + (size_t)b * 16384 + i * 4096
                                : (i < 16 ? reinterpret_cast<const char*>(P.wqkv_p[1]) + (size_t)b * 49152 + (i - 4) * 4096
                                          : reinterpret_cast<const char*>(P.wo_p[1]) + (size_t)b * 16384 + (i - 16) * 4096);
        asm volatile("prefetch.global.L2 [%0];" ::"l"(src + lane * 128));
        __nanosleep(TRICKLE);
      }
#pragma unroll 1
      for (int inst = 2; inst < 10; inst++) {
        const int L = inst >> 1, ch = inst & 1, gb = ch * 8 + qr;
        {
          uint32_t xb = w_out(inst - 2);
          unsigned* f = g_fx[ch * 8 + (rt >> 1)][ct * 2];
          const CUtensorMap* mx = &P.x[L];
          int c0 = ct * 128, r0 = ch * 1024 + rt * 64;
          pin64(f), pin64(mx);
          asm volatile("" : "+r"(xb), "+r"(c0), "+r"(r0));
#pragma unroll
          for (int h = 0; h < 2; h++) {
            mbar_wait(bars + 8u * (B_XS + h), ch);
            if (elect_one()) {
              tma_store_2d(mx, xb + h * UNIT, c0 + h * 64, r0);
              if (L < 4) bulk_announce(f + 4 * h);
              bulk_commit();
              if (h == 1) {
                bulk_wait_read0();
                mbar_arrive(bars + 8u * (B_RF + B_E));
              }
            }
          }
          if (L == 4) continue;
          __nanosleep(SDLY);
        }
#pragma unroll 1
        for (int h = 0; h < 4; h++) {
          const float4* sp = &g_stats[0][gb * 128 + h * 32 + lane];
          const float4 s0 = sum_recs<4>(sp, S_LEN, 4u * ep1 + L), s1 = sum_recs<4>(sp + 4 * S_LEN, S_LEN, 4u * ep1 + L);
          sts32(base + OFF_RS + (ch * 128 + h * 32 + lane) * 4, ln_params(s0.x + s1.x, s0.y + s1.y));
        }
        if (inst == 2) {
#pragma unroll 1
          for (int hf = 0; hf < 2; hf++) {
            const float4* cp = &g_cs[1][hp][0][hf * 32 + lane];
            const float4 s0 = sum_recs<4>(cp, 64, ep1), s1 = sum_recs<4>(cp + 4 * 64, 64, ep1);
            put_colsums(1, hf * 32 + lane, make_float4(s0.x + s1.x, s0.y + s1.y, s0.z + s1.z, 0.f));
          }
        }
        fence_proxy_async_smem();
        __syncwarp();
        if (lane == 0) mbar_arrive(bars + 8u * (B_PREP + ch));
      }
    }
  } else {
    const bool asst = warp >= 8;
    GTL(0);
    if (warp >= 4) named_bar_sync(0, 512);
    if (warp >= 4 && !asst) {
      PHASE_IDS
      {
        const unsigned ep1 = launch_epoch();
        const int row = b * 16 + (tid >> 3);
        const uint4* src = reinterpret_cast<const uint4*>(P.in_x + (size_t)row * DM) + (tid & 7);
        float s1 = 0.f, s2 = 0.f;
#pragma unroll 1
        for (int k = 0; k < 4; k++) {
          mbar_pace(bars + 8u * (B_QF + B_E + ((2 * k) & 3)), k >> 1, k ? PN2 : 30);
          uint4 v[4];
#pragma unroll
          for (int j = 0; j < 4; j++) v[j] = __ldg(src + (k * 4 + j) * 8);
#pragma unroll
          for (int j = 0; j < 4; j++) {
            const uint32_t w[4] = {v[j].x, v[j].y, v[j].z, v[j].w};
#pragma unroll
            for (int e = 0; e < 4; e++) {
              const float x0 = bf_lo(w[e]), x1 = bf_hi(w[e]);
              s1 += x0 + x1;
              s2 = fmaf(x0, x0, fmaf(x1, x1, s2));
            }
          }
        }
#pragma unroll
        for (int o = 1; o < 8; o <<= 1) {
          s1 += __shfl_xor_sync(0xffffffffu, s1, o);
          s2 += __shfl_xor_sync(0xffffffffu, s2, o);
        }
        if ((tid & 7) == 0) st_rec(&g_stats[0][row], s1, s2, 0.f, 4u * ep1);
        if (tid == 0) sts32(base + OFF_EPOCH, ep1);
        if (tid < 64) {
          const float4 s0 = sum_recs<8>(&g_cs[0][hp][0][tid], 64, ep1);
          put_colsums(0, tid, s0);
        } else {
          put_colsums(1, tid - 64, make_float4(0.f, 0.f, 0.f, 0.f));
        }
#pragma unroll 1
        for (int cc = 0; cc < 2; cc++) {
          const float4 s0 = sum_recs<1>(&g_stats[0][(cc * 8 + qr) * 128 + tid], 0, 4u * ep1);
          sts32(base + OFF_RS + (cc * 128 + tid) * 4, ln_params(s0.x, s0.y));
        }
        fence_proxy_async_smem();
        named_bar_sync(2, 128);
        if (tid < 2) mbar_arrive(bars + 8u * (B_PREP + tid));
      }
    }
#pragma unroll 1
    for (int inst = asst ? 0 : warp >> 2; inst < 8; inst += asst ? 1 : 2) {
      const int L = inst >> 1, ch = inst & 1, gb = ch * 8 + qr;
      uint32_t q[2][2][4];
      if (asst) {
        if (inst < 2) colsum_part(&P.wqkv[inst], inst, qr, hp);
        setmaxnreg_dec<24>();
        named_bar_sync(4, 256);
        setmaxnreg_inc<128>();
        const uint32_t ra = q_row_addr(L & 1, 1, warp & 3, fresh_tid() & 31);
#pragma unroll
        for (int j = 0; j < 4; j++) ldmatrix_x4(q[j >> 1][j & 1], ra ^ (j << 5));
      } else {
      setmaxnreg_inc<224>();
      {
        float acc[2][96];
        const int ksp = q_split(inst);
        constexpr uint32_t STG = 5 * (UNIT >> 4), D0 = ((base + 3 * UNIT) >> 4) + 0x10000u;
        constexpr uint32_t DB = ((UNIT >> 4) << 16) - 0x10000u - 3 * (UNIT >> 4);
        const uint32_t toff = ((fresh_tid() & 127) << 7) + ((fresh_tid() & 7) << 4);
        const bool lane0 = (toff & 0xf80u) == 0u;
        uint32_t xt = x_tag(L), tro = (warp & 3) * 2048 + (toff & 0x7f0u) + ((toff << 2) & 0x2000u);
        auto check_x = [&](uint32_t bar, uint32_t par, uint32_t ta, int kt, uint32_t mask) {
          fix_lines(bar, par, ta, xt, mask, 7, [&](int l) {
            return g_x + (size_t)(gb * 128 + (l >> 4) * 64 + tile_row(L & 1, warp & 3, (l >> 3) & 1, l & 7)) * DM + qk(kt) * 64;
          });
        };
        uint32_t rsa = base + OFF_RS + (ch * 128 + tile_row(L & 1, warp & 3, 0, (toff >> 9) & 7)) * 4;
        uint32_t rsb = rsa + ((L & 1) ? 32 : 128);
        uint32_t lnm = ((toff >> 7) & 3) == (L & 1) ? 0xffffffffu : 0u, tmk = L > 0;
        uint32_t soff = tile_row(L & 1, warp & 3, (toff >> 10) & 1, (toff >> 7) & 7) * 128 + ((toff ^ (toff >> 7)) & 0x10u) + (toff & 0x60u);
        uint32_t bprep = bars + 8u * (B_PREP + ch), bturn = bars + 8u * (B_TURN + (ch ^ 1));
        const bool stg = inst > 0 && w_stg(inst - 1);
        uint32_t bfree = bars + 8u * (inst == 1 ? B_CSD : (stg ? B_RF + B_E : B_RDONE));
        uint32_t pfree = inst == 1 ? 0 : (inst & 1) ^ stg, pprep = L & 1;
        asm volatile("" : "+r"(rsa), "+r"(rsb), "+r"(lnm), "+r"(soff), "+r"(xt), "+r"(tmk), "+r"(tro));
        asm volatile("" : "+r"(bprep), "+r"(bturn), "+r"(bfree), "+r"(pfree), "+r"(pprep));
        if (inst == 0) named_bar_sync(0, 512);
        if (inst == 1 || (inst > 1 && q_split(inst - 1) < 16)) mbar_wait_lazy<TLAZY>(bars + 8u * (B_TURN + ch), (turn_par(0) >> inst) & 1u);
        if (L == 3) GTL(37);
        check_x(bars + 8u * B_QF, 0, base + 3 * UNIT + tro, 0, tmk);
        GTL(1 + L * 8);
        {
          const uint64_t da = desc_lo(D0) + P.zero;
          wgmma_fence();
          wgmma_n192_ssz_ta0_tb1(acc[1], da + (UNIT >> 4), da + DB);
          wgmma_commit();
          wgmma_n192_ssz_ta0_tb1(acc[0], da, da + DB);
          wgmma_commit();
        }
        int left = ksp;
        asm volatile("" : "+r"(left));
        uint64_t da = desc_lo(D0) + P.zero, dn = da + STG;
        uint32_t fn = bars + 8u * (B_QF + 1), pn = 0, ta = base + 8 * UNIT + tro;
#pragma unroll 1
        for (int kt = 0; kt < 15; kt++) {
          bool ok, last;
          uint32_t tw;
#pragma unroll
          for (int k16 = 0; k16 < 4; k16++) {
            if (k16 == 0 && kt == 0) continue;
            wgmma_fence();
            wgmma_n192_ss_ta0_tb1(acc[1], da + ((UNIT >> 4) + k16 * 2), da + (DB + k16 * 128), 1);
            wgmma_commit();
            if (k16 == 0) {
              const int s1 = (kt + 1) & 3;
              dn = desc_lo(D0 + s1 * STG) + P.zero;
              ta = base + 3 * UNIT + s1 * 5 * UNIT + tro;
            }
            if (k16 == 1) last = --left == 0;
            if (k16 == 3) ok = !__any_sync(0xffffffffu, !ok || ((tw ^ xt) & tmk)) && !last;
            wgmma_wait<1>();
            if (k16 == 0 && lane0 && left != 0) mbar_arrive(bars + 8u * (B_QF + B_E + ((kt - 1) & 3)));
            wgmma_fence();
            wgmma_n192_ss_ta0_tb1(acc[0], da + k16 * 2, da + (DB + k16 * 128), 1);
            wgmma_commit();
            if (k16 == 0) {
              fn = bars + 8u * (B_QF + ((kt + 1) & 3));
              pn = ((kt + 1) >> 2) & 1;
            }
            if (k16 == 2) {
              ok = mbar_test(fn, pn);
              tw = lds32(ta);
              if (last && lane0) mbar_arrive(bturn);
            }
            if (k16 < 3) wgmma_wait<1>();
          }
          da = dn;
          if (!ok) {
            if (last) {
              wgmma_wait<0>();
              if (lane0) mbar_arrive(bars + 8u * (B_QF + B_E + (kt & 3)));
            }
            if (last) mbar_wait_lazy<TLAZY>(bars + 8u * (B_TURN + ch), (turn_par(1) >> inst) & 1u);
            check_x(fn, pn, ta, kt + 1, tmk);
          }
        }
        constexpr uint32_t DL = D0 + 3 * STG;
        wgmma_fence();
#pragma unroll
        for (int k16 = 0; k16 < 4; k16++) wgmma_n192_ss_ta0_tb1(acc[1], desc_lo(DL + (UNIT >> 4) + k16 * 2), desc_lo(DL + DB + k16 * 128), 1);
        wgmma_commit();
        mbar_wait(bprep, pprep);
        uint32_t rs[2][2];
        constexpr uint64_t DCS = (uint64_t)((base + OFF_CS) >> 4) | (4ull << 32);
        auto ln_mma = [&](float (&d)[96], uint32_t (&r)[2], int h) {
          uint32_t a[4];
#pragma unroll
          for (int i = 0; i < 2; i++) {
            if (h) r[i] = lds32((i ? rsb : rsa) + 256);
            a[i] = (__byte_perm(r[i], 0u, 0x1010) ^ 0x80008000u) & lnm;
            a[i + 2] = r[i] & P.zero;
          }
#pragma unroll
          for (int i = 0; i < 4; i++) asm volatile("" : "+r"(a[i]));
          wgmma_fence();
          wgmma_n192_rs_tb1(d, a, DCS, 1);
          wgmma_commit();
        };
        ln_mma(acc[1], rs[1], 1);
        wgmma_wait<2>();
        if (lane0 && ksp != 15) mbar_arrive(bars + 8u * (B_QF + B_E + 2));
        wgmma_fence();
#pragma unroll
        for (int k16 = 0; k16 < 4; k16++) wgmma_n192_ss_ta0_tb1(acc[0], desc_lo(DL + k16 * 2), desc_lo(DL + DB + k16 * 128), 1);
        wgmma_commit();
        if (lane0) mbar_arrive(bturn);
        rs[0][0] = lds32(rsa);
        rs[0][1] = lds32(rsb);
        static_assert(SP1 < 16 && (PREMASK & 1u) && !(STGMASK & 1u), "column sums of B");
        const bool afree = mbar_test(bfree, pfree) & (mbar_test(bars + 8u * (B_WF + B_E + 7), 1) | (ksp == 16));
        float rinv[2];
#pragma unroll
        for (int r = 0; r < 2; r++) {
          rinv[r] = rcp_fast(bf_hi(rs[1][r]));
          asm volatile("" : "+f"(rinv[r]));
        }
        const uint32_t kdst = ((L & 1) ? KB_ROW0 : slots) + soff, vdst = ((L & 1) ? VB_ROW0 : slots + 8192) + soff;
        const uint32_t hs = (L & 1) ? 8192 : 16384, c0 = (toff & 0x180u) == 0u;
        wgmma_wait<1>();
        ln_mma(acc[0], rs[0], 0);
        reg_fence<96>(acc[1]);
        GTL(2 + L * 8);
        if (!afree) {
          mbar_wait(bfree, pfree);
          if (ksp < 16) mbar_wait(bars + 8u * (B_WF + B_E + 7), 1);
        }
#pragma unroll
        for (int t = 0; t < 24; t++) {
          const int h = t < 12 ? 1 : 0, p = ((t % 12) / 4 + 1) % 3, jp = t & 3;
          if (t == QREL) {
            wgmma_wait<0>();
            reg_fence<96>(acc[0]);
            if (lane0) mbar_arrive(bars + 8u * (B_QF + B_E + 3));
          }
          if (t == 8 || t == 20) {
            rinv[0] *= SM_C;
            rinv[1] *= SM_C;
          }
          const float* a = &acc[h][4 * (p * 8 + 2 * jp)];
          uint32_t r0 = pack_bf16x2(a[0] * rinv[0], a[1] * rinv[0]);
          uint32_t r1 = pack_bf16x2(a[2] * rinv[1], a[3] * rinv[1]);
          if (p != 0 && jp == 0) {
            r0 = set_tag(r0, c0, kv_tag(L));
            r1 = set_tag(r1, c0, kv_tag(L));
          }
          const uint32_t r2 = pack_bf16x2(a[4] * rinv[0], a[5] * rinv[0]);
          const uint32_t r3 = pack_bf16x2(a[6] * rinv[1], a[7] * rinv[1]);
          const uint32_t dst = p == 0 ? slots + 3 * 16384 + soff + h * 8192 : (p == 1 ? kdst : vdst) + h * hs;
          stmatrix_x4(dst ^ (jp << 5), r0, r1, r2, r3);
          if (t >= 20) {
            q[jp >> 1][jp & 1][0] = r0;
            q[jp >> 1][jp & 1][1] = r1;
            q[jp >> 1][jp & 1][2] = r2;
            q[jp >> 1][jp & 1][3] = r3;
          }
          if (t == 7 || t == 19) signal_async(bars + 8u * (t == 7 ? B_KV : B_LOC), lane0);
          if (t == 11) {
            setmaxnreg_dec<128>();
            named_bar_arrive(4, 256);
#pragma unroll
            for (int r = 0; r < 2; r++) rinv[r] = rcp_fast(bf_hi(rs[0][r]));
          }
        }
        mbar_wait(bars + 8u * B_LOC, inst & 1);
      }
      }
      GTL(3 + L * 8);
      if ((L & 1) == 0) attention_a(q, asst, L, gb, hp, ch, warp & 3, P.zero);
      else attention_b(q, asst, gb, inst & 1, warp & 3);
      GTL(4 + L * 8);
      signal_async(bars + 8u * (asst ? B_OS1 : B_OS0), (fresh_tid() & 31) == 0);
      if (asst) continue;
      GTL(5 + L * 8);

      {
        float acc[64];
        const int sp = inst < 7 ? q_split(inst + 1) : 0;
        const int st = sp & 3;
        const bool pre = w_pre(inst);
        const uint32_t toff = ((fresh_tid() & 63) << 7) + ((fresh_tid() & 7) << 4);
        uint32_t tro = (warp & 3) * 2048 + (toff & 0x7f0u);
        auto check_o = [&](uint32_t bar, uint32_t par, uint32_t sa, int kt) {
          fix_lines(bar, par, sa + tro, o_tag(L), 1u, 7, [&](int l) {
            return g_o + (size_t)(ch * 1024 + rt * 64 + (warp & 3) * 16 + (l & 15)) * DM + wk(kt) * 64;
          });
        };
        const bool lane0 = (toff & 0xf80u) == 0u;
        constexpr uint32_t U4 = UNIT >> 4, LA = 0x10000u, LB = U4 << 16;
        reg_define<64>(acc);
        reg_fence<64>(acc);
        uint32_t xv[8][4];
        {
          PHASE_IDS_W
          const uint32_t xr = slots + 6 * UNIT + (wwarp * 16 + (lane & 15)) * 128 + (((lane >> 4) ^ (lane & 7)) << 4);
          mbar_wait(bars + 8u * B_RF, inst & 1);
#pragma unroll
          for (int jp = 0; jp < 8; jp++) ldmatrix_x4(xv[jp], (xr ^ ((jp & 3) << 5)) + (jp >> 2) * UNIT);
          signal_async(bars + 8u * B_RDONE, lane0);
          if (L > 0) {
            uint32_t lsb;
            asm volatile("ld.shared.u8 %0, [%1];" : "=r"(lsb) : "r"(base + OFF_LSB + ch * 32 + wwarp * 8 + g) : "memory");
#pragma unroll
            for (int k = 0; k < 4; k++) xv[(k >> 1) * 4][k & 1] = set_tag(xv[(k >> 1) * 4][k & 1], c == 0, lsb >> k);
          }
        }
        uint32_t tmx = L < 3 && (toff & 0x180u) == 0u, xt = x_tag(L + 1);
        uint32_t xrow = w_out(inst) + (warp & 3) * 2048 + (toff & 0x7e0u) + ((toff ^ (toff >> 7)) & 0x10u);
        asm volatile("" : "+r"(tmx), "+r"(xt), "+r"(xrow), "+r"(tro));
        const uint64_t dz = desc_lo(0) + P.zero;
        auto nexts = [&](uint32_t a) { return a == base + 15 * UNIT ? base : a + 5 * UNIT; };
        uint32_t s0 = base + st * 5 * UNIT, sp3 = slots, fb = bars + 8u * B_WF;
        int turn = lane0 && (sp < 16 || inst == 6) ? 3 : -1;
        asm volatile("" : "+r"(turn));
        if (inst < 7 || SP7 == 16) mbar_wait_lazy<TLAZY>(bars + 8u * (B_TURN + ch), (turn_par(2) >> inst) & 1u);
        check_o(bars + 8u * B_WF, 0, s0, 0);
        GTL(6 + L * 8);
#pragma unroll 1
        for (int m = 0; m < 4; m++) {
          uint32_t s1, s2;
#pragma unroll
          for (int i = 0; i < 4; i++) {
            const uint64_t da = dz + ((i == 0 ? s0 : s1) >> 4) + (LA + (i == 2 ? 1 : (i == 3 ? 4 : 0)) * U4);
            const uint64_t db = dz + ((i < 2 ? s0 : (i == 2 ? s1 : s2)) >> 4) + (LB + (i == 0 ? 1 : (i == 1 ? 3 : (i == 2 ? 2 : 0))) * U4);
            wgmma_fence();
#pragma unroll
            for (int k16 = 0; k16 < 4; k16++) wgmma_n128_ss_ta0_tb1(acc, da + 2 * k16, db + 128 * k16, 1);
            wgmma_commit();
            if (i == 0) s1 = nexts(s0);
            if (i == 1) s0 = nexts(s1);
            if (i == 2) {
              s2 = pre ? sp3 : s0;
              s0 = pre ? s0 : nexts(s0);
              sp3 += 2 * UNIT;
            }
            const uint32_t fn = i < 3 ? fb + 8u * (i + 1) : fb ^ 96u;
            const uint32_t pn = i < 3 ? m >> 1 : m > 0;
            const uint32_t an = i < 3 ? s1 + (i == 1 ? 1 : (i == 2 ? 4 : 0)) * UNIT : s0;
            bool ok = mbar_test(fn, pn);
            const uint32_t tw = lds32(an + tro);
            ok = !__any_sync(0xffffffffu, (!ok || ((tw ^ o_tag(L)) & 1u)) && (i < 3 || m < 3));
            wgmma_wait<1>();
            if (lane0 && (i > 0 || m > 0)) mbar_arrive((i > 0 ? fb + 8u * (i - 1) : (fb ^ 96u) + 24u) + 8u * B_E);
            if (i == 2 && m == turn) mbar_arrive(bars + 8u * (B_TURN + (ch ^ 1)));
            if (!ok) check_o(fn, pn, an, 4 * m + i + 1);
          }
          fb ^= 96u;
        }
        wgmma_wait<0>();
        reg_fence<64>(acc);
        if (lane0) mbar_arrive(bars + 8u * (B_WF + B_E + 7));
        GTL(7 + L * 8);
#pragma unroll
        for (int jp = 0; jp < 8; jp++) {
#pragma unroll
          for (int q = 0; q < 4; q++) xv[jp][q] = add_bf16x2(xv[jp][q], pack_bf16x2(acc[8 * jp + 2 * q], acc[8 * jp + 2 * q + 1]));
          const bool tg = (jp & 3) == 0;
          stmatrix_x4((xrow ^ ((jp & 3) << 5)) + (jp >> 2) * UNIT,
                      tg ? set_tag(xv[jp][0], tmx, xt) : xv[jp][0], tg ? set_tag(xv[jp][1], tmx, xt) : xv[jp][1], xv[jp][2], xv[jp][3]);
          if ((jp & 3) == 3) signal_async(bars + 8u * (B_XS + (jp >> 2)), lane0);
        }
        if (L < 3) {
          PHASE_IDS_W
          const int grow = ch * 1024 + rt * 64;
          const unsigned ep1 = lds32(base + OFF_EPOCH);
          if (c == 0)
            asm volatile("st.shared.u8 [%0], %1;" ::"r"(base + OFF_LSB + ch * 32 + wwarp * 8 + g),
                         "r"((xv[0][0] & 1u) | ((xv[0][1] & 1u) << 1) | ((xv[4][0] & 1u) << 2) | ((xv[4][1] & 1u) << 3)) : "memory");
          float s1[2] = {0.f, 0.f}, s2[2] = {0.f, 0.f};
#pragma unroll
          for (int jp = 0; jp < 8; jp++)
#pragma unroll
            for (int q = 0; q < 4; q++) {
              const float x0 = bf_lo(xv[jp][q]), x1 = bf_hi(xv[jp][q]);
              s1[q & 1] += x0 + x1;
              s2[q & 1] = fmaf(x0, x0, fmaf(x1, x1, s2[q & 1]));
            }
#pragma unroll
          for (int r = 0; r < 2; r++) {
            s1[r] += __shfl_xor_sync(0xffffffffu, s1[r], 1);
            s2[r] += __shfl_xor_sync(0xffffffffu, s2[r], 1);
            s1[r] += __shfl_xor_sync(0xffffffffu, s1[r], 2);
            s2[r] += __shfl_xor_sync(0xffffffffu, s2[r], 2);
            if (c == 0) st_rec(&g_stats[ct][grow + wwarp * 16 + g + 8 * r], s1[r], s2[r], 0.f, 4u * ep1 + L + 1);
          }
        }
        GTL(8 + L * 8);
      }
    }
    if (threadIdx.x == 128) atomicAdd(g_done, 1u);
  }
}

typedef CUresult (*PFN_tmEncode)(CUtensorMap*, CUtensorMapDataType, cuuint32_t, void*, const cuuint64_t*,
                                 const cuuint64_t*, const cuuint32_t*, const cuuint32_t*, CUtensorMapInterleave,
                                 CUtensorMapSwizzle, CUtensorMapL2promotion, CUtensorMapFloatOOBfill);

PFN_tmEncode get_encode_fn() {
  static PFN_tmEncode fn = nullptr;
  if (!fn) {
    cudaDriverEntryPointQueryResult qr;
    void* p = nullptr;
    cudaGetDriverEntryPoint("cuTensorMapEncodeTiled", &p, cudaEnableDefault, &qr);
    fn = (PFN_tmEncode)p;
  }
  return fn;
}

CUtensorMap make_map(const void* ptr, int rows, int cols) {
  CUtensorMap m;
  cuuint64_t gdim[2] = {(cuuint64_t)cols, (cuuint64_t)rows};
  cuuint64_t gstr[1] = {(cuuint64_t)cols * 2};
  cuuint32_t box[2] = {64, 64};
  cuuint32_t estr[2] = {1, 1};
  get_encode_fn()(&m, CU_TENSOR_MAP_DATA_TYPE_BFLOAT16, 2, const_cast<void*>(ptr), gdim, gstr, box, estr,
                  CU_TENSOR_MAP_INTERLEAVE_NONE, CU_TENSOR_MAP_SWIZZLE_128B, CU_TENSOR_MAP_L2_PROMOTION_L2_128B,
                  CU_TENSOR_MAP_FLOAT_OOB_FILL_NONE);
  return m;
}

CUtensorMap make_map3(const void* ptr, int rows, int cols, int n, int step) {
  CUtensorMap m;
  cuuint64_t gdim[3] = {(cuuint64_t)(cols - (n - 1) * step), (cuuint64_t)rows, (cuuint64_t)n};
  cuuint64_t gstr[2] = {(cuuint64_t)cols * 2, (cuuint64_t)step * 2};
  cuuint32_t box[3] = {64, 64, (cuuint32_t)n};
  cuuint32_t estr[3] = {1, 1, 1};
  get_encode_fn()(&m, CU_TENSOR_MAP_DATA_TYPE_BFLOAT16, 3, const_cast<void*>(ptr), gdim, gstr, box, estr,
                  CU_TENSOR_MAP_INTERLEAVE_NONE, CU_TENSOR_MAP_SWIZZLE_128B, CU_TENSOR_MAP_L2_PROMOTION_L2_128B,
                  CU_TENSOR_MAP_FLOAT_OOB_FILL_NONE);
  return m;
}

CUtensorMap make_map_q(const void* ptr, int sw, int sr) {
  CUtensorMap m;
  cuuint64_t gdim[5] = {DM, 8, 2, 4, S_LEN / 64};
  cuuint64_t gstr[4] = {DM * 2, (cuuint64_t)sr * DM * 2, (cuuint64_t)sw * DM * 2, 64 * DM * 2};
  cuuint32_t box[5] = {64, 8, 2, 4, 2};
  cuuint32_t estr[5] = {1, 1, 1, 1, 1};
  get_encode_fn()(&m, CU_TENSOR_MAP_DATA_TYPE_BFLOAT16, 5, const_cast<void*>(ptr), gdim, gstr, box, estr,
                  CU_TENSOR_MAP_INTERLEAVE_NONE, CU_TENSOR_MAP_SWIZZLE_128B, CU_TENSOR_MAP_L2_PROMOTION_L2_128B,
                  CU_TENSOR_MAP_FLOAT_OOB_FILL_NONE);
  return m;
}

}

extern "C" void kernel_launch(void* const* d_in, const int* in_sizes, int n_in, void* d_out, int out_size) {
  (void)in_sizes; (void)n_in; (void)out_size;
  void *p_o, *p_x;
  cudaGetSymbolAddress(&p_o, g_o);
  cudaGetSymbolAddress(&p_x, g_x);
  static bool attr_done = false;
  if (!attr_done) {
    cudaFuncSetAttribute(fused_kernel, cudaFuncAttributeMaxDynamicSharedMemorySize, SMEM_BYTES);
    attr_done = true;
  }
  Params P;
  P.in_x = (const __nv_bfloat16*)d_in[0];
  P.wqkv_p[0] = (const __nv_bfloat16*)d_in[1];
  P.wo_p[0] = (const __nv_bfloat16*)d_in[2];
  P.wqkv_p[1] = (const __nv_bfloat16*)d_in[4];
  P.wo_p[1] = (const __nv_bfloat16*)d_in[5];
  P.out = (__nv_bfloat16*)d_out;
  P.zero = 0;
  for (int L = 0; L < 5; L++) {
    const void* px = L == 0 ? (const void*)P.in_x : (L == 4 ? d_out : p_x);
    P.x[L] = make_map(px, S_LEN, DM);
    if (L < 4) P.xq[L] = (L & 1) ? make_map_q(px, 16, 8) : make_map_q(px, 8, 32);
  }
  P.o = make_map(p_o, S_LEN, DM);
  for (int t = 0; t < 2; t++) {
    P.wqkv[t] = make_map(P.wqkv_p[t], DM, NQKV);
    P.wqkv3[t] = make_map3(P.wqkv_p[t], DM, NQKV, 3, 1024);
    P.wo3[t] = make_map3(P.wo_p[t], DM, DM, 2, 64);
  }
  fused_kernel<<<NCTA, 512, SMEM_BYTES>>>(P);
}
```

```cpp
#include <cuda_runtime.h>
#include <cuda_bf16.h>
#include <cuda.h>
#include <stdint.h>

namespace {

constexpr int S_LEN = 2048;
constexpr int DM = 1024;
constexpr int NQKV = 3072;
constexpr int NCTA = 128;

__device__ __align__(1024) uint8_t g_kvA[16][16][2][16384];
__device__ __align__(1024) uint8_t g_kvB[16][16][4096];
__device__ __align__(1024) uint8_t g_zero[16384];
__device__ __align__(1024) __nv_bfloat16 g_o[S_LEN * DM];
__device__ __align__(1024) __nv_bfloat16 g_x[S_LEN * DM];
__device__ __align__(1024) float4 g_stats[8][S_LEN];
__device__ __align__(1024) float4 g_cs[2][16][8][64];
__device__ __align__(128) unsigned g_fx[16][16][4];
__device__ __align__(128) unsigned g_fo[32][16][4];
__device__ __align__(128) unsigned g_fk[16][16][4];
__device__ __align__(128) unsigned g_done[32];

constexpr uint32_t SBASE = 1024;
constexpr int UNIT = 8192;
constexpr int NUNITS = 20;
constexpr int OFF_SLOT = NUNITS * UNIT;
constexpr int OFF_BAR = OFF_SLOT + 4 * 16384;
constexpr int OFF_EPOCH = OFF_BAR + 424;
constexpr int OFF_LSB = OFF_BAR + 432;
constexpr int OFF_CS = OFF_BAR + 496;
constexpr int OFF_RS = OFF_CS + 1536;
constexpr int OFF_ONE = OFF_RS + 1024;
constexpr int SMEM_BYTES = OFF_ONE + 16;
constexpr int B_QF = 0, B_WF = 4, B_RF = 12, B_E = 13, B_PREP = 26, B_LOC = 28, B_HALO = 29, B_REL = 33, B_OS0 = 36,
              B_TURN = 37, B_XS = 39, B_CS = 41, B_CSD = 42, B_GO = 43, B_PRE = 44, B_HV = 45, B_REDO = 46,
              B_RDONE = 48, B_PRE2 = 49, B_HL = 50, B_KV = 52, B_OS1 = B_GO;
static_assert(SMEM_BYTES <= 232448, "shared memory");

__device__ __forceinline__ uint32_t smem_u32(const void* p) { return (uint32_t)__cvta_generic_to_shared(p); }

__device__ __forceinline__ void mbar_init(uint32_t bar, uint32_t cnt) {
  asm volatile("mbarrier.init.shared::cta.b64 [%0], %1;" ::"r"(bar), "r"(cnt));
}
__device__ __forceinline__ void mbar_expect_tx(uint32_t bar, uint32_t bytes) {
  asm volatile("mbarrier.arrive.expect_tx.shared::cta.b64 _, [%0], %1;" ::"r"(bar), "r"(bytes) : "memory");
}
__device__ __forceinline__ void mbar_arrive(uint32_t bar) {
  asm volatile("mbarrier.arrive.shared::cta.b64 _, [%0];" ::"r"(bar) : "memory");
}
__device__ __forceinline__ bool mbar_try_wait(uint32_t bar, uint32_t parity) {
  uint32_t ok;
  asm volatile(
      "{\n.reg .pred p;\nmbarrier.try_wait.parity.shared::cta.b64 p, [%1], %2;\nselp.b32 %0, 1, 0, p;\n}\n"
      : "=r"(ok)
      : "r"(bar), "r"(parity)
      : "memory");
  return ok != 0;
}
__device__ __forceinline__ bool mbar_test(uint32_t bar, uint32_t parity) {
  uint32_t ok;
  asm volatile(
      "{\n.reg .pred p;\nmbarrier.test_wait.parity.shared::cta.b64 p, [%1], %2;\nselp.b32 %0, 1, 0, p;\n}\n"
      : "=r"(ok)
      : "r"(bar), "r"(parity)
      : "memory");
  return ok != 0;
}
__device__ __forceinline__ void mbar_wait(uint32_t bar, uint32_t parity) {
#pragma unroll 1
  for (uint32_t it = 0; it < (1u << 18); ++it) {
    if (mbar_try_wait(bar, parity)) return;
  }
}
__device__ __forceinline__ void mbar_pace(uint32_t bar, uint32_t parity, uint32_t n) {
#pragma unroll 1
  for (uint32_t it = 0; it < n; ++it) {
    if (mbar_test(bar, parity)) return;
    __nanosleep(100);
  }
}
template <int NS>
__device__ __forceinline__ void mbar_wait_lazy(uint32_t bar, uint32_t parity) {
#pragma unroll 1
  for (uint32_t it = 0; it < (1u << 18); ++it) {
    if (mbar_try_wait(bar, parity)) return;
    __nanosleep(NS);
  }
}
__device__ __forceinline__ bool elect_one() {
  uint32_t ok;
  asm volatile("{\n.reg .pred p;\nelect.sync _|p, 0xffffffff;\nselp.b32 %0, 1, 0, p;\n}\n" : "=r"(ok));
  return ok != 0;
}
__device__ __forceinline__ void fence_barrier_init() { asm volatile("fence.mbarrier_init.release.cluster;" ::: "memory"); }
__device__ __forceinline__ void fence_proxy_async_smem() { asm volatile("fence.proxy.async.shared::cta;" ::: "memory"); }

__device__ __forceinline__ void signal_async(uint32_t bar, bool lane0) {
  fence_proxy_async_smem();
  __syncwarp();
  asm volatile("{\n.reg .pred p;\nsetp.ne.b32 p, %1, 0;\n@p mbarrier.arrive.shared::cta.b64 _, [%0];\n}\n" ::"r"(bar), "r"((int)lane0) : "memory");
}
template <class T>
__device__ __forceinline__ void pin64(T*& p) { asm volatile("" : "+l"(p)); }

__device__ __forceinline__ void tma_load_2d(uint32_t dst, const CUtensorMap* map, uint32_t bar, int c0, int c1) {
  asm volatile(
      "cp.async.bulk.tensor.2d.shared::cluster.global.mbarrier::complete_tx::bytes [%0], [%1, {%3, %4}], [%2];" ::"r"(dst),
      "l"(map), "r"(bar), "r"(c0), "r"(c1)
      : "memory");
}
__device__ __forceinline__ void tma_load_3d(uint32_t dst, const CUtensorMap* map, uint32_t bar, int c0, int c1) {
  asm volatile(
      "cp.async.bulk.tensor.3d.shared::cluster.global.mbarrier::complete_tx::bytes [%0], [%1, {%3, %4, %5}], [%2];" ::"r"(dst),
      "l"(map), "r"(bar), "r"(c0), "r"(c1), "r"(0)
      : "memory");
}
__device__ __forceinline__ void tma_load_5d(uint32_t dst, const CUtensorMap* map, uint32_t bar, int c0, int c4) {
  asm volatile(
      "cp.async.bulk.tensor.5d.shared::cluster.global.mbarrier::complete_tx::bytes [%0], [%1, {%3, %5, %5, %5, %4}], [%2];" ::"r"(dst),
      "l"(map), "r"(bar), "r"(c0), "r"(c4), "r"(0)
      : "memory");
}
__device__ __forceinline__ void bulk_load(uint32_t dst, const void* src, uint32_t bytes, uint32_t bar) {
  asm volatile("cp.async.bulk.shared::cluster.global.mbarrier::complete_tx::bytes [%0], [%1], %2, [%3];" ::"r"(dst),
               "l"(src), "r"(bytes), "r"(bar)
               : "memory");
}
__device__ __forceinline__ void bulk_store(void* dst, uint32_t src, uint32_t bytes) {
  asm volatile("cp.async.bulk.global.shared::cta.bulk_group [%0], [%1], %2;" ::"l"(dst), "r"(src), "r"(bytes) : "memory");
}
__device__ __forceinline__ void tma_store_2d(const CUtensorMap* map, uint32_t src, int c0, int c1) {
  asm volatile("cp.async.bulk.tensor.2d.global.shared::cta.bulk_group [%0, {%2, %3}], [%1];" ::"l"(map), "r"(src),
               "r"(c0), "r"(c1)
               : "memory");
}
__device__ __forceinline__ void bulk_announce(unsigned* p) {
  asm volatile("cp.reduce.async.bulk.global.shared::cta.bulk_group.add.u32 [%0], [%1], 16;" ::"l"(p), "r"(SBASE + OFF_ONE) : "memory");
}
__device__ __forceinline__ void bulk_commit() { asm volatile("cp.async.bulk.commit_group;" ::: "memory"); }
__device__ __forceinline__ void bulk_wait_read0() { asm volatile("cp.async.bulk.wait_group.read 0;" ::: "memory"); }
__device__ __forceinline__ void bulk_wait0() { asm volatile("cp.async.bulk.wait_group 0;" ::: "memory"); }
__device__ __forceinline__ void named_bar_sync(int id, int nthreads) {
  asm volatile("bar.sync %0, %1;" ::"r"(id), "r"(nthreads) : "memory");
}
__device__ __forceinline__ void named_bar_arrive(int id, int nthreads) {
  asm volatile("bar.arrive %0, %1;" ::"r"(id), "r"(nthreads) : "memory");
}

__device__ __forceinline__ void wgmma_fence() { asm volatile("wgmma.fence.sync.aligned;\n" ::: "memory"); }
__device__ __forceinline__ void wgmma_commit() { asm volatile("wgmma.commit_group.sync.aligned;\n" ::: "memory"); }
template <int N>
__device__ __forceinline__ void wgmma_wait() {
  asm volatile("wgmma.wait_group.sync.aligned %0;\n" ::"n"(N) : "memory");
}
template <int R>
__device__ __forceinline__ void setmaxnreg_inc() { asm volatile("setmaxnreg.inc.sync.aligned.u32 %0;\n" ::"n"(R)); }
template <int R>
__device__ __forceinline__ void setmaxnreg_dec() { asm volatile("setmaxnreg.dec.sync.aligned.u32 %0;\n" ::"n"(R)); }
template <int N>
__device__ __forceinline__ void reg_fence(float* r) {
#pragma unroll
  for (int i = 0; i < N; i++) asm volatile("" : "+f"(r[i])::"memory");
}

template <int N>
__device__ __forceinline__ void reg_define(float* r) {
#pragma unroll
  for (int i = 0; i < N; i++) r[i] = 0.f;
}

__device__ __forceinline__ uint64_t desc_lo(uint32_t lo) {
  uint64_t d;
  asm("mov.b64 %0, {%1, %2};" : "=l"(d) : "r"(lo), "r"(0x40000040u));
  return d;
}
__device__ __forceinline__ uint64_t make_desc(uint32_t addr, uint32_t lbo_bytes) {
  return desc_lo((addr >> 4) + ((lbo_bytes >> 4) << 16));
}

__device__ __forceinline__ void wgmma_n192_ss_ta0_tb1(float* d, uint64_t descA, uint64_t descB, int scaleD) {
  asm volatile("{\n.reg .pred p;\nsetp.ne.b32 p, %98, 0;\n"
    "wgmma.mma_async.sync.aligned.m64n192k16.f32.bf16.bf16 {%0, %1, %2, %3, %4, %5, %6, %7, %8, %9, %10, %11, %12, %13, %14, %15, %16, %17, %18, %19, %20, %21, %22, %23, %24, %25, %26, %27, %28, %29, %30, %31, %32, %33, %34, %35, %36, %37, %38, %39, %40, %41, %42, %43, %44, %45, %46, %47, %48, %49, %50, %51, %52, %53, %54, %55, %56, %57, %58, %59, %60, %61, %62, %63, %64, %65, %66, %67, %68, %69, %70, %71, %72, %73, %74, %75, %76, %77, %78, %79, %80, %81, %82, %83, %84, %85, %86, %87, %88, %89, %90, %91, %92, %93, %94, %95}, %96, %97, p, 1, 1, 0, 1;\n}\n"
    : "+f"(d[0]), "+f"(d[1]), "+f"(d[2]), "+f"(d[3]), "+f"(d[4]), "+f"(d[5]), "+f"(d[6]), "+f"(d[7]), "+f"(d[8]), "+f"(d[9]), "+f"(d[10]), "+f"(d[11]), "+f"(d[12]), "+f"(d[13]), "+f"(d[14]), "+f"(d[15]), "+f"(d[16]), "+f"(d[17]), "+f"(d[18]), "+f"(d[19]), "+f"(d[20]), "+f"(d[21]), "+f"(d[22]), "+f"(d[23]), "+f"(d[24]), "+f"(d[25]), "+f"(d[26]), "+f"(d[27]), "+f"(d[28]), "+f"(d[29]), "+f"(d[30]), "+f"(d[31]), "+f"(d[32]), "+f"(d[33]), "+f"(d[34]), "+f"(d[35]), "+f"(d[36]), "+f"(d[37]), "+f"(d[38]), "+f"(d[39]), "+f"(d[40]), "+f"(d[41]), "+f"(d[42]), "+f"(d[43]), "+f"(d[44]), "+f"(d[45]), "+f"(d[46]), "+f"(d[47]), "+f"(d[48]), "+f"(d[49]), "+f"(d[50]), "+f"(d[51]), "+f"(d[52]), "+f"(d[53]), "+f"(d[54]), "+f"(d[55]), "+f"(d[56]), "+f"(d[57]), "+f"(d[58]), "+f"(d[59]), "+f"(d[60]), "+f"(d[61]), "+f"(d[62]), "+f"(d[63]), "+f"(d[64]), "+f"(d[65]), "+f"(d[66]), "+f"(d[67]), "+f"(d[68]), "+f"(d[69]), "+f"(d[70]), "+f"(d[71]), "+f"(d[72]), "+f"(d[73]), "+f"(d[74]), "+f"(d[75]), "+f"(d[76]), "+f"(d[77]), "+f"(d[78]), "+f"(d[79]), "+f"(d[80]), "+f"(d[81]), "+f"(d[82]), "+f"(d[83]), "+f"(d[84]), "+f"(d[85]), "+f"(d[86]), "+f"(d[87]), "+f"(d[88]), "+f"(d[89]), "+f"(d[90]), "+f"(d[91]), "+f"(d[92]), "+f"(d[93]), "+f"(d[94]), "+f"(d[95])
    : "l"(descA), "l"(descB), "r"(scaleD));
}

__device__ __forceinline__ void wgmma_n128_ss_ta0_tb1(float* d, uint64_t descA, uint64_t descB, int scaleD) {
  asm volatile("{\n.reg .pred p;\nsetp.ne.b32 p, %66, 0;\n"
    "wgmma.mma_async.sync.aligned.m64n128k16.f32.bf16.bf16 {%0, %1, %2, %3, %4, %5, %6, %7, %8, %9, %10, %11, %12, %13, %14, %15, %16, %17, %18, %19, %20, %21, %22, %23, %24, %25, %26, %27, %28, %29, %30, %31, %32, %33, %34, %35, %36, %37, %38, %39, %40, %41, %42, %43, %44, %45, %46, %47, %48, %49, %50, %51, %52, %53, %54, %55, %56, %57, %58, %59, %60, %61, %62, %63}, %64, %65, p, 1, 1, 0, 1;\n}\n"
    : "+f"(d[0]), "+f"(d[1]), "+f"(d[2]), "+f"(d[3]), "+f"(d[4]), "+f"(d[5]), "+f"(d[6]), "+f"(d[7]), "+f"(d[8]), "+f"(d[9]), "+f"(d[10]), "+f"(d[11]), "+f"(d[12]), "+f"(d[13]), "+f"(d[14]), "+f"(d[15]), "+f"(d[16]), "+f"(d[17]), "+f"(d[18]), "+f"(d[19]), "+f"(d[20]), "+f"(d[21]), "+f"(d[22]), "+f"(d[23]), "+f"(d[24]), "+f"(d[25]), "+f"(d[26]), "+f"(d[27]), "+f"(d[28]), "+f"(d[29]), "+f"(d[30]), "+f"(d[31]), "+f"(d[32]), "+f"(d[33]), "+f"(d[34]), "+f"(d[35]), "+f"(d[36]), "+f"(d[37]), "+f"(d[38]), "+f"(d[39]), "+f"(d[40]), "+f"(d[41]), "+f"(d[42]), "+f"(d[43]), "+f"(d[44]), "+f"(d[45]), "+f"(d[46]), "+f"(d[47]), "+f"(d[48]), "+f"(d[49]), "+f"(d[50]), "+f"(d[51]), "+f"(d[52]), "+f"(d[53]), "+f"(d[54]), "+f"(d[55]), "+f"(d[56]), "+f"(d[57]), "+f"(d[58]), "+f"(d[59]), "+f"(d[60]), "+f"(d[61]), "+f"(d[62]), "+f"(d[63])
    : "l"(descA), "l"(descB), "r"(scaleD));
}

__device__ __forceinline__ void wgmma_n192_ssz_ta0_tb1(float* d, uint64_t descA, uint64_t descB) {
  asm volatile("{\n.reg .pred p;\nsetp.ne.b32 p, 0, 0;\n"
    "wgmma.mma_async.sync.aligned.m64n192k16.f32.bf16.bf16 {%0, %1, %2, %3, %4, %5, %6, %7, %8, %9, %10, %11, %12, %13, %14, %15, %16, %17, %18, %19, %20, %21, %22, %23, %24, %25, %26, %27, %28, %29, %30, %31, %32, %33, %34, %35, %36, %37, %38, %39, %40, %41, %42, %43, %44, %45, %46, %47, %48, %49, %50, %51, %52, %53, %54, %55, %56, %57, %58, %59, %60, %61, %62, %63, %64, %65, %66, %67, %68, %69, %70, %71, %72, %73, %74, %75, %76, %77, %78, %79, %80, %81, %82, %83, %84, %85, %86, %87, %88, %89, %90, %91, %92, %93, %94, %95}, %96, %97, p, 1, 1, 0, 1;\n}\n"
    : "=f"(d[0]), "=f"(d[1]), "=f"(d[2]), "=f"(d[3]), "=f"(d[4]), "=f"(d[5]), "=f"(d[6]), "=f"(d[7]), "=f"(d[8]), "=f"(d[9]), "=f"(d[10]), "=f"(d[11]), "=f"(d[12]), "=f"(d[13]), "=f"(d[14]), "=f"(d[15]), "=f"(d[16]), "=f"(d[17]), "=f"(d[18]), "=f"(d[19]), "=f"(d[20]), "=f"(d[21]), "=f"(d[22]), "=f"(d[23]), "=f"(d[24]), "=f"(d[25]), "=f"(d[26]), "=f"(d[27]), "=f"(d[28]), "=f"(d[29]), "=f"(d[30]), "=f"(d[31]), "=f"(d[32]), "=f"(d[33]), "=f"(d[34]), "=f"(d[35]), "=f"(d[36]), "=f"(d[37]), "=f"(d[38]), "=f"(d[39]), "=f"(d[40]), "=f"(d[41]), "=f"(d[42]), "=f"(d[43]), "=f"(d[44]), "=f"(d[45]), "=f"(d[46]), "=f"(d[47]), "=f"(d[48]), "=f"(d[49]), "=f"(d[50]), "=f"(d[51]), "=f"(d[52]), "=f"(d[53]), "=f"(d[54]), "=f"(d[55]), "=f"(d[56]), "=f"(d[57]), "=f"(d[58]), "=f"(d[59]), "=f"(d[60]), "=f"(d[61]), "=f"(d[62]), "=f"(d[63]), "=f"(d[64]), "=f"(d[65]), "=f"(d[66]), "=f"(d[67]), "=f"(d[68]), "=f"(d[69]), "=f"(d[70]), "=f"(d[71]), "=f"(d[72]), "=f"(d[73]), "=f"(d[74]), "=f"(d[75]), "=f"(d[76]), "=f"(d[77]), "=f"(d[78]), "=f"(d[79]), "=f"(d[80]), "=f"(d[81]), "=f"(d[82]), "=f"(d[83]), "=f"(d[84]), "=f"(d[85]), "=f"(d[86]), "=f"(d[87]), "=f"(d[88]), "=f"(d[89]), "=f"(d[90]), "=f"(d[91]), "=f"(d[92]), "=f"(d[93]), "=f"(d[94]), "=f"(d[95])
    : "l"(descA), "l"(descB));
}

__device__ __forceinline__ void wgmma_n8_ss_ta1_tb0(float* d, uint64_t descA, uint64_t descB, int scaleD) {
  asm volatile("{\n.reg .pred p;\nsetp.ne.b32 p, %6, 0;\n"
    "wgmma.mma_async.sync.aligned.m64n8k16.f32.bf16.bf16 {%0, %1, %2, %3}, %4, %5, p, 1, 1, 1, 0;\n}\n"
    : "+f"(d[0]), "+f"(d[1]), "+f"(d[2]), "+f"(d[3])
    : "l"(descA), "l"(descB), "r"(scaleD));
}

__device__ __forceinline__ void wgmma_n8_ssz_ta1_tb0(float* d, uint64_t descA, uint64_t descB) {
  asm volatile("{\n.reg .pred p;\nsetp.ne.b32 p, 0, 0;\n"
    "wgmma.mma_async.sync.aligned.m64n8k16.f32.bf16.bf16 {%0, %1, %2, %3}, %4, %5, p, 1, 1, 1, 0;\n}\n"
    : "=f"(d[0]), "=f"(d[1]), "=f"(d[2]), "=f"(d[3])
    : "l"(descA), "l"(descB));
}

__device__ __forceinline__ void wgmma_n192_rs_tb1(float* d, const uint32_t* a, uint64_t descB, int scaleD) {
  asm volatile("{\n.reg .pred p;\nsetp.ne.b32 p, %101, 0;\n"
    "wgmma.mma_async.sync.aligned.m64n192k16.f32.bf16.bf16 {%0, %1, %2, %3, %4, %5, %6, %7, %8, %9, %10, %11, %12, %13, %14, %15, %16, %17, %18, %19, %20, %21, %22, %23, %24, %25, %26, %27, %28, %29, %30, %31, %32, %33, %34, %35, %36, %37, %38, %39, %40, %41, %42, %43, %44, %45, %46, %47, %48, %49, %50, %51, %52, %53, %54, %55, %56, %57, %58, %59, %60, %61, %62, %63, %64, %65, %66, %67, %68, %69, %70, %71, %72, %73, %74, %75, %76, %77, %78, %79, %80, %81, %82, %83, %84, %85, %86, %87, %88, %89, %90, %91, %92, %93, %94, %95}, {%96, %97, %98, %99}, %100, p, 1, 1, 1;\n}\n"
    : "+f"(d[0]), "+f"(d[1]), "+f"(d[2]), "+f"(d[3]), "+f"(d[4]), "+f"(d[5]), "+f"(d[6]), "+f"(d[7]), "+f"(d[8]), "+f"(d[9]), "+f"(d[10]), "+f"(d[11]), "+f"(d[12]), "+f"(d[13]), "+f"(d[14]), "+f"(d[15]), "+f"(d[16]), "+f"(d[17]), "+f"(d[18]), "+f"(d[19]), "+f"(d[20]), "+f"(d[21]), "+f"(d[22]), "+f"(d[23]), "+f"(d[24]), "+f"(d[25]), "+f"(d[26]), "+f"(d[27]), "+f"(d[28]), "+f"(d[29]), "+f"(d[30]), "+f"(d[31]), "+f"(d[32]), "+f"(d[33]), "+f"(d[34]), "+f"(d[35]), "+f"(d[36]), "+f"(d[37]), "+f"(d[38]), "+f"(d[39]), "+f"(d[40]), "+f"(d[41]), "+f"(d[42]), "+f"(d[43]), "+f"(d[44]), "+f"(d[45]), "+f"(d[46]), "+f"(d[47]), "+f"(d[48]), "+f"(d[49]), "+f"(d[50]), "+f"(d[51]), "+f"(d[52]), "+f"(d[53]), "+f"(d[54]), "+f"(d[55]), "+f"(d[56]), "+f"(d[57]), "+f"(d[58]), "+f"(d[59]), "+f"(d[60]), "+f"(d[61]), "+f"(d[62]), "+f"(d[63]), "+f"(d[64]), "+f"(d[65]), "+f"(d[66]), "+f"(d[67]), "+f"(d[68]), "+f"(d[69]), "+f"(d[70]), "+f"(d[71]), "+f"(d[72]), "+f"(d[73]), "+f"(d[74]), "+f"(d[75]), "+f"(d[76]), "+f"(d[77]), "+f"(d[78]), "+f"(d[79]), "+f"(d[80]), "+f"(d[81]), "+f"(d[82]), "+f"(d[83]), "+f"(d[84]), "+f"(d[85]), "+f"(d[86]), "+f"(d[87]), "+f"(d[88]), "+f"(d[89]), "+f"(d[90]), "+f"(d[91]), "+f"(d[92]), "+f"(d[93]), "+f"(d[94]), "+f"(d[95])
    : "r"(a[0]), "r"(a[1]), "r"(a[2]), "r"(a[3]), "l"(descB), "r"(scaleD));
}

__device__ __forceinline__ void wgmma_n80_rs_tb0(float* d, const uint32_t* a, uint64_t descB, int scaleD) {
  asm volatile("{\n.reg .pred p;\nsetp.ne.b32 p, %45, 0;\n"
    "wgmma.mma_async.sync.aligned.m64n80k16.f32.bf16.bf16 {%0, %1, %2, %3, %4, %5, %6, %7, %8, %9, %10, %11, %12, %13, %14, %15, %16, %17, %18, %19, %20, %21, %22, %23, %24, %25, %26, %27, %28, %29, %30, %31, %32, %33, %34, %35, %36, %37, %38, %39}, {%40, %41, %42, %43}, %44, p, 1, 1, 0;\n}\n"
    : "+f"(d[0]), "+f"(d[1]), "+f"(d[2]), "+f"(d[3]), "+f"(d[4]), "+f"(d[5]), "+f"(d[6]), "+f"(d[7]), "+f"(d[8]), "+f"(d[9]), "+f"(d[10]), "+f"(d[11]), "+f"(d[12]), "+f"(d[13]), "+f"(d[14]), "+f"(d[15]), "+f"(d[16]), "+f"(d[17]), "+f"(d[18]), "+f"(d[19]), "+f"(d[20]), "+f"(d[21]), "+f"(d[22]), "+f"(d[23]), "+f"(d[24]), "+f"(d[25]), "+f"(d[26]), "+f"(d[27]), "+f"(d[28]), "+f"(d[29]), "+f"(d[30]), "+f"(d[31]), "+f"(d[32]), "+f"(d[33]), "+f"(d[34]), "+f"(d[35]), "+f"(d[36]), "+f"(d[37]), "+f"(d[38]), "+f"(d[39])
    : "r"(a[0]), "r"(a[1]), "r"(a[2]), "r"(a[3]), "l"(descB), "r"(scaleD));
}

__device__ __forceinline__ void wgmma_n80_rsz_tb0(float* d, const uint32_t* a, uint64_t descB) {
  asm volatile("{\n.reg .pred p;\nsetp.ne.b32 p, 0, 0;\n"
    "wgmma.mma_async.sync.aligned.m64n80k16.f32.bf16.bf16 {%0, %1, %2, %3, %4, %5, %6, %7, %8, %9, %10, %11, %12, %13, %14, %15, %16, %17, %18, %19, %20, %21, %22, %23, %24, %25, %26, %27, %28, %29, %30, %31, %32, %33, %34, %35, %36, %37, %38, %39}, {%40, %41, %42, %43}, %44, p, 1, 1, 0;\n}\n"
    : "=f"(d[0]), "=f"(d[1]), "=f"(d[2]), "=f"(d[3]), "=f"(d[4]), "=f"(d[5]), "=f"(d[6]), "=f"(d[7]), "=f"(d[8]), "=f"(d[9]), "=f"(d[10]), "=f"(d[11]), "=f"(d[12]), "=f"(d[13]), "=f"(d[14]), "=f"(d[15]), "=f"(d[16]), "=f"(d[17]), "=f"(d[18]), "=f"(d[19]), "=f"(d[20]), "=f"(d[21]), "=f"(d[22]), "=f"(d[23]), "=f"(d[24]), "=f"(d[25]), "=f"(d[26]), "=f"(d[27]), "=f"(d[28]), "=f"(d[29]), "=f"(d[30]), "=f"(d[31]), "=f"(d[32]), "=f"(d[33]), "=f"(d[34]), "=f"(d[35]), "=f"(d[36]), "=f"(d[37]), "=f"(d[38]), "=f"(d[39])
    : "r"(a[0]), "r"(a[1]), "r"(a[2]), "r"(a[3]), "l"(descB));
}

__device__ __forceinline__ void wgmma_n32_rs_tb1(float* d, const uint32_t* a, uint64_t descB, int scaleD) {
  asm volatile("{\n.reg .pred p;\nsetp.ne.b32 p, %21, 0;\n"
    "wgmma.mma_async.sync.aligned.m64n32k16.f32.bf16.bf16 {%0, %1, %2, %3, %4, %5, %6, %7, %8, %9, %10, %11, %12, %13, %14, %15}, {%16, %17, %18, %19}, %20, p, 1, 1, 1;\n}\n"
    : "+f"(d[0]), "+f"(d[1]), "+f"(d[2]), "+f"(d[3]), "+f"(d[4]), "+f"(d[5]), "+f"(d[6]), "+f"(d[7]), "+f"(d[8]), "+f"(d[9]), "+f"(d[10]), "+f"(d[11]), "+f"(d[12]), "+f"(d[13]), "+f"(d[14]), "+f"(d[15])
    : "r"(a[0]), "r"(a[1]), "r"(a[2]), "r"(a[3]), "l"(descB), "r"(scaleD));
}

__device__ __forceinline__ void wgmma_n32_rsz_tb1(float* d, const uint32_t* a, uint64_t descB) {
  asm volatile("{\n.reg .pred p;\nsetp.ne.b32 p, 0, 0;\n"
    "wgmma.mma_async.sync.aligned.m64n32k16.f32.bf16.bf16 {%0, %1, %2, %3, %4, %5, %6, %7, %8, %9, %10, %11, %12, %13, %14, %15}, {%16, %17, %18, %19}, %20, p, 1, 1, 1;\n}\n"
    : "=f"(d[0]), "=f"(d[1]), "=f"(d[2]), "=f"(d[3]), "=f"(d[4]), "=f"(d[5]), "=f"(d[6]), "=f"(d[7]), "=f"(d[8]), "=f"(d[9]), "=f"(d[10]), "=f"(d[11]), "=f"(d[12]), "=f"(d[13]), "=f"(d[14]), "=f"(d[15])
    : "r"(a[0]), "r"(a[1]), "r"(a[2]), "r"(a[3]), "l"(descB));
}

__device__ __forceinline__ void wgmma_n32_rs_tb0(float* d, const uint32_t* a, uint64_t descB, int scaleD) {
  asm volatile("{\n.reg .pred p;\nsetp.ne.b32 p, %21, 0;\n"
    "wgmma.mma_async.sync.aligned.m64n32k16.f32.bf16.bf16 {%0, %1, %2, %3, %4, %5, %6, %7, %8, %9, %10, %11, %12, %13, %14, %15}, {%16, %17, %18, %19}, %20, p, 1, 1, 0;\n}\n"
    : "+f"(d[0]), "+f"(d[1]), "+f"(d[2]), "+f"(d[3]), "+f"(d[4]), "+f"(d[5]), "+f"(d[6]), "+f"(d[7]), "+f"(d[8]), "+f"(d[9]), "+f"(d[10]), "+f"(d[11]), "+f"(d[12]), "+f"(d[13]), "+f"(d[14]), "+f"(d[15])
    : "r"(a[0]), "r"(a[1]), "r"(a[2]), "r"(a[3]), "l"(descB), "r"(scaleD));
}

__device__ __forceinline__ void wgmma_n32_rsz_tb0(float* d, const uint32_t* a, uint64_t descB) {
  asm volatile("{\n.reg .pred p;\nsetp.ne.b32 p, 0, 0;\n"
    "wgmma.mma_async.sync.aligned.m64n32k16.f32.bf16.bf16 {%0, %1, %2, %3, %4, %5, %6, %7, %8, %9, %10, %11, %12, %13, %14, %15}, {%16, %17, %18, %19}, %20, p, 1, 1, 0;\n}\n"
    : "=f"(d[0]), "=f"(d[1]), "=f"(d[2]), "=f"(d[3]), "=f"(d[4]), "=f"(d[5]), "=f"(d[6]), "=f"(d[7]), "=f"(d[8]), "=f"(d[9]), "=f"(d[10]), "=f"(d[11]), "=f"(d[12]), "=f"(d[13]), "=f"(d[14]), "=f"(d[15])
    : "r"(a[0]), "r"(a[1]), "r"(a[2]), "r"(a[3]), "l"(descB));
}

__device__ __forceinline__ uint32_t pack_bf16x2(float lo, float hi) {
  uint32_t r;
  asm("cvt.rn.bf16x2.f32 %0, %1, %2;" : "=r"(r) : "f"(hi), "f"(lo));
  return r;
}
__device__ __forceinline__ float bf_lo(uint32_t p) { return __uint_as_float(p << 16); }
__device__ __forceinline__ float bf_hi(uint32_t p) { return __uint_as_float(p & 0xffff0000u); }
__device__ __forceinline__ float bf16_round(float v) { return __bfloat162float(__float2bfloat16_rn(v)); }
__device__ __forceinline__ float ex2_approx(float x) {
  float r;
  asm("ex2.approx.ftz.f32 %0, %1;" : "=f"(r) : "f"(x));
  return r;
}
__device__ __forceinline__ float rcp_fast(float x) {
  float r;
  asm("rcp.approx.ftz.f32 %0, %1;" : "=f"(r) : "f"(x));
  return r;
}
__device__ __forceinline__ void ldmatrix_x4(uint32_t (&r)[4], uint32_t addr) {
  asm volatile("ldmatrix.sync.aligned.m8n8.x4.shared.b16 {%0,%1,%2,%3}, [%4];"
               : "=r"(r[0]), "=r"(r[1]), "=r"(r[2]), "=r"(r[3])
               : "r"(addr)
               : "memory");
}
__device__ __forceinline__ void stmatrix_x4(uint32_t addr, uint32_t r0, uint32_t r1, uint32_t r2, uint32_t r3) {
  asm volatile("stmatrix.sync.aligned.m8n8.x4.shared.b16 [%0], {%1,%2,%3,%4};" ::"r"(addr), "r"(r0), "r"(r1), "r"(r2),
               "r"(r3));
}
__device__ __forceinline__ uint32_t add_bf16x2(uint32_t a, uint32_t b) {
  uint32_t r;
  asm("add.rn.bf16x2 %0, %1, %2;" : "=r"(r) : "r"(a), "r"(b));
  return r;
}
__device__ __forceinline__ uint4 lds128(uint32_t addr) {
  uint4 v;
  asm volatile("ld.shared.v4.b32 {%0,%1,%2,%3}, [%4];" : "=r"(v.x), "=r"(v.y), "=r"(v.z), "=r"(v.w) : "r"(addr) : "memory");
  return v;
}
__device__ __forceinline__ uint32_t lds32(uint32_t addr) {
  uint32_t v;
  asm volatile("ld.shared.b32 %0, [%1];" : "=r"(v) : "r"(addr) : "memory");
  return v;
}
__device__ __forceinline__ void sts32(uint32_t addr, uint32_t v) {
  asm volatile("st.shared.b32 [%0], %1;" ::"r"(addr), "r"(v) : "memory");
}

__device__ __forceinline__ int fresh_tid() {
  int t;
  asm volatile("mov.u32 %0, %%tid.x;" : "=r"(t));
  return t;
}
__device__ __forceinline__ unsigned ld_relaxed_u32(const void* p) {
  unsigned v;
  asm volatile("ld.relaxed.gpu.global.u32 %0, [%1];" : "=r"(v) : "l"(p) : "memory");
  return v;
}
__device__ __forceinline__ unsigned launch_epoch() { return (*(volatile unsigned*)g_done) / NCTA + 1u; }
__device__ __forceinline__ uint32_t set_tag(uint32_t w, uint32_t m, uint32_t tag) { return (w & ~m) | (tag & m); }
__device__ __forceinline__ uint32_t o_tag(int L) { return (L + 1) & 1; }
__device__ __forceinline__ uint32_t x_tag(int L) { return L & 1; }
__device__ __forceinline__ uint32_t kv_tag(int L) { return L < 2; }

#define SPINT 0
template <class F>
__device__ __forceinline__ void fix_lines(uint32_t bar, uint32_t par, uint32_t ta, uint32_t tag, uint32_t mask, int bar_id, F line) {
  uint32_t m;
  mbar_wait(bar, par);
  m = lds32(ta);
  m = __ballot_sync(0xffffffffu, (m ^ tag) & mask);
  if (m == 0u) return;
#pragma unroll 1
  for (uint32_t it = 0; it < (1u << 17) && m != 0u; ++it) {
    const int l = __ffs(m) - 1, j = fresh_tid() & 7;
    uint4 v;
    asm volatile("ld.relaxed.gpu.global.v4.b32 {%0,%1,%2,%3}, [%4];" : "=r"(v.x), "=r"(v.y), "=r"(v.z), "=r"(v.w) : "l"(line(l) + j * 8) : "memory");
    const uint32_t a = __shfl_sync(0xffffffffu, ta, l) ^ (j << 4);
    if (((__shfl_sync(0xffffffffu, v.x, 0) ^ tag) & 1u) == 0u) {
      asm volatile("st.shared.v4.b32 [%0], {%1,%2,%3,%4};" ::"r"(a), "r"(v.x), "r"(v.y), "r"(v.z), "r"(v.w) : "memory");
      m &= m - 1u;
    }
  }
  fence_proxy_async_smem();
  named_bar_sync(bar_id, 32);
}
__device__ __forceinline__ uint32_t peek_counts(const unsigned* f, unsigned target, int lane) {
  return __ballot_sync(0xffffffffu, (int)(ld_relaxed_u32(f + (lane & 15) * 4) - target) >= 0);
}
__device__ __forceinline__ void wait_count(const unsigned* f, unsigned target, int i, uint32_t& seen, int lane) {
  if ((seen >> i) & 1u) return;
#pragma unroll 1
  for (uint32_t it = 0; it < (1u << 17); ++it) {
    seen = peek_counts(f, target, lane);
    if ((seen >> i) & 1u) break;
  }
}
__device__ __forceinline__ float4 ld_rec(const float4* p) {
  float4 v;
  asm volatile("ld.relaxed.gpu.global.v4.f32 {%0,%1,%2,%3}, [%4];" : "=f"(v.x), "=f"(v.y), "=f"(v.z), "=f"(v.w) : "l"(p) : "memory");
  return v;
}
__device__ __forceinline__ void st_rec(float4* p, float a, float b, float c, unsigned tag) {
  asm volatile("st.relaxed.gpu.global.v4.f32 [%0], {%1,%2,%3,%4};" ::"l"(p), "f"(a), "f"(b), "f"(c), "f"(__uint_as_float(tag)) : "memory");
}
template <int N>
__device__ __forceinline__ float4 sum_recs(const float4* p, int stride, unsigned tag) {
  float4 s;
#pragma unroll 1
  for (uint32_t it = 0; it < (1u << 17); ++it) {
    float4 v[N];
#pragma unroll
    for (int t = 0; t < N; t++) v[t] = ld_rec(p + t * stride);
    bool ok = true;
    s = make_float4(0.f, 0.f, 0.f, 0.f);
#pragma unroll
    for (int t = 0; t < N; t++) {
      ok &= __float_as_uint(v[t].w) == tag;
      s.x += v[t].x;
      s.y += v[t].y;
      s.z += v[t].z;
    }
    if (ok) break;
    __nanosleep(200);
  }
  return s;
}

#define PHASE_IDS                                  \
  const int tid_ = fresh_tid();                    \
  const int lane = tid_ & 31, wwarp = __shfl_sync(0xffffffffu, (tid_ >> 5) & 3, 0), tid = tid_ & 127; \
  const int g = lane >> 2, c = lane & 3;           \
  (void)tid; (void)g; (void)c; (void)wwarp;

#define PHASE_IDS_W                                \
  const int lane = fresh_tid() & 31, wwarp = warp & 3; \
  const int g = lane >> 2, c = lane & 3;

#define GTL(i) do { } while (0)
#define TGET(v) do { } while (0)
#define TPUT(c, i, v) do { } while (0)

constexpr float SM_C = 0.17677669529663687f * 1.4426950408889634f;

__device__ __forceinline__ void stmatrix_x4_if(bool ok, uint32_t addr, uint32_t r0, uint32_t r1, uint32_t r2, uint32_t r3) {
  asm volatile("{\n.reg .pred p;\nsetp.ne.b32 p, %5, 0;\n@p stmatrix.sync.aligned.m8n8.x4.shared.b16 [%0], {%1,%2,%3,%4};\n}\n" ::"r"(addr),
               "r"(r0), "r"(r1), "r"(r2), "r"(r3), "r"((int)ok));
}

__device__ __forceinline__ void attn_a_slow(const uint8_t* __restrict__ kvimg, int L, int gb, int hp, uint32_t bad,
                                            int row0, int lane) {
  constexpr uint32_t sq = SBASE + OFF_SLOT + 3 * 16384;
#pragma unroll 1
  for (int j = 0; j < 8; j++) {
    const uint8_t* tp = kvimg + (size_t)(gb * 16 + hp) * 32768 + (j * 32 + lane) * 128 + ((lane & 7) << 4);
#pragma unroll 1
    for (uint32_t it = 0; it < (1u << 17); ++it)
      if (((ld_relaxed_u32(tp) ^ kv_tag(L)) & 1u) == 0u) break;
  }
  __syncwarp();
#pragma unroll 1
  for (int t = 0; t < 32; t++) {
    const int hh = t >> 4, row = row0 + (t & 7) + (t & 8) * 4;
    if (!((bad >> hh) & 1u)) continue;
    const int qpos = gb * 128 + row;
    const uint32_t qaddr = sq + row * 128;
    float mx = -INFINITY, sum = 0.f, acc = 0.f;
#pragma unroll 1
    for (int pass = 0; pass < 2; pass++) {
#pragma unroll 1
      for (int j = 0; j < 8; j++) {
        const int kp = qpos - (lane + 32 * j);
        const uint8_t* kr = kvimg + ((size_t)((kp >> 7) * 16 + hp) * 2 + ((kp >> 6) & 1)) * 16384 + (kp & 63) * 128;
        float d = -INFINITY;
        if (kp >= 0) {
          d = 0.f;
#pragma unroll 1
          for (int q = 0; q < 4; q++) {
            const uint4 kv = __ldcg(reinterpret_cast<const uint4*>(kr + (((hh * 4 + q) ^ (kp & 7)) << 4)));
            const uint4 qv = lds128(qaddr + (((hh * 4 + q) ^ (row & 7)) << 4));
            const uint32_t kw[4] = {kv.x, kv.y, kv.z, kv.w}, qw[4] = {qv.x, qv.y, qv.z, qv.w};
#pragma unroll
            for (int e = 0; e < 4; e++) d = fmaf(bf_lo(kw[e]), bf_lo(qw[e]), fmaf(bf_hi(kw[e]), bf_hi(qw[e]), d));
          }
        }
        if (pass == 0) {
          mx = fmaxf(mx, d);
        } else {
          const float ev = ex2_approx(d - mx);
          sum += ev;
          const float pv = bf16_round(ev);
#pragma unroll 1
          for (int kk = 0; kk < 32; kk++) {
            const float pk = __shfl_sync(0xffffffffu, pv, kk);
            const int k2 = qpos - (kk + 32 * j);
            if (k2 >= 0) {
              const uint8_t* vr = kvimg + ((size_t)((k2 >> 7) * 16 + hp) * 2 + ((k2 >> 6) & 1)) * 16384 + 8192 + (k2 & 63) * 128;
              const unsigned short vv =
                  __ldcg(reinterpret_cast<const unsigned short*>(vr + (((hh * 4 + (lane >> 3)) ^ (k2 & 7)) << 4) + (lane & 7) * 2));
              acc = fmaf(pk, __uint_as_float((uint32_t)vv << 16), acc);
            }
          }
        }
      }
      if (pass == 0) {
#pragma unroll
        for (int o = 16; o > 0; o >>= 1) mx = fmaxf(mx, __shfl_xor_sync(0xffffffffu, mx, o));
      }
    }
#pragma unroll
    for (int o = 16; o > 0; o >>= 1) sum += __shfl_xor_sync(0xffffffffu, sum, o);
    acc *= rcp_fast(sum);
    const float hi = __shfl_down_sync(0xffffffffu, acc, 1);
    __syncwarp();
    if ((lane & 1) == 0) sts32(qaddr + (((hh * 4 + (lane >> 3)) ^ (row & 7)) << 4) + (lane & 7) * 2,
                               set_tag(pack_bf16x2(acc, hi), hh == 0 && lane == 0, o_tag(L)));
    __syncwarp();
  }
}

template <int HH>
__device__ __forceinline__ void store_o(const float (&o)[16], const float (&inv)[2], uint32_t ra, uint32_t tag, bool ok) {
  const uint32_t m = HH == 0 && (fresh_tid() & 3) == 0;
#pragma unroll
  for (int jp = 0; jp < 2; jp++) {
    uint32_t w0 = pack_bf16x2(o[8 * jp] * inv[0], o[8 * jp + 1] * inv[0]);
    uint32_t w1 = pack_bf16x2(o[8 * jp + 2] * inv[1], o[8 * jp + 3] * inv[1]);
    if (HH == 0 && jp == 0) {
      w0 = set_tag(w0, m, tag);
      w1 = set_tag(w1, m, tag);
    }
    stmatrix_x4_if(ok, ra ^ ((HH * 4 + 2 * jp) << 4), w0, w1, pack_bf16x2(o[8 * jp + 4] * inv[0], o[8 * jp + 5] * inv[0]),
                   pack_bf16x2(o[8 * jp + 6] * inv[1], o[8 * jp + 7] * inv[1]));
  }
}
__device__ __forceinline__ int tile_row(bool B, int w, int r, int g) { return (B ? 16 * w + 8 * r : 8 * w + 32 * r) + g; }
__device__ __forceinline__ uint32_t q_row_addr(bool B, int R, int w, int lane) {
  return SBASE + OFF_SLOT + 3 * 16384 + R * 8192 + tile_row(B, w, (lane >> 3) & 1, lane & 7) * 128 + (((lane >> 4) ^ (lane & 7)) << 4);
}

struct AttnA {
  float s[2][16], o[2][16], l[2][2], sh[2][3];
  uint32_t p[2][4], t[2], me[4], ra, bad, zero;
};
#define ATS_(i) do { } while (0)
template <int V>
__device__ __forceinline__ void attn_sum(AttnA& a, int nv) {
  constexpr int hh = (V >> 1) & 1, kh = V & 1, i = V >> 2;
#pragma unroll
  for (int r = 0; r < 2; r++) {
    const uint32_t t1 = add_bf16x2(add_bf16x2(a.p[0][r], a.p[0][2 + r]), add_bf16x2(a.p[1][r], a.p[1][2 + r]));
    if (kh == 0) {
      a.t[r] = t1;
    } else {
      uint32_t tt = add_bf16x2(a.t[r], t1);
      if (i > 0) tt = i <= nv ? tt : 0u;
      const float v = bf_lo(tt) + bf_hi(tt);
      a.l[hh][r] = i == 0 ? v : a.l[hh][r] + v;
    }
  }
}
template <int HH>
__device__ __forceinline__ void attn_shfl(AttnA& a) {
#pragma unroll
  for (int r = 0; r < 2; r++)
#pragma unroll
    for (int j = 0; j < 3; j++) a.sh[r][j] = __shfl_xor_sync(0xffffffffu, a.l[HH][r], j + 1);
}
template <int HH>
__device__ __forceinline__ void attn_fin(AttnA& a) {
  bool bad = false;
  float inv[2];
#pragma unroll
  for (int r = 0; r < 2; r++) {
    const float v = (a.l[HH][r] + a.sh[r][0]) + (a.sh[r][1] + a.sh[r][2]);
    bad |= !(v <= 1.152921504606846976e18f && v >= 8.673617379884035e-19f);
    inv[r] = rcp_fast(v);
  }
  bad = __any_sync(0xffffffffu, bad);
  if (HH == 1) wgmma_wait<0>();
  reg_fence<16>(a.o[HH]);
  store_o<HH>(a.o[HH], inv, a.ra, o_tag(0), !bad);
  a.bad = (HH == 0 ? 0u : a.bad) | (bad ? 1u << HH : 0u);
}
__device__ __forceinline__ void attn_masks(AttnA& a, int wr) {
  const int lane = fresh_tid() & 31, d = (lane >> 2) - 2 * (lane & 3);
  const uint32_t tri = d >= 1 ? 0xffffffffu : (d == 0 ? 0xffffu : 0u);
#pragma unroll
  for (int t = 0; t < 4; t++) a.me[t] = wr > t ? 0xffffffffu : (wr == t ? tri : 0u);
}
template <int V, int K>
__device__ __forceinline__ uint32_t attn_exp(AttnA& a) {
  constexpr int i = V >> 2, kh = V & 1, r = K & 1;
  if ((i == 0 && kh > r) || (i == 4 && kh < r)) return 0u;
  const uint32_t w = pack_bf16x2(ex2_approx(a.s[V & 1][2 * K]), ex2_approx(a.s[V & 1][2 * K + 1]));
  if (i == 0 && kh == r) return w & a.me[K >> 1];
  if (i == 4 && kh == r) return w & ~a.me[K >> 1];
  return w;
}
template <int V>
__device__ __forceinline__ void attn_unit(AttnA& a, const uint32_t (&q)[2][2][4], uint64_t dcur, uint64_t dnext, int R, int wr, int nv,
                                          uint32_t hbar, uint32_t hpar, uint32_t rbar, bool rel) {
  constexpr int hh = (V >> 1) & 1, kh = V & 1, i = V >> 2;
  ATS_(V + 1);
  asm volatile("" : "+l"(dcur), "+l"(dnext));
  wgmma_wait<1>();
  reg_fence<16>(a.s[V & 1]);
  bool hok = true;
  if (V == 4) hbar = SBASE + OFF_BAR + 8u * (R ? B_LOC : B_HV);
  if (((V & 3) == 2 && V < 16) || V == 4) hok = mbar_test(hbar, hpar);
  const uint64_t d0 = ((V & 3) >= 2 ? dnext : dcur) + ((hh ^ 1) * 4 + kh * 256), d1 = ((V & 3) >= 2 ? dnext : dcur) + ((hh ^ 1) * 4 + kh * 256 + 2);
  const uint64_t d2 = dcur + (512 + hh * 4 + kh * 256), d3 = dcur + (640 + hh * 4 + kh * 256);
  if ((V & 3) == 1 && V > 4 && rel) mbar_arrive(rbar);
  if (V > 0) attn_sum<V - 1>(a, nv);
  if (V == 15) attn_masks(a, wr);
  if (V == 18) {
    attn_shfl<0>(a);
    a.ra = q_row_addr(false, R, wr, fresh_tid() & 31);
  }
  if (V == 19) attn_fin<0>(a);
  uint32_t p[2][4];
  p[0][0] = attn_exp<V, 0>(a);
  p[0][1] = attn_exp<V, 1>(a);
  p[0][2] = attn_exp<V, 2>(a);
  p[0][3] = attn_exp<V, 3>(a);
  p[1][0] = attn_exp<V, 4>(a);
  p[1][1] = attn_exp<V, 5>(a);
  p[1][2] = attn_exp<V, 6>(a);
  p[1][3] = attn_exp<V, 7>(a);
  if (V > 0) {
#pragma unroll
    for (int r = 0; r < 2; r++) p[1][r] ^= (kh ? a.t[r] : __float_as_uint(a.l[hh ^ 1][r])) & a.zero;
  }
#pragma unroll
  for (int k = 0; k < 8; k++) {
    asm volatile("" : "+r"(p[k >> 2][k & 3]));
    a.p[k >> 2][k & 3] = p[k >> 2][k & 3];
  }
  if (!hok) mbar_wait(hbar, hpar);
  wgmma_fence();
  if (V < 18) wgmma_n32_rsz_tb0(a.s[V & 1], q[hh ^ 1][0], d0);
  if (i == 0 && kh == 0) wgmma_n32_rsz_tb1(a.o[hh], a.p[0], d2);
  else wgmma_n32_rs_tb1(a.o[hh], a.p[0], d2, 1);
  if (V < 18) wgmma_n32_rs_tb0(a.s[V & 1], q[hh ^ 1][1], d1, 1);
  wgmma_n32_rs_tb1(a.o[hh], a.p[1], d3, 1);
  wgmma_commit();
}
template <int I>
__device__ __forceinline__ void attn_step(AttnA& a, const uint32_t (&q)[2][2][4], uint64_t dcur, uint64_t dnext, int R, int wr, int nv,
                                          uint32_t hbar, uint32_t hpar, uint32_t rbar, bool rel) {
  attn_unit<4 * I>(a, q, dcur, dnext, R, wr, nv, hbar, hpar, rbar, rel);
  attn_unit<4 * I + 1>(a, q, dcur, dnext, R, wr, nv, hbar, hpar, rbar, rel);
  attn_unit<4 * I + 2>(a, q, dcur, dnext, R, wr, nv, hbar, hpar, rbar, rel);
  attn_unit<4 * I + 3>(a, q, dcur, dnext, R, wr, nv, hbar, hpar, rbar, rel);
}

__device__ __forceinline__ void attention_a(const uint32_t (&q)[2][2][4], int R, int L, int gb, int hp, uint32_t par, int wr,
                                            uint32_t zero) {
  constexpr uint32_t bars = SBASE + OFF_BAR;
  constexpr uint32_t dslot = ((SBASE + OFF_SLOT) >> 4) + 0x10000u;
  auto next = [&](uint64_t d) { return desc_lo((uint32_t)d == dslot ? dslot + 2048 : (uint32_t)d - 1024) + zero; };
  uint64_t d0 = desc_lo(dslot + R * 1024) + zero, d1 = next(d0);
  AttnA a;
  ATS_(0);
  wgmma_fence();
#pragma unroll
  for (int v = 0; v < 2; v++) {
    wgmma_n32_rsz_tb0(a.s[v], q[0][0], d0 + v * 256);
    wgmma_n32_rs_tb0(a.s[v], q[0][1], d0 + (v * 256 + 2), 1);
    wgmma_commit();
  }
  a.zero = zero;
  const bool lane0 = (fresh_tid() & 31) == 0;
  attn_masks(a, wr);
  const int nv = 2 * gb + R;
  const uint32_t hb = bars + 8u * (B_HALO - R), rb = bars + 8u * (B_REL - R);
  attn_step<0>(a, q, d0, d1, R, wr, nv, hb, par, 0, false);
  d0 = next(d1);
  attn_step<1>(a, q, d1, d0, R, wr, nv, R ? bars + 8u * B_HV : hb + 8, par, rb + 8, lane0);
  d1 = next(d0);
  attn_step<2>(a, q, d0, d1, R, wr, nv, hb + 16, par, rb + 16, lane0);
  d0 = next(d1);
  attn_step<3>(a, q, d1, d0, R, wr, nv, hb + 24, par, rb + 24, lane0 && R);
  attn_step<4>(a, q, d0, d0, R, wr, nv, 0, 0, rb, false);
  ATS_(21);
  attn_sum<19>(a, nv);
  attn_shfl<1>(a);
  attn_fin<1>(a);
  ATS_(22);
  if (a.bad != 0u) {
    attn_a_slow(g_kvA[0][0][0], L, gb, hp, a.bad, R * 64 + wr * 8, fresh_tid() & 31);
    named_bar_sync(7, 32);
  }
}

constexpr uint32_t KB_ROW0 = SBASE + OFF_SLOT + 2048, VB_ROW0 = SBASE + OFF_SLOT + 24576 + 2048;

__device__ __forceinline__ void attention_b(const uint32_t (&q)[2][2][4], int R, int gb, uint32_t par0, int wr) {
  constexpr uint32_t bars = SBASE + OFF_BAR;
  const uint32_t dk = ((KB_ROW0 - 2048) >> 4) + 0x10000u + R * 512, dv = dk + ((VB_ROW0 - KB_ROW0) >> 4);
  float s[2][40];
  mbar_wait(bars + 8u * (B_HALO - R), par0);
  wgmma_fence();
#pragma unroll
  for (int hh = 0; hh < 2; hh++) {
    wgmma_n80_rsz_tb0(s[hh], q[hh][0], desc_lo(dk + hh * 4));
    wgmma_n80_rs_tb0(s[hh], q[hh][1], desc_lo(dk + hh * 4 + 2), 1);
  }
  wgmma_commit();
  const int lane = fresh_tid() & 31, g = lane >> 2;
  const bool odd = g & 1, edge = R == 0 && gb == 0 && wr == 0;
  const int D = 2 * (lane & 3) + (g & 1) - g;
  const uint32_t ra = q_row_addr(true, R, wr, lane);
  wgmma_wait<0>();
  reg_fence<40>(s[0]);
  reg_fence<40>(s[1]);
  float z[2][2], y[2][2];
#define GATHER_(W)                                                                                          \
  _Pragma("unroll") for (int hh = 0; hh < 2; hh++) _Pragma("unroll") for (int r = 0; r < 2; r++) {          \
    const float* e = &s[hh][4 * (2 * W + r) + 2 * r];                                                       \
    z[hh][r] = odd ? e[5] : e[4];                                                                           \
    y[hh][r] = D >= 2 ? (odd ? e[1] : e[0]) : (odd ? e[9] : e[8]);                                          \
  }
  if (wr < 2) {
    if (wr == 0) { GATHER_(0) } else { GATHER_(1) }
  } else {
    if (wr == 2) { GATHER_(2) } else { GATHER_(3) }
  }
#undef GATHER_
  float o[2][16], inv[2][2];
  uint32_t p[2][5][4];
  const int sh = odd ? 16 : 0, kb = wr + (D >= 2 ? 0 : 1);
#pragma unroll
  for (int hh = 0; hh < 2; hh++) {
    if (edge) {
      z[hh][0] = -INFINITY;
      if (D >= 2) y[hh][0] = y[hh][1] = -INFINITY;
    }
    uint32_t ab[2][2];
#pragma unroll
    for (int r = 0; r < 2; r++) {
      float m = fmaxf(z[hh][r], y[hh][r]);
      m = fmaxf(m, __shfl_xor_sync(0xffffffffu, m, 1));
      m = fmaxf(m, __shfl_xor_sync(0xffffffffu, m, 2));
      const float e0 = ex2_approx(z[hh][r] - m), e1 = ex2_approx(y[hh][r] - m);
      inv[hh][r] = e0 + e1;
      ab[r][0] = pack_bf16x2(e0, 0.f) << sh;
      ab[r][1] = pack_bf16x2(e1, 0.f) << sh;
    }
#pragma unroll
    for (int k = 0; k < 5; k++) {
      p[hh][k][0] = k == kb ? ab[0][1] : 0u;
      p[hh][k][1] = k == wr + 1 ? ab[1][0] : 0u;
      p[hh][k][2] = k == wr ? ab[0][0] : 0u;
      p[hh][k][3] = k == kb ? ab[1][1] : 0u;
#pragma unroll
      for (int j = 0; j < 4; j++) asm volatile("" : "+r"(p[hh][k][j]));
    }
  }
  wgmma_fence();
#pragma unroll
  for (int hh = 0; hh < 2; hh++) {
    wgmma_n32_rsz_tb1(o[hh], p[hh][0], desc_lo(dv + hh * 4));
#pragma unroll
    for (int k = 1; k < 5; k++) wgmma_n32_rs_tb1(o[hh], p[hh][k], desc_lo(dv + hh * 4 + k * 128), 1);
  }
  wgmma_commit();
#pragma unroll
  for (int hh = 0; hh < 2; hh++)
#pragma unroll
    for (int r = 0; r < 2; r++) {
      inv[hh][r] += __shfl_xor_sync(0xffffffffu, inv[hh][r], 1);
      inv[hh][r] += __shfl_xor_sync(0xffffffffu, inv[hh][r], 2);
      inv[hh][r] = rcp_fast(inv[hh][r]);
    }
  wgmma_wait<0>();
  reg_fence<16>(o[0]);
  reg_fence<16>(o[1]);
  store_o<0>(o[0], inv[0], ra, o_tag(1), true);
  store_o<1>(o[1], inv[1], ra, o_tag(1), true);
}

#define KTQM 0
#define TRICKLE 300
#define QREL 5
#define PRESLEEP 200
#define CSA 5
#define PN1 4
#define PN2 5
#define TLAZY 100
#define SDLY 1500
#define HTS(i) do { } while (0)
struct Params {
  CUtensorMap x[5], xq[4], o, wqkv[2], wqkv3[2], wo3[2];
  const __nv_bfloat16* in_x;
  const __nv_bfloat16* wqkv_p[2];
  const __nv_bfloat16* wo_p[2];
  __nv_bfloat16* out;
  uint32_t zero;
};

__device__ __forceinline__ void colsum_part(const CUtensorMap* wmap, int ty, int qr, int hp) {
  constexpr uint32_t bars = SBASE + OFF_BAR, slots = SBASE + OFF_SLOT;
  PHASE_IDS
  const unsigned ep1 = launch_epoch();
  if (wwarp == 0 && elect_one()) {
    mbar_expect_tx(bars + 8u * B_CS, 6 * UNIT);
#pragma unroll 1
    for (int j = 0; j < 6; j++) {
      if (ty == 0) mbar_pace(bars + 8u * (B_QF + B_E + ((j * CSA / 6) & 3)), (j * CSA / 6) >> 2, j ? PN1 : 30);
      else mbar_wait_lazy<100>(bars + 8u * (B_WF + B_E + ((2 * j + 3 - (j & 1)) & 7)), j >= 3);
      tma_load_2d(slots + j * UNIT, wmap, bars + 8u * B_CS, (j >> 1) * 1024 + hp * 64, qr * 128 + (j & 1) * 64);
    }
  }
  constexpr uint64_t ones = (SBASE + OFF_LSB + 32) >> 4;
  float s[3][4];
  mbar_wait_lazy<100>(bars + 8u * B_CS, ty);
  wgmma_fence();
#pragma unroll
  for (int p = 0; p < 3; p++) {
    wgmma_n8_ssz_ta1_tb0(s[p], make_desc(slots + p * 2 * UNIT, 16), ones);
#pragma unroll
    for (int k = 1; k < 8; k++) wgmma_n8_ss_ta1_tb0(s[p], make_desc(slots + p * 2 * UNIT + k * 2048, 16), ones, 1);
  }
  wgmma_commit();
  wgmma_wait<0>();
  reg_fence<12>(&s[0][0]);
  if (lane == 0) mbar_arrive(bars + 8u * (ty ? B_CSD : B_RDONE));
  if (c == 0) {
#pragma unroll
    for (int r = 0; r < 2; r++) st_rec(&g_cs[ty][hp][qr][wwarp * 16 + 8 * r + g], s[0][2 * r], s[1][2 * r], s[2][2 * r], ep1);
  }
}

__device__ __forceinline__ void put_colsums(int ty, int col, const float4& s) {
  const float v[3] = {s.x, s.y, s.z};
#pragma unroll
  for (int p = 0; p < 3; p++) {
    const uint32_t a = SBASE + OFF_CS + (p * 8 + (col >> 3)) * 64 + ty * 32 + (col & 7) * 2;
    const float hi = bf16_round(v[p]);
    const uint32_t w = pack_bf16x2(hi, v[p] - hi);
    asm volatile("st.shared.b16 [%0], %1;" ::"r"(a), "h"((unsigned short)w) : "memory");
    asm volatile("st.shared.b16 [%0], %1;" ::"r"(a + 16), "h"((unsigned short)(w >> 16)) : "memory");
  }
}

__device__ __forceinline__ uint32_t ln_params(float s1, float s2) {
  const float mean = s1 * (1.0f / DM);
  const float var = fmaxf(fmaf(-mean, mean, s2 * (1.0f / DM)), 0.f);
  float sd;
  asm("sqrt.approx.f32 %0, %1;" : "=f"(sd) : "f"(bf16_round(bf16_round(var) + 1e-5f)));
  return pack_bf16x2(mean, sd);
}

__host__ __device__ constexpr uint32_t w_rel(int kt) { return ((B_WF + (kt & 7)) << 1) | (kt >> 3); }
__host__ __device__ constexpr uint32_t w_rel4(int a, int b, int c, int d) { return w_rel(a) | (w_rel(b) << 8) | (w_rel(c) << 16) | (w_rel(d) << 24); }
__device__ __forceinline__ void ring_wait(uint32_t e) { mbar_wait(SBASE + OFF_BAR + 8u * B_E + ((e << 2) & 0x3f8u), e & 1u); }
struct RingProd {
  uint32_t rel = ((B_QF << 1) | 1) * 0x01010101u + 0x06040200u;
  __device__ __forceinline__ void q_step(int kt) {
    const int sh = 8 * (kt & 3);
    const uint32_t e = rel >> sh;
    rel ^= ((e ^ (((B_QF + (kt & 3)) << 1) | ((kt >> 2) & 1))) & 255u) << sh;
    ring_wait(e);
  }
  __device__ __forceinline__ void w_job(int st, bool pre, uint32_t sel0, uint32_t sel1, uint32_t last, uint32_t& w0, uint32_t& w1) {
    const uint32_t r = __funnelshift_r(rel, rel, 8 * st);
    w0 = __byte_perm(r, 0u, sel0);
    w1 = __byte_perm(r, w_rel4(0, 1, 2, 3), pre ? sel1 : 0x6543u);
    const uint32_t n = pre ? (w_rel4(9, 11, 13, 0) & 0xffffffu) | (last << 24) : (w_rel4(11, 13, 0, 15) & 0xff00ffffu) | (last << 16);
    rel = __funnelshift_l(n, n, 8 * st);
  }
};

#define SP1 15
#define SP2 13
#define SP3 11
#define SP4 11
#define SP5 15
#define SP6 13
#define SP7 16
__device__ __forceinline__ int q_split(int inst) {
  constexpr uint32_t T = 15u | ((SP1 - 1) << 4) | ((SP2 - 1) << 8) | ((SP3 - 1) << 12) | ((SP4 - 1) << 16) | ((SP5 - 1) << 20) |
                         ((SP6 - 1) << 24) | ((uint32_t)(SP7 - 1) << 28);
  return (int)((T >> (4 * inst)) & 15u) + 1;
}
#define QROT 4
#define WROT 2
__device__ __forceinline__ int qk(int kt) { return (((kt & 12) | ((kt & 1) << 1) | ((kt >> 1) & 1)) + QROT) & 15; }
__device__ __forceinline__ int wk(int kt) { return (kt + WROT) & 15; }
__host__ __device__ constexpr uint32_t turn_par(int kind) {
  const int sp[8] = {16, SP1, SP2, SP3, SP4, SP5, SP6, SP7};
  int cnt[2] = {0, 0};
  uint32_t m = 0;
  for (int i = 0; i < 8; i++)
    for (int k = 0; k < 3; k++) {
      if (k == kind) m |= (uint32_t)(cnt[i & 1] & 1) << i;
      if (k == 0 ? (i == 1 || (i > 1 && sp[i - 1] < 16)) : (k == 2 || sp[i] < 16)) cnt[i & 1]++;
    }
  return m;
}
#define PREMASK 0xBFu
__device__ __forceinline__ bool w_pre(int inst) { return (PREMASK >> inst) & 1u; }
#define STGMASK 0x2Eu
__device__ __forceinline__ bool w_stg(int inst) { return (STGMASK >> inst) & 1u; }
__device__ __forceinline__ uint32_t w_out(int inst) {
  return w_stg(inst) ? SBASE + OFF_SLOT : SBASE + (((inst < 7 ? q_split(inst + 1) : 0) + (w_pre(inst) ? 3 : 2)) & 3) * 5 * UNIT;
}
__host__ __device__ constexpr unsigned long long bar_counts(int i0) {
  unsigned long long t = 0;
  for (int i = i0; i < i0 + 32; i++) {
    int l = 0;
    if (i < B_RF) l = 1;
    if ((i >= B_E && i < B_E + B_RF) || i == B_LOC || i == B_REL || i == B_OS0 || i == B_TURN || i == B_TURN + 1 || i == B_XS ||
        i == B_XS + 1 || i == B_CSD || i == B_GO || i == B_RDONE || i == B_KV)
      l = 2;
    if (i == B_REL + 1 || i == B_REL + 2) l = 3;
    t |= (unsigned long long)l << (2 * (i - i0));
  }
  return t;
}

__global__ void __launch_bounds__(512, 1) fused_kernel(const __grid_constant__ Params P) {
  extern __shared__ __align__(1024) uint8_t smem_raw[];
  constexpr uint32_t base = SBASE, bars = base + OFF_BAR, slots = base + OFF_SLOT;
  if (smem_u32(smem_raw) != base) __trap();
  const int warp = __shfl_sync(0xffffffffu, threadIdx.x >> 5, 0), lane = threadIdx.x & 31;
  const int b = blockIdx.x;
#define QS 1
#define WS 1
  const int qr = ((b & ((8 << QS) - 1)) >> QS) ^ (((b >> (3 + QS)) & 1) * 7);
  const int hp = ((b >> (3 + QS)) << QS) + (b & ((1 << QS) - 1));
  const int rt = ((b & ((16 << WS) - 1)) >> WS) ^ (((b >> (4 + WS)) & 1) * 15);
  const int ct = ((b >> (4 + WS)) << WS) + (b & ((1 << WS) - 1));

  if (warp == 12) {
    if (elect_one()) {
#pragma unroll 1
      for (int s = 0; s < 4; s++) {
        const uint32_t fb = bars + 8u * (B_QF + s), sa = base + s * 5 * UNIT;
        mbar_init(fb, 2);
        fence_barrier_init();
        mbar_expect_tx(fb, 5 * UNIT);
        mbar_arrive(fb);
        tma_load_5d(sa + 3 * UNIT, &P.xq[0], fb, s * 64, qr * 2);
        tma_load_3d(sa, &P.wqkv3[0], fb, hp * 64, s * 64);
      }
    }
    __syncwarp();
  } else if (warp >= 4 && warp < 12) {
    if (elect_one()) {
#pragma unroll 1
      for (int i = warp; i <= B_KV; i += 8) mbar_init(bars + 8u * i, 1u << (((i < 32 ? bar_counts(0) : bar_counts(32)) >> (2 * (i & 31))) & 3u));
      sts32(warp < 8 ? base + OFF_ONE - 16 + 4 * warp : base + OFF_LSB + 4 * warp, warp < 8 ? warp == 4 : 0x3f803f80u);
      fence_proxy_async_smem();
      fence_barrier_init();
    }
    __syncwarp();
  }

  if (warp >= 12) {
    setmaxnreg_dec<32>();
    if (warp == 12) {
      named_bar_sync(0, 512);
      if (elect_one()) {
#pragma unroll 1
        for (int s = 4; s < 16; s++) {
          const uint32_t fb = bars + 8u * (B_QF + (s & 3)), sa = base + (s & 3) * 5 * UNIT;
          mbar_wait(fb + 8u * B_E, ((s >> 2) & 1) ^ 1);
          mbar_expect_tx(fb, 5 * UNIT);
          mbar_arrive(fb);
          tma_load_5d(sa + 3 * UNIT, &P.xq[0], fb, s * 64, qr * 2);
          tma_load_3d(sa, &P.wqkv3[0], fb, hp * 64, s * 64);
        }
#pragma unroll
        for (int s = 0; s < 4; s++) mbar_arrive(bars + 8u * B_GO);
        RingProd rp;
#pragma unroll 1
        for (int sg = 4; sg < 34; sg++) {
          const int part = sg & 3, inst = (sg >> 2) - (part & 1);
          if (part == 3 || inst == 8) continue;
          const int ty = (inst >> 1) & 1;
          if (part != 1) {
            const int k0 = part ? q_split(inst) : 0, k1 = part ? 16 : q_split(inst);
#pragma unroll 1
            for (int kt = k0; kt < k1; kt++) {
              const uint32_t sa = base + (kt & 3) * 5 * UNIT, fb = bars + 8u * (B_QF + (kt & 3));
              rp.q_step(kt);
              mbar_expect_tx(fb, 3 * UNIT);
              tma_load_3d(sa, &P.wqkv3[ty], fb, hp * 64, qk(kt) * 64);
            }
          } else {
            const bool pre = w_pre(inst);
            int st = inst < 7 ? q_split(inst + 1) & 3 : 0;
            uint32_t w0, w1;
            rp.w_job(st, pre, pre ? 0x1100u : 0x2100u, 0x3322u, w_stg(inst) ? w_rel(15) : (B_RF << 1) | (inst & 1), w0, w1);
#pragma unroll 1
            for (int m = 0; m < 4; m++) {
              const uint32_t fb = bars + 8u * (B_WF + 4 * (m & 1));
#pragma unroll
              for (int i = 0; i < 4; i++) {
                if (i < 3 || !pre) {
                  ring_wait(w0 >> (8 * i));
                  mbar_expect_tx(fb + 8u * i, 2 * UNIT);
                  tma_load_3d(base + ((st + (i ? i - 1 : 0)) & 3) * 5 * UNIT + ((0x2d >> (2 * i)) & 3) * UNIT, &P.wo3[ty], fb + 8u * i,
                              ct * 128, wk(4 * m + i) * 64);
                }
              }
              st += pre ? 2 : 3;
              w0 = w1;
              w1 = m == 0 ? (pre ? w_rel4(0, 1, 2, 3) : w_rel4(3, 4, 5, 6)) : (pre ? w_rel4(4, 5, 6, 7) : w_rel4(7, 8, 9, 10));
            }
          }
        }
      }
    } else if (warp == 13) {
      RingProd rp;
      unsigned ep1 = 0;
      uint32_t seenx = 0;
      named_bar_sync(0, 512);
      mbar_wait(bars + 8u * B_GO, 0);
#pragma unroll 1
      for (int sg = 4; sg < 34; sg++) {
        const int part = sg & 3, inst = (sg >> 2) - (part & 1);
        if (part == 3 || inst == 8) continue;
        const int L = inst >> 1, ch = inst & 1;
        if (part != 1) {
          const CUtensorMap* tx = &P.xq[L];
          const int k0 = part ? q_split(inst) : 0, k1 = part ? 16 : q_split(inst);
          if (sg == 4) ep1 = launch_epoch();
          if (part == 0) seenx = L == 0 ? 0xffffffffu : peek_counts(g_fx[ch * 8 + qr][0], 6u * ep1 - 6u + 2u * L, lane);
          const int m0 = ch * 16 + qr * 2;
#pragma unroll 1
          for (int kt = k0; kt < k1; kt++) {
            const uint32_t fb = bars + 8u * (B_QF + (kt & 3));
            rp.q_step(kt);
            if (lane == 0) mbar_expect_tx(fb, 2 * UNIT);
            wait_count(g_fx[ch * 8 + qr][0], 6u * ep1 - 6u + 2u * L, qk(kt), seenx, lane);
            TGET(t38);
            if (elect_one()) tma_load_5d(base + ((kt & 3) * 5 + 3) * UNIT, tx, fb, qk(kt) * 64, m0);
            TGET(t39);
            if (L == 3 && kt == 0 && lane == 0) { TPUT(ch, 38, t38); TPUT(ch, 39, t39); }
          }
        } else {
          const int m0 = ch * 1024 + rt * 64;
          const bool pre = w_pre(inst);
          int st = inst < 7 ? q_split(inst + 1) & 3 : 0;
          uint32_t w0, w1;
          uint32_t seen = peek_counts(g_fo[ch * 16 + rt][0], 4u * ep1 - 3u + L, lane);
          rp.w_job(st, pre, 0x1110u, 0x3332u, inst == 6 && SP7 == 16 ? B_RF << 1 : w_rel(15), w0, w1);
#pragma unroll 1
          for (int m = 0; m < 4; m++) {
            const uint32_t fb = bars + 8u * (B_WF + 4 * (m & 1));
#pragma unroll
            for (int i = 0; i < 4; i++) {
              ring_wait(w0 >> (8 * i));
              if (lane == 0) mbar_expect_tx(fb + 8u * i, UNIT);
              wait_count(g_fo[ch * 16 + rt][0], 4u * ep1 - 3u + L, wk(4 * m + i), seen, lane);
              if (elect_one())
                tma_load_2d(base + ((st + (i > 0)) & 3) * 5 * UNIT + (i == 2 ? 1 : (i == 3 ? 4 : 0)) * UNIT, &P.o, fb + 8u * i, wk(4 * m + i) * 64, m0);
            }
            st += pre ? 2 : 3;
            w0 = w1;
            w1 = m == 0 ? (pre ? w_rel4(0, 1, 2, 3) : w_rel4(3, 4, 5, 6)) : (pre ? w_rel4(4, 5, 6, 7) : w_rel4(7, 8, 9, 10));
          }
        }
      }
#pragma unroll 1
      for (int j = 0; j < 8; j++)
        g_x[(size_t)((j >> 2) * 1024 + rt * 64 + (j & 3) * 16 + (lane >> 1)) * DM + ct * 128 + (lane & 1) * 64] = __ushort_as_bfloat16(0);
    } else if (warp == 14) {
      const unsigned ep1 = launch_epoch();
      uint32_t hpar = 0;
      named_bar_sync(0, 512);
#pragma unroll 1
      for (int inst = 0; inst < 8; inst++) {
        const int L = inst >> 1, ch = inst & 1, gb = ch * 8 + qr;
        const unsigned kv0 = 8u * ep1 - 8u + 2u * L + (L & 1);
        const uint32_t tag = kv_tag(L);
        if (L >= 2) {
#pragma unroll 1
          for (uint32_t it = 0; it < (1u << 17); ++it)
            if (__all_sync(0xffffffffu, (int)(ld_relaxed_u32(g_fk[hp][min(gb + 1 + (lane & 1), 15)]) - kv0) >= 0)) break;
        }
        if ((L & 1) == 0) {
          uint8_t* img = g_kvA[gb][hp][0];
          const uint8_t* s1 = gb > 0 ? img - 16 * 32768 : g_zero;
          const uint8_t* s2 = gb > 1 ? img - 32 * 32768 : g_zero;
          const uint32_t h1 = gb > 0 ? 16384 : 0, h2 = gb > 1 ? 16384 : 0;
          const unsigned* cp = g_fk[hp][max(gb - 1 - (lane >= 3), 0)];
          const unsigned ct0 = kv0 + ((0x32321u >> (4 * (lane & 7))) & 3u);
          uint32_t fr = gb == 0 ? 31u : (gb == 1 ? 24u : 0u);
          const uint32_t toff = slots + lane * 128 + ((lane & 7) << 4);
          auto seen = [&](uint32_t m) {
#pragma unroll 1
            for (uint32_t it = 0; it < (1u << 17) && !(fr & m); ++it)
              fr |= __ballot_sync(0xffffffffu, (int)(ld_relaxed_u32(cp) - ct0) >= 0);
          };
          auto load = [&](uint32_t off, const uint8_t* src, uint32_t bytes, int bi) {
            if (elect_one()) {
              mbar_expect_tx(bars + 8u * (B_HL + bi), bytes);
              bulk_load(slots + off, src, bytes, bars + 8u * (B_HL + bi));
            }
          };
          auto check = [&](uint32_t off, const uint8_t* src, uint32_t bytes, int bi, bool real, int done) {
#pragma unroll 1
            for (int tries = 0; tries < 4096; tries++) {
              mbar_wait(bars + 8u * (B_HL + bi), (hpar >> bi) & 1u);
              hpar ^= 1u << bi;
              uint32_t t = (lds32(toff + off) ^ tag) | (lds32(toff + off + 4096) ^ tag);
              if (bytes > 8192) t |= (lds32(toff + off + 8192) ^ tag) | (lds32(toff + off + 12288) ^ tag);
              if (!__any_sync(0xffffffffu, real && (t & 1u))) break;
              fence_proxy_async_smem();
              load(off, src, bytes, bi);
            }
            if (lane == 0) mbar_arrive(bars + 8u * done);
          };
          uint8_t *pk = img + 16384, *pv = img + 24576;
          unsigned* f = g_fk[hp][gb];
          pin64(pk), pin64(pv), pin64(f);
          mbar_wait(bars + 8u * B_KV, inst & 1);
          if (ch) mbar_wait(bars + 8u * (B_RF + B_E), 0);
          if (elect_one()) {
            bulk_store(pk, slots + 16384, 8192);
            bulk_announce(f);
            bulk_store(pv, slots + 24576, 8192);
            bulk_announce(f);
            bulk_commit();
          }
          HTS(44);
          seen(1);
          HTS(46);
          load(32768, s1 + h1, 8192, 0);
          seen(2);
          HTS(47);
          load(40960, s1 + h1 + 8192, 8192, 1);
          mbar_wait(bars + 8u * B_LOC, inst & 1);
          HTS(45);
          if (elect_one()) {
            bulk_store(img, slots, 16384);
            bulk_announce(g_fk[hp][gb]);
            bulk_commit();
            asm volatile("cp.async.bulk.wait_group.read 1;" ::: "memory");
          }
          check(32768, s1 + h1, 8192, 0, gb > 0, B_HALO);
          HTS(52);
          check(40960, s1 + h1 + 8192, 8192, 1, gb > 0, B_HV);
          HTS(53);
#pragma unroll 1
          for (int n = 1; n < 4; n++) {
            const uint8_t* src = n == 1 ? s1 : (n == 2 ? s2 + h2 : s2);
            const uint32_t off = n == 3 ? 32768 : 32768 - n * 16384;
            seen(2u << n);
            if (n == 2 && elect_one()) bulk_wait_read0();
            mbar_wait(bars + 8u * (B_REL - 1) + 8u * n, ch);
            HTS(47 + n);
            load(off, src, 16384, 0);
            check(off, src, 16384, 0, gb > (n >> 1), B_HALO + n);
            HTS(53 + n);
          }
        } else {
          uint8_t *pk = g_kvB[gb][hp], *pv = pk + 2048;
          const uint8_t* src = gb >= 1 ? pk - 16 * 4096 : g_zero;
          unsigned* f = g_fk[hp][gb];
          pin64(pk), pin64(pv), pin64(f), pin64(src);
          mbar_wait(bars + 8u * B_KV, inst & 1);
          if (elect_one()) {
            bulk_store(pk, KB_ROW0 + 112 * 128, 2048);
            bulk_store(pv, VB_ROW0 + 112 * 128, 2048);
            bulk_announce(f);
            bulk_commit();
          }
          HTS(44);
          if (gb > 0) {
#pragma unroll 1
            for (uint32_t it = 0; it < (1u << 17); ++it)
              if (__any_sync(0xffffffffu, (int)(ld_relaxed_u32(f - 4) - kv0) > 0)) break;
          }
          HTS(46);
#pragma unroll 1
          for (uint32_t it = 0; it < (1u << 17); ++it) {
            if (elect_one()) {
              mbar_expect_tx(bars + 8u * B_HL, 4096);
              bulk_load(KB_ROW0 - 2048, src, 2048, bars + 8u * B_HL);
              bulk_load(VB_ROW0 - 2048, src + 2048, 2048, bars + 8u * B_HL);
            }
            mbar_wait(bars + 8u * B_HL, hpar & 1u);
            hpar ^= 1u;
            const uint32_t t = lds32((lane < 16 ? KB_ROW0 - 2048 : VB_ROW0 - 4096) + lane * 128 + ((lane & 7) << 4)) ^ tag;
            if (!__any_sync(0xffffffffu, gb > 0 && (t & 1u))) break;
            fence_proxy_async_smem();
          }
          if (lane == 0) mbar_arrive(bars + 8u * B_HALO);
          HTS(52);
        }
        if (elect_one()) {
          const CUtensorMap* mo = &P.o;
          unsigned *f1 = g_fo[gb * 2 + 1][hp], *f0 = g_fo[gb * 2][hp];
          int c0 = hp * 64, r0 = gb * 128, r1 = r0 + 64;
          pin64(mo), pin64(f1), pin64(f0);
          asm volatile("" : "+r"(c0), "+r"(r0), "+r"(r1));
          mbar_wait(bars + 8u * B_OS1, (inst & 1) ^ 1);
          tma_store_2d(mo, slots + 7 * UNIT, c0, r1);
          bulk_announce(f1);
          bulk_commit();
          mbar_wait(bars + 8u * B_OS0, inst & 1);
          tma_store_2d(mo, slots + 6 * UNIT, c0, r0);
          bulk_announce(f0);
          bulk_commit();
          HTS(57);
          const bool pre = w_pre(inst);
          bulk_wait_read0();
          HTS(58 - 15);
          mbar_expect_tx(bars + 8u * B_RF, 2 * UNIT);
          tma_load_2d(slots + 6 * UNIT, &P.x[L], bars + 8u * B_RF, ct * 128, ch * 1024 + rt * 64);
          tma_load_2d(slots + 7 * UNIT, &P.x[L], bars + 8u * B_RF, ct * 128 + 64, ch * 1024 + rt * 64);
          if (pre) {
            const uint32_t pp = __popc(PREMASK & ((1u << inst) - 1u)) & 1;
            mbar_expect_tx(bars + 8u * B_PRE, 2 * UNIT);
            mbar_expect_tx(bars + 8u * B_PRE2, 6 * UNIT);
#pragma unroll 1
            for (int j = 0; j < 4; j++) {
              __nanosleep(PRESLEEP);
              if (j == 3) mbar_wait(bars + 8u * B_RDONE, (inst & 1) ^ 1);
              tma_load_3d(slots + j * 2 * UNIT, &P.wo3[L & 1], bars + 8u * (j ? B_PRE2 : B_PRE), ct * 128, wk(4 * j + 3) * 64);
            }
#pragma unroll 1
            for (int j = 0; j < 4; j++) {
              const uint32_t fb = bars + 8u * (B_WF + 3 + 4 * (j & 1));
              if (j < 2) mbar_wait(bars + 8u * (j ? B_PRE2 : B_PRE), pp);
              if (j < 2 && inst == 7 && SP7 == 16) mbar_wait(bars + 8u * (B_TURN + 1), (turn_par(2) >> 7) & 1u);
              mbar_wait(fb + 8u * B_E, j < 2);
              mbar_arrive(fb);
            }
          }
        }
        __syncwarp();
      }
    } else {
      const unsigned ep1 = launch_epoch();
      named_bar_sync(0, 512);
      mbar_wait(bars + 8u * B_GO, 0);
#pragma unroll 1
      for (int i = 0; i < 20; i++) {
        const char* src = i < 4 ? reinterpret_cast<const char*>(P.wo_p[0]) + (size_t)b * 16384 + i * 4096
                                : (i < 16 ? reinterpret_cast<const char*>(P.wqkv_p[1]) + (size_t)b * 49152 + (i - 4) * 4096
                                          : reinterpret_cast<const char*>(P.wo_p[1]) + (size_t)b * 16384 + (i - 16) * 4096);
        asm volatile("prefetch.global.L2 [%0];" ::"l"(src + lane * 128));
        __nanosleep(TRICKLE);
      }
#pragma unroll 1
      for (int inst = 2; inst < 10; inst++) {
        const int L = inst >> 1, ch = inst & 1, gb = ch * 8 + qr;
        {
          uint32_t xb = w_out(inst - 2);
          unsigned* f = g_fx[ch * 8 + (rt >> 1)][ct * 2];
          const CUtensorMap* mx = &P.x[L];
          int c0 = ct * 128, r0 = ch * 1024 + rt * 64;
          pin64(f), pin64(mx);
          asm volatile("" : "+r"(xb), "+r"(c0), "+r"(r0));
#pragma unroll
          for (int h = 0; h < 2; h++) {
            mbar_wait(bars + 8u * (B_XS + h), ch);
            if (elect_one()) {
              tma_store_2d(mx, xb + h * UNIT, c0 + h * 64, r0);
              if (L < 4) bulk_announce(f + 4 * h);
              bulk_commit();
              if (h == 1) {
                bulk_wait_read0();
                mbar_arrive(bars + 8u * (B_RF + B_E));
              }
            }
          }
          if (L == 4) continue;
          __nanosleep(SDLY);
        }
#pragma unroll 1
        for (int h = 0; h < 4; h++) {
          const float4* sp = &g_stats[0][gb * 128 + h * 32 + lane];
          const float4 s0 = sum_recs<4>(sp, S_LEN, 4u * ep1 + L), s1 = sum_recs<4>(sp + 4 * S_LEN, S_LEN, 4u * ep1 + L);
          sts32(base + OFF_RS + (ch * 128 + h * 32 + lane) * 4, ln_params(s0.x + s1.x, s0.y + s1.y));
        }
        if (inst == 2) {
#pragma unroll 1
          for (int hf = 0; hf < 2; hf++) {
            const float4* cp = &g_cs[1][hp][0][hf * 32 + lane];
            const float4 s0 = sum_recs<4>(cp, 64, ep1), s1 = sum_recs<4>(cp + 4 * 64, 64, ep1);
            put_colsums(1, hf * 32 + lane, make_float4(s0.x + s1.x, s0.y + s1.y, s0.z + s1.z, 0.f));
          }
        }
        fence_proxy_async_smem();
        __syncwarp();
        if (lane == 0) mbar_arrive(bars + 8u * (B_PREP + ch));
      }
    }
  } else {
    const bool asst = warp >= 8;
    GTL(0);
    if (warp >= 4) named_bar_sync(0, 512);
    if (warp >= 4 && !asst) {
      PHASE_IDS
      {
        const unsigned ep1 = launch_epoch();
        const int row = b * 16 + (tid >> 3);
        const uint4* src = reinterpret_cast<const uint4*>(P.in_x + (size_t)row * DM) + (tid & 7);
        float s1 = 0.f, s2 = 0.f;
#pragma unroll 1
        for (int k = 0; k < 4; k++) {
          mbar_pace(bars + 8u * (B_QF + B_E + ((2 * k) & 3)), k >> 1, k ? PN2 : 30);
          uint4 v[4];
#pragma unroll
          for (int j = 0; j < 4; j++) v[j] = __ldg(src + (k * 4 + j) * 8);
#pragma unroll
          for (int j = 0; j < 4; j++) {
            const uint32_t w[4] = {v[j].x, v[j].y, v[j].z, v[j].w};
#pragma unroll
            for (int e = 0; e < 4; e++) {
              const float x0 = bf_lo(w[e]), x1 = bf_hi(w[e]);
              s1 += x0 + x1;
              s2 = fmaf(x0, x0, fmaf(x1, x1, s2));
            }
          }
        }
#pragma unroll
        for (int o = 1; o < 8; o <<= 1) {
          s1 += __shfl_xor_sync(0xffffffffu, s1, o);
          s2 += __shfl_xor_sync(0xffffffffu, s2, o);
        }
        if ((tid & 7) == 0) st_rec(&g_stats[0][row], s1, s2, 0.f, 4u * ep1);
        if (tid == 0) sts32(base + OFF_EPOCH, ep1);
        if (tid < 64) {
          const float4 s0 = sum_recs<8>(&g_cs[0][hp][0][tid], 64, ep1);
          put_colsums(0, tid, s0);
        } else {
          put_colsums(1, tid - 64, make_float4(0.f, 0.f, 0.f, 0.f));
        }
#pragma unroll 1
        for (int cc = 0; cc < 2; cc++) {
          const float4 s0 = sum_recs<1>(&g_stats[0][(cc * 8 + qr) * 128 + tid], 0, 4u * ep1);
          sts32(base + OFF_RS + (cc * 128 + tid) * 4, ln_params(s0.x, s0.y));
        }
        fence_proxy_async_smem();
        named_bar_sync(2, 128);
        if (tid < 2) mbar_arrive(bars + 8u * (B_PREP + tid));
      }
    }
#pragma unroll 1
    for (int inst = asst ? 0 : warp >> 2; inst < 8; inst += asst ? 1 : 2) {
      const int L = inst >> 1, ch = inst & 1, gb = ch * 8 + qr;
      uint32_t q[2][2][4];
      if (asst) {
        if (inst < 2) colsum_part(&P.wqkv[inst], inst, qr, hp);
        setmaxnreg_dec<24>();
        named_bar_sync(4, 256);
        setmaxnreg_inc<128>();
        const uint32_t ra = q_row_addr(L & 1, 1, warp & 3, fresh_tid() & 31);
#pragma unroll
        for (int j = 0; j < 4; j++) ldmatrix_x4(q[j >> 1][j & 1], ra ^ (j << 5));
      } else {
      setmaxnreg_inc<224>();
      {
        float acc[2][96];
        const int ksp = q_split(inst);
        constexpr uint32_t STG = 5 * (UNIT >> 4), D0 = ((base + 3 * UNIT) >> 4) + 0x10000u;
        constexpr uint32_t DB = ((UNIT >> 4) << 16) - 0x10000u - 3 * (UNIT >> 4);
        const uint32_t toff = ((fresh_tid() & 127) << 7) + ((fresh_tid() & 7) << 4);
        const bool lane0 = (toff & 0xf80u) == 0u;
        uint32_t xt = x_tag(L), tro = (warp & 3) * 2048 + (toff & 0x7f0u) + ((toff << 2) & 0x2000u);
        auto check_x = [&](uint32_t bar, uint32_t par, uint32_t ta, int kt, uint32_t mask) {
          fix_lines(bar, par, ta, xt, mask, 7, [&](int l) {
            return g_x + (size_t)(gb * 128 + (l >> 4) * 64 + tile_row(L & 1, warp & 3, (l >> 3) & 1, l & 7)) * DM + qk(kt) * 64;
          });
        };
        uint32_t rsa = base + OFF_RS + (ch * 128 + tile_row(L & 1, warp & 3, 0, (toff >> 9) & 7)) * 4;
        uint32_t rsb = rsa + ((L & 1) ? 32 : 128);
        uint32_t lnm = ((toff >> 7) & 3) == (L & 1) ? 0xffffffffu : 0u, tmk = L > 0;
        uint32_t soff = tile_row(L & 1, warp & 3, (toff >> 10) & 1, (toff >> 7) & 7) * 128 + ((toff ^ (toff >> 7)) & 0x10u) + (toff & 0x60u);
        uint32_t bprep = bars + 8u * (B_PREP + ch), bturn = bars + 8u * (B_TURN + (ch ^ 1));
        const bool stg = inst > 0 && w_stg(inst - 1);
        uint32_t bfree = bars + 8u * (inst == 1 ? B_CSD : (stg ? B_RF + B_E : B_RDONE));
        uint32_t pfree = inst == 1 ? 0 : (inst & 1) ^ stg, pprep = L & 1;
        asm volatile("" : "+r"(rsa), "+r"(rsb), "+r"(lnm), "+r"(soff), "+r"(xt), "+r"(tmk), "+r"(tro));
        asm volatile("" : "+r"(bprep), "+r"(bturn), "+r"(bfree), "+r"(pfree), "+r"(pprep));
        if (inst == 0) named_bar_sync(0, 512);
        if (inst == 1 || (inst > 1 && q_split(inst - 1) < 16)) mbar_wait_lazy<TLAZY>(bars + 8u * (B_TURN + ch), (turn_par(0) >> inst) & 1u);
        if (L == 3) GTL(37);
        check_x(bars + 8u * B_QF, 0, base + 3 * UNIT + tro, 0, tmk);
        GTL(1 + L * 8);
        {
          const uint64_t da = desc_lo(D0) + P.zero;
          wgmma_fence();
          wgmma_n192_ssz_ta0_tb1(acc[1], da + (UNIT >> 4), da + DB);
          wgmma_commit();
          wgmma_n192_ssz_ta0_tb1(acc[0], da, da + DB);
          wgmma_commit();
        }
        int left = ksp;
        asm volatile("" : "+r"(left));
        uint64_t da = desc_lo(D0) + P.zero, dn = da + STG;
        uint32_t fn = bars + 8u * (B_QF + 1), pn = 0, ta = base + 8 * UNIT + tro;
#pragma unroll 1
        for (int kt = 0; kt < 15; kt++) {
          bool ok, last;
          uint32_t tw;
#pragma unroll
          for (int k16 = 0; k16 < 4; k16++) {
            if (k16 == 0 && kt == 0) continue;
            wgmma_fence();
            wgmma_n192_ss_ta0_tb1(acc[1], da + ((UNIT >> 4) + k16 * 2), da + (DB + k16 * 128), 1);
            wgmma_commit();
            if (k16 == 0) {
              const int s1 = (kt + 1) & 3;
              dn = desc_lo(D0 + s1 * STG) + P.zero;
              ta = base + 3 * UNIT + s1 * 5 * UNIT + tro;
            }
            if (k16 == 1) last = --left == 0;
            if (k16 == 3) ok = !__any_sync(0xffffffffu, !ok || ((tw ^ xt) & tmk)) && !last;
            wgmma_wait<1>();
            if (k16 == 0 && lane0 && left != 0) mbar_arrive(bars + 8u * (B_QF + B_E + ((kt - 1) & 3)));
            wgmma_fence();
            wgmma_n192_ss_ta0_tb1(acc[0], da + k16 * 2, da + (DB + k16 * 128), 1);
            wgmma_commit();
            if (k16 == 0) {
              fn = bars + 8u * (B_QF + ((kt + 1) & 3));
              pn = ((kt + 1) >> 2) & 1;
            }
            if (k16 == 2) {
              ok = mbar_test(fn, pn);
              tw = lds32(ta);
              if (last && lane0) mbar_arrive(bturn);
            }
            if (k16 < 3) wgmma_wait<1>();
          }
          da = dn;
          if (!ok) {
            if (last) {
              wgmma_wait<0>();
              if (lane0) mbar_arrive(bars + 8u * (B_QF + B_E + (kt & 3)));
            }
            if (last) mbar_wait_lazy<TLAZY>(bars + 8u * (B_TURN + ch), (turn_par(1) >> inst) & 1u);
            check_x(fn, pn, ta, kt + 1, tmk);
          }
        }
        constexpr uint32_t DL = D0 + 3 * STG;
        wgmma_fence();
#pragma unroll
        for (int k16 = 0; k16 < 4; k16++) wgmma_n192_ss_ta0_tb1(acc[1], desc_lo(DL + (UNIT >> 4) + k16 * 2), desc_lo(DL + DB + k16 * 128), 1);
        wgmma_commit();
        mbar_wait(bprep, pprep);
        uint32_t rs[2][2];
        constexpr uint64_t DCS = (uint64_t)((base + OFF_CS) >> 4) | (4ull << 32);
        auto ln_mma = [&](float (&d)[96], uint32_t (&r)[2], int h) {
          uint32_t a[4];
#pragma unroll
          for (int i = 0; i < 2; i++) {
            if (h) r[i] = lds32((i ? rsb : rsa) + 256);
            a[i] = (__byte_perm(r[i], 0u, 0x1010) ^ 0x80008000u) & lnm;
            a[i + 2] = r[i] & P.zero;
          }
#pragma unroll
          for (int i = 0; i < 4; i++) asm volatile("" : "+r"(a[i]));
          wgmma_fence();
          wgmma_n192_rs_tb1(d, a, DCS, 1);
          wgmma_commit();
        };
        ln_mma(acc[1], rs[1], 1);
        wgmma_wait<2>();
        if (lane0 && ksp != 15) mbar_arrive(bars + 8u * (B_QF + B_E + 2));
        wgmma_fence();
#pragma unroll
        for (int k16 = 0; k16 < 4; k16++) wgmma_n192_ss_ta0_tb1(acc[0], desc_lo(DL + k16 * 2), desc_lo(DL + DB + k16 * 128), 1);
        wgmma_commit();
        if (lane0) mbar_arrive(bturn);
        rs[0][0] = lds32(rsa);
        rs[0][1] = lds32(rsb);
        static_assert(SP1 < 16 && SP5 < 16 && (PREMASK & 1u) && !(STGMASK & 1u), "column sums of B");
        const bool afree = mbar_test(bfree, pfree) & (mbar_test(bars + 8u * (B_WF + B_E + 7), 1) | (ksp == 16));
        float rinv[2];
#pragma unroll
        for (int r = 0; r < 2; r++) {
          rinv[r] = rcp_fast(bf_hi(rs[1][r]));
          asm volatile("" : "+f"(rinv[r]));
        }
        const uint32_t kdst = ((L & 1) ? KB_ROW0 : slots) + soff, vdst = ((L & 1) ? VB_ROW0 : slots + 8192) + soff;
        const uint32_t hs = (L & 1) ? 8192 : 16384, c0 = (toff & 0x180u) == 0u;
        wgmma_wait<1>();
        ln_mma(acc[0], rs[0], 0);
        reg_fence<96>(acc[1]);
        GTL(2 + L * 8);
        if (!afree) {
          mbar_wait(bfree, pfree);
          if (ksp < 16) mbar_wait(bars + 8u * (B_WF + B_E + 7), 1);
        }
#pragma unroll
        for (int t = 0; t < 24; t++) {
          const int h = t < 12 ? 1 : 0, p = ((t % 12) / 4 + 1) % 3, jp = t & 3;
          if (t == QREL) {
            wgmma_wait<0>();
            reg_fence<96>(acc[0]);
            if (lane0) mbar_arrive(bars + 8u * (B_QF + B_E + 3));
          }
          if (t == 8 || t == 20) {
            rinv[0] *= SM_C;
            rinv[1] *= SM_C;
          }
          const float* a = &acc[h][4 * (p * 8 + 2 * jp)];
          uint32_t r0 = pack_bf16x2(a[0] * rinv[0], a[1] * rinv[0]);
          uint32_t r1 = pack_bf16x2(a[2] * rinv[1], a[3] * rinv[1]);
          if (p != 0 && jp == 0) {
            r0 = set_tag(r0, c0, kv_tag(L));
            r1 = set_tag(r1, c0, kv_tag(L));
          }
          const uint32_t r2 = pack_bf16x2(a[4] * rinv[0], a[5] * rinv[0]);
          const uint32_t r3 = pack_bf16x2(a[6] * rinv[1], a[7] * rinv[1]);
          const uint32_t dst = p == 0 ? slots + 3 * 16384 + soff + h * 8192 : (p == 1 ? kdst : vdst) + h * hs;
          stmatrix_x4(dst ^ (jp << 5), r0, r1, r2, r3);
          if (t >= 20) {
            q[jp >> 1][jp & 1][0] = r0;
            q[jp >> 1][jp & 1][1] = r1;
            q[jp >> 1][jp & 1][2] = r2;
            q[jp >> 1][jp & 1][3] = r3;
          }
          if (t == 7 || t == 19) signal_async(bars + 8u * (t == 7 ? B_KV : B_LOC), lane0);
          if (t == 11) {
            setmaxnreg_dec<128>();
            named_bar_arrive(4, 256);
#pragma unroll
            for (int r = 0; r < 2; r++) rinv[r] = rcp_fast(bf_hi(rs[0][r]));
          }
        }
        mbar_wait(bars + 8u * B_LOC, inst & 1);
      }
      }
      GTL(3 + L * 8);
      if ((L & 1) == 0) attention_a(q, asst, L, gb, hp, ch, warp & 3, P.zero);
      else attention_b(q, asst, gb, inst & 1, warp & 3);
      GTL(4 + L * 8);
      signal_async(bars + 8u * (asst ? B_OS1 : B_OS0), (fresh_tid() & 31) == 0);
      if (asst) continue;
      GTL(5 + L * 8);

      {
        float acc[64];
        const int sp = inst < 7 ? q_split(inst + 1) : 0;
        const int st = sp & 3;
        const bool pre = w_pre(inst);
        const uint32_t toff = ((fresh_tid() & 63) << 7) + ((fresh_tid() & 7) << 4);
        uint32_t tro = (warp & 3) * 2048 + (toff & 0x7f0u);
        auto check_o = [&](uint32_t bar, uint32_t par, uint32_t sa, int kt) {
          fix_lines(bar, par, sa + tro, o_tag(L), 1u, 7, [&](int l) {
            return g_o + (size_t)(ch * 1024 + rt * 64 + (warp & 3) * 16 + (l & 15)) * DM + wk(kt) * 64;
          });
        };
        const bool lane0 = (toff & 0xf80u) == 0u;
        constexpr uint32_t U4 = UNIT >> 4, LA = 0x10000u, LB = U4 << 16;
        reg_define<64>(acc);
        reg_fence<64>(acc);
        uint32_t xv[8][4];
        {
          PHASE_IDS_W
          const uint32_t xr = slots + 6 * UNIT + (wwarp * 16 + (lane & 15)) * 128 + (((lane >> 4) ^ (lane & 7)) << 4);
          mbar_wait(bars + 8u * B_RF, inst & 1);
#pragma unroll
          for (int jp = 0; jp < 8; jp++) ldmatrix_x4(xv[jp], (xr ^ ((jp & 3) << 5)) + (jp >> 2) * UNIT);
          signal_async(bars + 8u * B_RDONE, lane0);
          if (L > 0) {
            uint32_t lsb;
            asm volatile("ld.shared.u8 %0, [%1];" : "=r"(lsb) : "r"(base + OFF_LSB + ch * 32 + wwarp * 8 + g) : "memory");
#pragma unroll
            for (int k = 0; k < 4; k++) xv[(k >> 1) * 4][k & 1] = set_tag(xv[(k >> 1) * 4][k & 1], c == 0, lsb >> k);
          }
        }
        uint32_t tmx = L < 3 && (toff & 0x180u) == 0u, xt = x_tag(L + 1);
        uint32_t xrow = w_out(inst) + (warp & 3) * 2048 + (toff & 0x7e0u) + ((toff ^ (toff >> 7)) & 0x10u);
        asm volatile("" : "+r"(tmx), "+r"(xt), "+r"(xrow), "+r"(tro));
        const uint64_t dz = desc_lo(0) + P.zero;
        auto nexts = [&](uint32_t a) { return a == base + 15 * UNIT ? base : a + 5 * UNIT; };
        uint32_t s0 = base + st * 5 * UNIT, sp3 = slots, fb = bars + 8u * B_WF;
        int turn = lane0 && (sp < 16 || inst == 6) ? 3 : -1;
        asm volatile("" : "+r"(turn));
        if (inst < 7 || SP7 == 16) mbar_wait_lazy<TLAZY>(bars + 8u * (B_TURN + ch), (turn_par(2) >> inst) & 1u);
        check_o(bars + 8u * B_WF, 0, s0, 0);
        GTL(6 + L * 8);
#pragma unroll 1
        for (int m = 0; m < 4; m++) {
          uint32_t s1, s2;
#pragma unroll
          for (int i = 0; i < 4; i++) {
            const uint64_t da = dz + ((i == 0 ? s0 : s1) >> 4) + (LA + (i == 2 ? 1 : (i == 3 ? 4 : 0)) * U4);
            const uint64_t db = dz + ((i < 2 ? s0 : (i == 2 ? s1 : s2)) >> 4) + (LB + (i == 0 ? 1 : (i == 1 ? 3 : (i == 2 ? 2 : 0))) * U4);
            wgmma_fence();
#pragma unroll
            for (int k16 = 0; k16 < 4; k16++) wgmma_n128_ss_ta0_tb1(acc, da + 2 * k16, db + 128 * k16, 1);
            wgmma_commit();
            if (i == 0) s1 = nexts(s0);
            if (i == 1) s0 = nexts(s1);
            if (i == 2) {
              s2 = pre ? sp3 : s0;
              s0 = pre ? s0 : nexts(s0);
              sp3 += 2 * UNIT;
            }
            const uint32_t fn = i < 3 ? fb + 8u * (i + 1) : fb ^ 96u;
            const uint32_t pn = i < 3 ? m >> 1 : m > 0;
            const uint32_t an = i < 3 ? s1 + (i == 1 ? 1 : (i == 2 ? 4 : 0)) * UNIT : s0;
            bool ok = mbar_test(fn, pn);
            const uint32_t tw = lds32(an + tro);
            ok = !__any_sync(0xffffffffu, (!ok || ((tw ^ o_tag(L)) & 1u)) && (i < 3 || m < 3));
            wgmma_wait<1>();
            if (lane0 && (i > 0 || m > 0)) mbar_arrive((i > 0 ? fb + 8u * (i - 1) : (fb ^ 96u) + 24u) + 8u * B_E);
            if (i == 2 && m == turn) mbar_arrive(bars + 8u * (B_TURN + (ch ^ 1)));
            if (!ok) check_o(fn, pn, an, 4 * m + i + 1);
          }
          fb ^= 96u;
        }
        wgmma_wait<0>();
        reg_fence<64>(acc);
        if (lane0) mbar_arrive(bars + 8u * (B_WF + B_E + 7));
        GTL(7 + L * 8);
#pragma unroll
        for (int jp = 0; jp < 8; jp++) {
#pragma unroll
          for (int q = 0; q < 4; q++) xv[jp][q] = add_bf16x2(xv[jp][q], pack_bf16x2(acc[8 * jp + 2 * q], acc[8 * jp + 2 * q + 1]));
          const bool tg = (jp & 3) == 0;
          stmatrix_x4((xrow ^ ((jp & 3) << 5)) + (jp >> 2) * UNIT,
                      tg ? set_tag(xv[jp][0], tmx, xt) : xv[jp][0], tg ? set_tag(xv[jp][1], tmx, xt) : xv[jp][1], xv[jp][2], xv[jp][3]);
          if ((jp & 3) == 3) signal_async(bars + 8u * (B_XS + (jp >> 2)), lane0);
        }
        if (L < 3) {
          PHASE_IDS_W
          const int grow = ch * 1024 + rt * 64;
          const unsigned ep1 = lds32(base + OFF_EPOCH);
          if (c == 0)
            asm volatile("st.shared.u8 [%0], %1;" ::"r"(base + OFF_LSB + ch * 32 + wwarp * 8 + g),
                         "r"((xv[0][0] & 1u) | ((xv[0][1] & 1u) << 1) | ((xv[4][0] & 1u) << 2) | ((xv[4][1] & 1u) << 3)) : "memory");
          float s1[2] = {0.f, 0.f}, s2[2] = {0.f, 0.f};
#pragma unroll
          for (int jp = 0; jp < 8; jp++)
#pragma unroll
            for (int q = 0; q < 4; q++) {
              const float x0 = bf_lo(xv[jp][q]), x1 = bf_hi(xv[jp][q]);
              s1[q & 1] += x0 + x1;
              s2[q & 1] = fmaf(x0, x0, fmaf(x1, x1, s2[q & 1]));
            }
#pragma unroll
          for (int r = 0; r < 2; r++) {
            s1[r] += __shfl_xor_sync(0xffffffffu, s1[r], 1);
            s2[r] += __shfl_xor_sync(0xffffffffu, s2[r], 1);
            s1[r] += __shfl_xor_sync(0xffffffffu, s1[r], 2);
            s2[r] += __shfl_xor_sync(0xffffffffu, s2[r], 2);
            if (c == 0) st_rec(&g_stats[ct][grow + wwarp * 16 + g + 8 * r], s1[r], s2[r], 0.f, 4u * ep1 + L + 1);
          }
        }
        GTL(8 + L * 8);
      }
    }
    if (threadIdx.x == 128) atomicAdd(g_done, 1u);
  }
}

typedef CUresult (*PFN_tmEncode)(CUtensorMap*, CUtensorMapDataType, cuuint32_t, void*, const cuuint64_t*,
                                 const cuuint64_t*, const cuuint32_t*, const cuuint32_t*, CUtensorMapInterleave,
                                 CUtensorMapSwizzle, CUtensorMapL2promotion, CUtensorMapFloatOOBfill);

PFN_tmEncode get_encode_fn() {
  static PFN_tmEncode fn = nullptr;
  if (!fn) {
    cudaDriverEntryPointQueryResult qr;
    void* p = nullptr;
    cudaGetDriverEntryPoint("cuTensorMapEncodeTiled", &p, cudaEnableDefault, &qr);
    fn = (PFN_tmEncode)p;
  }
  return fn;
}

CUtensorMap make_map(const void* ptr, int rows, int cols) {
  CUtensorMap m;
  cuuint64_t gdim[2] = {(cuuint64_t)cols, (cuuint64_t)rows};
  cuuint64_t gstr[1] = {(cuuint64_t)cols * 2};
  cuuint32_t box[2] = {64, 64};
  cuuint32_t estr[2] = {1, 1};
  get_encode_fn()(&m, CU_TENSOR_MAP_DATA_TYPE_BFLOAT16, 2, const_cast<void*>(ptr), gdim, gstr, box, estr,
                  CU_TENSOR_MAP_INTERLEAVE_NONE, CU_TENSOR_MAP_SWIZZLE_128B, CU_TENSOR_MAP_L2_PROMOTION_L2_128B,
                  CU_TENSOR_MAP_FLOAT_OOB_FILL_NONE);
  return m;
}

CUtensorMap make_map3(const void* ptr, int rows, int cols, int n, int step) {
  CUtensorMap m;
  cuuint64_t gdim[3] = {(cuuint64_t)(cols - (n - 1) * step), (cuuint64_t)rows, (cuuint64_t)n};
  cuuint64_t gstr[2] = {(cuuint64_t)cols * 2, (cuuint64_t)step * 2};
  cuuint32_t box[3] = {64, 64, (cuuint32_t)n};
  cuuint32_t estr[3] = {1, 1, 1};
  get_encode_fn()(&m, CU_TENSOR_MAP_DATA_TYPE_BFLOAT16, 3, const_cast<void*>(ptr), gdim, gstr, box, estr,
                  CU_TENSOR_MAP_INTERLEAVE_NONE, CU_TENSOR_MAP_SWIZZLE_128B, CU_TENSOR_MAP_L2_PROMOTION_L2_128B,
                  CU_TENSOR_MAP_FLOAT_OOB_FILL_NONE);
  return m;
}

CUtensorMap make_map_q(const void* ptr, int sw, int sr) {
  CUtensorMap m;
  cuuint64_t gdim[5] = {DM, 8, 2, 4, S_LEN / 64};
  cuuint64_t gstr[4] = {DM * 2, (cuuint64_t)sr * DM * 2, (cuuint64_t)sw * DM * 2, 64 * DM * 2};
  cuuint32_t box[5] = {64, 8, 2, 4, 2};
  cuuint32_t estr[5] = {1, 1, 1, 1, 1};
  get_encode_fn()(&m, CU_TENSOR_MAP_DATA_TYPE_BFLOAT16, 5, const_cast<void*>(ptr), gdim, gstr, box, estr,
                  CU_TENSOR_MAP_INTERLEAVE_NONE, CU_TENSOR_MAP_SWIZZLE_128B, CU_TENSOR_MAP_L2_PROMOTION_L2_128B,
                  CU_TENSOR_MAP_FLOAT_OOB_FILL_NONE);
  return m;
}

}

extern "C" void kernel_launch(void* const* d_in, const int* in_sizes, int n_in, void* d_out, int out_size) {
  (void)in_sizes; (void)n_in; (void)out_size;
  void *p_o, *p_x;
  cudaGetSymbolAddress(&p_o, g_o);
  cudaGetSymbolAddress(&p_x, g_x);
  static bool attr_done = false;
  if (!attr_done) {
    cudaFuncSetAttribute(fused_kernel, cudaFuncAttributeMaxDynamicSharedMemorySize, SMEM_BYTES);
    attr_done = true;
  }
  Params P;
  P.in_x = (const __nv_bfloat16*)d_in[0];
  P.wqkv_p[0] = (const __nv_bfloat16*)d_in[1];
  P.wo_p[0] = (const __nv_bfloat16*)d_in[2];
  P.wqkv_p[1] = (const __nv_bfloat16*)d_in[4];
  P.wo_p[1] = (const __nv_bfloat16*)d_in[5];
  P.out = (__nv_bfloat16*)d_out;
  P.zero = 0;
  for (int L = 0; L < 5; L++) {
    const void* px = L == 0 ? (const void*)P.in_x : (L == 4 ? d_out : p_x);
    P.x[L] = make_map(px, S_LEN, DM);
    if (L < 4) P.xq[L] = (L & 1) ? make_map_q(px, 16, 8) : make_map_q(px, 8, 32);
  }
  P.o = make_map(p_o, S_LEN, DM);
  for (int t = 0; t < 2; t++) {
    P.wqkv[t] = make_map(P.wqkv_p[t], DM, NQKV);
    P.wqkv3[t] = make_map3(P.wqkv_p[t], DM, NQKV, 3, 1024);
    P.wo3[t] = make_map3(P.wo_p[t], DM, DM, 2, 64);
  }
    fused_kernel<<<NCTA, 512, SMEM_BYTES>>>(P);
}
```

```cpp
#include <cuda_runtime.h>
#include <cuda_bf16.h>
#include <cuda.h>
#include <stdint.h>

namespace {

constexpr int S_LEN = 2048;
constexpr int DM = 1024;
constexpr int NQKV = 3072;
constexpr int NCTA = 128;

__device__ __align__(1024) uint8_t g_kvA[16][16][2][16384];
__device__ __align__(1024) uint8_t g_kvB[16][16][4096];
__device__ __align__(1024) uint8_t g_zero[16384];
__device__ __align__(1024) __nv_bfloat16 g_o[S_LEN * DM];
__device__ __align__(1024) __nv_bfloat16 g_x[S_LEN * DM];
__device__ __align__(1024) float4 g_stats[8][S_LEN];
__device__ __align__(1024) float4 g_cs[2][16][8][64];
__device__ __align__(128) unsigned g_fx[16][16][4];
__device__ __align__(128) unsigned g_fo[32][16][4];
__device__ __align__(128) unsigned g_fk[16][16][4];
__device__ __align__(128) unsigned g_done[32];

constexpr uint32_t SBASE = 1024;
constexpr int UNIT = 8192;
constexpr int NUNITS = 20;
constexpr int OFF_SLOT = NUNITS * UNIT;
constexpr int OFF_BAR = OFF_SLOT + 4 * 16384;
constexpr int OFF_EPOCH = OFF_BAR + 424;
constexpr int OFF_LSB = OFF_BAR + 432;
constexpr int OFF_CS = OFF_BAR + 496;
constexpr int OFF_RS = OFF_CS + 1536;
constexpr int OFF_ONE = OFF_RS + 1024;
constexpr int SMEM_BYTES = OFF_ONE + 16;
constexpr int B_QF = 0, B_WF = 4, B_RF = 12, B_E = 13, B_PREP = 26, B_LOC = 28, B_HALO = 29, B_REL = 33, B_OS0 = 36,
              B_TURN = 37, B_XS = 39, B_CS = 41, B_CSD = 42, B_GO = 43, B_PRE = 44, B_HV = 45, B_REDO = 46,
              B_RDONE = 48, B_PRE2 = 49, B_HL = 50, B_KV = 52, B_OS1 = B_GO;
static_assert(SMEM_BYTES <= 232448, "shared memory");

__device__ __forceinline__ uint32_t smem_u32(const void* p) { return (uint32_t)__cvta_generic_to_shared(p); }

__device__ __forceinline__ void mbar_init(uint32_t bar, uint32_t cnt) {
  asm volatile("mbarrier.init.shared::cta.b64 [%0], %1;" ::"r"(bar), "r"(cnt));
}
__device__ __forceinline__ void mbar_expect_tx(uint32_t bar, uint32_t bytes) {
  asm volatile("mbarrier.arrive.expect_tx.shared::cta.b64 _, [%0], %1;" ::"r"(bar), "r"(bytes) : "memory");
}
__device__ __forceinline__ void mbar_arrive(uint32_t bar) {
  asm volatile("mbarrier.arrive.shared::cta.b64 _, [%0];" ::"r"(bar) : "memory");
}
__device__ __forceinline__ bool mbar_try_wait(uint32_t bar, uint32_t parity) {
  uint32_t ok;
  asm volatile(
      "{\n.reg .pred p;\nmbarrier.try_wait.parity.shared::cta.b64 p, [%1], %2;\nselp.b32 %0, 1, 0, p;\n}\n"
      : "=r"(ok)
      : "r"(bar), "r"(parity)
      : "memory");
  return ok != 0;
}
__device__ __forceinline__ bool mbar_test(uint32_t bar, uint32_t parity) {
  uint32_t ok;
  asm volatile(
      "{\n.reg .pred p;\nmbarrier.test_wait.parity.shared::cta.b64 p, [%1], %2;\nselp.b32 %0, 1, 0, p;\n}\n"
      : "=r"(ok)
      : "r"(bar), "r"(parity)
      : "memory");
  return ok != 0;
}
__device__ __forceinline__ void mbar_wait(uint32_t bar, uint32_t parity) {
#pragma unroll 1
  for (uint32_t it = 0; it < (1u << 18); ++it) {
    if (mbar_try_wait(bar, parity)) return;
  }
}
__device__ __forceinline__ void mbar_pace(uint32_t bar, uint32_t parity, uint32_t n) {
#pragma unroll 1
  for (uint32_t it = 0; it < n; ++it) {
    if (mbar_test(bar, parity)) return;
    __nanosleep(100);
  }
}
template <int NS>
__device__ __forceinline__ void mbar_wait_lazy(uint32_t bar, uint32_t parity) {
#pragma unroll 1
  for (uint32_t it = 0; it < (1u << 18); ++it) {
    if (mbar_try_wait(bar, parity)) return;
    __nanosleep(NS);
  }
}
__device__ __forceinline__ bool elect_one() {
  uint32_t ok;
  asm volatile("{\n.reg .pred p;\nelect.sync _|p, 0xffffffff;\nselp.b32 %0, 1, 0, p;\n}\n" : "=r"(ok));
  return ok != 0;
}
__device__ __forceinline__ void fence_barrier_init() { asm volatile("fence.mbarrier_init.release.cluster;" ::: "memory"); }
__device__ __forceinline__ void fence_proxy_async_smem() { asm volatile("fence.proxy.async.shared::cta;" ::: "memory"); }

__device__ __forceinline__ void signal_async(uint32_t bar, bool lane0) {
  fence_proxy_async_smem();
  __syncwarp();
  asm volatile("{\n.reg .pred p;\nsetp.ne.b32 p, %1, 0;\n@p mbarrier.arrive.shared::cta.b64 _, [%0];\n}\n" ::"r"(bar), "r"((int)lane0) : "memory");
}
template <class T>
__device__ __forceinline__ void pin64(T*& p) { asm volatile("" : "+l"(p)); }

__device__ __forceinline__ void tma_load_2d(uint32_t dst, const CUtensorMap* map, uint32_t bar, int c0, int c1) {
  asm volatile(
      "cp.async.bulk.tensor.2d.shared::cluster.global.mbarrier::complete_tx::bytes [%0], [%1, {%3, %4}], [%2];" ::"r"(dst),
      "l"(map), "r"(bar), "r"(c0), "r"(c1)
      : "memory");
}
__device__ __forceinline__ void tma_load_3d(uint32_t dst, const CUtensorMap* map, uint32_t bar, int c0, int c1) {
  asm volatile(
      "cp.async.bulk.tensor.3d.shared::cluster.global.mbarrier::complete_tx::bytes [%0], [%1, {%3, %4, %5}], [%2];" ::"r"(dst),
      "l"(map), "r"(bar), "r"(c0), "r"(c1), "r"(0)
      : "memory");
}
__device__ __forceinline__ void tma_load_5d(uint32_t dst, const CUtensorMap* map, uint32_t bar, int c0, int c4) {
  asm volatile(
      "cp.async.bulk.tensor.5d.shared::cluster.global.mbarrier::complete_tx::bytes [%0], [%1, {%3, %5, %5, %5, %4}], [%2];" ::"r"(dst),
      "l"(map), "r"(bar), "r"(c0), "r"(c4), "r"(0)
      : "memory");
}
__device__ __forceinline__ void bulk_load(uint32_t dst, const void* src, uint32_t bytes, uint32_t bar) {
  asm volatile("cp.async.bulk.shared::cluster.global.mbarrier::complete_tx::bytes [%0], [%1], %2, [%3];" ::"r"(dst),
               "l"(src), "r"(bytes), "r"(bar)
               : "memory");
}
__device__ __forceinline__ void bulk_store(void* dst, uint32_t src, uint32_t bytes) {
  asm volatile("cp.async.bulk.global.shared::cta.bulk_group [%0], [%1], %2;" ::"l"(dst), "r"(src), "r"(bytes) : "memory");
}
__device__ __forceinline__ void tma_store_2d(const CUtensorMap* map, uint32_t src, int c0, int c1) {
  asm volatile("cp.async.bulk.tensor.2d.global.shared::cta.bulk_group [%0, {%2, %3}], [%1];" ::"l"(map), "r"(src),
               "r"(c0), "r"(c1)
               : "memory");
}
__device__ __forceinline__ void bulk_announce(unsigned* p) {
  asm volatile("cp.reduce.async.bulk.global.shared::cta.bulk_group.add.u32 [%0], [%1], 16;" ::"l"(p), "r"(SBASE + OFF_ONE) : "memory");
}
__device__ __forceinline__ void bulk_commit() { asm volatile("cp.async.bulk.commit_group;" ::: "memory"); }
__device__ __forceinline__ void bulk_wait_read0() { asm volatile("cp.async.bulk.wait_group.read 0;" ::: "memory"); }
__device__ __forceinline__ void bulk_wait0() { asm volatile("cp.async.bulk.wait_group 0;" ::: "memory"); }
__device__ __forceinline__ void named_bar_sync(int id, int nthreads) {
  asm volatile("bar.sync %0, %1;" ::"r"(id), "r"(nthreads) : "memory");
}
__device__ __forceinline__ void named_bar_arrive(int id, int nthreads) {
  asm volatile("bar.arrive %0, %1;" ::"r"(id), "r"(nthreads) : "memory");
}

__device__ __forceinline__ void wgmma_fence() { asm volatile("wgmma.fence.sync.aligned;\n" ::: "memory"); }
__device__ __forceinline__ void wgmma_commit() { asm volatile("wgmma.commit_group.sync.aligned;\n" ::: "memory"); }
template <int N>
__device__ __forceinline__ void wgmma_wait() {
  asm volatile("wgmma.wait_group.sync.aligned %0;\n" ::"n"(N) : "memory");
}
template <int R>
__device__ __forceinline__ void setmaxnreg_inc() { asm volatile("setmaxnreg.inc.sync.aligned.u32 %0;\n" ::"n"(R)); }
template <int R>
__device__ __forceinline__ void setmaxnreg_dec() { asm volatile("setmaxnreg.dec.sync.aligned.u32 %0;\n" ::"n"(R)); }
template <int N>
__device__ __forceinline__ void reg_fence(float* r) {
#pragma unroll
  for (int i = 0; i < N; i++) asm volatile("" : "+f"(r[i])::"memory");
}

template <int N>
__device__ __forceinline__ void reg_define(float* r) {
#pragma unroll
  for (int i = 0; i < N; i++) r[i] = 0.f;
}

__device__ __forceinline__ uint64_t desc_lo(uint32_t lo) {
  uint64_t d;
  asm("mov.b64 %0, {%1, %2};" : "=l"(d) : "r"(lo), "r"(0x40000040u));
  return d;
}
__device__ __forceinline__ uint64_t make_desc(uint32_t addr, uint32_t lbo_bytes) {
  return desc_lo((addr >> 4) + ((lbo_bytes >> 4) << 16));
}

__device__ __forceinline__ void wgmma_n192_ss_ta0_tb1(float* d, uint64_t descA, uint64_t descB, int scaleD) {
  asm volatile("{\n.reg .pred p;\nsetp.ne.b32 p, %98, 0;\n"
    "wgmma.mma_async.sync.aligned.m64n192k16.f32.bf16.bf16 {%0, %1, %2, %3, %4, %5, %6, %7, %8, %9, %10, %11, %12, %13, %14, %15, %16, %17, %18, %19, %20, %21, %22, %23, %24, %25, %26, %27, %28, %29, %30, %31, %32, %33, %34, %35, %36, %37, %38, %39, %40, %41, %42, %43, %44, %45, %46, %47, %48, %49, %50, %51, %52, %53, %54, %55, %56, %57, %58, %59, %60, %61, %62, %63, %64, %65, %66, %67, %68, %69, %70, %71, %72, %73, %74, %75, %76, %77, %78, %79, %80, %81, %82, %83, %84, %85, %86, %87, %88, %89, %90, %91, %92, %93, %94, %95}, %96, %97, p, 1, 1, 0, 1;\n}\n"
    : "+f"(d[0]), "+f"(d[1]), "+f"(d[2]), "+f"(d[3]), "+f"(d[4]), "+f"(d[5]), "+f"(d[6]), "+f"(d[7]), "+f"(d[8]), "+f"(d[9]), "+f"(d[10]), "+f"(d[11]), "+f"(d[12]), "+f"(d[13]), "+f"(d[14]), "+f"(d[15]), "+f"(d[16]), "+f"(d[17]), "+f"(d[18]), "+f"(d[19]), "+f"(d[20]), "+f"(d[21]), "+f"(d[22]), "+f"(d[23]), "+f"(d[24]), "+f"(d[25]), "+f"(d[26]), "+f"(d[27]), "+f"(d[28]), "+f"(d[29]), "+f"(d[30]), "+f"(d[31]), "+f"(d[32]), "+f"(d[33]), "+f"(d[34]), "+f"(d[35]), "+f"(d[36]), "+f"(d[37]), "+f"(d[38]), "+f"(d[39]), "+f"(d[40]), "+f"(d[41]), "+f"(d[42]), "+f"(d[43]), "+f"(d[44]), "+f"(d[45]), "+f"(d[46]), "+f"(d[47]), "+f"(d[48]), "+f"(d[49]), "+f"(d[50]), "+f"(d[51]), "+f"(d[52]), "+f"(d[53]), "+f"(d[54]), "+f"(d[55]), "+f"(d[56]), "+f"(d[57]), "+f"(d[58]), "+f"(d[59]), "+f"(d[60]), "+f"(d[61]), "+f"(d[62]), "+f"(d[63]), "+f"(d[64]), "+f"(d[65]), "+f"(d[66]), "+f"(d[67]), "+f"(d[68]), "+f"(d[69]), "+f"(d[70]), "+f"(d[71]), "+f"(d[72]), "+f"(d[73]), "+f"(d[74]), "+f"(d[75]), "+f"(d[76]), "+f"(d[77]), "+f"(d[78]), "+f"(d[79]), "+f"(d[80]), "+f"(d[81]), "+f"(d[82]), "+f"(d[83]), "+f"(d[84]), "+f"(d[85]), "+f"(d[86]), "+f"(d[87]), "+f"(d[88]), "+f"(d[89]), "+f"(d[90]), "+f"(d[91]), "+f"(d[92]), "+f"(d[93]), "+f"(d[94]), "+f"(d[95])
    : "l"(descA), "l"(descB), "r"(scaleD));
}

__device__ __forceinline__ void wgmma_n128_ss_ta0_tb1(float* d, uint64_t descA, uint64_t descB, int scaleD) {
  asm volatile("{\n.reg .pred p;\nsetp.ne.b32 p, %66, 0;\n"
    "wgmma.mma_async.sync.aligned.m64n128k16.f32.bf16.bf16 {%0, %1, %2, %3, %4, %5, %6, %7, %8, %9, %10, %11, %12, %13, %14, %15, %16, %17, %18, %19, %20, %21, %22, %23, %24, %25, %26, %27, %28, %29, %30, %31, %32, %33, %34, %35, %36, %37, %38, %39, %40, %41, %42, %43, %44, %45, %46, %47, %48, %49, %50, %51, %52, %53, %54, %55, %56, %57, %58, %59, %60, %61, %62, %63}, %64, %65, p, 1, 1, 0, 1;\n}\n"
    : "+f"(d[0]), "+f"(d[1]), "+f"(d[2]), "+f"(d[3]), "+f"(d[4]), "+f"(d[5]), "+f"(d[6]), "+f"(d[7]), "+f"(d[8]), "+f"(d[9]), "+f"(d[10]), "+f"(d[11]), "+f"(d[12]), "+f"(d[13]), "+f"(d[14]), "+f"(d[15]), "+f"(d[16]), "+f"(d[17]), "+f"(d[18]), "+f"(d[19]), "+f"(d[20]), "+f"(d[21]), "+f"(d[22]), "+f"(d[23]), "+f"(d[24]), "+f"(d[25]), "+f"(d[26]), "+f"(d[27]), "+f"(d[28]), "+f"(d[29]), "+f"(d[30]), "+f"(d[31]), "+f"(d[32]), "+f"(d[33]), "+f"(d[34]), "+f"(d[35]), "+f"(d[36]), "+f"(d[37]), "+f"(d[38]), "+f"(d[39]), "+f"(d[40]), "+f"(d[41]), "+f"(d[42]), "+f"(d[43]), "+f"(d[44]), "+f"(d[45]), "+f"(d[46]), "+f"(d[47]), "+f"(d[48]), "+f"(d[49]), "+f"(d[50]), "+f"(d[51]), "+f"(d[52]), "+f"(d[53]), "+f"(d[54]), "+f"(d[55]), "+f"(d[56]), "+f"(d[57]), "+f"(d[58]), "+f"(d[59]), "+f"(d[60]), "+f"(d[61]), "+f"(d[62]), "+f"(d[63])
    : "l"(descA), "l"(descB), "r"(scaleD));
}

__device__ __forceinline__ void wgmma_n192_ssz_ta0_tb1(float* d, uint64_t descA, uint64_t descB) {
  asm volatile("{\n.reg .pred p;\nsetp.ne.b32 p, 0, 0;\n"
    "wgmma.mma_async.sync.aligned.m64n192k16.f32.bf16.bf16 {%0, %1, %2, %3, %4, %5, %6, %7, %8, %9, %10, %11, %12, %13, %14, %15, %16, %17, %18, %19, %20, %21, %22, %23, %24, %25, %26, %27, %28, %29, %30, %31, %32, %33, %34, %35, %36, %37, %38, %39, %40, %41, %42, %43, %44, %45, %46, %47, %48, %49, %50, %51, %52, %53, %54, %55, %56, %57, %58, %59, %60, %61, %62, %63, %64, %65, %66, %67, %68, %69, %70, %71, %72, %73, %74, %75, %76, %77, %78, %79, %80, %81, %82, %83, %84, %85, %86, %87, %88, %89, %90, %91, %92, %93, %94, %95}, %96, %97, p, 1, 1, 0, 1;\n}\n"
    : "=f"(d[0]), "=f"(d[1]), "=f"(d[2]), "=f"(d[3]), "=f"(d[4]), "=f"(d[5]), "=f"(d[6]), "=f"(d[7]), "=f"(d[8]), "=f"(d[9]), "=f"(d[10]), "=f"(d[11]), "=f"(d[12]), "=f"(d[13]), "=f"(d[14]), "=f"(d[15]), "=f"(d[16]), "=f"(d[17]), "=f"(d[18]), "=f"(d[19]), "=f"(d[20]), "=f"(d[21]), "=f"(d[22]), "=f"(d[23]), "=f"(d[24]), "=f"(d[25]), "=f"(d[26]), "=f"(d[27]), "=f"(d[28]), "=f"(d[29]), "=f"(d[30]), "=f"(d[31]), "=f"(d[32]), "=f"(d[33]), "=f"(d[34]), "=f"(d[35]), "=f"(d[36]), "=f"(d[37]), "=f"(d[38]), "=f"(d[39]), "=f"(d[40]), "=f"(d[41]), "=f"(d[42]), "=f"(d[43]), "=f"(d[44]), "=f"(d[45]), "=f"(d[46]), "=f"(d[47]), "=f"(d[48]), "=f"(d[49]), "=f"(d[50]), "=f"(d[51]), "=f"(d[52]), "=f"(d[53]), "=f"(d[54]), "=f"(d[55]), "=f"(d[56]), "=f"(d[57]), "=f"(d[58]), "=f"(d[59]), "=f"(d[60]), "=f"(d[61]), "=f"(d[62]), "=f"(d[63]), "=f"(d[64]), "=f"(d[65]), "=f"(d[66]), "=f"(d[67]), "=f"(d[68]), "=f"(d[69]), "=f"(d[70]), "=f"(d[71]), "=f"(d[72]), "=f"(d[73]), "=f"(d[74]), "=f"(d[75]), "=f"(d[76]), "=f"(d[77]), "=f"(d[78]), "=f"(d[79]), "=f"(d[80]), "=f"(d[81]), "=f"(d[82]), "=f"(d[83]), "=f"(d[84]), "=f"(d[85]), "=f"(d[86]), "=f"(d[87]), "=f"(d[88]), "=f"(d[89]), "=f"(d[90]), "=f"(d[91]), "=f"(d[92]), "=f"(d[93]), "=f"(d[94]), "=f"(d[95])
    : "l"(descA), "l"(descB));
}

__device__ __forceinline__ void wgmma_n8_ss_ta1_tb0(float* d, uint64_t descA, uint64_t descB, int scaleD) {
  asm volatile("{\n.reg .pred p;\nsetp.ne.b32 p, %6, 0;\n"
    "wgmma.mma_async.sync.aligned.m64n8k16.f32.bf16.bf16 {%0, %1, %2, %3}, %4, %5, p, 1, 1, 1, 0;\n}\n"
    : "+f"(d[0]), "+f"(d[1]), "+f"(d[2]), "+f"(d[3])
    : "l"(descA), "l"(descB), "r"(scaleD));
}

__device__ __forceinline__ void wgmma_n8_ssz_ta1_tb0(float* d, uint64_t descA, uint64_t descB) {
  asm volatile("{\n.reg .pred p;\nsetp.ne.b32 p, 0, 0;\n"
    "wgmma.mma_async.sync.aligned.m64n8k16.f32.bf16.bf16 {%0, %1, %2, %3}, %4, %5, p, 1, 1, 1, 0;\n}\n"
    : "=f"(d[0]), "=f"(d[1]), "=f"(d[2]), "=f"(d[3])
    : "l"(descA), "l"(descB));
}

__device__ __forceinline__ void wgmma_n192_rs_tb1(float* d, const uint32_t* a, uint64_t descB, int scaleD) {
  asm volatile("{\n.reg .pred p;\nsetp.ne.b32 p, %101, 0;\n"
    "wgmma.mma_async.sync.aligned.m64n192k16.f32.bf16.bf16 {%0, %1, %2, %3, %4, %5, %6, %7, %8, %9, %10, %11, %12, %13, %14, %15, %16, %17, %18, %19, %20, %21, %22, %23, %24, %25, %26, %27, %28, %29, %30, %31, %32, %33, %34, %35, %36, %37, %38, %39, %40, %41, %42, %43, %44, %45, %46, %47, %48, %49, %50, %51, %52, %53, %54, %55, %56, %57, %58, %59, %60, %61, %62, %63, %64, %65, %66, %67, %68, %69, %70, %71, %72, %73, %74, %75, %76, %77, %78, %79, %80, %81, %82, %83, %84, %85, %86, %87, %88, %89, %90, %91, %92, %93, %94, %95}, {%96, %97, %98, %99}, %100, p, 1, 1, 1;\n}\n"
    : "+f"(d[0]), "+f"(d[1]), "+f"(d[2]), "+f"(d[3]), "+f"(d[4]), "+f"(d[5]), "+f"(d[6]), "+f"(d[7]), "+f"(d[8]), "+f"(d[9]), "+f"(d[10]), "+f"(d[11]), "+f"(d[12]), "+f"(d[13]), "+f"(d[14]), "+f"(d[15]), "+f"(d[16]), "+f"(d[17]), "+f"(d[18]), "+f"(d[19]), "+f"(d[20]), "+f"(d[21]), "+f"(d[22]), "+f"(d[23]), "+f"(d[24]), "+f"(d[25]), "+f"(d[26]), "+f"(d[27]), "+f"(d[28]), "+f"(d[29]), "+f"(d[30]), "+f"(d[31]), "+f"(d[32]), "+f"(d[33]), "+f"(d[34]), "+f"(d[35]), "+f"(d[36]), "+f"(d[37]), "+f"(d[38]), "+f"(d[39]), "+f"(d[40]), "+f"(d[41]), "+f"(d[42]), "+f"(d[43]), "+f"(d[44]), "+f"(d[45]), "+f"(d[46]), "+f"(d[47]), "+f"(d[48]), "+f"(d[49]), "+f"(d[50]), "+f"(d[51]), "+f"(d[52]), "+f"(d[53]), "+f"(d[54]), "+f"(d[55]), "+f"(d[56]), "+f"(d[57]), "+f"(d[58]), "+f"(d[59]), "+f"(d[60]), "+f"(d[61]), "+f"(d[62]), "+f"(d[63]), "+f"(d[64]), "+f"(d[65]), "+f"(d[66]), "+f"(d[67]), "+f"(d[68]), "+f"(d[69]), "+f"(d[70]), "+f"(d[71]), "+f"(d[72]), "+f"(d[73]), "+f"(d[74]), "+f"(d[75]), "+f"(d[76]), "+f"(d[77]), "+f"(d[78]), "+f"(d[79]), "+f"(d[80]), "+f"(d[81]), "+f"(d[82]), "+f"(d[83]), "+f"(d[84]), "+f"(d[85]), "+f"(d[86]), "+f"(d[87]), "+f"(d[88]), "+f"(d[89]), "+f"(d[90]), "+f"(d[91]), "+f"(d[92]), "+f"(d[93]), "+f"(d[94]), "+f"(d[95])
    : "r"(a[0]), "r"(a[1]), "r"(a[2]), "r"(a[3]), "l"(descB), "r"(scaleD));
}

__device__ __forceinline__ void wgmma_n80_rs_tb0(float* d, const uint32_t* a, uint64_t descB, int scaleD) {
  asm volatile("{\n.reg .pred p;\nsetp.ne.b32 p, %45, 0;\n"
    "wgmma.mma_async.sync.aligned.m64n80k16.f32.bf16.bf16 {%0, %1, %2, %3, %4, %5, %6, %7, %8, %9, %10, %11, %12, %13, %14, %15, %16, %17, %18, %19, %20, %21, %22, %23, %24, %25, %26, %27, %28, %29, %30, %31, %32, %33, %34, %35, %36, %37, %38, %39}, {%40, %41, %42, %43}, %44, p, 1, 1, 0;\n}\n"
    : "+f"(d[0]), "+f"(d[1]), "+f"(d[2]), "+f"(d[3]), "+f"(d[4]), "+f"(d[5]), "+f"(d[6]), "+f"(d[7]), "+f"(d[8]), "+f"(d[9]), "+f"(d[10]), "+f"(d[11]), "+f"(d[12]), "+f"(d[13]), "+f"(d[14]), "+f"(d[15]), "+f"(d[16]), "+f"(d[17]), "+f"(d[18]), "+f"(d[19]), "+f"(d[20]), "+f"(d[21]), "+f"(d[22]), "+f"(d[23]), "+f"(d[24]), "+f"(d[25]), "+f"(d[26]), "+f"(d[27]), "+f"(d[28]), "+f"(d[29]), "+f"(d[30]), "+f"(d[31]), "+f"(d[32]), "+f"(d[33]), "+f"(d[34]), "+f"(d[35]), "+f"(d[36]), "+f"(d[37]), "+f"(d[38]), "+f"(d[39])
    : "r"(a[0]), "r"(a[1]), "r"(a[2]), "r"(a[3]), "l"(descB), "r"(scaleD));
}

__device__ __forceinline__ void wgmma_n80_rsz_tb0(float* d, const uint32_t* a, uint64_t descB) {
  asm volatile("{\n.reg .pred p;\nsetp.ne.b32 p, 0, 0;\n"
    "wgmma.mma_async.sync.aligned.m64n80k16.f32.bf16.bf16 {%0, %1, %2, %3, %4, %5, %6, %7, %8, %9, %10, %11, %12, %13, %14, %15, %16, %17, %18, %19, %20, %21, %22, %23, %24, %25, %26, %27, %28, %29, %30, %31, %32, %33, %34, %35, %36, %37, %38, %39}, {%40, %41, %42, %43}, %44, p, 1, 1, 0;\n}\n"
    : "=f"(d[0]), "=f"(d[1]), "=f"(d[2]), "=f"(d[3]), "=f"(d[4]), "=f"(d[5]), "=f"(d[6]), "=f"(d[7]), "=f"(d[8]), "=f"(d[9]), "=f"(d[10]), "=f"(d[11]), "=f"(d[12]), "=f"(d[13]), "=f"(d[14]), "=f"(d[15]), "=f"(d[16]), "=f"(d[17]), "=f"(d[18]), "=f"(d[19]), "=f"(d[20]), "=f"(d[21]), "=f"(d[22]), "=f"(d[23]), "=f"(d[24]), "=f"(d[25]), "=f"(d[26]), "=f"(d[27]), "=f"(d[28]), "=f"(d[29]), "=f"(d[30]), "=f"(d[31]), "=f"(d[32]), "=f"(d[33]), "=f"(d[34]), "=f"(d[35]), "=f"(d[36]), "=f"(d[37]), "=f"(d[38]), "=f"(d[39])
    : "r"(a[0]), "r"(a[1]), "r"(a[2]), "r"(a[3]), "l"(descB));
}

__device__ __forceinline__ void wgmma_n32_rs_tb1(float* d, const uint32_t* a, uint64_t descB, int scaleD) {
  asm volatile("{\n.reg .pred p;\nsetp.ne.b32 p, %21, 0;\n"
    "wgmma.mma_async.sync.aligned.m64n32k16.f32.bf16.bf16 {%0, %1, %2, %3, %4, %5, %6, %7, %8, %9, %10, %11, %12, %13, %14, %15}, {%16, %17, %18, %19}, %20, p, 1, 1, 1;\n}\n"
    : "+f"(d[0]), "+f"(d[1]), "+f"(d[2]), "+f"(d[3]), "+f"(d[4]), "+f"(d[5]), "+f"(d[6]), "+f"(d[7]), "+f"(d[8]), "+f"(d[9]), "+f"(d[10]), "+f"(d[11]), "+f"(d[12]), "+f"(d[13]), "+f"(d[14]), "+f"(d[15])
    : "r"(a[0]), "r"(a[1]), "r"(a[2]), "r"(a[3]), "l"(descB), "r"(scaleD));
}

__device__ __forceinline__ void wgmma_n32_rsz_tb1(float* d, const uint32_t* a, uint64_t descB) {
  asm volatile("{\n.reg .pred p;\nsetp.ne.b32 p, 0, 0;\n"
    "wgmma.mma_async.sync.aligned.m64n32k16.f32.bf16.bf16 {%0, %1, %2, %3, %4, %5, %6, %7, %8, %9, %10, %11, %12, %13, %14, %15}, {%16, %17, %18, %19}, %20, p, 1, 1, 1;\n}\n"
    : "=f"(d[0]), "=f"(d[1]), "=f"(d[2]), "=f"(d[3]), "=f"(d[4]), "=f"(d[5]), "=f"(d[6]), "=f"(d[7]), "=f"(d[8]), "=f"(d[9]), "=f"(d[10]), "=f"(d[11]), "=f"(d[12]), "=f"(d[13]), "=f"(d[14]), "=f"(d[15])
    : "r"(a[0]), "r"(a[1]), "r"(a[2]), "r"(a[3]), "l"(descB));
}

__device__ __forceinline__ void wgmma_n32_rs_tb0(float* d, const uint32_t* a, uint64_t descB, int scaleD) {
  asm volatile("{\n.reg .pred p;\nsetp.ne.b32 p, %21, 0;\n"
    "wgmma.mma_async.sync.aligned.m64n32k16.f32.bf16.bf16 {%0, %1, %2, %3, %4, %5, %6, %7, %8, %9, %10, %11, %12, %13, %14, %15}, {%16, %17, %18, %19}, %20, p, 1, 1, 0;\n}\n"
    : "+f"(d[0]), "+f"(d[1]), "+f"(d[2]), "+f"(d[3]), "+f"(d[4]), "+f"(d[5]), "+f"(d[6]), "+f"(d[7]), "+f"(d[8]), "+f"(d[9]), "+f"(d[10]), "+f"(d[11]), "+f"(d[12]), "+f"(d[13]), "+f"(d[14]), "+f"(d[15])
    : "r"(a[0]), "r"(a[1]), "r"(a[2]), "r"(a[3]), "l"(descB), "r"(scaleD));
}

__device__ __forceinline__ void wgmma_n32_rsz_tb0(float* d, const uint32_t* a, uint64_t descB) {
  asm volatile("{\n.reg .pred p;\nsetp.ne.b32 p, 0, 0;\n"
    "wgmma.mma_async.sync.aligned.m64n32k16.f32.bf16.bf16 {%0, %1, %2, %3, %4, %5, %6, %7, %8, %9, %10, %11, %12, %13, %14, %15}, {%16, %17, %18, %19}, %20, p, 1, 1, 0;\n}\n"
    : "=f"(d[0]), "=f"(d[1]), "=f"(d[2]), "=f"(d[3]), "=f"(d[4]), "=f"(d[5]), "=f"(d[6]), "=f"(d[7]), "=f"(d[8]), "=f"(d[9]), "=f"(d[10]), "=f"(d[11]), "=f"(d[12]), "=f"(d[13]), "=f"(d[14]), "=f"(d[15])
    : "r"(a[0]), "r"(a[1]), "r"(a[2]), "r"(a[3]), "l"(descB));
}

__device__ __forceinline__ uint32_t pack_bf16x2(float lo, float hi) {
  uint32_t r;
  asm("cvt.rn.bf16x2.f32 %0, %1, %2;" : "=r"(r) : "f"(hi), "f"(lo));
  return r;
}
__device__ __forceinline__ float bf_lo(uint32_t p) { return __uint_as_float(p << 16); }
__device__ __forceinline__ float bf_hi(uint32_t p) { return __uint_as_float(p & 0xffff0000u); }
__device__ __forceinline__ float bf16_round(float v) { return __bfloat162float(__float2bfloat16_rn(v)); }
__device__ __forceinline__ float ex2_approx(float x) {
  float r;
  asm("ex2.approx.ftz.f32 %0, %1;" : "=f"(r) : "f"(x));
  return r;
}
__device__ __forceinline__ float rcp_fast(float x) {
  float r;
  asm("rcp.approx.ftz.f32 %0, %1;" : "=f"(r) : "f"(x));
  return r;
}
__device__ __forceinline__ void ldmatrix_x4(uint32_t (&r)[4], uint32_t addr) {
  asm volatile("ldmatrix.sync.aligned.m8n8.x4.shared.b16 {%0,%1,%2,%3}, [%4];"
               : "=r"(r[0]), "=r"(r[1]), "=r"(r[2]), "=r"(r[3])
               : "r"(addr)
               : "memory");
}
__device__ __forceinline__ void stmatrix_x4(uint32_t addr, uint32_t r0, uint32_t r1, uint32_t r2, uint32_t r3) {
  asm volatile("stmatrix.sync.aligned.m8n8.x4.shared.b16 [%0], {%1,%2,%3,%4};" ::"r"(addr), "r"(r0), "r"(r1), "r"(r2),
               "r"(r3));
}
__device__ __forceinline__ uint32_t add_bf16x2(uint32_t a, uint32_t b) {
  uint32_t r;
  asm("add.rn.bf16x2 %0, %1, %2;" : "=r"(r) : "r"(a), "r"(b));
  return r;
}
__device__ __forceinline__ uint4 lds128(uint32_t addr) {
  uint4 v;
  asm volatile("ld.shared.v4.b32 {%0,%1,%2,%3}, [%4];" : "=r"(v.x), "=r"(v.y), "=r"(v.z), "=r"(v.w) : "r"(addr) : "memory");
  return v;
}
__device__ __forceinline__ uint32_t lds32(uint32_t addr) {
  uint32_t v;
  asm volatile("ld.shared.b32 %0, [%1];" : "=r"(v) : "r"(addr) : "memory");
  return v;
}
__device__ __forceinline__ void sts32(uint32_t addr, uint32_t v) {
  asm volatile("st.shared.b32 [%0], %1;" ::"r"(addr), "r"(v) : "memory");
}

__device__ __forceinline__ int fresh_tid() {
  int t;
  asm volatile("mov.u32 %0, %%tid.x;" : "=r"(t));
  return t;
}
__device__ __forceinline__ unsigned ld_relaxed_u32(const void* p) {
  unsigned v;
  asm volatile("ld.relaxed.gpu.global.u32 %0, [%1];" : "=r"(v) : "l"(p) : "memory");
  return v;
}
__device__ __forceinline__ unsigned launch_epoch() { return (*(volatile unsigned*)g_done) / NCTA + 1u; }
__device__ __forceinline__ uint32_t set_tag(uint32_t w, uint32_t m, uint32_t tag) { return (w & ~m) | (tag & m); }
__device__ __forceinline__ uint32_t o_tag(int L) { return (L + 1) & 1; }
__device__ __forceinline__ uint32_t x_tag(int L) { return L & 1; }
__device__ __forceinline__ uint32_t kv_tag(int L) { return L < 2; }

#define SPINT 0
template <class F>
__device__ __forceinline__ void fix_lines(uint32_t bar, uint32_t par, uint32_t ta, uint32_t tag, uint32_t mask, int bar_id, F line) {
  uint32_t m;
  mbar_wait(bar, par);
  m = lds32(ta);
  m = __ballot_sync(0xffffffffu, (m ^ tag) & mask);
  if (m == 0u) return;
#pragma unroll 1
  for (uint32_t it = 0; it < (1u << 17) && m != 0u; ++it) {
    const int l = __ffs(m) - 1, j = fresh_tid() & 7;
    uint4 v;
    asm volatile("ld.relaxed.gpu.global.v4.b32 {%0,%1,%2,%3}, [%4];" : "=r"(v.x), "=r"(v.y), "=r"(v.z), "=r"(v.w) : "l"(line(l) + j * 8) : "memory");
    const uint32_t a = __shfl_sync(0xffffffffu, ta, l) ^ (j << 4);
    if (((__shfl_sync(0xffffffffu, v.x, 0) ^ tag) & 1u) == 0u) {
      asm volatile("st.shared.v4.b32 [%0], {%1,%2,%3,%4};" ::"r"(a), "r"(v.x), "r"(v.y), "r"(v.z), "r"(v.w) : "memory");
      m &= m - 1u;
    }
  }
  fence_proxy_async_smem();
  named_bar_sync(bar_id, 32);
}
__device__ __forceinline__ uint32_t peek_counts(const unsigned* f, unsigned target, int lane) {
  return __ballot_sync(0xffffffffu, (int)(ld_relaxed_u32(f + (lane & 15) * 4) - target) >= 0);
}
__device__ __forceinline__ void wait_count(const unsigned* f, unsigned target, int i, uint32_t& seen, int lane) {
  if ((seen >> i) & 1u) return;
#pragma unroll 1
  for (uint32_t it = 0; it < (1u << 17); ++it) {
    seen = peek_counts(f, target, lane);
    if ((seen >> i) & 1u) break;
  }
}
__device__ __forceinline__ float4 ld_rec(const float4* p) {
  float4 v;
  asm volatile("ld.relaxed.gpu.global.v4.f32 {%0,%1,%2,%3}, [%4];" : "=f"(v.x), "=f"(v.y), "=f"(v.z), "=f"(v.w) : "l"(p) : "memory");
  return v;
}
__device__ __forceinline__ void st_rec(float4* p, float a, float b, float c, unsigned tag) {
  asm volatile("st.relaxed.gpu.global.v4.f32 [%0], {%1,%2,%3,%4};" ::"l"(p), "f"(a), "f"(b), "f"(c), "f"(__uint_as_float(tag)) : "memory");
}
template <int N>
__device__ __forceinline__ float4 sum_recs(const float4* p, int stride, unsigned tag) {
  float4 s;
#pragma unroll 1
  for (uint32_t it = 0; it < (1u << 17); ++it) {
    float4 v[N];
#pragma unroll
    for (int t = 0; t < N; t++) v[t] = ld_rec(p + t * stride);
    bool ok = true;
    s = make_float4(0.f, 0.f, 0.f, 0.f);
#pragma unroll
    for (int t = 0; t < N; t++) {
      ok &= __float_as_uint(v[t].w) == tag;
      s.x += v[t].x;
      s.y += v[t].y;
      s.z += v[t].z;
    }
    if (ok) break;
    __nanosleep(200);
  }
  return s;
}

#define PHASE_IDS                                  \
  const int tid_ = fresh_tid();                    \
  const int lane = tid_ & 31, wwarp = __shfl_sync(0xffffffffu, (tid_ >> 5) & 3, 0), tid = tid_ & 127; \
  const int g = lane >> 2, c = lane & 3;           \
  (void)tid; (void)g; (void)c; (void)wwarp;

#define PHASE_IDS_W                                \
  const int lane = fresh_tid() & 31, wwarp = warp & 3; \
  const int g = lane >> 2, c = lane & 3;

#define GTL(i) do { } while (0)
#define TGET(v) do { } while (0)
#define TPUT(c, i, v) do { } while (0)

constexpr float SM_C = 0.17677669529663687f * 1.4426950408889634f;

__device__ __forceinline__ void stmatrix_x4_if(bool ok, uint32_t addr, uint32_t r0, uint32_t r1, uint32_t r2, uint32_t r3) {
  asm volatile("{\n.reg .pred p;\nsetp.ne.b32 p, %5, 0;\n@p stmatrix.sync.aligned.m8n8.x4.shared.b16 [%0], {%1,%2,%3,%4};\n}\n" ::"r"(addr),
               "r"(r0), "r"(r1), "r"(r2), "r"(r3), "r"((int)ok));
}

__device__ __forceinline__ void attn_a_slow(const uint8_t* __restrict__ kvimg, int L, int gb, int hp, uint32_t bad,
                                            int row0, int lane) {
  constexpr uint32_t sq = SBASE + OFF_SLOT + 3 * 16384;
#pragma unroll 1
  for (int j = 0; j < 8; j++) {
    const uint8_t* tp = kvimg + (size_t)(gb * 16 + hp) * 32768 + (j * 32 + lane) * 128 + ((lane & 7) << 4);
#pragma unroll 1
    for (uint32_t it = 0; it < (1u << 17); ++it)
      if (((ld_relaxed_u32(tp) ^ kv_tag(L)) & 1u) == 0u) break;
  }
  __syncwarp();
#pragma unroll 1
  for (int t = 0; t < 32; t++) {
    const int hh = t >> 4, row = row0 + (t & 7) + (t & 8) * 4;
    if (!((bad >> hh) & 1u)) continue;
    const int qpos = gb * 128 + row;
    const uint32_t qaddr = sq + row * 128;
    float mx = -INFINITY, sum = 0.f, acc = 0.f;
#pragma unroll 1
    for (int pass = 0; pass < 2; pass++) {
#pragma unroll 1
      for (int j = 0; j < 8; j++) {
        const int kp = qpos - (lane + 32 * j);
        const uint8_t* kr = kvimg + ((size_t)((kp >> 7) * 16 + hp) * 2 + ((kp >> 6) & 1)) * 16384 + (kp & 63) * 128;
        float d = -INFINITY;
        if (kp >= 0) {
          d = 0.f;
#pragma unroll 1
          for (int q = 0; q < 4; q++) {
            const uint4 kv = __ldcg(reinterpret_cast<const uint4*>(kr + (((hh * 4 + q) ^ (kp & 7)) << 4)));
            const uint4 qv = lds128(qaddr + (((hh * 4 + q) ^ (row & 7)) << 4));
            const uint32_t kw[4] = {kv.x, kv.y, kv.z, kv.w}, qw[4] = {qv.x, qv.y, qv.z, qv.w};
#pragma unroll
            for (int e = 0; e < 4; e++) d = fmaf(bf_lo(kw[e]), bf_lo(qw[e]), fmaf(bf_hi(kw[e]), bf_hi(qw[e]), d));
          }
        }
        if (pass == 0) {
          mx = fmaxf(mx, d);
        } else {
          const float ev = ex2_approx(d - mx);
          sum += ev;
          const float pv = bf16_round(ev);
#pragma unroll 1
          for (int kk = 0; kk < 32; kk++) {
            const float pk = __shfl_sync(0xffffffffu, pv, kk);
            const int k2 = qpos - (kk + 32 * j);
            if (k2 >= 0) {
              const uint8_t* vr = kvimg + ((size_t)((k2 >> 7) * 16 + hp) * 2 + ((k2 >> 6) & 1)) * 16384 + 8192 + (k2 & 63) * 128;
              const unsigned short vv =
                  __ldcg(reinterpret_cast<const unsigned short*>(vr + (((hh * 4 + (lane >> 3)) ^ (k2 & 7)) << 4) + (lane & 7) * 2));
              acc = fmaf(pk, __uint_as_float((uint32_t)vv << 16), acc);
            }
          }
        }
      }
      if (pass == 0) {
#pragma unroll
        for (int o = 16; o > 0; o >>= 1) mx = fmaxf(mx, __shfl_xor_sync(0xffffffffu, mx, o));
      }
    }
#pragma unroll
    for (int o = 16; o > 0; o >>= 1) sum += __shfl_xor_sync(0xffffffffu, sum, o);
    acc *= rcp_fast(sum);
    const float hi = __shfl_down_sync(0xffffffffu, acc, 1);
    __syncwarp();
    if ((lane & 1) == 0) sts32(qaddr + (((hh * 4 + (lane >> 3)) ^ (row & 7)) << 4) + (lane & 7) * 2,
                               set_tag(pack_bf16x2(acc, hi), hh == 0 && lane == 0, o_tag(L)));
    __syncwarp();
  }
}

template <int HH>
__device__ __forceinline__ void store_o(const float (&o)[16], const float (&inv)[2], uint32_t ra, uint32_t tag, bool ok) {
  const uint32_t m = HH == 0 && (fresh_tid() & 3) == 0;
#pragma unroll
  for (int jp = 0; jp < 2; jp++) {
    uint32_t w0 = pack_bf16x2(o[8 * jp] * inv[0], o[8 * jp + 1] * inv[0]);
    uint32_t w1 = pack_bf16x2(o[8 * jp + 2] * inv[1], o[8 * jp + 3] * inv[1]);
    if (HH == 0 && jp == 0) {
      w0 = set_tag(w0, m, tag);
      w1 = set_tag(w1, m, tag);
    }
    stmatrix_x4_if(ok, ra ^ ((HH * 4 + 2 * jp) << 4), w0, w1, pack_bf16x2(o[8 * jp + 4] * inv[0], o[8 * jp + 5] * inv[0]),
                   pack_bf16x2(o[8 * jp + 6] * inv[1], o[8 * jp + 7] * inv[1]));
  }
}
__device__ __forceinline__ int tile_row(bool B, int w, int r, int g) { return (B ? 16 * w + 8 * r : 8 * w + 32 * r) + g; }
__device__ __forceinline__ uint32_t q_row_addr(bool B, int R, int w, int lane) {
  return SBASE + OFF_SLOT + 3 * 16384 + R * 8192 + tile_row(B, w, (lane >> 3) & 1, lane & 7) * 128 + (((lane >> 4) ^ (lane & 7)) << 4);
}

struct AttnA {
  float s[2][16], o[2][16], l[2][2], sh[2][3];
  uint32_t p[2][4], t[2], me[4], ra, bad, zero;
};
#define ATS_(i) do { } while (0)
template <int V>
__device__ __forceinline__ void attn_sum(AttnA& a, int nv) {
  constexpr int hh = (V >> 1) & 1, kh = V & 1, i = V >> 2;
#pragma unroll
  for (int r = 0; r < 2; r++) {
    const uint32_t t1 = add_bf16x2(add_bf16x2(a.p[0][r], a.p[0][2 + r]), add_bf16x2(a.p[1][r], a.p[1][2 + r]));
    if (kh == 0) {
      a.t[r] = t1;
    } else {
      uint32_t tt = add_bf16x2(a.t[r], t1);
      if (i > 0) tt = i <= nv ? tt : 0u;
      const float v = bf_lo(tt) + bf_hi(tt);
      a.l[hh][r] = i == 0 ? v : a.l[hh][r] + v;
    }
  }
}
template <int HH>
__device__ __forceinline__ void attn_shfl(AttnA& a) {
#pragma unroll
  for (int r = 0; r < 2; r++)
#pragma unroll
    for (int j = 0; j < 3; j++) a.sh[r][j] = __shfl_xor_sync(0xffffffffu, a.l[HH][r], j + 1);
}
template <int HH>
__device__ __forceinline__ void attn_fin(AttnA& a) {
  bool bad = false;
  float inv[2];
#pragma unroll
  for (int r = 0; r < 2; r++) {
    const float v = (a.l[HH][r] + a.sh[r][0]) + (a.sh[r][1] + a.sh[r][2]);
    bad |= !(v <= 1.152921504606846976e18f && v >= 8.673617379884035e-19f);
    inv[r] = rcp_fast(v);
  }
  bad = __any_sync(0xffffffffu, bad);
  if (HH == 1) wgmma_wait<0>();
  reg_fence<16>(a.o[HH]);
  store_o<HH>(a.o[HH], inv, a.ra, o_tag(0), !bad);
  a.bad = (HH == 0 ? 0u : a.bad) | (bad ? 1u << HH : 0u);
}
__device__ __forceinline__ void attn_masks(AttnA& a, int wr) {
  const int lane = fresh_tid() & 31, d = (lane >> 2) - 2 * (lane & 3);
  const uint32_t tri = d >= 1 ? 0xffffffffu : (d == 0 ? 0xffffu : 0u);
#pragma unroll
  for (int t = 0; t < 4; t++) a.me[t] = wr > t ? 0xffffffffu : (wr == t ? tri : 0u);
}
template <int V, int K>
__device__ __forceinline__ uint32_t attn_exp(AttnA& a) {
  constexpr int i = V >> 2, kh = V & 1, r = K & 1;
  if ((i == 0 && kh > r) || (i == 4 && kh < r)) return 0u;
  const uint32_t w = pack_bf16x2(ex2_approx(a.s[V & 1][2 * K]), ex2_approx(a.s[V & 1][2 * K + 1]));
  if (i == 0 && kh == r) return w & a.me[K >> 1];
  if (i == 4 && kh == r) return w & ~a.me[K >> 1];
  return w;
}
template <int V>
__device__ __forceinline__ void attn_unit(AttnA& a, const uint32_t (&q)[2][2][4], uint64_t dcur, uint64_t dnext, int R, int wr, int nv,
                                          uint32_t hbar, uint32_t hpar, uint32_t rbar, bool rel) {
  constexpr int hh = (V >> 1) & 1, kh = V & 1, i = V >> 2;
  ATS_(V + 1);
  asm volatile("" : "+l"(dcur), "+l"(dnext));
  wgmma_wait<1>();
  reg_fence<16>(a.s[V & 1]);
  bool hok = true;
  if (V == 4) hbar = SBASE + OFF_BAR + 8u * (R ? B_LOC : B_HV);
  if (((V & 3) == 2 && V < 16) || V == 4) hok = mbar_test(hbar, hpar);
  const uint64_t d0 = ((V & 3) >= 2 ? dnext : dcur) + ((hh ^ 1) * 4 + kh * 256), d1 = ((V & 3) >= 2 ? dnext : dcur) + ((hh ^ 1) * 4 + kh * 256 + 2);
  const uint64_t d2 = dcur + (512 + hh * 4 + kh * 256), d3 = dcur + (640 + hh * 4 + kh * 256);
  if ((V & 3) == 1 && V > 4 && rel) mbar_arrive(rbar);
  if (V > 0) attn_sum<V - 1>(a, nv);
  if (V == 15) attn_masks(a, wr);
  if (V == 18) {
    attn_shfl<0>(a);
    a.ra = q_row_addr(false, R, wr, fresh_tid() & 31);
  }
  if (V == 19) attn_fin<0>(a);
  uint32_t p[2][4];
  p[0][0] = attn_exp<V, 0>(a);
  p[0][1] = attn_exp<V, 1>(a);
  p[0][2] = attn_exp<V, 2>(a);
  p[0][3] = attn_exp<V, 3>(a);
  p[1][0] = attn_exp<V, 4>(a);
  p[1][1] = attn_exp<V, 5>(a);
  p[1][2] = attn_exp<V, 6>(a);
  p[1][3] = attn_exp<V, 7>(a);
  if (V > 0) {
#pragma unroll
    for (int r = 0; r < 2; r++) p[1][r] ^= (kh ? a.t[r] : __float_as_uint(a.l[hh ^ 1][r])) & a.zero;
  }
#pragma unroll
  for (int k = 0; k < 8; k++) {
    asm volatile("" : "+r"(p[k >> 2][k & 3]));
    a.p[k >> 2][k & 3] = p[k >> 2][k & 3];
  }
  if (!hok) mbar_wait(hbar, hpar);
  wgmma_fence();
  if (V < 18) wgmma_n32_rsz_tb0(a.s[V & 1], q[hh ^ 1][0], d0);
  if (i == 0 && kh == 0) wgmma_n32_rsz_tb1(a.o[hh], a.p[0], d2);
  else wgmma_n32_rs_tb1(a.o[hh], a.p[0], d2, 1);
  if (V < 18) wgmma_n32_rs_tb0(a.s[V & 1], q[hh ^ 1][1], d1, 1);
  wgmma_n32_rs_tb1(a.o[hh], a.p[1], d3, 1);
  wgmma_commit();
}
template <int I>
__device__ __forceinline__ void attn_step(AttnA& a, const uint32_t (&q)[2][2][4], uint64_t dcur, uint64_t dnext, int R, int wr, int nv,
                                          uint32_t hbar, uint32_t hpar, uint32_t rbar, bool rel) {
  attn_unit<4 * I>(a, q, dcur, dnext, R, wr, nv, hbar, hpar, rbar, rel);
  attn_unit<4 * I + 1>(a, q, dcur, dnext, R, wr, nv, hbar, hpar, rbar, rel);
  attn_unit<4 * I + 2>(a, q, dcur, dnext, R, wr, nv, hbar, hpar, rbar, rel);
  attn_unit<4 * I + 3>(a, q, dcur, dnext, R, wr, nv, hbar, hpar, rbar, rel);
}

__device__ __forceinline__ void attention_a(const uint32_t (&q)[2][2][4], int R, int L, int gb, int hp, uint32_t par, int wr,
                                            uint32_t zero) {
  constexpr uint32_t bars = SBASE + OFF_BAR;
  constexpr uint32_t dslot = ((SBASE + OFF_SLOT) >> 4) + 0x10000u;
  auto next = [&](uint64_t d) { return desc_lo((uint32_t)d == dslot ? dslot + 2048 : (uint32_t)d - 1024) + zero; };
  uint64_t d0 = desc_lo(dslot + R * 1024) + zero, d1 = next(d0);
  AttnA a;
  ATS_(0);
  wgmma_fence();
#pragma unroll
  for (int v = 0; v < 2; v++) {
    wgmma_n32_rsz_tb0(a.s[v], q[0][0], d0 + v * 256);
    wgmma_n32_rs_tb0(a.s[v], q[0][1], d0 + (v * 256 + 2), 1);
    wgmma_commit();
  }
  a.zero = zero;
  const bool lane0 = (fresh_tid() & 31) == 0;
  attn_masks(a, wr);
  const int nv = 2 * gb + R;
  const uint32_t hb = bars + 8u * (B_HALO - R), rb = bars + 8u * (B_REL - R);
  attn_step<0>(a, q, d0, d1, R, wr, nv, hb, par, 0, false);
  d0 = next(d1);
  attn_step<1>(a, q, d1, d0, R, wr, nv, R ? bars + 8u * B_HV : hb + 8, par, rb + 8, lane0);
  d1 = next(d0);
  attn_step<2>(a, q, d0, d1, R, wr, nv, hb + 16, par, rb + 16, lane0);
  d0 = next(d1);
  attn_step<3>(a, q, d1, d0, R, wr, nv, hb + 24, par, rb + 24, lane0 && R);
  attn_step<4>(a, q, d0, d0, R, wr, nv, 0, 0, rb, false);
  ATS_(21);
  attn_sum<19>(a, nv);
  attn_shfl<1>(a);
  attn_fin<1>(a);
  ATS_(22);
  if (a.bad != 0u) {
    attn_a_slow(g_kvA[0][0][0], L, gb, hp, a.bad, R * 64 + wr * 8, fresh_tid() & 31);
    named_bar_sync(7, 32);
  }
}

constexpr uint32_t KB_ROW0 = SBASE + OFF_SLOT + 2048, VB_ROW0 = SBASE + OFF_SLOT + 24576 + 2048;

__device__ __forceinline__ void attention_b(const uint32_t (&q)[2][2][4], int R, int gb, uint32_t par0, int wr) {
  constexpr uint32_t bars = SBASE + OFF_BAR;
  const uint32_t dk = ((KB_ROW0 - 2048) >> 4) + 0x10000u + R * 512, dv = dk + ((VB_ROW0 - KB_ROW0) >> 4);
  float s[2][40];
  mbar_wait(bars + 8u * (B_HALO - R), par0);
  wgmma_fence();
#pragma unroll
  for (int hh = 0; hh < 2; hh++) {
    wgmma_n80_rsz_tb0(s[hh], q[hh][0], desc_lo(dk + hh * 4));
    wgmma_n80_rs_tb0(s[hh], q[hh][1], desc_lo(dk + hh * 4 + 2), 1);
  }
  wgmma_commit();
  const int lane = fresh_tid() & 31, g = lane >> 2;
  const bool odd = g & 1, edge = R == 0 && gb == 0 && wr == 0;
  const int D = 2 * (lane & 3) + (g & 1) - g;
  const uint32_t ra = q_row_addr(true, R, wr, lane);
  wgmma_wait<0>();
  reg_fence<40>(s[0]);
  reg_fence<40>(s[1]);
  float z[2][2], y[2][2];
#define GATHER_(W)                                                                                          \
  _Pragma("unroll") for (int hh = 0; hh < 2; hh++) _Pragma("unroll") for (int r = 0; r < 2; r++) {          \
    const float* e = &s[hh][4 * (2 * W + r) + 2 * r];                                                       \
    z[hh][r] = odd ? e[5] : e[4];                                                                           \
    y[hh][r] = D >= 2 ? (odd ? e[1] : e[0]) : (odd ? e[9] : e[8]);                                          \
  }
  if (wr < 2) {
    if (wr == 0) { GATHER_(0) } else { GATHER_(1) }
  } else {
    if (wr == 2) { GATHER_(2) } else { GATHER_(3) }
  }
#undef GATHER_
  float o[2][16], inv[2][2];
  uint32_t p[2][5][4];
  const int sh = odd ? 16 : 0, kb = wr + (D >= 2 ? 0 : 1);
#pragma unroll
  for (int hh = 0; hh < 2; hh++) {
    if (edge) {
      z[hh][0] = -INFINITY;
      if (D >= 2) y[hh][0] = y[hh][1] = -INFINITY;
    }
    uint32_t ab[2][2];
#pragma unroll
    for (int r = 0; r < 2; r++) {
      float m = fmaxf(z[hh][r], y[hh][r]);
      m = fmaxf(m, __shfl_xor_sync(0xffffffffu, m, 1));
      m = fmaxf(m, __shfl_xor_sync(0xffffffffu, m, 2));
      const float e0 = ex2_approx(z[hh][r] - m), e1 = ex2_approx(y[hh][r] - m);
      inv[hh][r] = e0 + e1;
      ab[r][0] = pack_bf16x2(e0, 0.f) << sh;
      ab[r][1] = pack_bf16x2(e1, 0.f) << sh;
    }
#pragma unroll
    for (int k = 0; k < 5; k++) {
      p[hh][k][0] = k == kb ? ab[0][1] : 0u;
      p[hh][k][1] = k == wr + 1 ? ab[1][0] : 0u;
      p[hh][k][2] = k == wr ? ab[0][0] : 0u;
      p[hh][k][3] = k == kb ? ab[1][1] : 0u;
#pragma unroll
      for (int j = 0; j < 4; j++) asm volatile("" : "+r"(p[hh][k][j]));
    }
  }
  wgmma_fence();
#pragma unroll
  for (int hh = 0; hh < 2; hh++) {
    wgmma_n32_rsz_tb1(o[hh], p[hh][0], desc_lo(dv + hh * 4));
#pragma unroll
    for (int k = 1; k < 5; k++) wgmma_n32_rs_tb1(o[hh], p[hh][k], desc_lo(dv + hh * 4 + k * 128), 1);
  }
  wgmma_commit();
#pragma unroll
  for (int hh = 0; hh < 2; hh++)
#pragma unroll
    for (int r = 0; r < 2; r++) {
      inv[hh][r] += __shfl_xor_sync(0xffffffffu, inv[hh][r], 1);
      inv[hh][r] += __shfl_xor_sync(0xffffffffu, inv[hh][r], 2);
      inv[hh][r] = rcp_fast(inv[hh][r]);
    }
  wgmma_wait<0>();
  reg_fence<16>(o[0]);
  reg_fence<16>(o[1]);
  store_o<0>(o[0], inv[0], ra, o_tag(1), true);
  store_o<1>(o[1], inv[1], ra, o_tag(1), true);
}

#define KTQM 0
#define TRICKLE 300
#define QREL 5
#define PRESLEEP 200
#define CSA 5
#define PN1 4
#define PN2 5
#define TLAZY 100
#define SDLY 1500
#define HTS(i) do { } while (0)
struct Params {
  CUtensorMap x[5], xq[4], o, wqkv[2], wqkv3[2], wo3[2];
  const __nv_bfloat16* in_x;
  const __nv_bfloat16* wqkv_p[2];
  const __nv_bfloat16* wo_p[2];
  __nv_bfloat16* out;
  uint32_t zero;
};

__device__ __forceinline__ void colsum_part(const CUtensorMap* wmap, int ty, int qr, int hp) {
  constexpr uint32_t bars = SBASE + OFF_BAR, slots = SBASE + OFF_SLOT;
  PHASE_IDS
  const unsigned ep1 = launch_epoch();
  if (wwarp == 0 && elect_one()) {
    mbar_expect_tx(bars + 8u * B_CS, 6 * UNIT);
#pragma unroll 1
    for (int j = 0; j < 6; j++) {
      if (ty == 0) mbar_pace(bars + 8u * (B_QF + B_E + ((j * CSA / 6) & 3)), (j * CSA / 6) >> 2, j ? PN1 : 30);
      else mbar_wait_lazy<100>(bars + 8u * (B_WF + B_E + ((2 * j + 3 - (j & 1)) & 7)), j >= 3);
      tma_load_2d(slots + j * UNIT, wmap, bars + 8u * B_CS, (j >> 1) * 1024 + hp * 64, qr * 128 + (j & 1) * 64);
    }
  }
  constexpr uint64_t ones = (SBASE + OFF_LSB + 32) >> 4;
  float s[3][4];
  mbar_wait_lazy<100>(bars + 8u * B_CS, ty);
  wgmma_fence();
#pragma unroll
  for (int p = 0; p < 3; p++) {
    wgmma_n8_ssz_ta1_tb0(s[p], make_desc(slots + p * 2 * UNIT, 16), ones);
#pragma unroll
    for (int k = 1; k < 8; k++) wgmma_n8_ss_ta1_tb0(s[p], make_desc(slots + p * 2 * UNIT + k * 2048, 16), ones, 1);
  }
  wgmma_commit();
  wgmma_wait<0>();
  reg_fence<12>(&s[0][0]);
  if (lane == 0) mbar_arrive(bars + 8u * (ty ? B_CSD : B_RDONE));
  if (c == 0) {
#pragma unroll
    for (int r = 0; r < 2; r++) st_rec(&g_cs[ty][hp][qr][wwarp * 16 + 8 * r + g], s[0][2 * r], s[1][2 * r], s[2][2 * r], ep1);
  }
}

__device__ __forceinline__ void put_colsums(int ty, int col, const float4& s) {
  const float v[3] = {s.x, s.y, s.z};
#pragma unroll
  for (int p = 0; p < 3; p++) {
    const uint32_t a = SBASE + OFF_CS + (p * 8 + (col >> 3)) * 64 + ty * 32 + (col & 7) * 2;
    const float hi = bf16_round(v[p]);
    const uint32_t w = pack_bf16x2(hi, v[p] - hi);
    asm volatile("st.shared.b16 [%0], %1;" ::"r"(a), "h"((unsigned short)w) : "memory");
    asm volatile("st.shared.b16 [%0], %1;" ::"r"(a + 16), "h"((unsigned short)(w >> 16)) : "memory");
  }
}

__device__ __forceinline__ uint32_t ln_params(float s1, float s2) {
  const float mean = s1 * (1.0f / DM);
  const float var = fmaxf(fmaf(-mean, mean, s2 * (1.0f / DM)), 0.f);
  float sd;
  asm("sqrt.approx.f32 %0, %1;" : "=f"(sd) : "f"(bf16_round(bf16_round(var) + 1e-5f)));
  return pack_bf16x2(mean, sd);
}

__host__ __device__ constexpr uint32_t w_rel(int kt) { return ((B_WF + (kt & 7)) << 1) | (kt >> 3); }
__host__ __device__ constexpr uint32_t w_rel4(int a, int b, int c, int d) { return w_rel(a) | (w_rel(b) << 8) | (w_rel(c) << 16) | (w_rel(d) << 24); }
__device__ __forceinline__ void ring_wait(uint32_t e) { mbar_wait(SBASE + OFF_BAR + 8u * B_E + ((e << 2) & 0x3f8u), e & 1u); }
struct RingProd {
  uint32_t rel = ((B_QF << 1) | 1) * 0x01010101u + 0x06040200u;
  __device__ __forceinline__ void q_step(int kt) {
    const int sh = 8 * (kt & 3);
    const uint32_t e = rel >> sh;
    rel ^= ((e ^ (((B_QF + (kt & 3)) << 1) | ((kt >> 2) & 1))) & 255u) << sh;
    ring_wait(e);
  }
  __device__ __forceinline__ void w_job(int st, bool pre, uint32_t sel0, uint32_t sel1, uint32_t last, uint32_t& w0, uint32_t& w1) {
    const uint32_t r = __funnelshift_r(rel, rel, 8 * st);
    w0 = __byte_perm(r, 0u, sel0);
    w1 = __byte_perm(r, w_rel4(0, 1, 2, 3), pre ? sel1 : 0x6543u);
    const uint32_t n = pre ? (w_rel4(9, 11, 13, 0) & 0xffffffu) | (last << 24) : (w_rel4(11, 13, 0, 15) & 0xff00ffffu) | (last << 16);
    rel = __funnelshift_l(n, n, 8 * st);
  }
};

#define SP1 15
#define SP2 13
#define SP3 11
#define SP4 11
#define SP5 15
#define SP6 13
#define SP7 16
__device__ __forceinline__ int q_split(int inst) {
  constexpr uint32_t T = 15u | ((SP1 - 1) << 4) | ((SP2 - 1) << 8) | ((SP3 - 1) << 12) | ((SP4 - 1) << 16) | ((SP5 - 1) << 20) |
                         ((SP6 - 1) << 24) | ((uint32_t)(SP7 - 1) << 28);
  return (int)((T >> (4 * inst)) & 15u) + 1;
}
#define QROT 4
#define WROT 2
__device__ __forceinline__ int qk(int kt) { return (((kt & 12) | ((kt & 1) << 1) | ((kt >> 1) & 1)) + QROT) & 15; }
__device__ __forceinline__ int wk(int kt) { return (kt + WROT) & 15; }
__host__ __device__ constexpr uint32_t turn_par(int kind) {
  const int sp[8] = {16, SP1, SP2, SP3, SP4, SP5, SP6, SP7};
  int cnt[2] = {0, 0};
  uint32_t m = 0;
  for (int i = 0; i < 8; i++)
    for (int k = 0; k < 3; k++) {
      if (k == kind) m |= (uint32_t)(cnt[i & 1] & 1) << i;
      if (k == 0 ? (i == 1 || (i > 1 && sp[i - 1] < 16)) : (k == 2 || sp[i] < 16)) cnt[i & 1]++;
    }
  return m;
}
#define PREMASK 0xBFu
__device__ __forceinline__ bool w_pre(int inst) { return (PREMASK >> inst) & 1u; }
#define STGMASK 0x2Eu
__device__ __forceinline__ bool w_stg(int inst) { return (STGMASK >> inst) & 1u; }
__device__ __forceinline__ uint32_t w_out(int inst) {
  return w_stg(inst) ? SBASE + OFF_SLOT : SBASE + (((inst < 7 ? q_split(inst + 1) : 0) + (w_pre(inst) ? 3 : 2)) & 3) * 5 * UNIT;
}
__host__ __device__ constexpr unsigned long long bar_counts(int i0) {
  unsigned long long t = 0;
  for (int i = i0; i < i0 + 32; i++) {
    int l = 0;
    if (i < B_RF) l = 1;
    if ((i >= B_E && i < B_E + B_RF) || i == B_LOC || i == B_REL || i == B_OS0 || i == B_TURN || i == B_TURN + 1 || i == B_XS ||
        i == B_XS + 1 || i == B_CSD || i == B_GO || i == B_RDONE || i == B_KV)
      l = 2;
    if (i == B_REL + 1 || i == B_REL + 2) l = 3;
    t |= (unsigned long long)l << (2 * (i - i0));
  }
  return t;
}

__global__ void __launch_bounds__(512, 1) fused_kernel(const __grid_constant__ Params P) {
  extern __shared__ __align__(1024) uint8_t smem_raw[];
  constexpr uint32_t base = SBASE, bars = base + OFF_BAR, slots = base + OFF_SLOT;
  if (smem_u32(smem_raw) != base) __trap();
  const int warp = __shfl_sync(0xffffffffu, threadIdx.x >> 5, 0), lane = threadIdx.x & 31;
  const int b = blockIdx.x;
#define QS 1
#define WS 1
  const int qr = ((b & ((8 << QS) - 1)) >> QS) ^ (((b >> (3 + QS)) & 1) * 7);
  const int hp = ((b >> (3 + QS)) << QS) + (b & ((1 << QS) - 1));
  const int rt = ((b & ((16 << WS) - 1)) >> WS) ^ (((b >> (4 + WS)) & 1) * 15);
  const int ct = ((b >> (4 + WS)) << WS) + (b & ((1 << WS) - 1));

  if (warp < 12) {
    if (warp >= 4) {
      if (elect_one()) {
#pragma unroll 1
        for (int i = warp; i <= B_KV; i += 8) mbar_init(bars + 8u * i, 1u << (((i < 32 ? bar_counts(0) : bar_counts(32)) >> (2 * (i & 31))) & 3u));
        sts32(warp < 8 ? base + OFF_ONE - 16 + 4 * warp : base + OFF_LSB + 4 * warp, warp < 8 ? warp == 4 : 0x3f803f80u);
        fence_proxy_async_smem();
        fence_barrier_init();
      }
      __syncwarp();
    }
    const bool asst = warp >= 8;
    GTL(0);
    if (warp >= 4) named_bar_sync(0, 512);
    if (warp >= 4 && !asst) {
      PHASE_IDS
      {
        const unsigned ep1 = launch_epoch();
        const int row = b * 16 + (tid >> 3);
        const uint4* src = reinterpret_cast<const uint4*>(P.in_x + (size_t)row * DM) + (tid & 7);
        float s1 = 0.f, s2 = 0.f;
#pragma unroll 1
        for (int k = 0; k < 4; k++) {
          mbar_pace(bars + 8u * (B_QF + B_E + ((2 * k) & 3)), k >> 1, k ? PN2 : 30);
          uint4 v[4];
#pragma unroll
          for (int j = 0; j < 4; j++) v[j] = __ldg(src + (k * 4 + j) * 8);
#pragma unroll
          for (int j = 0; j < 4; j++) {
            const uint32_t w[4] = {v[j].x, v[j].y, v[j].z, v[j].w};
#pragma unroll
            for (int e = 0; e < 4; e++) {
              const float x0 = bf_lo(w[e]), x1 = bf_hi(w[e]);
              s1 += x0 + x1;
              s2 = fmaf(x0, x0, fmaf(x1, x1, s2));
            }
          }
        }
#pragma unroll
        for (int o = 1; o < 8; o <<= 1) {
          s1 += __shfl_xor_sync(0xffffffffu, s1, o);
          s2 += __shfl_xor_sync(0xffffffffu, s2, o);
        }
        if ((tid & 7) == 0) st_rec(&g_stats[0][row], s1, s2, 0.f, 4u * ep1);
        if (tid == 0) sts32(base + OFF_EPOCH, ep1);
        if (tid < 64) {
          const float4 s0 = sum_recs<8>(&g_cs[0][hp][0][tid], 64, ep1);
          put_colsums(0, tid, s0);
        } else {
          put_colsums(1, tid - 64, make_float4(0.f, 0.f, 0.f, 0.f));
        }
#pragma unroll 1
        for (int cc = 0; cc < 2; cc++) {
          const float4 s0 = sum_recs<1>(&g_stats[0][(cc * 8 + qr) * 128 + tid], 0, 4u * ep1);
          sts32(base + OFF_RS + (cc * 128 + tid) * 4, ln_params(s0.x, s0.y));
        }
        fence_proxy_async_smem();
        named_bar_sync(2, 128);
        if (tid < 2) mbar_arrive(bars + 8u * (B_PREP + tid));
      }
    }
#pragma unroll 1
    for (int inst = asst ? 0 : warp >> 2; inst < 8; inst += asst ? 1 : 2) {
      const int L = inst >> 1, ch = inst & 1, gb = ch * 8 + qr;
      uint32_t q[2][2][4];
      if (asst) {
        if (inst < 2) colsum_part(&P.wqkv[inst], inst, qr, hp);
        setmaxnreg_dec<24>();
        named_bar_sync(4, 256);
        setmaxnreg_inc<128>();
        const uint32_t ra = q_row_addr(L & 1, 1, warp & 3, fresh_tid() & 31);
#pragma unroll
        for (int j = 0; j < 4; j++) ldmatrix_x4(q[j >> 1][j & 1], ra ^ (j << 5));
      } else {
      setmaxnreg_inc<224>();
      {
        float acc[2][96];
        const int ksp = q_split(inst);
        constexpr uint32_t STG = 5 * (UNIT >> 4), D0 = ((base + 3 * UNIT) >> 4) + 0x10000u;
        constexpr uint32_t DB = ((UNIT >> 4) << 16) - 0x10000u - 3 * (UNIT >> 4);
        const uint32_t toff = ((fresh_tid() & 127) << 7) + ((fresh_tid() & 7) << 4);
        const bool lane0 = (toff & 0xf80u) == 0u;
        uint32_t xt = x_tag(L), tro = (warp & 3) * 2048 + (toff & 0x7f0u) + ((toff << 2) & 0x2000u);
        auto check_x = [&](uint32_t bar, uint32_t par, uint32_t ta, int kt, uint32_t mask) {
          fix_lines(bar, par, ta, xt, mask, 7, [&](int l) {
            return g_x + (size_t)(gb * 128 + (l >> 4) * 64 + tile_row(L & 1, warp & 3, (l >> 3) & 1, l & 7)) * DM + qk(kt) * 64;
          });
        };
        uint32_t rsa = base + OFF_RS + (ch * 128 + tile_row(L & 1, warp & 3, 0, (toff >> 9) & 7)) * 4;
        uint32_t rsb = rsa + ((L & 1) ? 32 : 128);
        uint32_t lnm = ((toff >> 7) & 3) == (L & 1) ? 0xffffffffu : 0u, tmk = L > 0;
        uint32_t soff = tile_row(L & 1, warp & 3, (toff >> 10) & 1, (toff >> 7) & 7) * 128 + ((toff ^ (toff >> 7)) & 0x10u) + (toff & 0x60u);
        uint32_t bprep = bars + 8u * (B_PREP + ch), bturn = bars + 8u * (B_TURN + (ch ^ 1));
        const bool stg = inst > 0 && w_stg(inst - 1);
        uint32_t bfree = bars + 8u * (inst == 1 ? B_CSD : (stg ? B_RF + B_E : B_RDONE));
        uint32_t pfree = inst == 1 ? 0 : (inst & 1) ^ stg, pprep = L & 1;
        asm volatile("" : "+r"(rsa), "+r"(rsb), "+r"(lnm), "+r"(soff), "+r"(xt), "+r"(tmk), "+r"(tro));
        asm volatile("" : "+r"(bprep), "+r"(bturn), "+r"(bfree), "+r"(pfree), "+r"(pprep));
        if (inst == 0) named_bar_sync(0, 512);
        if (inst == 1 || (inst > 1 && q_split(inst - 1) < 16)) mbar_wait_lazy<TLAZY>(bars + 8u * (B_TURN + ch), (turn_par(0) >> inst) & 1u);
        if (L == 3) GTL(37);
        check_x(bars + 8u * B_QF, 0, base + 3 * UNIT + tro, 0, tmk);
        GTL(1 + L * 8);
        {
          const uint64_t da = desc_lo(D0) + P.zero;
          wgmma_fence();
          wgmma_n192_ssz_ta0_tb1(acc[1], da + (UNIT >> 4), da + DB);
          wgmma_commit();
          wgmma_n192_ssz_ta0_tb1(acc[0], da, da + DB);
          wgmma_commit();
        }
        int left = ksp;
        asm volatile("" : "+r"(left));
        uint64_t da = desc_lo(D0) + P.zero, dn = da + STG;
        uint32_t fn = bars + 8u * (B_QF + 1), pn = 0, ta = base + 8 * UNIT + tro;
#pragma unroll 1
        for (int kt = 0; kt < 15; kt++) {
          bool ok, last;
          uint32_t tw;
#pragma unroll
          for (int k16 = 0; k16 < 4; k16++) {
            if (k16 == 0 && kt == 0) continue;
            wgmma_fence();
            wgmma_n192_ss_ta0_tb1(acc[1], da + ((UNIT >> 4) + k16 * 2), da + (DB + k16 * 128), 1);
            wgmma_commit();
            if (k16 == 0) {
              const int s1 = (kt + 1) & 3;
              dn = desc_lo(D0 + s1 * STG) + P.zero;
              ta = base + 3 * UNIT + s1 * 5 * UNIT + tro;
            }
            if (k16 == 1) last = --left == 0;
            if (k16 == 3) ok = !__any_sync(0xffffffffu, !ok || ((tw ^ xt) & tmk)) && !last;
            wgmma_wait<1>();
            if (k16 == 0 && lane0 && left != 0) mbar_arrive(bars + 8u * (B_QF + B_E + ((kt - 1) & 3)));
            wgmma_fence();
            wgmma_n192_ss_ta0_tb1(acc[0], da + k16 * 2, da + (DB + k16 * 128), 1);
            wgmma_commit();
            if (k16 == 0) {
              fn = bars + 8u * (B_QF + ((kt + 1) & 3));
              pn = ((kt + 1) >> 2) & 1;
            }
            if (k16 == 2) {
              ok = mbar_test(fn, pn);
              tw = lds32(ta);
              if (last && lane0) mbar_arrive(bturn);
            }
            if (k16 < 3) wgmma_wait<1>();
          }
          da = dn;
          if (!ok) {
            if (last) {
              wgmma_wait<0>();
              if (lane0) mbar_arrive(bars + 8u * (B_QF + B_E + (kt & 3)));
            }
            if (last) mbar_wait_lazy<TLAZY>(bars + 8u * (B_TURN + ch), (turn_par(1) >> inst) & 1u);
            check_x(fn, pn, ta, kt + 1, tmk);
          }
        }
        constexpr uint32_t DL = D0 + 3 * STG;
        wgmma_fence();
#pragma unroll
        for (int k16 = 0; k16 < 4; k16++) wgmma_n192_ss_ta0_tb1(acc[1], desc_lo(DL + (UNIT >> 4) + k16 * 2), desc_lo(DL + DB + k16 * 128), 1);
        wgmma_commit();
        mbar_wait(bprep, pprep);
        uint32_t rs[2][2];
        constexpr uint64_t DCS = (uint64_t)((base + OFF_CS) >> 4) | (4ull << 32);
        auto ln_mma = [&](float (&d)[96], uint32_t (&r)[2], int h) {
          uint32_t a[4];
#pragma unroll
          for (int i = 0; i < 2; i++) {
            if (h) r[i] = lds32((i ? rsb : rsa) + 256);
            a[i] = (__byte_perm(r[i], 0u, 0x1010) ^ 0x80008000u) & lnm;
            a[i + 2] = r[i] & P.zero;
          }
#pragma unroll
          for (int i = 0; i < 4; i++) asm volatile("" : "+r"(a[i]));
          wgmma_fence();
          wgmma_n192_rs_tb1(d, a, DCS, 1);
          wgmma_commit();
        };
        ln_mma(acc[1], rs[1], 1);
        wgmma_wait<2>();
        if (lane0 && ksp != 15) mbar_arrive(bars + 8u * (B_QF + B_E + 2));
        wgmma_fence();
#pragma unroll
        for (int k16 = 0; k16 < 4; k16++) wgmma_n192_ss_ta0_tb1(acc[0], desc_lo(DL + k16 * 2), desc_lo(DL + DB + k16 * 128), 1);
        wgmma_commit();
        if (lane0) mbar_arrive(bturn);
        rs[0][0] = lds32(rsa);
        rs[0][1] = lds32(rsb);
        static_assert(SP1 < 16 && SP5 < 16 && (PREMASK & 1u) && !(STGMASK & 1u), "column sums of B");
        const bool afree = mbar_test(bfree, pfree) & (mbar_test(bars + 8u * (B_WF + B_E + 7), 1) | (ksp == 16));
        float rinv[2];
#pragma unroll
        for (int r = 0; r < 2; r++) {
          rinv[r] = rcp_fast(bf_hi(rs[1][r]));
          asm volatile("" : "+f"(rinv[r]));
        }
        const uint32_t kdst = ((L & 1) ? KB_ROW0 : slots) + soff, vdst = ((L & 1) ? VB_ROW0 : slots + 8192) + soff;
        const uint32_t hs = (L & 1) ? 8192 : 16384, c0 = (toff & 0x180u) == 0u;
        wgmma_wait<1>();
        ln_mma(acc[0], rs[0], 0);
        reg_fence<96>(acc[1]);
        GTL(2 + L * 8);
        if (!afree) {
          mbar_wait(bfree, pfree);
          if (ksp < 16) mbar_wait(bars + 8u * (B_WF + B_E + 7), 1);
        }
#pragma unroll
        for (int t = 0; t < 24; t++) {
          const int h = t < 12 ? 1 : 0, p = ((t % 12) / 4 + 1) % 3, jp = t & 3;
          if (t == QREL) {
            wgmma_wait<0>();
            reg_fence<96>(acc[0]);
            if (lane0) mbar_arrive(bars + 8u * (B_QF + B_E + 3));
          }
          if (t == 8 || t == 20) {
            rinv[0] *= SM_C;
            rinv[1] *= SM_C;
          }
          const float* a = &acc[h][4 * (p * 8 + 2 * jp)];
          uint32_t r0 = pack_bf16x2(a[0] * rinv[0], a[1] * rinv[0]);
          uint32_t r1 = pack_bf16x2(a[2] * rinv[1], a[3] * rinv[1]);
          if (p != 0 && jp == 0) {
            r0 = set_tag(r0, c0, kv_tag(L));
            r1 = set_tag(r1, c0, kv_tag(L));
          }
          const uint32_t r2 = pack_bf16x2(a[4] * rinv[0], a[5] * rinv[0]);
          const uint32_t r3 = pack_bf16x2(a[6] * rinv[1], a[7] * rinv[1]);
          const uint32_t dst = p == 0 ? slots + 3 * 16384 + soff + h * 8192 : (p == 1 ? kdst : vdst) + h * hs;
          stmatrix_x4(dst ^ (jp << 5), r0, r1, r2, r3);
          if (t >= 20) {
            q[jp >> 1][jp & 1][0] = r0;
            q[jp >> 1][jp & 1][1] = r1;
            q[jp >> 1][jp & 1][2] = r2;
            q[jp >> 1][jp & 1][3] = r3;
          }
          if (t == 7 || t == 19) signal_async(bars + 8u * (t == 7 ? B_KV : B_LOC), lane0);
          if (t == 11) {
            setmaxnreg_dec<128>();
            named_bar_arrive(4, 256);
#pragma unroll
            for (int r = 0; r < 2; r++) rinv[r] = rcp_fast(bf_hi(rs[0][r]));
          }
        }
        mbar_wait(bars + 8u * B_LOC, inst & 1);
      }
      }
      GTL(3 + L * 8);
      if ((L & 1) == 0) attention_a(q, asst, L, gb, hp, ch, warp & 3, P.zero);
      else attention_b(q, asst, gb, inst & 1, warp & 3);
      GTL(4 + L * 8);
      signal_async(bars + 8u * (asst ? B_OS1 : B_OS0), (fresh_tid() & 31) == 0);
      if (asst) continue;
      GTL(5 + L * 8);

      {
        float acc[64];
        const int sp = inst < 7 ? q_split(inst + 1) : 0;
        const int st = sp & 3;
        const bool pre = w_pre(inst);
        const uint32_t toff = ((fresh_tid() & 63) << 7) + ((fresh_tid() & 7) << 4);
        uint32_t tro = (warp & 3) * 2048 + (toff & 0x7f0u);
        auto check_o = [&](uint32_t bar, uint32_t par, uint32_t sa, int kt) {
          fix_lines(bar, par, sa + tro, o_tag(L), 1u, 7, [&](int l) {
            return g_o + (size_t)(ch * 1024 + rt * 64 + (warp & 3) * 16 + (l & 15)) * DM + wk(kt) * 64;
          });
        };
        const bool lane0 = (toff & 0xf80u) == 0u;
        constexpr uint32_t U4 = UNIT >> 4, LA = 0x10000u, LB = U4 << 16;
        reg_define<64>(acc);
        reg_fence<64>(acc);
        uint32_t xv[8][4];
        {
          PHASE_IDS_W
          const uint32_t xr = slots + 6 * UNIT + (wwarp * 16 + (lane & 15)) * 128 + (((lane >> 4) ^ (lane & 7)) << 4);
          mbar_wait(bars + 8u * B_RF, inst & 1);
#pragma unroll
          for (int jp = 0; jp < 8; jp++) ldmatrix_x4(xv[jp], (xr ^ ((jp & 3) << 5)) + (jp >> 2) * UNIT);
          signal_async(bars + 8u * B_RDONE, lane0);
          if (L > 0) {
            uint32_t lsb;
            asm volatile("ld.shared.u8 %0, [%1];" : "=r"(lsb) : "r"(base + OFF_LSB + ch * 32 + wwarp * 8 + g) : "memory");
#pragma unroll
            for (int k = 0; k < 4; k++) xv[(k >> 1) * 4][k & 1] = set_tag(xv[(k >> 1) * 4][k & 1], c == 0, lsb >> k);
          }
        }
        uint32_t tmx = L < 3 && (toff & 0x180u) == 0u, xt = x_tag(L + 1);
        uint32_t xrow = w_out(inst) + (warp & 3) * 2048 + (toff & 0x7e0u) + ((toff ^ (toff >> 7)) & 0x10u);
        asm volatile("" : "+r"(tmx), "+r"(xt), "+r"(xrow), "+r"(tro));
        const uint64_t dz = desc_lo(0) + P.zero;
        auto nexts = [&](uint32_t a) { return a == base + 15 * UNIT ? base : a + 5 * UNIT; };
        uint32_t s0 = base + st * 5 * UNIT, sp3 = slots, fb = bars + 8u * B_WF;
        int turn = lane0 && (sp < 16 || inst == 6) ? 3 : -1;
        asm volatile("" : "+r"(turn));
        if (inst < 7 || SP7 == 16) mbar_wait_lazy<TLAZY>(bars + 8u * (B_TURN + ch), (turn_par(2) >> inst) & 1u);
        check_o(bars + 8u * B_WF, 0, s0, 0);
        GTL(6 + L * 8);
#pragma unroll 1
        for (int m = 0; m < 4; m++) {
          uint32_t s1, s2;
#pragma unroll
          for (int i = 0; i < 4; i++) {
            const uint64_t da = dz + ((i == 0 ? s0 : s1) >> 4) + (LA + (i == 2 ? 1 : (i == 3 ? 4 : 0)) * U4);
            const uint64_t db = dz + ((i < 2 ? s0 : (i == 2 ? s1 : s2)) >> 4) + (LB + (i == 0 ? 1 : (i == 1 ? 3 : (i == 2 ? 2 : 0))) * U4);
            wgmma_fence();
#pragma unroll
            for (int k16 = 0; k16 < 4; k16++) wgmma_n128_ss_ta0_tb1(acc, da + 2 * k16, db + 128 * k16, 1);
            wgmma_commit();
            if (i == 0) s1 = nexts(s0);
            if (i == 1) s0 = nexts(s1);
            if (i == 2) {
              s2 = pre ? sp3 : s0;
              s0 = pre ? s0 : nexts(s0);
              sp3 += 2 * UNIT;
            }
            const uint32_t fn = i < 3 ? fb + 8u * (i + 1) : fb ^ 96u;
            const uint32_t pn = i < 3 ? m >> 1 : m > 0;
            const uint32_t an = i < 3 ? s1 + (i == 1 ? 1 : (i == 2 ? 4 : 0)) * UNIT : s0;
            bool ok = mbar_test(fn, pn);
            const uint32_t tw = lds32(an + tro);
            ok = !__any_sync(0xffffffffu, (!ok || ((tw ^ o_tag(L)) & 1u)) && (i < 3 || m < 3));
            wgmma_wait<1>();
            if (lane0 && (i > 0 || m > 0)) mbar_arrive((i > 0 ? fb + 8u * (i - 1) : (fb ^ 96u) + 24u) + 8u * B_E);
            if (i == 2 && m == turn) mbar_arrive(bars + 8u * (B_TURN + (ch ^ 1)));
            if (!ok) check_o(fn, pn, an, 4 * m + i + 1);
          }
          fb ^= 96u;
        }
        wgmma_wait<0>();
        reg_fence<64>(acc);
        if (lane0) mbar_arrive(bars + 8u * (B_WF + B_E + 7));
        GTL(7 + L * 8);
#pragma unroll
        for (int jp = 0; jp < 8; jp++) {
#pragma unroll
          for (int q = 0; q < 4; q++) xv[jp][q] = add_bf16x2(xv[jp][q], pack_bf16x2(acc[8 * jp + 2 * q], acc[8 * jp + 2 * q + 1]));
          const bool tg = (jp & 3) == 0;
          stmatrix_x4((xrow ^ ((jp & 3) << 5)) + (jp >> 2) * UNIT,
                      tg ? set_tag(xv[jp][0], tmx, xt) : xv[jp][0], tg ? set_tag(xv[jp][1], tmx, xt) : xv[jp][1], xv[jp][2], xv[jp][3]);
          if ((jp & 3) == 3) signal_async(bars + 8u * (B_XS + (jp >> 2)), lane0);
        }
        if (L < 3) {
          PHASE_IDS_W
          const int grow = ch * 1024 + rt * 64;
          const unsigned ep1 = lds32(base + OFF_EPOCH);
          if (c == 0)
            asm volatile("st.shared.u8 [%0], %1;" ::"r"(base + OFF_LSB + ch * 32 + wwarp * 8 + g),
                         "r"((xv[0][0] & 1u) | ((xv[0][1] & 1u) << 1) | ((xv[4][0] & 1u) << 2) | ((xv[4][1] & 1u) << 3)) : "memory");
          float s1[2] = {0.f, 0.f}, s2[2] = {0.f, 0.f};
#pragma unroll
          for (int jp = 0; jp < 8; jp++)
#pragma unroll
            for (int q = 0; q < 4; q++) {
              const float x0 = bf_lo(xv[jp][q]), x1 = bf_hi(xv[jp][q]);
              s1[q & 1] += x0 + x1;
              s2[q & 1] = fmaf(x0, x0, fmaf(x1, x1, s2[q & 1]));
            }
#pragma unroll
          for (int r = 0; r < 2; r++) {
            s1[r] += __shfl_xor_sync(0xffffffffu, s1[r], 1);
            s2[r] += __shfl_xor_sync(0xffffffffu, s2[r], 1);
            s1[r] += __shfl_xor_sync(0xffffffffu, s1[r], 2);
            s2[r] += __shfl_xor_sync(0xffffffffu, s2[r], 2);
            if (c == 0) st_rec(&g_stats[ct][grow + wwarp * 16 + g + 8 * r], s1[r], s2[r], 0.f, 4u * ep1 + L + 1);
          }
        }
        GTL(8 + L * 8);
      }
    }
    if (threadIdx.x == 128) atomicAdd(g_done, 1u);
  } else {
    setmaxnreg_dec<32>();
    if (warp == 13) {
      RingProd rp;
      unsigned ep1 = 0;
      uint32_t seenx = 0;
      named_bar_sync(0, 512);
      mbar_wait(bars + 8u * B_GO, 0);
#pragma unroll 1
      for (int sg = 4; sg < 34; sg++) {
        const int part = sg & 3, inst = (sg >> 2) - (part & 1);
        if (part == 3 || inst == 8) continue;
        const int L = inst >> 1, ch = inst & 1;
        if (part != 1) {
          const CUtensorMap* tx = &P.xq[L];
          const int k0 = part ? q_split(inst) : 0, k1 = part ? 16 : q_split(inst);
          if (sg == 4) ep1 = launch_epoch();
          if (part == 0) seenx = L == 0 ? 0xffffffffu : peek_counts(g_fx[ch * 8 + qr][0], 6u * ep1 - 6u + 2u * L, lane);
          const int m0 = ch * 16 + qr * 2;
#pragma unroll 1
          for (int kt = k0; kt < k1; kt++) {
            const uint32_t fb = bars + 8u * (B_QF + (kt & 3));
            rp.q_step(kt);
            if (lane == 0) mbar_expect_tx(fb, 2 * UNIT);
            wait_count(g_fx[ch * 8 + qr][0], 6u * ep1 - 6u + 2u * L, qk(kt), seenx, lane);
            TGET(t38);
            if (elect_one()) tma_load_5d(base + ((kt & 3) * 5 + 3) * UNIT, tx, fb, qk(kt) * 64, m0);
            TGET(t39);
            if (L == 3 && kt == 0 && lane == 0) { TPUT(ch, 38, t38); TPUT(ch, 39, t39); }
          }
        } else {
          const int m0 = ch * 1024 + rt * 64;
          const bool pre = w_pre(inst);
          int st = inst < 7 ? q_split(inst + 1) & 3 : 0;
          uint32_t w0, w1;
          uint32_t seen = peek_counts(g_fo[ch * 16 + rt][0], 4u * ep1 - 3u + L, lane);
          rp.w_job(st, pre, 0x1110u, 0x3332u, inst == 6 && SP7 == 16 ? B_RF << 1 : w_rel(15), w0, w1);
#pragma unroll 1
          for (int m = 0; m < 4; m++) {
            const uint32_t fb = bars + 8u * (B_WF + 4 * (m & 1));
#pragma unroll
            for (int i = 0; i < 4; i++) {
              ring_wait(w0 >> (8 * i));
              if (lane == 0) mbar_expect_tx(fb + 8u * i, UNIT);
              wait_count(g_fo[ch * 16 + rt][0], 4u * ep1 - 3u + L, wk(4 * m + i), seen, lane);
              if (elect_one())
                tma_load_2d(base + ((st + (i > 0)) & 3) * 5 * UNIT + (i == 2 ? 1 : (i == 3 ? 4 : 0)) * UNIT, &P.o, fb + 8u * i, wk(4 * m + i) * 64, m0);
            }
            st += pre ? 2 : 3;
            w0 = w1;
            w1 = m == 0 ? (pre ? w_rel4(0, 1, 2, 3) : w_rel4(3, 4, 5, 6)) : (pre ? w_rel4(4, 5, 6, 7) : w_rel4(7, 8, 9, 10));
          }
        }
      }
#pragma unroll 1
      for (int j = 0; j < 8; j++)
        g_x[(size_t)((j >> 2) * 1024 + rt * 64 + (j & 3) * 16 + (lane >> 1)) * DM + ct * 128 + (lane & 1) * 64] = __ushort_as_bfloat16(0);
    } else if (warp == 14) {
      const unsigned ep1 = launch_epoch();
      uint32_t hpar = 0;
      named_bar_sync(0, 512);
#pragma unroll 1
      for (int inst = 0; inst < 8; inst++) {
        const int L = inst >> 1, ch = inst & 1, gb = ch * 8 + qr;
        const unsigned kv0 = 8u * ep1 - 8u + 2u * L + (L & 1);
        const uint32_t tag = kv_tag(L);
        if (L >= 2) {
#pragma unroll 1
          for (uint32_t it = 0; it < (1u << 17); ++it)
            if (__all_sync(0xffffffffu, (int)(ld_relaxed_u32(g_fk[hp][min(gb + 1 + (lane & 1), 15)]) - kv0) >= 0)) break;
        }
        if ((L & 1) == 0) {
          uint8_t* img = g_kvA[gb][hp][0];
          const uint8_t* s1 = gb > 0 ? img - 16 * 32768 : g_zero;
          const uint8_t* s2 = gb > 1 ? img - 32 * 32768 : g_zero;
          const uint32_t h1 = gb > 0 ? 16384 : 0, h2 = gb > 1 ? 16384 : 0;
          const unsigned* cp = g_fk[hp][max(gb - 1 - (lane >= 3), 0)];
          const unsigned ct0 = kv0 + ((0x32321u >> (4 * (lane & 7))) & 3u);
          uint32_t fr = gb == 0 ? 31u : (gb == 1 ? 24u : 0u);
          const uint32_t toff = slots + lane * 128 + ((lane & 7) << 4);
          auto seen = [&](uint32_t m) {
#pragma unroll 1
            for (uint32_t it = 0; it < (1u << 17) && !(fr & m); ++it)
              fr |= __ballot_sync(0xffffffffu, (int)(ld_relaxed_u32(cp) - ct0) >= 0);
          };
          auto load = [&](uint32_t off, const uint8_t* src, uint32_t bytes, int bi) {
            if (elect_one()) {
              mbar_expect_tx(bars + 8u * (B_HL + bi), bytes);
              bulk_load(slots + off, src, bytes, bars + 8u * (B_HL + bi));
            }
          };
          auto check = [&](uint32_t off, const uint8_t* src, uint32_t bytes, int bi, bool real, int done) {
#pragma unroll 1
            for (int tries = 0; tries < 4096; tries++) {
              mbar_wait(bars + 8u * (B_HL + bi), (hpar >> bi) & 1u);
              hpar ^= 1u << bi;
              uint32_t t = (lds32(toff + off) ^ tag) | (lds32(toff + off + 4096) ^ tag);
              if (bytes > 8192) t |= (lds32(toff + off + 8192) ^ tag) | (lds32(toff + off + 12288) ^ tag);
              if (!__any_sync(0xffffffffu, real && (t & 1u))) break;
              fence_proxy_async_smem();
              load(off, src, bytes, bi);
            }
            if (lane == 0) mbar_arrive(bars + 8u * done);
          };
          uint8_t *pk = img + 16384, *pv = img + 24576;
          unsigned* f = g_fk[hp][gb];
          pin64(pk), pin64(pv), pin64(f);
          mbar_wait(bars + 8u * B_KV, inst & 1);
          if (ch) mbar_wait(bars + 8u * (B_RF + B_E), 0);
          if (elect_one()) {
            bulk_store(pk, slots + 16384, 8192);
            bulk_announce(f);
            bulk_store(pv, slots + 24576, 8192);
            bulk_announce(f);
            bulk_commit();
          }
          HTS(44);
          seen(1);
          HTS(46);
          load(32768, s1 + h1, 8192, 0);
          seen(2);
          HTS(47);
          load(40960, s1 + h1 + 8192, 8192, 1);
          mbar_wait(bars + 8u * B_LOC, inst & 1);
          HTS(45);
          if (elect_one()) {
            bulk_store(img, slots, 16384);
            bulk_announce(g_fk[hp][gb]);
            bulk_commit();
            asm volatile("cp.async.bulk.wait_group.read 1;" ::: "memory");
          }
          check(32768, s1 + h1, 8192, 0, gb > 0, B_HALO);
          HTS(52);
          check(40960, s1 + h1 + 8192, 8192, 1, gb > 0, B_HV);
          HTS(53);
#pragma unroll 1
          for (int n = 1; n < 4; n++) {
            const uint8_t* src = n == 1 ? s1 : (n == 2 ? s2 + h2 : s2);
            const uint32_t off = n == 3 ? 32768 : 32768 - n * 16384;
            seen(2u << n);
            if (n == 2 && elect_one()) bulk_wait_read0();
            mbar_wait(bars + 8u * (B_REL - 1) + 8u * n, ch);
            HTS(47 + n);
            load(off, src, 16384, 0);
            check(off, src, 16384, 0, gb > (n >> 1), B_HALO + n);
            HTS(53 + n);
          }
        } else {
          uint8_t *pk = g_kvB[gb][hp], *pv = pk + 2048;
          const uint8_t* src = gb >= 1 ? pk - 16 * 4096 : g_zero;
          unsigned* f = g_fk[hp][gb];
          pin64(pk), pin64(pv), pin64(f), pin64(src);
          mbar_wait(bars + 8u * B_KV, inst & 1);
          if (elect_one()) {
            bulk_store(pk, KB_ROW0 + 112 * 128, 2048);
            bulk_store(pv, VB_ROW0 + 112 * 128, 2048);
            bulk_announce(f);
            bulk_commit();
          }
          HTS(44);
          if (gb > 0) {
#pragma unroll 1
            for (uint32_t it = 0; it < (1u << 17); ++it)
              if (__any_sync(0xffffffffu, (int)(ld_relaxed_u32(f - 4) - kv0) > 0)) break;
          }
          HTS(46);
#pragma unroll 1
          for (uint32_t it = 0; it < (1u << 17); ++it) {
            if (elect_one()) {
              mbar_expect_tx(bars + 8u * B_HL, 4096);
              bulk_load(KB_ROW0 - 2048, src, 2048, bars + 8u * B_HL);
              bulk_load(VB_ROW0 - 2048, src + 2048, 2048, bars + 8u * B_HL);
            }
            mbar_wait(bars + 8u * B_HL, hpar & 1u);
            hpar ^= 1u;
            const uint32_t t = lds32((lane < 16 ? KB_ROW0 - 2048 : VB_ROW0 - 4096) + lane * 128 + ((lane & 7) << 4)) ^ tag;
            if (!__any_sync(0xffffffffu, gb > 0 && (t & 1u))) break;
            fence_proxy_async_smem();
          }
          if (lane == 0) mbar_arrive(bars + 8u * B_HALO);
          HTS(52);
        }
        if (elect_one()) {
          const CUtensorMap* mo = &P.o;
          unsigned *f1 = g_fo[gb * 2 + 1][hp], *f0 = g_fo[gb * 2][hp];
          int c0 = hp * 64, r0 = gb * 128, r1 = r0 + 64;
          pin64(mo), pin64(f1), pin64(f0);
          asm volatile("" : "+r"(c0), "+r"(r0), "+r"(r1));
          mbar_wait(bars + 8u * B_OS1, (inst & 1) ^ 1);
          tma_store_2d(mo, slots + 7 * UNIT, c0, r1);
          bulk_announce(f1);
          bulk_commit();
          mbar_wait(bars + 8u * B_OS0, inst & 1);
          tma_store_2d(mo, slots + 6 * UNIT, c0, r0);
          bulk_announce(f0);
          bulk_commit();
          HTS(57);
          const bool pre = w_pre(inst);
          bulk_wait_read0();
          HTS(58 - 15);
          mbar_expect_tx(bars + 8u * B_RF, 2 * UNIT);
          tma_load_2d(slots + 6 * UNIT, &P.x[L], bars + 8u * B_RF, ct * 128, ch * 1024 + rt * 64);
          tma_load_2d(slots + 7 * UNIT, &P.x[L], bars + 8u * B_RF, ct * 128 + 64, ch * 1024 + rt * 64);
          if (pre) {
            const uint32_t pp = __popc(PREMASK & ((1u << inst) - 1u)) & 1;
            mbar_expect_tx(bars + 8u * B_PRE, 2 * UNIT);
            mbar_expect_tx(bars + 8u * B_PRE2, 6 * UNIT);
#pragma unroll 1
            for (int j = 0; j < 4; j++) {
              __nanosleep(PRESLEEP);
              if (j == 3) mbar_wait(bars + 8u * B_RDONE, (inst & 1) ^ 1);
              tma_load_3d(slots + j * 2 * UNIT, &P.wo3[L & 1], bars + 8u * (j ? B_PRE2 : B_PRE), ct * 128, wk(4 * j + 3) * 64);
            }
#pragma unroll 1
            for (int j = 0; j < 4; j++) {
              const uint32_t fb = bars + 8u * (B_WF + 3 + 4 * (j & 1));
              if (j < 2) mbar_wait(bars + 8u * (j ? B_PRE2 : B_PRE), pp);
              if (j < 2 && inst == 7 && SP7 == 16) mbar_wait(bars + 8u * (B_TURN + 1), (turn_par(2) >> 7) & 1u);
              mbar_wait(fb + 8u * B_E, j < 2);
              mbar_arrive(fb);
            }
          }
        }
        __syncwarp();
      }
    } else if (warp == 15) {
      const unsigned ep1 = launch_epoch();
      named_bar_sync(0, 512);
      mbar_wait(bars + 8u * B_GO, 0);
#pragma unroll 1
      for (int i = 0; i < 20; i++) {
        const char* src = i < 4 ? reinterpret_cast<const char*>(P.wo_p[0]) + (size_t)b * 16384 + i * 4096
                                : (i < 16 ? reinterpret_cast<const char*>(P.wqkv_p[1]) + (size_t)b * 49152 + (i - 4) * 4096
                                          : reinterpret_cast<const char*>(P.wo_p[1]) + (size_t)b * 16384 + (i - 16) * 4096);
        asm volatile("prefetch.global.L2 [%0];" ::"l"(src + lane * 128));
        __nanosleep(TRICKLE);
      }
#pragma unroll 1
      for (int inst = 2; inst < 10; inst++) {
        const int L = inst >> 1, ch = inst & 1, gb = ch * 8 + qr;
        {
          uint32_t xb = w_out(inst - 2);
          unsigned* f = g_fx[ch * 8 + (rt >> 1)][ct * 2];
          const CUtensorMap* mx = &P.x[L];
          int c0 = ct * 128, r0 = ch * 1024 + rt * 64;
          pin64(f), pin64(mx);
          asm volatile("" : "+r"(xb), "+r"(c0), "+r"(r0));
#pragma unroll
          for (int h = 0; h < 2; h++) {
            mbar_wait(bars + 8u * (B_XS + h), ch);
            if (elect_one()) {
              tma_store_2d(mx, xb + h * UNIT, c0 + h * 64, r0);
              if (L < 4) bulk_announce(f + 4 * h);
              bulk_commit();
              if (h == 1) {
                bulk_wait_read0();
                mbar_arrive(bars + 8u * (B_RF + B_E));
              }
            }
          }
          if (L == 4) continue;
          __nanosleep(SDLY);
        }
#pragma unroll 1
        for (int h = 0; h < 4; h++) {
          const float4* sp = &g_stats[0][gb * 128 + h * 32 + lane];
          const float4 s0 = sum_recs<4>(sp, S_LEN, 4u * ep1 + L), s1 = sum_recs<4>(sp + 4 * S_LEN, S_LEN, 4u * ep1 + L);
          sts32(base + OFF_RS + (ch * 128 + h * 32 + lane) * 4, ln_params(s0.x + s1.x, s0.y + s1.y));
        }
        if (inst == 2) {
#pragma unroll 1
          for (int hf = 0; hf < 2; hf++) {
            const float4* cp = &g_cs[1][hp][0][hf * 32 + lane];
            const float4 s0 = sum_recs<4>(cp, 64, ep1), s1 = sum_recs<4>(cp + 4 * 64, 64, ep1);
            put_colsums(1, hf * 32 + lane, make_float4(s0.x + s1.x, s0.y + s1.y, s0.z + s1.z, 0.f));
          }
        }
        fence_proxy_async_smem();
        __syncwarp();
        if (lane == 0) mbar_arrive(bars + 8u * (B_PREP + ch));
      }
    } else {
      if (elect_one()) {
#pragma unroll 1
        for (int s = 0; s < 4; s++) {
          const uint32_t fb = bars + 8u * (B_QF + s), sa = base + s * 5 * UNIT;
          mbar_init(fb, 2);
          fence_barrier_init();
          mbar_expect_tx(fb, 5 * UNIT);
          mbar_arrive(fb);
          tma_load_5d(sa + 3 * UNIT, &P.xq[0], fb, s * 64, qr * 2);
          tma_load_3d(sa, &P.wqkv3[0], fb, hp * 64, s * 64);
        }
      }
      __syncwarp();
      named_bar_sync(0, 512);
      if (elect_one()) {
#pragma unroll 1
        for (int s = 4; s < 16; s++) {
          const uint32_t fb = bars + 8u * (B_QF + (s & 3)), sa = base + (s & 3) * 5 * UNIT;
          mbar_wait(fb + 8u * B_E, ((s >> 2) & 1) ^ 1);
          mbar_expect_tx(fb, 5 * UNIT);
          mbar_arrive(fb);
          tma_load_5d(sa + 3 * UNIT, &P.xq[0], fb, s * 64, qr * 2);
          tma_load_3d(sa, &P.wqkv3[0], fb, hp * 64, s * 64);
        }
#pragma unroll
        for (int s = 0; s < 4; s++) mbar_arrive(bars + 8u * B_GO);
        RingProd rp;
#pragma unroll 1
        for (int sg = 4; sg < 34; sg++) {
          const int part = sg & 3, inst = (sg >> 2) - (part & 1);
          if (part == 3 || inst == 8) continue;
          const int ty = (inst >> 1) & 1;
          if (part != 1) {
            const int k0 = part ? q_split(inst) : 0, k1 = part ? 16 : q_split(inst);
#pragma unroll 1
            for (int kt = k0; kt < k1; kt++) {
              const uint32_t sa = base + (kt & 3) * 5 * UNIT, fb = bars + 8u * (B_QF + (kt & 3));
              rp.q_step(kt);
              mbar_expect_tx(fb, 3 * UNIT);
              tma_load_3d(sa, &P.wqkv3[ty], fb, hp * 64, qk(kt) * 64);
            }
          } else {
            const bool pre = w_pre(inst);
            int st = inst < 7 ? q_split(inst + 1) & 3 : 0;
            uint32_t w0, w1;
            rp.w_job(st, pre, pre ? 0x1100u : 0x2100u, 0x3322u, w_stg(inst) ? w_rel(15) : (B_RF << 1) | (inst & 1), w0, w1);
#pragma unroll 1
            for (int m = 0; m < 4; m++) {
              const uint32_t fb = bars + 8u * (B_WF + 4 * (m & 1));
#pragma unroll
              for (int i = 0; i < 4; i++) {
                if (i < 3 || !pre) {
                  ring_wait(w0 >> (8 * i));
                  mbar_expect_tx(fb + 8u * i, 2 * UNIT);
                  tma_load_3d(base + ((st + (i ? i - 1 : 0)) & 3) * 5 * UNIT + ((0x2d >> (2 * i)) & 3) * UNIT, &P.wo3[ty], fb + 8u * i,
                              ct * 128, wk(4 * m + i) * 64);
                }
              }
              st += pre ? 2 : 3;
              w0 = w1;
              w1 = m == 0 ? (pre ? w_rel4(0, 1, 2, 3) : w_rel4(3, 4, 5, 6)) : (pre ? w_rel4(4, 5, 6, 7) : w_rel4(7, 8, 9, 10));
            }
          }
        }
      }
    }
  }
}

typedef CUresult (*PFN_tmEncode)(CUtensorMap*, CUtensorMapDataType, cuuint32_t, void*, const cuuint64_t*,
                                 const cuuint64_t*, const cuuint32_t*, const cuuint32_t*, CUtensorMapInterleave,
                                 CUtensorMapSwizzle, CUtensorMapL2promotion, CUtensorMapFloatOOBfill);

PFN_tmEncode get_encode_fn() {
  static PFN_tmEncode fn = nullptr;
  if (!fn) {
    cudaDriverEntryPointQueryResult qr;
    void* p = nullptr;
    cudaGetDriverEntryPoint("cuTensorMapEncodeTiled", &p, cudaEnableDefault, &qr);
    fn = (PFN_tmEncode)p;
  }
  return fn;
}

CUtensorMap make_map(const void* ptr, int rows, int cols) {
  CUtensorMap m;
  cuuint64_t gdim[2] = {(cuuint64_t)cols, (cuuint64_t)rows};
  cuuint64_t gstr[1] = {(cuuint64_t)cols * 2};
  cuuint32_t box[2] = {64, 64};
  cuuint32_t estr[2] = {1, 1};
  get_encode_fn()(&m, CU_TENSOR_MAP_DATA_TYPE_BFLOAT16, 2, const_cast<void*>(ptr), gdim, gstr, box, estr,
                  CU_TENSOR_MAP_INTERLEAVE_NONE, CU_TENSOR_MAP_SWIZZLE_128B, CU_TENSOR_MAP_L2_PROMOTION_L2_128B,
                  CU_TENSOR_MAP_FLOAT_OOB_FILL_NONE);
  return m;
}

CUtensorMap make_map3(const void* ptr, int rows, int cols, int n, int step) {
  CUtensorMap m;
  cuuint64_t gdim[3] = {(cuuint64_t)(cols - (n - 1) * step), (cuuint64_t)rows, (cuuint64_t)n};
  cuuint64_t gstr[2] = {(cuuint64_t)cols * 2, (cuuint64_t)step * 2};
  cuuint32_t box[3] = {64, 64, (cuuint32_t)n};
  cuuint32_t estr[3] = {1, 1, 1};
  get_encode_fn()(&m, CU_TENSOR_MAP_DATA_TYPE_BFLOAT16, 3, const_cast<void*>(ptr), gdim, gstr, box, estr,
                  CU_TENSOR_MAP_INTERLEAVE_NONE, CU_TENSOR_MAP_SWIZZLE_128B, CU_TENSOR_MAP_L2_PROMOTION_L2_128B,
                  CU_TENSOR_MAP_FLOAT_OOB_FILL_NONE);
  return m;
}

CUtensorMap make_map_q(const void* ptr, int sw, int sr) {
  CUtensorMap m;
  cuuint64_t gdim[5] = {DM, 8, 2, 4, S_LEN / 64};
  cuuint64_t gstr[4] = {DM * 2, (cuuint64_t)sr * DM * 2, (cuuint64_t)sw * DM * 2, 64 * DM * 2};
  cuuint32_t box[5] = {64, 8, 2, 4, 2};
  cuuint32_t estr[5] = {1, 1, 1, 1, 1};
  get_encode_fn()(&m, CU_TENSOR_MAP_DATA_TYPE_BFLOAT16, 5, const_cast<void*>(ptr), gdim, gstr, box, estr,
                  CU_TENSOR_MAP_INTERLEAVE_NONE, CU_TENSOR_MAP_SWIZZLE_128B, CU_TENSOR_MAP_L2_PROMOTION_L2_128B,
                  CU_TENSOR_MAP_FLOAT_OOB_FILL_NONE);
  return m;
}

}

extern "C" void kernel_launch(void* const* d_in, const int* in_sizes, int n_in, void* d_out, int out_size) {
  (void)in_sizes; (void)n_in; (void)out_size;
  void *p_o, *p_x;
  cudaGetSymbolAddress(&p_o, g_o);
  cudaGetSymbolAddress(&p_x, g_x);
  static bool attr_done = false;
  if (!attr_done) {
    cudaFuncSetAttribute(fused_kernel, cudaFuncAttributeMaxDynamicSharedMemorySize, SMEM_BYTES);
    attr_done = true;
  }
  Params P;
  P.in_x = (const __nv_bfloat16*)d_in[0];
  P.wqkv_p[0] = (const __nv_bfloat16*)d_in[1];
  P.wo_p[0] = (const __nv_bfloat16*)d_in[2];
  P.wqkv_p[1] = (const __nv_bfloat16*)d_in[4];
  P.wo_p[1] = (const __nv_bfloat16*)d_in[5];
  P.out = (__nv_bfloat16*)d_out;
  P.zero = 0;
  for (int L = 0; L < 5; L++) {
    const void* px = L == 0 ? (const void*)P.in_x : (L == 4 ? d_out : p_x);
    P.x[L] = make_map(px, S_LEN, DM);
    if (L < 4) P.xq[L] = (L & 1) ? make_map_q(px, 16, 8) : make_map_q(px, 8, 32);
  }
  P.o = make_map(p_o, S_LEN, DM);
  for (int t = 0; t < 2; t++) {
    P.wqkv[t] = make_map(P.wqkv_p[t], DM, NQKV);
    P.wqkv3[t] = make_map3(P.wqkv_p[t], DM, NQKV, 3, 1024);
    P.wo3[t] = make_map3(P.wo_p[t], DM, DM, 2, 64);
  }
    fused_kernel<<<NCTA, 512, SMEM_BYTES>>>(P);
}
```

```cpp
#include <cuda_runtime.h>
#include <cuda_bf16.h>
#include <cuda.h>
#include <stdint.h>

namespace {

constexpr int S_LEN = 2048;
constexpr int DM = 1024;
constexpr int NQKV = 3072;
constexpr int NCTA = 128;

__device__ __align__(1024) uint8_t g_kvA[16][16][2][16384];
__device__ __align__(1024) uint8_t g_kvB[16][16][4096];
__device__ __align__(1024) uint8_t g_zero[16384];
__device__ __align__(1024) __nv_bfloat16 g_o[S_LEN * DM];
__device__ __align__(1024) __nv_bfloat16 g_x[S_LEN * DM];
__device__ __align__(1024) float4 g_stats[8][S_LEN];
__device__ __align__(1024) float4 g_cs[2][16][8][64];
__device__ __align__(128) unsigned g_fx[16][16][4];
__device__ __align__(128) unsigned g_fo[32][16][4];
__device__ __align__(128) unsigned g_fk[16][16][4];
__device__ __align__(128) unsigned g_done[32];

constexpr uint32_t SBASE = 1024;
constexpr int UNIT = 8192;
constexpr int NUNITS = 20;
constexpr int OFF_SLOT = NUNITS * UNIT;
constexpr int OFF_BAR = OFF_SLOT + 4 * 16384;
constexpr int OFF_EPOCH = OFF_BAR + 424;
constexpr int OFF_LSB = OFF_BAR + 432;
constexpr int OFF_CS = OFF_BAR + 496;
constexpr int OFF_RS = OFF_CS + 1536;
constexpr int OFF_ONE = OFF_RS + 1024;
constexpr int SMEM_BYTES = OFF_ONE + 16;
constexpr int B_QF = 0, B_WF = 4, B_RF = 12, B_E = 13, B_PREP = 26, B_LOC = 28, B_HALO = 29, B_REL = 33, B_OS0 = 36,
              B_TURN = 37, B_XS = 39, B_CS = 41, B_CSD = 42, B_GO = 43, B_PRE = 44, B_HV = 45, B_REDO = 46,
              B_RDONE = 48, B_PRE2 = 49, B_HL = 50, B_KV = 52, B_OS1 = B_GO;
static_assert(SMEM_BYTES <= 232448, "shared memory");

__device__ __forceinline__ uint32_t smem_u32(const void* p) { return (uint32_t)__cvta_generic_to_shared(p); }

__device__ __forceinline__ void mbar_init(uint32_t bar, uint32_t cnt) {
  asm volatile("mbarrier.init.shared::cta.b64 [%0], %1;" ::"r"(bar), "r"(cnt));
}
__device__ __forceinline__ void mbar_expect_tx(uint32_t bar, uint32_t bytes) {
  asm volatile("mbarrier.arrive.expect_tx.shared::cta.b64 _, [%0], %1;" ::"r"(bar), "r"(bytes) : "memory");
}
__device__ __forceinline__ void mbar_arrive(uint32_t bar) {
  asm volatile("mbarrier.arrive.shared::cta.b64 _, [%0];" ::"r"(bar) : "memory");
}
__device__ __forceinline__ bool mbar_try_wait(uint32_t bar, uint32_t parity) {
  uint32_t ok;
  asm volatile(
      "{\n.reg .pred p;\nmbarrier.try_wait.parity.shared::cta.b64 p, [%1], %2;\nselp.b32 %0, 1, 0, p;\n}\n"
      : "=r"(ok)
      : "r"(bar), "r"(parity)
      : "memory");
  return ok != 0;
}
__device__ __forceinline__ bool mbar_test(uint32_t bar, uint32_t parity) {
  uint32_t ok;
  asm volatile(
      "{\n.reg .pred p;\nmbarrier.test_wait.parity.shared::cta.b64 p, [%1], %2;\nselp.b32 %0, 1, 0, p;\n}\n"
      : "=r"(ok)
      : "r"(bar), "r"(parity)
      : "memory");
  return ok != 0;
}
__device__ __forceinline__ void mbar_wait(uint32_t bar, uint32_t parity) {
#pragma unroll 1
  for (uint32_t it = 0; it < (1u << 18); ++it) {
    if (mbar_try_wait(bar, parity)) return;
  }
}
__device__ __forceinline__ void mbar_pace(uint32_t bar, uint32_t parity, uint32_t n) {
#pragma unroll 1
  for (uint32_t it = 0; it < n; ++it) {
    if (mbar_test(bar, parity)) return;
    __nanosleep(100);
  }
}
template <int NS>
__device__ __forceinline__ void mbar_wait_lazy(uint32_t bar, uint32_t parity) {
#pragma unroll 1
  for (uint32_t it = 0; it < (1u << 18); ++it) {
    if (mbar_try_wait(bar, parity)) return;
    __nanosleep(NS);
  }
}
__device__ __forceinline__ bool elect_one() {
  uint32_t ok;
  asm volatile("{\n.reg .pred p;\nelect.sync _|p, 0xffffffff;\nselp.b32 %0, 1, 0, p;\n}\n" : "=r"(ok));
  return ok != 0;
}
__device__ __forceinline__ void fence_barrier_init() { asm volatile("fence.mbarrier_init.release.cluster;" ::: "memory"); }
__device__ __forceinline__ void fence_proxy_async_smem() { asm volatile("fence.proxy.async.shared::cta;" ::: "memory"); }

__device__ __forceinline__ void signal_async(uint32_t bar, bool lane0) {
  fence_proxy_async_smem();
  __syncwarp();
  asm volatile("{\n.reg .pred p;\nsetp.ne.b32 p, %1, 0;\n@p mbarrier.arrive.shared::cta.b64 _, [%0];\n}\n" ::"r"(bar), "r"((int)lane0) : "memory");
}
template <class T>
__device__ __forceinline__ void pin64(T*& p) { asm volatile("" : "+l"(p)); }

__device__ __forceinline__ void tma_load_2d(uint32_t dst, const CUtensorMap* map, uint32_t bar, int c0, int c1) {
  asm volatile(
      "cp.async.bulk.tensor.2d.shared::cluster.global.mbarrier::complete_tx::bytes [%0], [%1, {%3, %4}], [%2];" ::"r"(dst),
      "l"(map), "r"(bar), "r"(c0), "r"(c1)
      : "memory");
}
__device__ __forceinline__ void tma_load_3d(uint32_t dst, const CUtensorMap* map, uint32_t bar, int c0, int c1) {
  asm volatile(
      "cp.async.bulk.tensor.3d.shared::cluster.global.mbarrier::complete_tx::bytes [%0], [%1, {%3, %4, %5}], [%2];" ::"r"(dst),
      "l"(map), "r"(bar), "r"(c0), "r"(c1), "r"(0)
      : "memory");
}
__device__ __forceinline__ void tma_load_5d(uint32_t dst, const CUtensorMap* map, uint32_t bar, int c0, int c4) {
  asm volatile(
      "cp.async.bulk.tensor.5d.shared::cluster.global.mbarrier::complete_tx::bytes [%0], [%1, {%3, %5, %5, %5, %4}], [%2];" ::"r"(dst),
      "l"(map), "r"(bar), "r"(c0), "r"(c4), "r"(0)
      : "memory");
}
__device__ __forceinline__ void bulk_load(uint32_t dst, const void* src, uint32_t bytes, uint32_t bar) {
  asm volatile("cp.async.bulk.shared::cluster.global.mbarrier::complete_tx::bytes [%0], [%1], %2, [%3];" ::"r"(dst),
               "l"(src), "r"(bytes), "r"(bar)
               : "memory");
}
__device__ __forceinline__ void bulk_store(void* dst, uint32_t src, uint32_t bytes) {
  asm volatile("cp.async.bulk.global.shared::cta.bulk_group [%0], [%1], %2;" ::"l"(dst), "r"(src), "r"(bytes) : "memory");
}
__device__ __forceinline__ void tma_store_2d(const CUtensorMap* map, uint32_t src, int c0, int c1) {
  asm volatile("cp.async.bulk.tensor.2d.global.shared::cta.bulk_group [%0, {%2, %3}], [%1];" ::"l"(map), "r"(src),
               "r"(c0), "r"(c1)
               : "memory");
}
__device__ __forceinline__ void bulk_announce(unsigned* p) {
  asm volatile("cp.reduce.async.bulk.global.shared::cta.bulk_group.add.u32 [%0], [%1], 16;" ::"l"(p), "r"(SBASE + OFF_ONE) : "memory");
}
__device__ __forceinline__ void bulk_commit() { asm volatile("cp.async.bulk.commit_group;" ::: "memory"); }
__device__ __forceinline__ void bulk_wait_read0() { asm volatile("cp.async.bulk.wait_group.read 0;" ::: "memory"); }
__device__ __forceinline__ void bulk_wait0() { asm volatile("cp.async.bulk.wait_group 0;" ::: "memory"); }
__device__ __forceinline__ void named_bar_sync(int id, int nthreads) {
  asm volatile("bar.sync %0, %1;" ::"r"(id), "r"(nthreads) : "memory");
}
__device__ __forceinline__ void named_bar_arrive(int id, int nthreads) {
  asm volatile("bar.arrive %0, %1;" ::"r"(id), "r"(nthreads) : "memory");
}

__device__ __forceinline__ void wgmma_fence() { asm volatile("wgmma.fence.sync.aligned;\n" ::: "memory"); }
__device__ __forceinline__ void wgmma_commit() { asm volatile("wgmma.commit_group.sync.aligned;\n" ::: "memory"); }
template <int N>
__device__ __forceinline__ void wgmma_wait() {
  asm volatile("wgmma.wait_group.sync.aligned %0;\n" ::"n"(N) : "memory");
}
template <int R>
__device__ __forceinline__ void setmaxnreg_inc() { asm volatile("setmaxnreg.inc.sync.aligned.u32 %0;\n" ::"n"(R)); }
template <int R>
__device__ __forceinline__ void setmaxnreg_dec() { asm volatile("setmaxnreg.dec.sync.aligned.u32 %0;\n" ::"n"(R)); }
template <int N>
__device__ __forceinline__ void reg_fence(float* r) {
#pragma unroll
  for (int i = 0; i < N; i++) asm volatile("" : "+f"(r[i])::"memory");
}

template <int N>
__device__ __forceinline__ void reg_define(float* r) {
#pragma unroll
  for (int i = 0; i < N; i++) r[i] = 0.f;
}

__device__ __forceinline__ uint64_t desc_lo(uint32_t lo) {
  uint64_t d;
  asm("mov.b64 %0, {%1, %2};" : "=l"(d) : "r"(lo), "r"(0x40000040u));
  return d;
}
__device__ __forceinline__ uint64_t make_desc(uint32_t addr, uint32_t lbo_bytes) {
  return desc_lo((addr >> 4) + ((lbo_bytes >> 4) << 16));
}

__device__ __forceinline__ void wgmma_n192_ss_ta0_tb1(float* d, uint64_t descA, uint64_t descB, int scaleD) {
  asm volatile("{\n.reg .pred p;\nsetp.ne.b32 p, %98, 0;\n"
    "wgmma.mma_async.sync.aligned.m64n192k16.f32.bf16.bf16 {%0, %1, %2, %3, %4, %5, %6, %7, %8, %9, %10, %11, %12, %13, %14, %15, %16, %17, %18, %19, %20, %21, %22, %23, %24, %25, %26, %27, %28, %29, %30, %31, %32, %33, %34, %35, %36, %37, %38, %39, %40, %41, %42, %43, %44, %45, %46, %47, %48, %49, %50, %51, %52, %53, %54, %55, %56, %57, %58, %59, %60, %61, %62, %63, %64, %65, %66, %67, %68, %69, %70, %71, %72, %73, %74, %75, %76, %77, %78, %79, %80, %81, %82, %83, %84, %85, %86, %87, %88, %89, %90, %91, %92, %93, %94, %95}, %96, %97, p, 1, 1, 0, 1;\n}\n"
    : "+f"(d[0]), "+f"(d[1]), "+f"(d[2]), "+f"(d[3]), "+f"(d[4]), "+f"(d[5]), "+f"(d[6]), "+f"(d[7]), "+f"(d[8]), "+f"(d[9]), "+f"(d[10]), "+f"(d[11]), "+f"(d[12]), "+f"(d[13]), "+f"(d[14]), "+f"(d[15]), "+f"(d[16]), "+f"(d[17]), "+f"(d[18]), "+f"(d[19]), "+f"(d[20]), "+f"(d[21]), "+f"(d[22]), "+f"(d[23]), "+f"(d[24]), "+f"(d[25]), "+f"(d[26]), "+f"(d[27]), "+f"(d[28]), "+f"(d[29]), "+f"(d[30]), "+f"(d[31]), "+f"(d[32]), "+f"(d[33]), "+f"(d[34]), "+f"(d[35]), "+f"(d[36]), "+f"(d[37]), "+f"(d[38]), "+f"(d[39]), "+f"(d[40]), "+f"(d[41]), "+f"(d[42]), "+f"(d[43]), "+f"(d[44]), "+f"(d[45]), "+f"(d[46]), "+f"(d[47]), "+f"(d[48]), "+f"(d[49]), "+f"(d[50]), "+f"(d[51]), "+f"(d[52]), "+f"(d[53]), "+f"(d[54]), "+f"(d[55]), "+f"(d[56]), "+f"(d[57]), "+f"(d[58]), "+f"(d[59]), "+f"(d[60]), "+f"(d[61]), "+f"(d[62]), "+f"(d[63]), "+f"(d[64]), "+f"(d[65]), "+f"(d[66]), "+f"(d[67]), "+f"(d[68]), "+f"(d[69]), "+f"(d[70]), "+f"(d[71]), "+f"(d[72]), "+f"(d[73]), "+f"(d[74]), "+f"(d[75]), "+f"(d[76]), "+f"(d[77]), "+f"(d[78]), "+f"(d[79]), "+f"(d[80]), "+f"(d[81]), "+f"(d[82]), "+f"(d[83]), "+f"(d[84]), "+f"(d[85]), "+f"(d[86]), "+f"(d[87]), "+f"(d[88]), "+f"(d[89]), "+f"(d[90]), "+f"(d[91]), "+f"(d[92]), "+f"(d[93]), "+f"(d[94]), "+f"(d[95])
    : "l"(descA), "l"(descB), "r"(scaleD));
}

__device__ __forceinline__ void wgmma_n128_ss_ta0_tb1(float* d, uint64_t descA, uint64_t descB, int scaleD) {
  asm volatile("{\n.reg .pred p;\nsetp.ne.b32 p, %66, 0;\n"
    "wgmma.mma_async.sync.aligned.m64n128k16.f32.bf16.bf16 {%0, %1, %2, %3, %4, %5, %6, %7, %8, %9, %10, %11, %12, %13, %14, %15, %16, %17, %18, %19, %20, %21, %22, %23, %24, %25, %26, %27, %28, %29, %30, %31, %32, %33, %34, %35, %36, %37, %38, %39, %40, %41, %42, %43, %44, %45, %46, %47, %48, %49, %50, %51, %52, %53, %54, %55, %56, %57, %58, %59, %60, %61, %62, %63}, %64, %65, p, 1, 1, 0, 1;\n}\n"
    : "+f"(d[0]), "+f"(d[1]), "+f"(d[2]), "+f"(d[3]), "+f"(d[4]), "+f"(d[5]), "+f"(d[6]), "+f"(d[7]), "+f"(d[8]), "+f"(d[9]), "+f"(d[10]), "+f"(d[11]), "+f"(d[12]), "+f"(d[13]), "+f"(d[14]), "+f"(d[15]), "+f"(d[16]), "+f"(d[17]), "+f"(d[18]), "+f"(d[19]), "+f"(d[20]), "+f"(d[21]), "+f"(d[22]), "+f"(d[23]), "+f"(d[24]), "+f"(d[25]), "+f"(d[26]), "+f"(d[27]), "+f"(d[28]), "+f"(d[29]), "+f"(d[30]), "+f"(d[31]), "+f"(d[32]), "+f"(d[33]), "+f"(d[34]), "+f"(d[35]), "+f"(d[36]), "+f"(d[37]), "+f"(d[38]), "+f"(d[39]), "+f"(d[40]), "+f"(d[41]), "+f"(d[42]), "+f"(d[43]), "+f"(d[44]), "+f"(d[45]), "+f"(d[46]), "+f"(d[47]), "+f"(d[48]), "+f"(d[49]), "+f"(d[50]), "+f"(d[51]), "+f"(d[52]), "+f"(d[53]), "+f"(d[54]), "+f"(d[55]), "+f"(d[56]), "+f"(d[57]), "+f"(d[58]), "+f"(d[59]), "+f"(d[60]), "+f"(d[61]), "+f"(d[62]), "+f"(d[63])
    : "l"(descA), "l"(descB), "r"(scaleD));
}

__device__ __forceinline__ void wgmma_n192_ssz_ta0_tb1(float* d, uint64_t descA, uint64_t descB) {
  asm volatile("{\n.reg .pred p;\nsetp.ne.b32 p, 0, 0;\n"
    "wgmma.mma_async.sync.aligned.m64n192k16.f32.bf16.bf16 {%0, %1, %2, %3, %4, %5, %6, %7, %8, %9, %10, %11, %12, %13, %14, %15, %16, %17, %18, %19, %20, %21, %22, %23, %24, %25, %26, %27, %28, %29, %30, %31, %32, %33, %34, %35, %36, %37, %38, %39, %40, %41, %42, %43, %44, %45, %46, %47, %48, %49, %50, %51, %52, %53, %54, %55, %56, %57, %58, %59, %60, %61, %62, %63, %64, %65, %66, %67, %68, %69, %70, %71, %72, %73, %74, %75, %76, %77, %78, %79, %80, %81, %82, %83, %84, %85, %86, %87, %88, %89, %90, %91, %92, %93, %94, %95}, %96, %97, p, 1, 1, 0, 1;\n}\n"
    : "=f"(d[0]), "=f"(d[1]), "=f"(d[2]), "=f"(d[3]), "=f"(d[4]), "=f"(d[5]), "=f"(d[6]), "=f"(d[7]), "=f"(d[8]), "=f"(d[9]), "=f"(d[10]), "=f"(d[11]), "=f"(d[12]), "=f"(d[13]), "=f"(d[14]), "=f"(d[15]), "=f"(d[16]), "=f"(d[17]), "=f"(d[18]), "=f"(d[19]), "=f"(d[20]), "=f"(d[21]), "=f"(d[22]), "=f"(d[23]), "=f"(d[24]), "=f"(d[25]), "=f"(d[26]), "=f"(d[27]), "=f"(d[28]), "=f"(d[29]), "=f"(d[30]), "=f"(d[31]), "=f"(d[32]), "=f"(d[33]), "=f"(d[34]), "=f"(d[35]), "=f"(d[36]), "=f"(d[37]), "=f"(d[38]), "=f"(d[39]), "=f"(d[40]), "=f"(d[41]), "=f"(d[42]), "=f"(d[43]), "=f"(d[44]), "=f"(d[45]), "=f"(d[46]), "=f"(d[47]), "=f"(d[48]), "=f"(d[49]), "=f"(d[50]), "=f"(d[51]), "=f"(d[52]), "=f"(d[53]), "=f"(d[54]), "=f"(d[55]), "=f"(d[56]), "=f"(d[57]), "=f"(d[58]), "=f"(d[59]), "=f"(d[60]), "=f"(d[61]), "=f"(d[62]), "=f"(d[63]), "=f"(d[64]), "=f"(d[65]), "=f"(d[66]), "=f"(d[67]), "=f"(d[68]), "=f"(d[69]), "=f"(d[70]), "=f"(d[71]), "=f"(d[72]), "=f"(d[73]), "=f"(d[74]), "=f"(d[75]), "=f"(d[76]), "=f"(d[77]), "=f"(d[78]), "=f"(d[79]), "=f"(d[80]), "=f"(d[81]), "=f"(d[82]), "=f"(d[83]), "=f"(d[84]), "=f"(d[85]), "=f"(d[86]), "=f"(d[87]), "=f"(d[88]), "=f"(d[89]), "=f"(d[90]), "=f"(d[91]), "=f"(d[92]), "=f"(d[93]), "=f"(d[94]), "=f"(d[95])
    : "l"(descA), "l"(descB));
}

__device__ __forceinline__ void wgmma_n8_ss_ta1_tb0(float* d, uint64_t descA, uint64_t descB, int scaleD) {
  asm volatile("{\n.reg .pred p;\nsetp.ne.b32 p, %6, 0;\n"
    "wgmma.mma_async.sync.aligned.m64n8k16.f32.bf16.bf16 {%0, %1, %2, %3}, %4, %5, p, 1, 1, 1, 0;\n}\n"
    : "+f"(d[0]), "+f"(d[1]), "+f"(d[2]), "+f"(d[3])
    : "l"(descA), "l"(descB), "r"(scaleD));
}

__device__ __forceinline__ void wgmma_n8_ssz_ta1_tb0(float* d, uint64_t descA, uint64_t descB) {
  asm volatile("{\n.reg .pred p;\nsetp.ne.b32 p, 0, 0;\n"
    "wgmma.mma_async.sync.aligned.m64n8k16.f32.bf16.bf16 {%0, %1, %2, %3}, %4, %5, p, 1, 1, 1, 0;\n}\n"
    : "=f"(d[0]), "=f"(d[1]), "=f"(d[2]), "=f"(d[3])
    : "l"(descA), "l"(descB));
}

__device__ __forceinline__ void wgmma_n192_rs_tb1(float* d, const uint32_t* a, uint64_t descB, int scaleD) {
  asm volatile("{\n.reg .pred p;\nsetp.ne.b32 p, %101, 0;\n"
    "wgmma.mma_async.sync.aligned.m64n192k16.f32.bf16.bf16 {%0, %1, %2, %3, %4, %5, %6, %7, %8, %9, %10, %11, %12, %13, %14, %15, %16, %17, %18, %19, %20, %21, %22, %23, %24, %25, %26, %27, %28, %29, %30, %31, %32, %33, %34, %35, %36, %37, %38, %39, %40, %41, %42, %43, %44, %45, %46, %47, %48, %49, %50, %51, %52, %53, %54, %55, %56, %57, %58, %59, %60, %61, %62, %63, %64, %65, %66, %67, %68, %69, %70, %71, %72, %73, %74, %75, %76, %77, %78, %79, %80, %81, %82, %83, %84, %85, %86, %87, %88, %89, %90, %91, %92, %93, %94, %95}, {%96, %97, %98, %99}, %100, p, 1, 1, 1;\n}\n"
    : "+f"(d[0]), "+f"(d[1]), "+f"(d[2]), "+f"(d[3]), "+f"(d[4]), "+f"(d[5]), "+f"(d[6]), "+f"(d[7]), "+f"(d[8]), "+f"(d[9]), "+f"(d[10]), "+f"(d[11]), "+f"(d[12]), "+f"(d[13]), "+f"(d[14]), "+f"(d[15]), "+f"(d[16]), "+f"(d[17]), "+f"(d[18]), "+f"(d[19]), "+f"(d[20]), "+f"(d[21]), "+f"(d[22]), "+f"(d[23]), "+f"(d[24]), "+f"(d[25]), "+f"(d[26]), "+f"(d[27]), "+f"(d[28]), "+f"(d[29]), "+f"(d[30]), "+f"(d[31]), "+f"(d[32]), "+f"(d[33]), "+f"(d[34]), "+f"(d[35]), "+f"(d[36]), "+f"(d[37]), "+f"(d[38]), "+f"(d[39]), "+f"(d[40]), "+f"(d[41]), "+f"(d[42]), "+f"(d[43]), "+f"(d[44]), "+f"(d[45]), "+f"(d[46]), "+f"(d[47]), "+f"(d[48]), "+f"(d[49]), "+f"(d[50]), "+f"(d[51]), "+f"(d[52]), "+f"(d[53]), "+f"(d[54]), "+f"(d[55]), "+f"(d[56]), "+f"(d[57]), "+f"(d[58]), "+f"(d[59]), "+f"(d[60]), "+f"(d[61]), "+f"(d[62]), "+f"(d[63]), "+f"(d[64]), "+f"(d[65]), "+f"(d[66]), "+f"(d[67]), "+f"(d[68]), "+f"(d[69]), "+f"(d[70]), "+f"(d[71]), "+f"(d[72]), "+f"(d[73]), "+f"(d[74]), "+f"(d[75]), "+f"(d[76]), "+f"(d[77]), "+f"(d[78]), "+f"(d[79]), "+f"(d[80]), "+f"(d[81]), "+f"(d[82]), "+f"(d[83]), "+f"(d[84]), "+f"(d[85]), "+f"(d[86]), "+f"(d[87]), "+f"(d[88]), "+f"(d[89]), "+f"(d[90]), "+f"(d[91]), "+f"(d[92]), "+f"(d[93]), "+f"(d[94]), "+f"(d[95])
    : "r"(a[0]), "r"(a[1]), "r"(a[2]), "r"(a[3]), "l"(descB), "r"(scaleD));
}

__device__ __forceinline__ void wgmma_n80_rs_tb0(float* d, const uint32_t* a, uint64_t descB, int scaleD) {
  asm volatile("{\n.reg .pred p;\nsetp.ne.b32 p, %45, 0;\n"
    "wgmma.mma_async.sync.aligned.m64n80k16.f32.bf16.bf16 {%0, %1, %2, %3, %4, %5, %6, %7, %8, %9, %10, %11, %12, %13, %14, %15, %16, %17, %18, %19, %20, %21, %22, %23, %24, %25, %26, %27, %28, %29, %30, %31, %32, %33, %34, %35, %36, %37, %38, %39}, {%40, %41, %42, %43}, %44, p, 1, 1, 0;\n}\n"
    : "+f"(d[0]), "+f"(d[1]), "+f"(d[2]), "+f"(d[3]), "+f"(d[4]), "+f"(d[5]), "+f"(d[6]), "+f"(d[7]), "+f"(d[8]), "+f"(d[9]), "+f"(d[10]), "+f"(d[11]), "+f"(d[12]), "+f"(d[13]), "+f"(d[14]), "+f"(d[15]), "+f"(d[16]), "+f"(d[17]), "+f"(d[18]), "+f"(d[19]), "+f"(d[20]), "+f"(d[21]), "+f"(d[22]), "+f"(d[23]), "+f"(d[24]), "+f"(d[25]), "+f"(d[26]), "+f"(d[27]), "+f"(d[28]), "+f"(d[29]), "+f"(d[30]), "+f"(d[31]), "+f"(d[32]), "+f"(d[33]), "+f"(d[34]), "+f"(d[35]), "+f"(d[36]), "+f"(d[37]), "+f"(d[38]), "+f"(d[39])
    : "r"(a[0]), "r"(a[1]), "r"(a[2]), "r"(a[3]), "l"(descB), "r"(scaleD));
}

__device__ __forceinline__ void wgmma_n80_rsz_tb0(float* d, const uint32_t* a, uint64_t descB) {
  asm volatile("{\n.reg .pred p;\nsetp.ne.b32 p, 0, 0;\n"
    "wgmma.mma_async.sync.aligned.m64n80k16.f32.bf16.bf16 {%0, %1, %2, %3, %4, %5, %6, %7, %8, %9, %10, %11, %12, %13, %14, %15, %16, %17, %18, %19, %20, %21, %22, %23, %24, %25, %26, %27, %28, %29, %30, %31, %32, %33, %34, %35, %36, %37, %38, %39}, {%40, %41, %42, %43}, %44, p, 1, 1, 0;\n}\n"
    : "=f"(d[0]), "=f"(d[1]), "=f"(d[2]), "=f"(d[3]), "=f"(d[4]), "=f"(d[5]), "=f"(d[6]), "=f"(d[7]), "=f"(d[8]), "=f"(d[9]), "=f"(d[10]), "=f"(d[11]), "=f"(d[12]), "=f"(d[13]), "=f"(d[14]), "=f"(d[15]), "=f"(d[16]), "=f"(d[17]), "=f"(d[18]), "=f"(d[19]), "=f"(d[20]), "=f"(d[21]), "=f"(d[22]), "=f"(d[23]), "=f"(d[24]), "=f"(d[25]), "=f"(d[26]), "=f"(d[27]), "=f"(d[28]), "=f"(d[29]), "=f"(d[30]), "=f"(d[31]), "=f"(d[32]), "=f"(d[33]), "=f"(d[34]), "=f"(d[35]), "=f"(d[36]), "=f"(d[37]), "=f"(d[38]), "=f"(d[39])
    : "r"(a[0]), "r"(a[1]), "r"(a[2]), "r"(a[3]), "l"(descB));
}

__device__ __forceinline__ void wgmma_n32_rs_tb1(float* d, const uint32_t* a, uint64_t descB, int scaleD) {
  asm volatile("{\n.reg .pred p;\nsetp.ne.b32 p, %21, 0;\n"
    "wgmma.mma_async.sync.aligned.m64n32k16.f32.bf16.bf16 {%0, %1, %2, %3, %4, %5, %6, %7, %8, %9, %10, %11, %12, %13, %14, %15}, {%16, %17, %18, %19}, %20, p, 1, 1, 1;\n}\n"
    : "+f"(d[0]), "+f"(d[1]), "+f"(d[2]), "+f"(d[3]), "+f"(d[4]), "+f"(d[5]), "+f"(d[6]), "+f"(d[7]), "+f"(d[8]), "+f"(d[9]), "+f"(d[10]), "+f"(d[11]), "+f"(d[12]), "+f"(d[13]), "+f"(d[14]), "+f"(d[15])
    : "r"(a[0]), "r"(a[1]), "r"(a[2]), "r"(a[3]), "l"(descB), "r"(scaleD));
}

__device__ __forceinline__ void wgmma_n32_rsz_tb1(float* d, const uint32_t* a, uint64_t descB) {
  asm volatile("{\n.reg .pred p;\nsetp.ne.b32 p, 0, 0;\n"
    "wgmma.mma_async.sync.aligned.m64n32k16.f32.bf16.bf16 {%0, %1, %2, %3, %4, %5, %6, %7, %8, %9, %10, %11, %12, %13, %14, %15}, {%16, %17, %18, %19}, %20, p, 1, 1, 1;\n}\n"
    : "=f"(d[0]), "=f"(d[1]), "=f"(d[2]), "=f"(d[3]), "=f"(d[4]), "=f"(d[5]), "=f"(d[6]), "=f"(d[7]), "=f"(d[8]), "=f"(d[9]), "=f"(d[10]), "=f"(d[11]), "=f"(d[12]), "=f"(d[13]), "=f"(d[14]), "=f"(d[15])
    : "r"(a[0]), "r"(a[1]), "r"(a[2]), "r"(a[3]), "l"(descB));
}

__device__ __forceinline__ void wgmma_n32_rs_tb0(float* d, const uint32_t* a, uint64_t descB, int scaleD) {
  asm volatile("{\n.reg .pred p;\nsetp.ne.b32 p, %21, 0;\n"
    "wgmma.mma_async.sync.aligned.m64n32k16.f32.bf16.bf16 {%0, %1, %2, %3, %4, %5, %6, %7, %8, %9, %10, %11, %12, %13, %14, %15}, {%16, %17, %18, %19}, %20, p, 1, 1, 0;\n}\n"
    : "+f"(d[0]), "+f"(d[1]), "+f"(d[2]), "+f"(d[3]), "+f"(d[4]), "+f"(d[5]), "+f"(d[6]), "+f"(d[7]), "+f"(d[8]), "+f"(d[9]), "+f"(d[10]), "+f"(d[11]), "+f"(d[12]), "+f"(d[13]), "+f"(d[14]), "+f"(d[15])
    : "r"(a[0]), "r"(a[1]), "r"(a[2]), "r"(a[3]), "l"(descB), "r"(scaleD));
}

__device__ __forceinline__ void wgmma_n32_rsz_tb0(float* d, const uint32_t* a, uint64_t descB) {
  asm volatile("{\n.reg .pred p;\nsetp.ne.b32 p, 0, 0;\n"
    "wgmma.mma_async.sync.aligned.m64n32k16.f32.bf16.bf16 {%0, %1, %2, %3, %4, %5, %6, %7, %8, %9, %10, %11, %12, %13, %14, %15}, {%16, %17, %18, %19}, %20, p, 1, 1, 0;\n}\n"
    : "=f"(d[0]), "=f"(d[1]), "=f"(d[2]), "=f"(d[3]), "=f"(d[4]), "=f"(d[5]), "=f"(d[6]), "=f"(d[7]), "=f"(d[8]), "=f"(d[9]), "=f"(d[10]), "=f"(d[11]), "=f"(d[12]), "=f"(d[13]), "=f"(d[14]), "=f"(d[15])
    : "r"(a[0]), "r"(a[1]), "r"(a[2]), "r"(a[3]), "l"(descB));
}

__device__ __forceinline__ uint32_t pack_bf16x2(float lo, float hi) {
  uint32_t r;
  asm("cvt.rn.bf16x2.f32 %0, %1, %2;" : "=r"(r) : "f"(hi), "f"(lo));
  return r;
}
__device__ __forceinline__ float bf_lo(uint32_t p) { return __uint_as_float(p << 16); }
__device__ __forceinline__ float bf_hi(uint32_t p) { return __uint_as_float(p & 0xffff0000u); }
__device__ __forceinline__ float bf16_round(float v) { return __bfloat162float(__float2bfloat16_rn(v)); }
__device__ __forceinline__ float ex2_approx(float x) {
  float r;
  asm("ex2.approx.ftz.f32 %0, %1;" : "=f"(r) : "f"(x));
  return r;
}
__device__ __forceinline__ float rcp_fast(float x) {
  float r;
  asm("rcp.approx.ftz.f32 %0, %1;" : "=f"(r) : "f"(x));
  return r;
}
__device__ __forceinline__ void ldmatrix_x4(uint32_t (&r)[4], uint32_t addr) {
  asm volatile("ldmatrix.sync.aligned.m8n8.x4.shared.b16 {%0,%1,%2,%3}, [%4];"
               : "=r"(r[0]), "=r"(r[1]), "=r"(r[2]), "=r"(r[3])
               : "r"(addr)
               : "memory");
}
__device__ __forceinline__ void stmatrix_x4(uint32_t addr, uint32_t r0, uint32_t r1, uint32_t r2, uint32_t r3) {
  asm volatile("stmatrix.sync.aligned.m8n8.x4.shared.b16 [%0], {%1,%2,%3,%4};" ::"r"(addr), "r"(r0), "r"(r1), "r"(r2),
               "r"(r3));
}
__device__ __forceinline__ uint32_t add_bf16x2(uint32_t a, uint32_t b) {
  uint32_t r;
  asm("add.rn.bf16x2 %0, %1, %2;" : "=r"(r) : "r"(a), "r"(b));
  return r;
}
__device__ __forceinline__ uint4 lds128(uint32_t addr) {
  uint4 v;
  asm volatile("ld.shared.v4.b32 {%0,%1,%2,%3}, [%4];" : "=r"(v.x), "=r"(v.y), "=r"(v.z), "=r"(v.w) : "r"(addr) : "memory");
  return v;
}
__device__ __forceinline__ uint32_t lds32(uint32_t addr) {
  uint32_t v;
  asm volatile("ld.shared.b32 %0, [%1];" : "=r"(v) : "r"(addr) : "memory");
  return v;
}
__device__ __forceinline__ void sts32(uint32_t addr, uint32_t v) {
  asm volatile("st.shared.b32 [%0], %1;" ::"r"(addr), "r"(v) : "memory");
}

__device__ __forceinline__ int fresh_tid() {
  int t;
  asm volatile("mov.u32 %0, %%tid.x;" : "=r"(t));
  return t;
}
__device__ __forceinline__ unsigned ld_relaxed_u32(const void* p) {
  unsigned v;
  asm volatile("ld.relaxed.gpu.global.u32 %0, [%1];" : "=r"(v) : "l"(p) : "memory");
  return v;
}
__device__ __forceinline__ unsigned launch_epoch() { return (*(volatile unsigned*)g_done) / NCTA + 1u; }
__device__ __forceinline__ uint32_t set_tag(uint32_t w, uint32_t m, uint32_t tag) { return (w & ~m) | (tag & m); }
__device__ __forceinline__ uint32_t o_tag(int L) { return (L + 1) & 1; }
__device__ __forceinline__ uint32_t x_tag(int L) { return L & 1; }
__device__ __forceinline__ uint32_t kv_tag(int L) { return L < 2; }

template <class F>
__device__ __forceinline__ void fix_lines(uint32_t bar, uint32_t par, uint32_t ta, uint32_t tag, uint32_t mask, int bar_id, F line) {
  mbar_wait(bar, par);
  uint32_t m = __ballot_sync(0xffffffffu, (lds32(ta) ^ tag) & mask);
  if (m == 0u) return;
#pragma unroll 1
  for (uint32_t it = 0; it < (1u << 17) && m != 0u; ++it) {
    const int l = __ffs(m) - 1, j = fresh_tid() & 7;
    uint4 v;
    asm volatile("ld.relaxed.gpu.global.v4.b32 {%0,%1,%2,%3}, [%4];" : "=r"(v.x), "=r"(v.y), "=r"(v.z), "=r"(v.w) : "l"(line(l) + j * 8) : "memory");
    const uint32_t a = __shfl_sync(0xffffffffu, ta, l) ^ (j << 4);
    if (((__shfl_sync(0xffffffffu, v.x, 0) ^ tag) & 1u) == 0u) {
      asm volatile("st.shared.v4.b32 [%0], {%1,%2,%3,%4};" ::"r"(a), "r"(v.x), "r"(v.y), "r"(v.z), "r"(v.w) : "memory");
      m &= m - 1u;
    }
  }
  fence_proxy_async_smem();
  named_bar_sync(bar_id, 32);
}
__device__ __forceinline__ uint32_t peek_counts(const unsigned* f, unsigned target, int lane) {
  return __ballot_sync(0xffffffffu, (int)(ld_relaxed_u32(f + (lane & 15) * 4) - target) >= 0);
}
__device__ __forceinline__ void wait_count(const unsigned* f, unsigned target, int i, uint32_t& seen, int lane) {
  if ((seen >> i) & 1u) return;
#pragma unroll 1
  for (uint32_t it = 0; it < (1u << 17); ++it) {
    seen = peek_counts(f, target, lane);
    if ((seen >> i) & 1u) break;
  }
}
__device__ __forceinline__ float4 ld_rec(const float4* p) {
  float4 v;
  asm volatile("ld.relaxed.gpu.global.v4.f32 {%0,%1,%2,%3}, [%4];" : "=f"(v.x), "=f"(v.y), "=f"(v.z), "=f"(v.w) : "l"(p) : "memory");
  return v;
}
__device__ __forceinline__ void st_rec(float4* p, float a, float b, float c, unsigned tag) {
  asm volatile("st.relaxed.gpu.global.v4.f32 [%0], {%1,%2,%3,%4};" ::"l"(p), "f"(a), "f"(b), "f"(c), "f"(__uint_as_float(tag)) : "memory");
}
template <int N>
__device__ __forceinline__ float4 sum_recs(const float4* p, int stride, unsigned tag) {
  float4 s;
#pragma unroll 1
  for (uint32_t it = 0; it < (1u << 17); ++it) {
    float4 v[N];
#pragma unroll
    for (int t = 0; t < N; t++) v[t] = ld_rec(p + t * stride);
    bool ok = true;
    s = make_float4(0.f, 0.f, 0.f, 0.f);
#pragma unroll
    for (int t = 0; t < N; t++) {
      ok &= __float_as_uint(v[t].w) == tag;
      s.x += v[t].x;
      s.y += v[t].y;
      s.z += v[t].z;
    }
    if (ok) break;
    __nanosleep(200);
  }
  return s;
}

#define PHASE_IDS                                  \
  const int tid_ = fresh_tid();                    \
  const int lane = tid_ & 31, wwarp = __shfl_sync(0xffffffffu, (tid_ >> 5) & 3, 0), tid = tid_ & 127; \
  const int g = lane >> 2, c = lane & 3;           \
  (void)tid; (void)g; (void)c; (void)wwarp;

#define PHASE_IDS_W                                \
  const int lane = fresh_tid() & 31, wwarp = warp & 3; \
  const int g = lane >> 2, c = lane & 3;

#define GTL(i) do { } while (0)
#define TGET(v) do { } while (0)
#define TPUT(c, i, v) do { } while (0)

constexpr float SM_C = 0.17677669529663687f * 1.4426950408889634f;

__device__ __forceinline__ void stmatrix_x4_if(bool ok, uint32_t addr, uint32_t r0, uint32_t r1, uint32_t r2, uint32_t r3) {
  asm volatile("{\n.reg .pred p;\nsetp.ne.b32 p, %5, 0;\n@p stmatrix.sync.aligned.m8n8.x4.shared.b16 [%0], {%1,%2,%3,%4};\n}\n" ::"r"(addr),
               "r"(r0), "r"(r1), "r"(r2), "r"(r3), "r"((int)ok));
}

__device__ __forceinline__ void attn_a_slow(const uint8_t* __restrict__ kvimg, int L, int gb, int hp, uint32_t bad,
                                            int row0, int lane) {
  constexpr uint32_t sq = SBASE + OFF_SLOT + 3 * 16384;
#pragma unroll 1
  for (int j = 0; j < 8; j++) {
    const uint8_t* tp = kvimg + (size_t)(gb * 16 + hp) * 32768 + (j * 32 + lane) * 128 + ((lane & 7) << 4);
#pragma unroll 1
    for (uint32_t it = 0; it < (1u << 17); ++it)
      if (((ld_relaxed_u32(tp) ^ kv_tag(L)) & 1u) == 0u) break;
  }
  __syncwarp();
#pragma unroll 1
  for (int t = 0; t < 32; t++) {
    const int hh = t >> 4, row = row0 + (t & 7) + (t & 8) * 4;
    if (!((bad >> hh) & 1u)) continue;
    const int qpos = gb * 128 + row;
    const uint32_t qaddr = sq + row * 128;
    float mx = -INFINITY, sum = 0.f, acc = 0.f;
#pragma unroll 1
    for (int pass = 0; pass < 2; pass++) {
#pragma unroll 1
      for (int j = 0; j < 8; j++) {
        const int kp = qpos - (lane + 32 * j);
        const uint8_t* kr = kvimg + ((size_t)((kp >> 7) * 16 + hp) * 2 + ((kp >> 6) & 1)) * 16384 + (kp & 63) * 128;
        float d = -INFINITY;
        if (kp >= 0) {
          d = 0.f;
#pragma unroll 1
          for (int q = 0; q < 4; q++) {
            const uint4 kv = __ldcg(reinterpret_cast<const uint4*>(kr + (((hh * 4 + q) ^ (kp & 7)) << 4)));
            const uint4 qv = lds128(qaddr + (((hh * 4 + q) ^ (row & 7)) << 4));
            const uint32_t kw[4] = {kv.x, kv.y, kv.z, kv.w}, qw[4] = {qv.x, qv.y, qv.z, qv.w};
#pragma unroll
            for (int e = 0; e < 4; e++) d = fmaf(bf_lo(kw[e]), bf_lo(qw[e]), fmaf(bf_hi(kw[e]), bf_hi(qw[e]), d));
          }
        }
        if (pass == 0) {
          mx = fmaxf(mx, d);
        } else {
          const float ev = ex2_approx(d - mx);
          sum += ev;
          const float pv = bf16_round(ev);
#pragma unroll 1
          for (int kk = 0; kk < 32; kk++) {
            const float pk = __shfl_sync(0xffffffffu, pv, kk);
            const int k2 = qpos - (kk + 32 * j);
            if (k2 >= 0) {
              const uint8_t* vr = kvimg + ((size_t)((k2 >> 7) * 16 + hp) * 2 + ((k2 >> 6) & 1)) * 16384 + 8192 + (k2 & 63) * 128;
              const unsigned short vv =
                  __ldcg(reinterpret_cast<const unsigned short*>(vr + (((hh * 4 + (lane >> 3)) ^ (k2 & 7)) << 4) + (lane & 7) * 2));
              acc = fmaf(pk, __uint_as_float((uint32_t)vv << 16), acc);
            }
          }
        }
      }
      if (pass == 0) {
#pragma unroll
        for (int o = 16; o > 0; o >>= 1) mx = fmaxf(mx, __shfl_xor_sync(0xffffffffu, mx, o));
      }
    }
#pragma unroll
    for (int o = 16; o > 0; o >>= 1) sum += __shfl_xor_sync(0xffffffffu, sum, o);
    acc *= rcp_fast(sum);
    const float hi = __shfl_down_sync(0xffffffffu, acc, 1);
    __syncwarp();
    if ((lane & 1) == 0) sts32(qaddr + (((hh * 4 + (lane >> 3)) ^ (row & 7)) << 4) + (lane & 7) * 2,
                               set_tag(pack_bf16x2(acc, hi), hh == 0 && lane == 0, o_tag(L)));
    __syncwarp();
  }
}

template <int HH>
__device__ __forceinline__ void store_o(const float (&o)[16], const float (&inv)[2], uint32_t ra, uint32_t tag, bool ok) {
  const uint32_t m = HH == 0 && (fresh_tid() & 3) == 0;
#pragma unroll
  for (int jp = 0; jp < 2; jp++) {
    uint32_t w0 = pack_bf16x2(o[8 * jp] * inv[0], o[8 * jp + 1] * inv[0]);
    uint32_t w1 = pack_bf16x2(o[8 * jp + 2] * inv[1], o[8 * jp + 3] * inv[1]);
    if (HH == 0 && jp == 0) {
      w0 = set_tag(w0, m, tag);
      w1 = set_tag(w1, m, tag);
    }
    stmatrix_x4_if(ok, ra ^ ((HH * 4 + 2 * jp) << 4), w0, w1, pack_bf16x2(o[8 * jp + 4] * inv[0], o[8 * jp + 5] * inv[0]),
                   pack_bf16x2(o[8 * jp + 6] * inv[1], o[8 * jp + 7] * inv[1]));
  }
}
__device__ __forceinline__ int tile_row(bool B, int w, int r, int g) { return (B ? 16 * w + 8 * r : 8 * w + 32 * r) + g; }
__device__ __forceinline__ uint32_t q_row_addr(bool B, int R, int w, int lane) {
  return SBASE + OFF_SLOT + 3 * 16384 + R * 8192 + tile_row(B, w, (lane >> 3) & 1, lane & 7) * 128 + (((lane >> 4) ^ (lane & 7)) << 4);
}

struct AttnA {
  float s[2][16], o[2][16], l[2][2], sh[2][3];
  uint32_t p[2][4], t[2], me[4], ra, bad, zero;
};
#define ATS_(i) do { } while (0)
template <int V>
__device__ __forceinline__ void attn_sum(AttnA& a, int nv) {
  constexpr int hh = (V >> 1) & 1, kh = V & 1, i = V >> 2;
#pragma unroll
  for (int r = 0; r < 2; r++) {
    const uint32_t t1 = add_bf16x2(add_bf16x2(a.p[0][r], a.p[0][2 + r]), add_bf16x2(a.p[1][r], a.p[1][2 + r]));
    if (kh == 0) {
      a.t[r] = t1;
    } else {
      uint32_t tt = add_bf16x2(a.t[r], t1);
      if (i > 0) tt = i <= nv ? tt : 0u;
      const float v = bf_lo(tt) + bf_hi(tt);
      a.l[hh][r] = i == 0 ? v : a.l[hh][r] + v;
    }
  }
}
template <int HH>
__device__ __forceinline__ void attn_shfl(AttnA& a) {
#pragma unroll
  for (int r = 0; r < 2; r++)
#pragma unroll
    for (int j = 0; j < 3; j++) a.sh[r][j] = __shfl_xor_sync(0xffffffffu, a.l[HH][r], j + 1);
}
template <int HH>
__device__ __forceinline__ void attn_fin(AttnA& a) {
  bool bad = false;
  float inv[2];
#pragma unroll
  for (int r = 0; r < 2; r++) {
    const float v = (a.l[HH][r] + a.sh[r][0]) + (a.sh[r][1] + a.sh[r][2]);
    bad |= !(v <= 1.152921504606846976e18f && v >= 8.673617379884035e-19f);
    inv[r] = rcp_fast(v);
  }
  bad = __any_sync(0xffffffffu, bad);
  if (HH == 1) wgmma_wait<0>();
  reg_fence<16>(a.o[HH]);
  store_o<HH>(a.o[HH], inv, a.ra, o_tag(0), !bad);
  a.bad = (HH == 0 ? 0u : a.bad) | (bad ? 1u << HH : 0u);
}
__device__ __forceinline__ void attn_masks(AttnA& a, int wr) {
  const int lane = fresh_tid() & 31, d = (lane >> 2) - 2 * (lane & 3);
  const uint32_t tri = d >= 1 ? 0xffffffffu : (d == 0 ? 0xffffu : 0u);
#pragma unroll
  for (int t = 0; t < 4; t++) a.me[t] = wr > t ? 0xffffffffu : (wr == t ? tri : 0u);
}
template <int V, int K>
__device__ __forceinline__ uint32_t attn_exp(AttnA& a) {
  constexpr int i = V >> 2, kh = V & 1, r = K & 1;
  if ((i == 0 && kh > r) || (i == 4 && kh < r)) return 0u;
  const uint32_t w = pack_bf16x2(ex2_approx(a.s[V & 1][2 * K]), ex2_approx(a.s[V & 1][2 * K + 1]));
  if (i == 0 && kh == r) return w & a.me[K >> 1];
  if (i == 4 && kh == r) return w & ~a.me[K >> 1];
  return w;
}
template <int V>
__device__ __forceinline__ void attn_unit(AttnA& a, const uint32_t (&q)[2][2][4], uint64_t dcur, uint64_t dnext, int R, int wr, int nv,
                                          uint32_t hbar, uint32_t hpar, uint32_t rbar, bool rel) {
  constexpr int hh = (V >> 1) & 1, kh = V & 1, i = V >> 2;
  ATS_(V + 1);
  asm volatile("" : "+l"(dcur), "+l"(dnext));
  wgmma_wait<1>();
  reg_fence<16>(a.s[V & 1]);
  bool hok = true;
  if (V == 4) hbar = SBASE + OFF_BAR + 8u * (R ? B_LOC : B_HV);
  if (((V & 3) == 2 && V < 16) || V == 4) hok = mbar_test(hbar, hpar);
  const uint64_t d0 = ((V & 3) >= 2 ? dnext : dcur) + ((hh ^ 1) * 4 + kh * 256), d1 = ((V & 3) >= 2 ? dnext : dcur) + ((hh ^ 1) * 4 + kh * 256 + 2);
  const uint64_t d2 = dcur + (512 + hh * 4 + kh * 256), d3 = dcur + (640 + hh * 4 + kh * 256);
  if ((V & 3) == 1 && V > 4 && rel) mbar_arrive(rbar);
  if (V > 0) attn_sum<V - 1>(a, nv);
  if (V == 15) attn_masks(a, wr);
  if (V == 18) {
    attn_shfl<0>(a);
    a.ra = q_row_addr(false, R, wr, fresh_tid() & 31);
  }
  if (V == 19) attn_fin<0>(a);
  uint32_t p[2][4];
  p[0][0] = attn_exp<V, 0>(a);
  p[0][1] = attn_exp<V, 1>(a);
  p[0][2] = attn_exp<V, 2>(a);
  p[0][3] = attn_exp<V, 3>(a);
  p[1][0] = attn_exp<V, 4>(a);
  p[1][1] = attn_exp<V, 5>(a);
  p[1][2] = attn_exp<V, 6>(a);
  p[1][3] = attn_exp<V, 7>(a);
  if (V > 0) {
#pragma unroll
    for (int r = 0; r < 2; r++) p[1][r] ^= (kh ? a.t[r] : __float_as_uint(a.l[hh ^ 1][r])) & a.zero;
  }
#pragma unroll
  for (int k = 0; k < 8; k++) {
    asm volatile("" : "+r"(p[k >> 2][k & 3]));
    a.p[k >> 2][k & 3] = p[k >> 2][k & 3];
  }
  if (!hok) mbar_wait(hbar, hpar);
  wgmma_fence();
  if (V < 18) wgmma_n32_rsz_tb0(a.s[V & 1], q[hh ^ 1][0], d0);
  if (i == 0 && kh == 0) wgmma_n32_rsz_tb1(a.o[hh], a.p[0], d2);
  else wgmma_n32_rs_tb1(a.o[hh], a.p[0], d2, 1);
  if (V < 18) wgmma_n32_rs_tb0(a.s[V & 1], q[hh ^ 1][1], d1, 1);
  wgmma_n32_rs_tb1(a.o[hh], a.p[1], d3, 1);
  wgmma_commit();
}
template <int I>
__device__ __forceinline__ void attn_step(AttnA& a, const uint32_t (&q)[2][2][4], uint64_t dcur, uint64_t dnext, int R, int wr, int nv,
                                          uint32_t hbar, uint32_t hpar, uint32_t rbar, bool rel) {
  attn_unit<4 * I>(a, q, dcur, dnext, R, wr, nv, hbar, hpar, rbar, rel);
  attn_unit<4 * I + 1>(a, q, dcur, dnext, R, wr, nv, hbar, hpar, rbar, rel);
  attn_unit<4 * I + 2>(a, q, dcur, dnext, R, wr, nv, hbar, hpar, rbar, rel);
  attn_unit<4 * I + 3>(a, q, dcur, dnext, R, wr, nv, hbar, hpar, rbar, rel);
}

__device__ __forceinline__ void attention_a(const uint32_t (&q)[2][2][4], int R, int L, int gb, int hp, uint32_t par, int wr,
                                            uint32_t zero) {
  constexpr uint32_t bars = SBASE + OFF_BAR;
  constexpr uint32_t dslot = ((SBASE + OFF_SLOT) >> 4) + 0x10000u;
  auto next = [&](uint64_t d) { return desc_lo((uint32_t)d == dslot ? dslot + 2048 : (uint32_t)d - 1024) + zero; };
  uint64_t d0 = desc_lo(dslot + R * 1024) + zero, d1 = next(d0);
  AttnA a;
  ATS_(0);
  wgmma_fence();
#pragma unroll
  for (int v = 0; v < 2; v++) {
    wgmma_n32_rsz_tb0(a.s[v], q[0][0], d0 + v * 256);
    wgmma_n32_rs_tb0(a.s[v], q[0][1], d0 + (v * 256 + 2), 1);
    wgmma_commit();
  }
  a.zero = zero;
  const bool lane0 = (fresh_tid() & 31) == 0;
  attn_masks(a, wr);
  const int nv = 2 * gb + R;
  const uint32_t hb = bars + 8u * (B_HALO - R), rb = bars + 8u * (B_REL - R);
  attn_step<0>(a, q, d0, d1, R, wr, nv, hb, par, 0, false);
  d0 = next(d1);
  attn_step<1>(a, q, d1, d0, R, wr, nv, R ? bars + 8u * B_HV : hb + 8, par, rb + 8, lane0);
  d1 = next(d0);
  attn_step<2>(a, q, d0, d1, R, wr, nv, hb + 16, par, rb + 16, lane0);
  d0 = next(d1);
  attn_step<3>(a, q, d1, d0, R, wr, nv, hb + 24, par, rb + 24, lane0 && R);
  attn_step<4>(a, q, d0, d0, R, wr, nv, 0, 0, rb, false);
  ATS_(21);
  attn_sum<19>(a, nv);
  attn_shfl<1>(a);
  attn_fin<1>(a);
  ATS_(22);
  if (a.bad != 0u) {
    attn_a_slow(g_kvA[0][0][0], L, gb, hp, a.bad, R * 64 + wr * 8, fresh_tid() & 31);
    named_bar_sync(7, 32);
  }
}

constexpr uint32_t KB_ROW0 = SBASE + OFF_SLOT + 2048, VB_ROW0 = SBASE + OFF_SLOT + 24576 + 2048;

__device__ __forceinline__ void attention_b(const uint32_t (&q)[2][2][4], int R, int gb, uint32_t par0, int wr) {
  constexpr uint32_t bars = SBASE + OFF_BAR;
  const uint32_t dk = ((KB_ROW0 - 2048) >> 4) + 0x10000u + R * 512, dv = dk + ((VB_ROW0 - KB_ROW0) >> 4);
  float s[2][40];
  mbar_wait(bars + 8u * (B_HALO - R), par0);
  wgmma_fence();
#pragma unroll
  for (int hh = 0; hh < 2; hh++) {
    wgmma_n80_rsz_tb0(s[hh], q[hh][0], desc_lo(dk + hh * 4));
    wgmma_n80_rs_tb0(s[hh], q[hh][1], desc_lo(dk + hh * 4 + 2), 1);
  }
  wgmma_commit();
  const int lane = fresh_tid() & 31, g = lane >> 2;
  const bool odd = g & 1, edge = R == 0 && gb == 0 && wr == 0;
  const int D = 2 * (lane & 3) + (g & 1) - g;
  const uint32_t ra = q_row_addr(true, R, wr, lane);
  wgmma_wait<0>();
  reg_fence<40>(s[0]);
  reg_fence<40>(s[1]);
  float z[2][2], y[2][2];
#define GATHER_(W)                                                                                          \
  _Pragma("unroll") for (int hh = 0; hh < 2; hh++) _Pragma("unroll") for (int r = 0; r < 2; r++) {          \
    const float* e = &s[hh][4 * (2 * W + r) + 2 * r];                                                       \
    z[hh][r] = odd ? e[5] : e[4];                                                                           \
    y[hh][r] = D >= 2 ? (odd ? e[1] : e[0]) : (odd ? e[9] : e[8]);                                          \
  }
  if (wr < 2) {
    if (wr == 0) { GATHER_(0) } else { GATHER_(1) }
  } else {
    if (wr == 2) { GATHER_(2) } else { GATHER_(3) }
  }
#undef GATHER_
  float o[2][16], inv[2][2];
  uint32_t p[2][5][4];
  const int sh = odd ? 16 : 0, kb = wr + (D >= 2 ? 0 : 1);
#pragma unroll
  for (int hh = 0; hh < 2; hh++) {
    if (edge) {
      z[hh][0] = -INFINITY;
      if (D >= 2) y[hh][0] = y[hh][1] = -INFINITY;
    }
    uint32_t ab[2][2];
#pragma unroll
    for (int r = 0; r < 2; r++) {
      float m = fmaxf(z[hh][r], y[hh][r]);
      m = fmaxf(m, __shfl_xor_sync(0xffffffffu, m, 1));
      m = fmaxf(m, __shfl_xor_sync(0xffffffffu, m, 2));
      const float e0 = ex2_approx(z[hh][r] - m), e1 = ex2_approx(y[hh][r] - m);
      inv[hh][r] = e0 + e1;
      ab[r][0] = pack_bf16x2(e0, 0.f) << sh;
      ab[r][1] = pack_bf16x2(e1, 0.f) << sh;
    }
#pragma unroll
    for (int k = 0; k < 5; k++) {
      p[hh][k][0] = k == kb ? ab[0][1] : 0u;
      p[hh][k][1] = k == wr + 1 ? ab[1][0] : 0u;
      p[hh][k][2] = k == wr ? ab[0][0] : 0u;
      p[hh][k][3] = k == kb ? ab[1][1] : 0u;
#pragma unroll
      for (int j = 0; j < 4; j++) asm volatile("" : "+r"(p[hh][k][j]));
    }
  }
  wgmma_fence();
#pragma unroll
  for (int hh = 0; hh < 2; hh++) {
    wgmma_n32_rsz_tb1(o[hh], p[hh][0], desc_lo(dv + hh * 4));
#pragma unroll
    for (int k = 1; k < 5; k++) wgmma_n32_rs_tb1(o[hh], p[hh][k], desc_lo(dv + hh * 4 + k * 128), 1);
  }
  wgmma_commit();
#pragma unroll
  for (int hh = 0; hh < 2; hh++)
#pragma unroll
    for (int r = 0; r < 2; r++) {
      inv[hh][r] += __shfl_xor_sync(0xffffffffu, inv[hh][r], 1);
      inv[hh][r] += __shfl_xor_sync(0xffffffffu, inv[hh][r], 2);
      inv[hh][r] = rcp_fast(inv[hh][r]);
    }
  wgmma_wait<0>();
  reg_fence<16>(o[0]);
  reg_fence<16>(o[1]);
  store_o<0>(o[0], inv[0], ra, o_tag(1), true);
  store_o<1>(o[1], inv[1], ra, o_tag(1), true);
}

#define KTQM 0
#define TRICKLE 300
#define QREL 5
#define PRESLEEP 200
#define CSA 5
#define PN1 4
#define PN2 5
#define TLAZY 100
#define SDLY 1500
#define HTS(i) do { } while (0)
struct Params {
  CUtensorMap x[5], xq[4], o, wqkv[2], wqkv3[2], wo3[2];
  const __nv_bfloat16* in_x;
  const __nv_bfloat16* wqkv_p[2];
  const __nv_bfloat16* wo_p[2];
  __nv_bfloat16* out;
  uint32_t zero;
};

__device__ __forceinline__ void colsum_part(const CUtensorMap* wmap, int ty, int qr, int hp) {
  constexpr uint32_t bars = SBASE + OFF_BAR, slots = SBASE + OFF_SLOT;
  PHASE_IDS
  const unsigned ep1 = launch_epoch();
  if (wwarp == 0 && elect_one()) {
    mbar_expect_tx(bars + 8u * B_CS, 6 * UNIT);
#pragma unroll 1
    for (int j = 0; j < 6; j++) {
      if (ty == 0) mbar_pace(bars + 8u * (B_QF + B_E + ((j * CSA / 6) & 3)), (j * CSA / 6) >> 2, j ? PN1 : 30);
      else mbar_wait_lazy<100>(bars + 8u * (B_WF + B_E + ((2 * j + 3 - (j & 1)) & 7)), j >= 3);
      tma_load_2d(slots + j * UNIT, wmap, bars + 8u * B_CS, (j >> 1) * 1024 + hp * 64, qr * 128 + (j & 1) * 64);
    }
  }
  constexpr uint64_t ones = (SBASE + OFF_LSB + 32) >> 4;
  float s[3][4];
  mbar_wait_lazy<100>(bars + 8u * B_CS, ty);
  wgmma_fence();
#pragma unroll
  for (int p = 0; p < 3; p++) {
    wgmma_n8_ssz_ta1_tb0(s[p], make_desc(slots + p * 2 * UNIT, 16), ones);
#pragma unroll
    for (int k = 1; k < 8; k++) wgmma_n8_ss_ta1_tb0(s[p], make_desc(slots + p * 2 * UNIT + k * 2048, 16), ones, 1);
  }
  wgmma_commit();
  wgmma_wait<0>();
  reg_fence<12>(&s[0][0]);
  if (lane == 0) mbar_arrive(bars + 8u * (ty ? B_CSD : B_RDONE));
  if (c == 0) {
#pragma unroll
    for (int r = 0; r < 2; r++) st_rec(&g_cs[ty][hp][qr][wwarp * 16 + 8 * r + g], s[0][2 * r], s[1][2 * r], s[2][2 * r], ep1);
  }
}

__device__ __forceinline__ void put_colsums(int ty, int col, const float4& s) {
  const float v[3] = {s.x, s.y, s.z};
#pragma unroll
  for (int p = 0; p < 3; p++) {
    const uint32_t a = SBASE + OFF_CS + (p * 8 + (col >> 3)) * 64 + ty * 32 + (col & 7) * 2;
    const float hi = bf16_round(v[p]);
    const uint32_t w = pack_bf16x2(hi, v[p] - hi);
    asm volatile("st.shared.b16 [%0], %1;" ::"r"(a), "h"((unsigned short)w) : "memory");
    asm volatile("st.shared.b16 [%0], %1;" ::"r"(a + 16), "h"((unsigned short)(w >> 16)) : "memory");
  }
}

__device__ __forceinline__ uint32_t ln_params(float s1, float s2) {
  const float mean = s1 * (1.0f / DM);
  const float var = fmaxf(fmaf(-mean, mean, s2 * (1.0f / DM)), 0.f);
  float sd;
  asm("sqrt.approx.f32 %0, %1;" : "=f"(sd) : "f"(bf16_round(bf16_round(var) + 1e-5f)));
  return pack_bf16x2(mean, sd);
}

__host__ __device__ constexpr uint32_t w_rel(int kt) { return ((B_WF + (kt & 7)) << 1) | (kt >> 3); }
__host__ __device__ constexpr uint32_t w_rel4(int a, int b, int c, int d) { return w_rel(a) | (w_rel(b) << 8) | (w_rel(c) << 16) | (w_rel(d) << 24); }
__device__ __forceinline__ void ring_wait(uint32_t e) { mbar_wait(SBASE + OFF_BAR + 8u * B_E + ((e << 2) & 0x3f8u), e & 1u); }
struct RingProd {
  uint32_t rel = ((B_QF << 1) | 1) * 0x01010101u + 0x06040200u;
  __device__ __forceinline__ void q_step(int kt) {
    const int sh = 8 * (kt & 3);
    const uint32_t e = rel >> sh;
    rel ^= ((e ^ (((B_QF + (kt & 3)) << 1) | ((kt >> 2) & 1))) & 255u) << sh;
    ring_wait(e);
  }
  __device__ __forceinline__ void w_job(int st, bool pre, uint32_t sel0, uint32_t sel1, uint32_t last, uint32_t& w0, uint32_t& w1) {
    const uint32_t r = __funnelshift_r(rel, rel, 8 * st);
    w0 = __byte_perm(r, 0u, sel0);
    w1 = __byte_perm(r, w_rel4(0, 1, 2, 3), pre ? sel1 : 0x6543u);
    const uint32_t n = pre ? (w_rel4(9, 11, 13, 0) & 0xffffffu) | (last << 24) : (w_rel4(11, 13, 0, 15) & 0xff00ffffu) | (last << 16);
    rel = __funnelshift_l(n, n, 8 * st);
  }
};

#define SP1 15
#define SP2 13
#define SP3 11
#define SP4 11
#define SP5 15
#define SP6 13
#define SP7 16
__device__ __forceinline__ int q_split(int inst) {
  constexpr uint32_t T = 15u | ((SP1 - 1) << 4) | ((SP2 - 1) << 8) | ((SP3 - 1) << 12) | ((SP4 - 1) << 16) | ((SP5 - 1) << 20) |
                         ((SP6 - 1) << 24) | ((uint32_t)(SP7 - 1) << 28);
  return (int)((T >> (4 * inst)) & 15u) + 1;
}
#define QROT 4
#define WROT 2
__device__ __forceinline__ int qk(int kt) { return (((kt & 12) | ((kt & 1) << 1) | ((kt >> 1) & 1)) + QROT) & 15; }
__device__ __forceinline__ int wk(int kt) { return (kt + WROT) & 15; }
__host__ __device__ constexpr uint32_t turn_par(int kind) {
  const int sp[8] = {16, SP1, SP2, SP3, SP4, SP5, SP6, SP7};
  int cnt[2] = {0, 0};
  uint32_t m = 0;
  for (int i = 0; i < 8; i++)
    for (int k = 0; k < 3; k++) {
      if (k == kind) m |= (uint32_t)(cnt[i & 1] & 1) << i;
      if (k == 0 ? (i == 1 || (i > 1 && sp[i - 1] < 16)) : (k == 2 || sp[i] < 16)) cnt[i & 1]++;
    }
  return m;
}
#define PREMASK 0xBFu
__device__ __forceinline__ bool w_pre(int inst) { return (PREMASK >> inst) & 1u; }
#define STGMASK 0x2Eu
__device__ __forceinline__ bool w_stg(int inst) { return (STGMASK >> inst) & 1u; }
__device__ __forceinline__ uint32_t w_out(int inst) {
  return w_stg(inst) ? SBASE + OFF_SLOT : SBASE + (((inst < 7 ? q_split(inst + 1) : 0) + (w_pre(inst) ? 3 : 2)) & 3) * 5 * UNIT;
}
__host__ __device__ constexpr unsigned long long bar_counts(int i0) {
  unsigned long long t = 0;
  for (int i = i0; i < i0 + 32; i++) {
    int l = 0;
    if (i < B_RF) l = 1;
    if ((i >= B_E && i < B_E + B_RF) || i == B_LOC || i == B_REL || i == B_OS0 || i == B_TURN || i == B_TURN + 1 || i == B_XS ||
        i == B_XS + 1 || i == B_CSD || i == B_GO || i == B_RDONE || i == B_KV)
      l = 2;
    if (i == B_REL + 1 || i == B_REL + 2) l = 3;
    t |= (unsigned long long)l << (2 * (i - i0));
  }
  return t;
}

__global__ void __launch_bounds__(512, 1) fused_kernel(const __grid_constant__ Params P) {
  extern __shared__ __align__(1024) uint8_t smem_raw[];
  constexpr uint32_t base = SBASE, bars = base + OFF_BAR, slots = base + OFF_SLOT;
  if (smem_u32(smem_raw) != base) __trap();
  const int warp = __shfl_sync(0xffffffffu, threadIdx.x >> 5, 0), lane = threadIdx.x & 31;
  const int b = blockIdx.x;
#define QS 1
#define WS 1
  const int qr = ((b & ((8 << QS) - 1)) >> QS) ^ (((b >> (3 + QS)) & 1) * 7);
  const int hp = ((b >> (3 + QS)) << QS) + (b & ((1 << QS) - 1));
  const int rt = ((b & ((16 << WS) - 1)) >> WS) ^ (((b >> (4 + WS)) & 1) * 15);
  const int ct = ((b >> (4 + WS)) << WS) + (b & ((1 << WS) - 1));

  if (warp < 12) {
    if (warp >= 4) {
      if (elect_one()) {
#pragma unroll 1
        for (int i = warp; i <= B_KV; i += 8) mbar_init(bars + 8u * i, 1u << (((i < 32 ? bar_counts(0) : bar_counts(32)) >> (2 * (i & 31))) & 3u));
        sts32(warp < 8 ? base + OFF_ONE - 16 + 4 * warp : base + OFF_LSB + 4 * warp, warp < 8 ? warp == 4 : 0x3f803f80u);
        fence_proxy_async_smem();
        fence_barrier_init();
      }
      __syncwarp();
    }
    const bool asst = warp >= 8;
    GTL(0);
    if (warp >= 4) named_bar_sync(0, 512);
    if (warp >= 4 && !asst) {
      PHASE_IDS
      {
        const unsigned ep1 = launch_epoch();
        const int row = b * 16 + (tid >> 3);
        const uint4* src = reinterpret_cast<const uint4*>(P.in_x + (size_t)row * DM) + (tid & 7);
        float s1 = 0.f, s2 = 0.f;
#pragma unroll 1
        for (int k = 0; k < 4; k++) {
          mbar_pace(bars + 8u * (B_QF + B_E + ((2 * k) & 3)), k >> 1, k ? PN2 : 30);
          uint4 v[4];
#pragma unroll
          for (int j = 0; j < 4; j++) v[j] = __ldg(src + (k * 4 + j) * 8);
#pragma unroll
          for (int j = 0; j < 4; j++) {
            const uint32_t w[4] = {v[j].x, v[j].y, v[j].z, v[j].w};
#pragma unroll
            for (int e = 0; e < 4; e++) {
              const float x0 = bf_lo(w[e]), x1 = bf_hi(w[e]);
              s1 += x0 + x1;
              s2 = fmaf(x0, x0, fmaf(x1, x1, s2));
            }
          }
        }
#pragma unroll
        for (int o = 1; o < 8; o <<= 1) {
          s1 += __shfl_xor_sync(0xffffffffu, s1, o);
          s2 += __shfl_xor_sync(0xffffffffu, s2, o);
        }
        if ((tid & 7) == 0) st_rec(&g_stats[0][row], s1, s2, 0.f, 4u * ep1);
        if (tid == 0) sts32(base + OFF_EPOCH, ep1);
        if (tid < 64) {
          const float4 s0 = sum_recs<8>(&g_cs[0][hp][0][tid], 64, ep1);
          put_colsums(0, tid, s0);
        } else {
          put_colsums(1, tid - 64, make_float4(0.f, 0.f, 0.f, 0.f));
        }
#pragma unroll 1
        for (int cc = 0; cc < 2; cc++) {
          const float4 s0 = sum_recs<1>(&g_stats[0][(cc * 8 + qr) * 128 + tid], 0, 4u * ep1);
          sts32(base + OFF_RS + (cc * 128 + tid) * 4, ln_params(s0.x, s0.y));
        }
        fence_proxy_async_smem();
        named_bar_sync(2, 128);
        if (tid < 2) mbar_arrive(bars + 8u * (B_PREP + tid));
      }
    }
#pragma unroll 1
    for (int inst = asst ? 0 : warp >> 2; inst < 8; inst += asst ? 1 : 2) {
      const int L = inst >> 1, ch = inst & 1, gb = ch * 8 + qr;
      uint32_t q[2][2][4];
      if (asst) {
        if (inst < 2) colsum_part(&P.wqkv[inst], inst, qr, hp);
        setmaxnreg_dec<24>();
        named_bar_sync(4, 256);
        setmaxnreg_inc<128>();
        const uint32_t ra = q_row_addr(L & 1, 1, warp & 3, fresh_tid() & 31);
#pragma unroll
        for (int j = 0; j < 4; j++) ldmatrix_x4(q[j >> 1][j & 1], ra ^ (j << 5));
      } else {
      setmaxnreg_inc<224>();
      {
        float acc[2][96];
        const int ksp = q_split(inst);
        constexpr uint32_t STG = 5 * (UNIT >> 4), D0 = ((base + 3 * UNIT) >> 4) + 0x10000u;
        constexpr uint32_t DB = ((UNIT >> 4) << 16) - 0x10000u - 3 * (UNIT >> 4);
        const uint32_t toff = ((fresh_tid() & 127) << 7) + ((fresh_tid() & 7) << 4);
        const bool lane0 = (toff & 0xf80u) == 0u;
        uint32_t xt = x_tag(L), tro = (warp & 3) * 2048 + (toff & 0x7f0u) + ((toff << 2) & 0x2000u);
        auto check_x = [&](uint32_t bar, uint32_t par, uint32_t ta, int kt, uint32_t mask) {
          fix_lines(bar, par, ta, xt, mask, 7, [&](int l) {
            return g_x + (size_t)(gb * 128 + (l >> 4) * 64 + tile_row(L & 1, warp & 3, (l >> 3) & 1, l & 7)) * DM + qk(kt) * 64;
          });
        };
        uint32_t rsa = base + OFF_RS + (ch * 128 + tile_row(L & 1, warp & 3, 0, (toff >> 9) & 7)) * 4;
        uint32_t rsb = rsa + ((L & 1) ? 32 : 128);
        uint32_t lnm = ((toff >> 7) & 3) == (L & 1) ? 0xffffffffu : 0u, tmk = L > 0;
        uint32_t soff = tile_row(L & 1, warp & 3, (toff >> 10) & 1, (toff >> 7) & 7) * 128 + ((toff ^ (toff >> 7)) & 0x10u) + (toff & 0x60u);
        uint32_t bprep = bars + 8u * (B_PREP + ch), bturn = bars + 8u * (B_TURN + (ch ^ 1));
        const bool stg = inst > 0 && w_stg(inst - 1);
        uint32_t bfree = bars + 8u * (inst == 1 ? B_CSD : (stg ? B_RF + B_E : B_RDONE));
        uint32_t pfree = inst == 1 ? 0 : (inst & 1) ^ stg, pprep = L & 1;
        asm volatile("" : "+r"(rsa), "+r"(rsb), "+r"(lnm), "+r"(soff), "+r"(xt), "+r"(tmk), "+r"(tro));
        asm volatile("" : "+r"(bprep), "+r"(bturn), "+r"(bfree), "+r"(pfree), "+r"(pprep));
        if (inst == 0) named_bar_sync(0, 512);
        if (inst == 1 || (inst > 1 && q_split(inst - 1) < 16)) mbar_wait_lazy<TLAZY>(bars + 8u * (B_TURN + ch), (turn_par(0) >> inst) & 1u);
        if (L == 3) GTL(37);
        check_x(bars + 8u * B_QF, 0, base + 3 * UNIT + tro, 0, tmk);
        GTL(1 + L * 8);
        {
          const uint64_t da = desc_lo(D0) + P.zero;
          wgmma_fence();
          wgmma_n192_ssz_ta0_tb1(acc[1], da + (UNIT >> 4), da + DB);
          wgmma_commit();
          wgmma_n192_ssz_ta0_tb1(acc[0], da, da + DB);
          wgmma_commit();
        }
        int left = ksp;
        asm volatile("" : "+r"(left));
        const uint64_t d0 = desc_lo(D0) + P.zero;
#pragma unroll 1
        for (int k4 = 0;; k4++) {
#pragma unroll
          for (int ks = 0; ks < 4; ks++) {
            const uint64_t da = d0 + ks * STG, dn = d0 + ((ks + 1) & 3) * STG;
            const uint32_t fn = bars + 8u * (B_QF + ((ks + 1) & 3)), pn = (k4 + (ks == 3)) & 1;
            const uint32_t ta = base + (3 + ((ks + 1) & 3) * 5) * UNIT + tro;
            bool ok, last;
            uint32_t tw;
#pragma unroll
            for (int k16 = 1; k16 < 4; k16++) {
              if (k16 > 1 || ks > 0) wgmma_wait<1>();
              else wgmma_fence();
              wgmma_n192_ss_ta0_tb1(acc[1], da + ((UNIT >> 4) + k16 * 2), da + (DB + k16 * 128), 1);
              wgmma_commit();
              if (k16 == 1) last = --left == 0;
              if (k16 == 2) {
                ok = mbar_test(fn, pn);
                tw = lds32(ta);
              }
              wgmma_wait<1>();
              wgmma_n192_ss_ta0_tb1(acc[0], da + k16 * 2, da + (DB + k16 * 128), 1);
              wgmma_commit();
              if (k16 == 2) {
                if (last && lane0) mbar_arrive(bturn);
                ok = !__any_sync(0xffffffffu, !ok || ((tw ^ xt) & tmk)) && !last;
              }
            }
            if (!ok) {
              if (last) {
                wgmma_wait<0>();
                if (lane0) mbar_arrive(bars + 8u * (B_QF + B_E + ks));
                mbar_wait_lazy<TLAZY>(bars + 8u * (B_TURN + ch), (turn_par(1) >> inst) & 1u);
              }
              check_x(fn, pn, ta, 4 * k4 + ks + 1, tmk);
            }
            if (ks == 2 && k4 == 3) goto q_last;
            wgmma_fence();
            wgmma_wait<1>();
            wgmma_n192_ss_ta0_tb1(acc[1], dn + (UNIT >> 4), dn + DB, 1);
            wgmma_commit();
            wgmma_wait<1>();
            wgmma_n192_ss_ta0_tb1(acc[0], dn, dn + DB, 1);
            wgmma_commit();
            if (lane0 && !last) mbar_arrive(bars + 8u * (B_QF + B_E + ks));
          }
        }
      q_last:
        constexpr uint32_t DL = D0 + 3 * STG;
        wgmma_fence();
#pragma unroll
        for (int k16 = 0; k16 < 4; k16++) wgmma_n192_ss_ta0_tb1(acc[1], desc_lo(DL + (UNIT >> 4) + k16 * 2), desc_lo(DL + DB + k16 * 128), 1);
        wgmma_commit();
        mbar_wait(bprep, pprep);
        uint32_t rs[2][2];
        constexpr uint64_t DCS = (uint64_t)((base + OFF_CS) >> 4) | (4ull << 32);
        auto ln_mma = [&](float (&d)[96], uint32_t (&r)[2], int h) {
          uint32_t a[4];
#pragma unroll
          for (int i = 0; i < 2; i++) {
            if (h) r[i] = lds32((i ? rsb : rsa) + 256);
            a[i] = (__byte_perm(r[i], 0u, 0x1010) ^ 0x80008000u) & lnm;
            a[i + 2] = r[i] & P.zero;
          }
#pragma unroll
          for (int i = 0; i < 4; i++) asm volatile("" : "+r"(a[i]));
          wgmma_fence();
          wgmma_n192_rs_tb1(d, a, DCS, 1);
          wgmma_commit();
        };
        ln_mma(acc[1], rs[1], 1);
        wgmma_wait<2>();
        if (lane0 && ksp != 15) mbar_arrive(bars + 8u * (B_QF + B_E + 2));
        wgmma_fence();
#pragma unroll
        for (int k16 = 0; k16 < 4; k16++) wgmma_n192_ss_ta0_tb1(acc[0], desc_lo(DL + k16 * 2), desc_lo(DL + DB + k16 * 128), 1);
        wgmma_commit();
        if (lane0) mbar_arrive(bturn);
        rs[0][0] = lds32(rsa);
        rs[0][1] = lds32(rsb);
        static_assert(SP1 < 16 && SP5 < 16 && (PREMASK & 1u) && !(STGMASK & 1u), "column sums of B");
        const bool afree = mbar_test(bfree, pfree) & (mbar_test(bars + 8u * (B_WF + B_E + 7), 1) | (ksp == 16));
        float rinv[2];
#pragma unroll
        for (int r = 0; r < 2; r++) {
          rinv[r] = rcp_fast(bf_hi(rs[1][r]));
          asm volatile("" : "+f"(rinv[r]));
        }
        const uint32_t kdst = ((L & 1) ? KB_ROW0 : slots) + soff, vdst = ((L & 1) ? VB_ROW0 : slots + 8192) + soff;
        const uint32_t hs = (L & 1) ? 8192 : 16384, c0 = (toff & 0x180u) == 0u;
        wgmma_wait<1>();
        ln_mma(acc[0], rs[0], 0);
        reg_fence<96>(acc[1]);
        GTL(2 + L * 8);
        if (!afree) {
          mbar_wait(bfree, pfree);
          if (ksp < 16) mbar_wait(bars + 8u * (B_WF + B_E + 7), 1);
        }
#pragma unroll
        for (int t = 0; t < 24; t++) {
          const int h = t < 12 ? 1 : 0, p = ((t % 12) / 4 + 1) % 3, jp = t & 3;
          if (t == QREL) {
            wgmma_wait<0>();
            reg_fence<96>(acc[0]);
            if (lane0) mbar_arrive(bars + 8u * (B_QF + B_E + 3));
          }
          if (t == 8 || t == 20) {
            rinv[0] *= SM_C;
            rinv[1] *= SM_C;
          }
          const float* a = &acc[h][4 * (p * 8 + 2 * jp)];
          uint32_t r0 = pack_bf16x2(a[0] * rinv[0], a[1] * rinv[0]);
          uint32_t r1 = pack_bf16x2(a[2] * rinv[1], a[3] * rinv[1]);
          if (p != 0 && jp == 0) {
            r0 = set_tag(r0, c0, kv_tag(L));
            r1 = set_tag(r1, c0, kv_tag(L));
          }
          const uint32_t r2 = pack_bf16x2(a[4] * rinv[0], a[5] * rinv[0]);
          const uint32_t r3 = pack_bf16x2(a[6] * rinv[1], a[7] * rinv[1]);
          const uint32_t dst = p == 0 ? slots + 3 * 16384 + soff + h * 8192 : (p == 1 ? kdst : vdst) + h * hs;
          stmatrix_x4(dst ^ (jp << 5), r0, r1, r2, r3);
          if (t >= 20) {
            q[jp >> 1][jp & 1][0] = r0;
            q[jp >> 1][jp & 1][1] = r1;
            q[jp >> 1][jp & 1][2] = r2;
            q[jp >> 1][jp & 1][3] = r3;
          }
          if (t == 7 || t == 19) signal_async(bars + 8u * (t == 7 ? B_KV : B_LOC), lane0);
          if (t == 11) {
            setmaxnreg_dec<128>();
            named_bar_arrive(4, 256);
#pragma unroll
            for (int r = 0; r < 2; r++) rinv[r] = rcp_fast(bf_hi(rs[0][r]));
          }
        }
        mbar_wait(bars + 8u * B_LOC, inst & 1);
      }
      }
      GTL(3 + L * 8);
      if ((L & 1) == 0) attention_a(q, asst, L, gb, hp, ch, warp & 3, P.zero);
      else attention_b(q, asst, gb, inst & 1, warp & 3);
      GTL(4 + L * 8);
      signal_async(bars + 8u * (asst ? B_OS1 : B_OS0), (fresh_tid() & 31) == 0);
      if (asst) continue;
      GTL(5 + L * 8);

      {
        float acc[64];
        const int sp = inst < 7 ? q_split(inst + 1) : 0;
        const int st = sp & 3;
        const bool pre = w_pre(inst);
        const uint32_t toff = ((fresh_tid() & 63) << 7) + ((fresh_tid() & 7) << 4);
        uint32_t tro = (warp & 3) * 2048 + (toff & 0x7f0u);
        auto check_o = [&](uint32_t bar, uint32_t par, uint32_t sa, int kt) {
          fix_lines(bar, par, sa + tro, o_tag(L), 1u, 7, [&](int l) {
            return g_o + (size_t)(ch * 1024 + rt * 64 + (warp & 3) * 16 + (l & 15)) * DM + wk(kt) * 64;
          });
        };
        const bool lane0 = (toff & 0xf80u) == 0u;
        constexpr uint32_t U4 = UNIT >> 4, LA = 0x10000u, LB = U4 << 16;
        reg_define<64>(acc);
        reg_fence<64>(acc);
        uint32_t xv[8][4];
        {
          PHASE_IDS_W
          const uint32_t xr = slots + 6 * UNIT + (wwarp * 16 + (lane & 15)) * 128 + (((lane >> 4) ^ (lane & 7)) << 4);
          mbar_wait(bars + 8u * B_RF, inst & 1);
#pragma unroll
          for (int jp = 0; jp < 8; jp++) ldmatrix_x4(xv[jp], (xr ^ ((jp & 3) << 5)) + (jp >> 2) * UNIT);
          signal_async(bars + 8u * B_RDONE, lane0);
          if (L > 0) {
            uint32_t lsb;
            asm volatile("ld.shared.u8 %0, [%1];" : "=r"(lsb) : "r"(base + OFF_LSB + ch * 32 + wwarp * 8 + g) : "memory");
#pragma unroll
            for (int k = 0; k < 4; k++) xv[(k >> 1) * 4][k & 1] = set_tag(xv[(k >> 1) * 4][k & 1], c == 0, lsb >> k);
          }
        }
        uint32_t tmx = L < 3 && (toff & 0x180u) == 0u, xt = x_tag(L + 1);
        uint32_t xrow = w_out(inst) + (warp & 3) * 2048 + (toff & 0x7e0u) + ((toff ^ (toff >> 7)) & 0x10u);
        asm volatile("" : "+r"(tmx), "+r"(xt), "+r"(xrow), "+r"(tro));
        const uint64_t dz = desc_lo(0) + P.zero;
        auto nexts = [&](uint32_t a) { return a == base + 15 * UNIT ? base : a + 5 * UNIT; };
        uint32_t s0 = base + st * 5 * UNIT, sp3 = slots, fb = bars + 8u * B_WF;
        int turn = lane0 && (sp < 16 || inst == 6) ? 3 : -1;
        asm volatile("" : "+r"(turn));
        if (inst < 7 || SP7 == 16) mbar_wait_lazy<TLAZY>(bars + 8u * (B_TURN + ch), (turn_par(2) >> inst) & 1u);
        check_o(bars + 8u * B_WF, 0, s0, 0);
        GTL(6 + L * 8);
#pragma unroll 1
        for (int m = 0; m < 4; m++) {
          uint32_t s1, s2;
#pragma unroll
          for (int i = 0; i < 4; i++) {
            const uint64_t da = dz + ((i == 0 ? s0 : s1) >> 4) + (LA + (i == 2 ? 1 : (i == 3 ? 4 : 0)) * U4);
            const uint64_t db = dz + ((i < 2 ? s0 : (i == 2 ? s1 : s2)) >> 4) + (LB + (i == 0 ? 1 : (i == 1 ? 3 : (i == 2 ? 2 : 0))) * U4);
            wgmma_fence();
#pragma unroll
            for (int k16 = 0; k16 < 4; k16++) wgmma_n128_ss_ta0_tb1(acc, da + 2 * k16, db + 128 * k16, 1);
            wgmma_commit();
            if (i == 0) s1 = nexts(s0);
            if (i == 1) s0 = nexts(s1);
            if (i == 2) {
              s2 = pre ? sp3 : s0;
              s0 = pre ? s0 : nexts(s0);
              sp3 += 2 * UNIT;
            }
            const uint32_t fn = i < 3 ? fb + 8u * (i + 1) : fb ^ 96u;
            const uint32_t pn = i < 3 ? m >> 1 : m > 0;
            const uint32_t an = i < 3 ? s1 + (i == 1 ? 1 : (i == 2 ? 4 : 0)) * UNIT : s0;
            bool ok = mbar_test(fn, pn);
            const uint32_t tw = lds32(an + tro);
            ok = !__any_sync(0xffffffffu, (!ok || ((tw ^ o_tag(L)) & 1u)) && (i < 3 || m < 3));
            wgmma_wait<1>();
            if (lane0 && (i > 0 || m > 0)) mbar_arrive((i > 0 ? fb + 8u * (i - 1) : (fb ^ 96u) + 24u) + 8u * B_E);
            if (i == 2 && m == turn) mbar_arrive(bars + 8u * (B_TURN + (ch ^ 1)));
            if (!ok) check_o(fn, pn, an, 4 * m + i + 1);
          }
          fb ^= 96u;
        }
        wgmma_wait<0>();
        reg_fence<64>(acc);
        if (lane0) mbar_arrive(bars + 8u * (B_WF + B_E + 7));
        GTL(7 + L * 8);
#pragma unroll
        for (int jp = 0; jp < 8; jp++) {
#pragma unroll
          for (int q = 0; q < 4; q++) xv[jp][q] = add_bf16x2(xv[jp][q], pack_bf16x2(acc[8 * jp + 2 * q], acc[8 * jp + 2 * q + 1]));
          const bool tg = (jp & 3) == 0;
          stmatrix_x4((xrow ^ ((jp & 3) << 5)) + (jp >> 2) * UNIT,
                      tg ? set_tag(xv[jp][0], tmx, xt) : xv[jp][0], tg ? set_tag(xv[jp][1], tmx, xt) : xv[jp][1], xv[jp][2], xv[jp][3]);
          if ((jp & 3) == 3) signal_async(bars + 8u * (B_XS + (jp >> 2)), lane0);
        }
        if (L < 3) {
          PHASE_IDS_W
          const int grow = ch * 1024 + rt * 64;
          const unsigned ep1 = lds32(base + OFF_EPOCH);
          if (c == 0)
            asm volatile("st.shared.u8 [%0], %1;" ::"r"(base + OFF_LSB + ch * 32 + wwarp * 8 + g),
                         "r"((xv[0][0] & 1u) | ((xv[0][1] & 1u) << 1) | ((xv[4][0] & 1u) << 2) | ((xv[4][1] & 1u) << 3)) : "memory");
          float s1[2] = {0.f, 0.f}, s2[2] = {0.f, 0.f};
#pragma unroll
          for (int jp = 0; jp < 8; jp++)
#pragma unroll
            for (int q = 0; q < 4; q++) {
              const float x0 = bf_lo(xv[jp][q]), x1 = bf_hi(xv[jp][q]);
              s1[q & 1] += x0 + x1;
              s2[q & 1] = fmaf(x0, x0, fmaf(x1, x1, s2[q & 1]));
            }
#pragma unroll
          for (int r = 0; r < 2; r++) {
            s1[r] += __shfl_xor_sync(0xffffffffu, s1[r], 1);
            s2[r] += __shfl_xor_sync(0xffffffffu, s2[r], 1);
            s1[r] += __shfl_xor_sync(0xffffffffu, s1[r], 2);
            s2[r] += __shfl_xor_sync(0xffffffffu, s2[r], 2);
            if (c == 0) st_rec(&g_stats[ct][grow + wwarp * 16 + g + 8 * r], s1[r], s2[r], 0.f, 4u * ep1 + L + 1);
          }
        }
        GTL(8 + L * 8);
      }
    }
    if (threadIdx.x == 128) atomicAdd(g_done, 1u);
  } else {
    setmaxnreg_dec<32>();
    if (warp == 13) {
      RingProd rp;
      unsigned ep1 = 0;
      uint32_t seenx = 0;
      named_bar_sync(0, 512);
      mbar_wait(bars + 8u * B_GO, 0);
#pragma unroll 1
      for (int sg = 4; sg < 34; sg++) {
        const int part = sg & 3, inst = (sg >> 2) - (part & 1);
        if (part == 3 || inst == 8) continue;
        const int L = inst >> 1, ch = inst & 1;
        if (part != 1) {
          const CUtensorMap* tx = &P.xq[L];
          const int k0 = part ? q_split(inst) : 0, k1 = part ? 16 : q_split(inst);
          if (sg == 4) ep1 = launch_epoch();
          if (part == 0) seenx = L == 0 ? 0xffffffffu : peek_counts(g_fx[ch * 8 + qr][0], 6u * ep1 - 6u + 2u * L, lane);
          const int m0 = ch * 16 + qr * 2;
#pragma unroll 1
          for (int kt = k0; kt < k1; kt++) {
            const uint32_t fb = bars + 8u * (B_QF + (kt & 3));
            rp.q_step(kt);
            if (lane == 0) mbar_expect_tx(fb, 2 * UNIT);
            wait_count(g_fx[ch * 8 + qr][0], 6u * ep1 - 6u + 2u * L, qk(kt), seenx, lane);
            TGET(t38);
            if (elect_one()) tma_load_5d(base + ((kt & 3) * 5 + 3) * UNIT, tx, fb, qk(kt) * 64, m0);
            TGET(t39);
            if (L == 3 && kt == 0 && lane == 0) { TPUT(ch, 38, t38); TPUT(ch, 39, t39); }
          }
        } else {
          const int m0 = ch * 1024 + rt * 64;
          const bool pre = w_pre(inst);
          int st = inst < 7 ? q_split(inst + 1) & 3 : 0;
          uint32_t w0, w1;
          uint32_t seen = peek_counts(g_fo[ch * 16 + rt][0], 4u * ep1 - 3u + L, lane);
          rp.w_job(st, pre, 0x1110u, 0x3332u, inst == 6 && SP7 == 16 ? B_RF << 1 : w_rel(15), w0, w1);
#pragma unroll 1
          for (int m = 0; m < 4; m++) {
            const uint32_t fb = bars + 8u * (B_WF + 4 * (m & 1));
#pragma unroll
            for (int i = 0; i < 4; i++) {
              ring_wait(w0 >> (8 * i));
              if (lane == 0) mbar_expect_tx(fb + 8u * i, UNIT);
              wait_count(g_fo[ch * 16 + rt][0], 4u * ep1 - 3u + L, wk(4 * m + i), seen, lane);
              if (elect_one())
                tma_load_2d(base + ((st + (i > 0)) & 3) * 5 * UNIT + (i == 2 ? 1 : (i == 3 ? 4 : 0)) * UNIT, &P.o, fb + 8u * i, wk(4 * m + i) * 64, m0);
            }
            st += pre ? 2 : 3;
            w0 = w1;
            w1 = m == 0 ? (pre ? w_rel4(0, 1, 2, 3) : w_rel4(3, 4, 5, 6)) : (pre ? w_rel4(4, 5, 6, 7) : w_rel4(7, 8, 9, 10));
          }
        }
      }
#pragma unroll 1
      for (int j = 0; j < 8; j++)
        g_x[(size_t)((j >> 2) * 1024 + rt * 64 + (j & 3) * 16 + (lane >> 1)) * DM + ct * 128 + (lane & 1) * 64] = __ushort_as_bfloat16(0);
    } else if (warp == 14) {
      const unsigned ep1 = launch_epoch();
      uint32_t hpar = 0;
      named_bar_sync(0, 512);
#pragma unroll 1
      for (int inst = 0; inst < 8; inst++) {
        const int L = inst >> 1, ch = inst & 1, gb = ch * 8 + qr;
        const unsigned kv0 = 8u * ep1 - 8u + 2u * L + (L & 1);
        const uint32_t tag = kv_tag(L);
        if (L >= 2) {
#pragma unroll 1
          for (uint32_t it = 0; it < (1u << 17); ++it)
            if (__all_sync(0xffffffffu, (int)(ld_relaxed_u32(g_fk[hp][min(gb + 1 + (lane & 1), 15)]) - kv0) >= 0)) break;
        }
        if ((L & 1) == 0) {
          uint8_t* img = g_kvA[gb][hp][0];
          const uint8_t* s1 = gb > 0 ? img - 16 * 32768 : g_zero;
          const uint8_t* s2 = gb > 1 ? img - 32 * 32768 : g_zero;
          const uint32_t h1 = gb > 0 ? 16384 : 0, h2 = gb > 1 ? 16384 : 0;
          const unsigned* cp = g_fk[hp][max(gb - 1 - (lane >= 3), 0)];
          const unsigned ct0 = kv0 + ((0x32321u >> (4 * (lane & 7))) & 3u);
          uint32_t fr = gb == 0 ? 31u : (gb == 1 ? 24u : 0u);
          const uint32_t toff = slots + lane * 128 + ((lane & 7) << 4);
          auto seen = [&](uint32_t m) {
#pragma unroll 1
            for (uint32_t it = 0; it < (1u << 17) && !(fr & m); ++it)
              fr |= __ballot_sync(0xffffffffu, (int)(ld_relaxed_u32(cp) - ct0) >= 0);
          };
          auto load = [&](uint32_t off, const uint8_t* src, uint32_t bytes, int bi) {
            if (elect_one()) {
              mbar_expect_tx(bars + 8u * (B_HL + bi), bytes);
              bulk_load(slots + off, src, bytes, bars + 8u * (B_HL + bi));
            }
          };
          auto check = [&](uint32_t off, const uint8_t* src, uint32_t bytes, int bi, bool real, int done) {
#pragma unroll 1
            for (int tries = 0; tries < 4096; tries++) {
              mbar_wait(bars + 8u * (B_HL + bi), (hpar >> bi) & 1u);
              hpar ^= 1u << bi;
              uint32_t t = (lds32(toff + off) ^ tag) | (lds32(toff + off + 4096) ^ tag);
              if (bytes > 8192) t |= (lds32(toff + off + 8192) ^ tag) | (lds32(toff + off + 12288) ^ tag);
              if (!__any_sync(0xffffffffu, real && (t & 1u))) break;
              fence_proxy_async_smem();
              load(off, src, bytes, bi);
            }
            if (lane == 0) mbar_arrive(bars + 8u * done);
          };
          uint8_t *pk = img + 16384, *pv = img + 24576;
          unsigned* f = g_fk[hp][gb];
          pin64(pk), pin64(pv), pin64(f);
          mbar_wait(bars + 8u * B_KV, inst & 1);
          if (ch) mbar_wait(bars + 8u * (B_RF + B_E), 0);
          if (elect_one()) {
            bulk_store(pk, slots + 16384, 8192);
            bulk_announce(f);
            bulk_store(pv, slots + 24576, 8192);
            bulk_announce(f);
            bulk_commit();
          }
          HTS(44);
          seen(1);
          HTS(46);
          load(32768, s1 + h1, 8192, 0);
          seen(2);
          HTS(47);
          load(40960, s1 + h1 + 8192, 8192, 1);
          mbar_wait(bars + 8u * B_LOC, inst & 1);
          HTS(45);
          if (elect_one()) {
            bulk_store(img, slots, 16384);
            bulk_announce(g_fk[hp][gb]);
            bulk_commit();
            asm volatile("cp.async.bulk.wait_group.read 1;" ::: "memory");
          }
          check(32768, s1 + h1, 8192, 0, gb > 0, B_HALO);
          HTS(52);
          check(40960, s1 + h1 + 8192, 8192, 1, gb > 0, B_HV);
          HTS(53);
#pragma unroll 1
          for (int n = 1; n < 4; n++) {
            const uint8_t* src = n == 1 ? s1 : (n == 2 ? s2 + h2 : s2);
            const uint32_t off = n == 3 ? 32768 : 32768 - n * 16384;
            seen(2u << n);
            if (n == 2 && elect_one()) bulk_wait_read0();
            mbar_wait(bars + 8u * (B_REL - 1) + 8u * n, ch);
            HTS(47 + n);
            load(off, src, 16384, 0);
            check(off, src, 16384, 0, gb > (n >> 1), B_HALO + n);
            HTS(53 + n);
          }
        } else {
          uint8_t *pk = g_kvB[gb][hp], *pv = pk + 2048;
          const uint8_t* src = gb >= 1 ? pk - 16 * 4096 : g_zero;
          unsigned* f = g_fk[hp][gb];
          pin64(pk), pin64(pv), pin64(f), pin64(src);
          mbar_wait(bars + 8u * B_KV, inst & 1);
          if (elect_one()) {
            bulk_store(pk, KB_ROW0 + 112 * 128, 2048);
            bulk_store(pv, VB_ROW0 + 112 * 128, 2048);
            bulk_announce(f);
            bulk_commit();
          }
          HTS(44);
          if (gb > 0) {
#pragma unroll 1
            for (uint32_t it = 0; it < (1u << 17); ++it)
              if (__any_sync(0xffffffffu, (int)(ld_relaxed_u32(f - 4) - kv0) > 0)) break;
          }
          HTS(46);
#pragma unroll 1
          for (uint32_t it = 0; it < (1u << 17); ++it) {
            if (elect_one()) {
              mbar_expect_tx(bars + 8u * B_HL, 4096);
              bulk_load(KB_ROW0 - 2048, src, 2048, bars + 8u * B_HL);
              bulk_load(VB_ROW0 - 2048, src + 2048, 2048, bars + 8u * B_HL);
            }
            mbar_wait(bars + 8u * B_HL, hpar & 1u);
            hpar ^= 1u;
            const uint32_t t = lds32((lane < 16 ? KB_ROW0 - 2048 : VB_ROW0 - 4096) + lane * 128 + ((lane & 7) << 4)) ^ tag;
            if (!__any_sync(0xffffffffu, gb > 0 && (t & 1u))) break;
            fence_proxy_async_smem();
          }
          if (lane == 0) mbar_arrive(bars + 8u * B_HALO);
          HTS(52);
        }
        if (elect_one()) {
          const CUtensorMap* mo = &P.o;
          unsigned *f1 = g_fo[gb * 2 + 1][hp], *f0 = g_fo[gb * 2][hp];
          int c0 = hp * 64, r0 = gb * 128, r1 = r0 + 64;
          pin64(mo), pin64(f1), pin64(f0);
          asm volatile("" : "+r"(c0), "+r"(r0), "+r"(r1));
          mbar_wait(bars + 8u * B_OS1, (inst & 1) ^ 1);
          tma_store_2d(mo, slots + 7 * UNIT, c0, r1);
          bulk_announce(f1);
          bulk_commit();
          mbar_wait(bars + 8u * B_OS0, inst & 1);
          tma_store_2d(mo, slots + 6 * UNIT, c0, r0);
          bulk_announce(f0);
          bulk_commit();
          HTS(57);
          const bool pre = w_pre(inst);
          bulk_wait_read0();
          HTS(58 - 15);
          mbar_expect_tx(bars + 8u * B_RF, 2 * UNIT);
          tma_load_2d(slots + 6 * UNIT, &P.x[L], bars + 8u * B_RF, ct * 128, ch * 1024 + rt * 64);
          tma_load_2d(slots + 7 * UNIT, &P.x[L], bars + 8u * B_RF, ct * 128 + 64, ch * 1024 + rt * 64);
          if (pre) {
            const uint32_t pp = __popc(PREMASK & ((1u << inst) - 1u)) & 1;
            mbar_expect_tx(bars + 8u * B_PRE, 2 * UNIT);
            mbar_expect_tx(bars + 8u * B_PRE2, 6 * UNIT);
#pragma unroll 1
            for (int j = 0; j < 4; j++) {
              __nanosleep(PRESLEEP);
              if (j == 3) mbar_wait(bars + 8u * B_RDONE, (inst & 1) ^ 1);
              tma_load_3d(slots + j * 2 * UNIT, &P.wo3[L & 1], bars + 8u * (j ? B_PRE2 : B_PRE), ct * 128, wk(4 * j + 3) * 64);
            }
#pragma unroll 1
            for (int j = 0; j < 4; j++) {
              const uint32_t fb = bars + 8u * (B_WF + 3 + 4 * (j & 1));
              if (j < 2) mbar_wait(bars + 8u * (j ? B_PRE2 : B_PRE), pp);
              if (j < 2 && inst == 7 && SP7 == 16) mbar_wait(bars + 8u * (B_TURN + 1), (turn_par(2) >> 7) & 1u);
              mbar_wait(fb + 8u * B_E, j < 2);
              mbar_arrive(fb);
            }
          }
        }
        __syncwarp();
      }
    } else if (warp == 15) {
      const unsigned ep1 = launch_epoch();
      named_bar_sync(0, 512);
      mbar_wait(bars + 8u * B_GO, 0);
#pragma unroll 1
      for (int i = 0; i < 20; i++) {
        const char* src = i < 4 ? reinterpret_cast<const char*>(P.wo_p[0]) + (size_t)b * 16384 + i * 4096
                                : (i < 16 ? reinterpret_cast<const char*>(P.wqkv_p[1]) + (size_t)b * 49152 + (i - 4) * 4096
                                          : reinterpret_cast<const char*>(P.wo_p[1]) + (size_t)b * 16384 + (i - 16) * 4096);
        asm volatile("prefetch.global.L2 [%0];" ::"l"(src + lane * 128));
        __nanosleep(TRICKLE);
      }
#pragma unroll 1
      for (int inst = 2; inst < 10; inst++) {
        const int L = inst >> 1, ch = inst & 1, gb = ch * 8 + qr;
        {
          uint32_t xb = w_out(inst - 2);
          unsigned* f = g_fx[ch * 8 + (rt >> 1)][ct * 2];
          const CUtensorMap* mx = &P.x[L];
          int c0 = ct * 128, r0 = ch * 1024 + rt * 64;
          pin64(f), pin64(mx);
          asm volatile("" : "+r"(xb), "+r"(c0), "+r"(r0));
#pragma unroll
          for (int h = 0; h < 2; h++) {
            mbar_wait(bars + 8u * (B_XS + h), ch);
            if (elect_one()) {
              tma_store_2d(mx, xb + h * UNIT, c0 + h * 64, r0);
              if (L < 4) bulk_announce(f + 4 * h);
              bulk_commit();
              if (h == 1) {
                bulk_wait_read0();
                mbar_arrive(bars + 8u * (B_RF + B_E));
              }
            }
          }
          if (L == 4) continue;
          __nanosleep(SDLY);
        }
#pragma unroll 1
        for (int h = 0; h < 4; h++) {
          const float4* sp = &g_stats[0][gb * 128 + h * 32 + lane];
          const float4 s0 = sum_recs<4>(sp, S_LEN, 4u * ep1 + L), s1 = sum_recs<4>(sp + 4 * S_LEN, S_LEN, 4u * ep1 + L);
          sts32(base + OFF_RS + (ch * 128 + h * 32 + lane) * 4, ln_params(s0.x + s1.x, s0.y + s1.y));
        }
        if (inst == 2) {
#pragma unroll 1
          for (int hf = 0; hf < 2; hf++) {
            const float4* cp = &g_cs[1][hp][0][hf * 32 + lane];
            const float4 s0 = sum_recs<4>(cp, 64, ep1), s1 = sum_recs<4>(cp + 4 * 64, 64, ep1);
            put_colsums(1, hf * 32 + lane, make_float4(s0.x + s1.x, s0.y + s1.y, s0.z + s1.z, 0.f));
          }
        }
        fence_proxy_async_smem();
        __syncwarp();
        if (lane == 0) mbar_arrive(bars + 8u * (B_PREP + ch));
      }
    } else {
      if (elect_one()) {
#pragma unroll 1
        for (int s = 0; s < 4; s++) {
          const uint32_t fb = bars + 8u * (B_QF + s), sa = base + s * 5 * UNIT;
          mbar_init(fb, 2);
          fence_barrier_init();
          mbar_expect_tx(fb, 5 * UNIT);
          mbar_arrive(fb);
          tma_load_5d(sa + 3 * UNIT, &P.xq[0], fb, s * 64, qr * 2);
          tma_load_3d(sa, &P.wqkv3[0], fb, hp * 64, s * 64);
        }
      }
      __syncwarp();
      named_bar_sync(0, 512);
      if (elect_one()) {
#pragma unroll 1
        for (int s = 4; s < 16; s++) {
          const uint32_t fb = bars + 8u * (B_QF + (s & 3)), sa = base + (s & 3) * 5 * UNIT;
          mbar_wait(fb + 8u * B_E, ((s >> 2) & 1) ^ 1);
          mbar_expect_tx(fb, 5 * UNIT);
          mbar_arrive(fb);
          tma_load_5d(sa + 3 * UNIT, &P.xq[0], fb, s * 64, qr * 2);
          tma_load_3d(sa, &P.wqkv3[0], fb, hp * 64, s * 64);
        }
#pragma unroll
        for (int s = 0; s < 4; s++) mbar_arrive(bars + 8u * B_GO);
        RingProd rp;
#pragma unroll 1
        for (int sg = 4; sg < 34; sg++) {
          const int part = sg & 3, inst = (sg >> 2) - (part & 1);
          if (part == 3 || inst == 8) continue;
          const int ty = (inst >> 1) & 1;
          if (part != 1) {
            const int k0 = part ? q_split(inst) : 0, k1 = part ? 16 : q_split(inst);
#pragma unroll 1
            for (int kt = k0; kt < k1; kt++) {
              const uint32_t sa = base + (kt & 3) * 5 * UNIT, fb = bars + 8u * (B_QF + (kt & 3));
              rp.q_step(kt);
              mbar_expect_tx(fb, 3 * UNIT);
              tma_load_3d(sa, &P.wqkv3[ty], fb, hp * 64, qk(kt) * 64);
            }
          } else {
            const bool pre = w_pre(inst);
            int st = inst < 7 ? q_split(inst + 1) & 3 : 0;
            uint32_t w0, w1;
            rp.w_job(st, pre, pre ? 0x1100u : 0x2100u, 0x3322u, w_stg(inst) ? w_rel(15) : (B_RF << 1) | (inst & 1), w0, w1);
#pragma unroll 1
            for (int m = 0; m < 4; m++) {
              const uint32_t fb = bars + 8u * (B_WF + 4 * (m & 1));
#pragma unroll
              for (int i = 0; i < 4; i++) {
                if (i < 3 || !pre) {
                  ring_wait(w0 >> (8 * i));
                  mbar_expect_tx(fb + 8u * i, 2 * UNIT);
                  tma_load_3d(base + ((st + (i ? i - 1 : 0)) & 3) * 5 * UNIT + ((0x2d >> (2 * i)) & 3) * UNIT, &P.wo3[ty], fb + 8u * i,
                              ct * 128, wk(4 * m + i) * 64);
                }
              }
              st += pre ? 2 : 3;
              w0 = w1;
              w1 = m == 0 ? (pre ? w_rel4(0, 1, 2, 3) : w_rel4(3, 4, 5, 6)) : (pre ? w_rel4(4, 5, 6, 7) : w_rel4(7, 8, 9, 10));
            }
          }
        }
      }
    }
  }
}

typedef CUresult (*PFN_tmEncode)(CUtensorMap*, CUtensorMapDataType, cuuint32_t, void*, const cuuint64_t*,
                                 const cuuint64_t*, const cuuint32_t*, const cuuint32_t*, CUtensorMapInterleave,
                                 CUtensorMapSwizzle, CUtensorMapL2promotion, CUtensorMapFloatOOBfill);

PFN_tmEncode get_encode_fn() {
  static PFN_tmEncode fn = nullptr;
  if (!fn) {
    cudaDriverEntryPointQueryResult qr;
    void* p = nullptr;
    cudaGetDriverEntryPoint("cuTensorMapEncodeTiled", &p, cudaEnableDefault, &qr);
    fn = (PFN_tmEncode)p;
  }
  return fn;
}

CUtensorMap make_map(const void* ptr, int rows, int cols) {
  CUtensorMap m;
  cuuint64_t gdim[2] = {(cuuint64_t)cols, (cuuint64_t)rows};
  cuuint64_t gstr[1] = {(cuuint64_t)cols * 2};
  cuuint32_t box[2] = {64, 64};
  cuuint32_t estr[2] = {1, 1};
  get_encode_fn()(&m, CU_TENSOR_MAP_DATA_TYPE_BFLOAT16, 2, const_cast<void*>(ptr), gdim, gstr, box, estr,
                  CU_TENSOR_MAP_INTERLEAVE_NONE, CU_TENSOR_MAP_SWIZZLE_128B, CU_TENSOR_MAP_L2_PROMOTION_L2_128B,
                  CU_TENSOR_MAP_FLOAT_OOB_FILL_NONE);
  return m;
}

CUtensorMap make_map3(const void* ptr, int rows, int cols, int n, int step) {
  CUtensorMap m;
  cuuint64_t gdim[3] = {(cuuint64_t)(cols - (n - 1) * step), (cuuint64_t)rows, (cuuint64_t)n};
  cuuint64_t gstr[2] = {(cuuint64_t)cols * 2, (cuuint64_t)step * 2};
  cuuint32_t box[3] = {64, 64, (cuuint32_t)n};
  cuuint32_t estr[3] = {1, 1, 1};
  get_encode_fn()(&m, CU_TENSOR_MAP_DATA_TYPE_BFLOAT16, 3, const_cast<void*>(ptr), gdim, gstr, box, estr,
                  CU_TENSOR_MAP_INTERLEAVE_NONE, CU_TENSOR_MAP_SWIZZLE_128B, CU_TENSOR_MAP_L2_PROMOTION_L2_128B,
                  CU_TENSOR_MAP_FLOAT_OOB_FILL_NONE);
  return m;
}

CUtensorMap make_map_q(const void* ptr, int sw, int sr) {
  CUtensorMap m;
  cuuint64_t gdim[5] = {DM, 8, 2, 4, S_LEN / 64};
  cuuint64_t gstr[4] = {DM * 2, (cuuint64_t)sr * DM * 2, (cuuint64_t)sw * DM * 2, 64 * DM * 2};
  cuuint32_t box[5] = {64, 8, 2, 4, 2};
  cuuint32_t estr[5] = {1, 1, 1, 1, 1};
  get_encode_fn()(&m, CU_TENSOR_MAP_DATA_TYPE_BFLOAT16, 5, const_cast<void*>(ptr), gdim, gstr, box, estr,
                  CU_TENSOR_MAP_INTERLEAVE_NONE, CU_TENSOR_MAP_SWIZZLE_128B, CU_TENSOR_MAP_L2_PROMOTION_L2_128B,
                  CU_TENSOR_MAP_FLOAT_OOB_FILL_NONE);
  return m;
}

}

extern "C" void kernel_launch(void* const* d_in, const int* in_sizes, int n_in, void* d_out, int out_size) {
  (void)in_sizes; (void)n_in; (void)out_size;
  void *p_o, *p_x;
  cudaGetSymbolAddress(&p_o, g_o);
  cudaGetSymbolAddress(&p_x, g_x);
  static bool attr_done = false;
  if (!attr_done) {
    cudaFuncSetAttribute(fused_kernel, cudaFuncAttributeMaxDynamicSharedMemorySize, SMEM_BYTES);
    attr_done = true;
  }
  Params P;
  P.in_x = (const __nv_bfloat16*)d_in[0];
  P.wqkv_p[0] = (const __nv_bfloat16*)d_in[1];
  P.wo_p[0] = (const __nv_bfloat16*)d_in[2];
  P.wqkv_p[1] = (const __nv_bfloat16*)d_in[4];
  P.wo_p[1] = (const __nv_bfloat16*)d_in[5];
  P.out = (__nv_bfloat16*)d_out;
  P.zero = 0;
  for (int L = 0; L < 5; L++) {
    const void* px = L == 0 ? (const void*)P.in_x : (L == 4 ? d_out : p_x);
    P.x[L] = make_map(px, S_LEN, DM);
    if (L < 4) P.xq[L] = (L & 1) ? make_map_q(px, 16, 8) : make_map_q(px, 8, 32);
  }
  P.o = make_map(p_o, S_LEN, DM);
  for (int t = 0; t < 2; t++) {
    P.wqkv[t] = make_map(P.wqkv_p[t], DM, NQKV);
    P.wqkv3[t] = make_map3(P.wqkv_p[t], DM, NQKV, 3, 1024);
    P.wo3[t] = make_map3(P.wo_p[t], DM, DM, 2, 64);
  }
    fused_kernel<<<NCTA, 512, SMEM_BYTES>>>(P);
}
```

```cpp
#include <cuda_runtime.h>
#include <cuda_bf16.h>
#include <cuda.h>
#include <stdint.h>

namespace {

constexpr int S_LEN = 2048;
constexpr int DM = 1024;
constexpr int NQKV = 3072;
constexpr int NCTA = 128;

__device__ __align__(1024) uint8_t g_kvA[16][16][2][16384];
__device__ __align__(1024) uint8_t g_kvB[16][16][4096];
__device__ __align__(1024) uint8_t g_zero[16384];
__device__ __align__(1024) __nv_bfloat16 g_o[S_LEN * DM];
__device__ __align__(1024) __nv_bfloat16 g_x[S_LEN * DM];
__device__ __align__(1024) float4 g_stats[8][S_LEN];
__device__ __align__(1024) float4 g_cs[2][16][8][64];
__device__ __align__(128) unsigned g_fx[16][16][4];
__device__ __align__(128) unsigned g_fo[32][16][4];
__device__ __align__(128) unsigned g_fk[16][16][4];
__device__ __align__(128) unsigned g_done[32];

constexpr uint32_t SBASE = 1024;
constexpr int UNIT = 8192;
constexpr int NUNITS = 20;
constexpr int OFF_SLOT = NUNITS * UNIT;
constexpr int OFF_BAR = OFF_SLOT + 4 * 16384;
constexpr int OFF_EPOCH = OFF_BAR + 424;
constexpr int OFF_LSB = OFF_BAR + 432;
constexpr int OFF_CS = OFF_BAR + 496;
constexpr int OFF_RS = OFF_CS + 1536;
constexpr int OFF_ONE = OFF_RS + 1024;
constexpr int SMEM_BYTES = OFF_ONE + 16;
constexpr int B_QF = 0, B_WF = 4, B_RF = 12, B_E = 13, B_PREP = 26, B_LOC = 28, B_HALO = 29, B_REL = 33, B_OS0 = 36,
              B_TURN = 37, B_XS = 39, B_CS = 41, B_CSD = 42, B_GO = 43, B_PRE = 44, B_HV = 45, B_OS1 = 46,
              B_RDONE = 47, B_PRE2 = 48, B_HL = 49, B_KV = 51;
static_assert(SMEM_BYTES <= 232448, "shared memory");

__device__ __forceinline__ uint32_t smem_u32(const void* p) { return (uint32_t)__cvta_generic_to_shared(p); }

__device__ __forceinline__ void mbar_init(uint32_t bar, uint32_t cnt) {
  asm volatile("mbarrier.init.shared::cta.b64 [%0], %1;" ::"r"(bar), "r"(cnt));
}
__device__ __forceinline__ void mbar_expect_tx(uint32_t bar, uint32_t bytes) {
  asm volatile("mbarrier.arrive.expect_tx.shared::cta.b64 _, [%0], %1;" ::"r"(bar), "r"(bytes) : "memory");
}
__device__ __forceinline__ void mbar_arrive(uint32_t bar) {
  asm volatile("mbarrier.arrive.shared::cta.b64 _, [%0];" ::"r"(bar) : "memory");
}
__device__ __forceinline__ bool mbar_try_wait(uint32_t bar, uint32_t parity) {
  uint32_t ok;
  asm volatile(
      "{\n.reg .pred p;\nmbarrier.try_wait.parity.shared::cta.b64 p, [%1], %2;\nselp.b32 %0, 1, 0, p;\n}\n"
      : "=r"(ok)
      : "r"(bar), "r"(parity)
      : "memory");
  return ok != 0;
}
__device__ __forceinline__ bool mbar_test(uint32_t bar, uint32_t parity) {
  uint32_t ok;
  asm volatile(
      "{\n.reg .pred p;\nmbarrier.test_wait.parity.shared::cta.b64 p, [%1], %2;\nselp.b32 %0, 1, 0, p;\n}\n"
      : "=r"(ok)
      : "r"(bar), "r"(parity)
      : "memory");
  return ok != 0;
}
__device__ __forceinline__ void mbar_wait(uint32_t bar, uint32_t parity) {
#pragma unroll 1
  for (uint32_t it = 0; it < (1u << 18); ++it) {
    if (mbar_try_wait(bar, parity)) return;
  }
}
__device__ __forceinline__ void mbar_pace(uint32_t bar, uint32_t parity, uint32_t n) {
#pragma unroll 1
  for (uint32_t it = 0; it < n; ++it) {
    if (mbar_test(bar, parity)) return;
    __nanosleep(100);
  }
}
template <int NS>
__device__ __forceinline__ void mbar_wait_lazy(uint32_t bar, uint32_t parity) {
#pragma unroll 1
  for (uint32_t it = 0; it < (1u << 18); ++it) {
    if (mbar_try_wait(bar, parity)) return;
    __nanosleep(NS);
  }
}
__device__ __forceinline__ bool elect_one() {
  uint32_t ok;
  asm volatile("{\n.reg .pred p;\nelect.sync _|p, 0xffffffff;\nselp.b32 %0, 1, 0, p;\n}\n" : "=r"(ok));
  return ok != 0;
}
__device__ __forceinline__ void fence_barrier_init() { asm volatile("fence.mbarrier_init.release.cluster;" ::: "memory"); }
__device__ __forceinline__ void fence_proxy_async_smem() { asm volatile("fence.proxy.async.shared::cta;" ::: "memory"); }

__device__ __forceinline__ void signal_async(uint32_t bar, bool lane0) {
  fence_proxy_async_smem();
  __syncwarp();
  asm volatile("{\n.reg .pred p;\nsetp.ne.b32 p, %1, 0;\n@p mbarrier.arrive.shared::cta.b64 _, [%0];\n}\n" ::"r"(bar), "r"((int)lane0) : "memory");
}
template <class T>
__device__ __forceinline__ void pin64(T*& p) { asm volatile("" : "+l"(p)); }

__device__ __forceinline__ void tma_load_2d(uint32_t dst, const CUtensorMap* map, uint32_t bar, int c0, int c1) {
  asm volatile(
      "cp.async.bulk.tensor.2d.shared::cluster.global.mbarrier::complete_tx::bytes [%0], [%1, {%3, %4}], [%2];" ::"r"(dst),
      "l"(map), "r"(bar), "r"(c0), "r"(c1)
      : "memory");
}
__device__ __forceinline__ void tma_load_3d(uint32_t dst, const CUtensorMap* map, uint32_t bar, int c0, int c1) {
  asm volatile(
      "cp.async.bulk.tensor.3d.shared::cluster.global.mbarrier::complete_tx::bytes [%0], [%1, {%3, %4, %5}], [%2];" ::"r"(dst),
      "l"(map), "r"(bar), "r"(c0), "r"(c1), "r"(0)
      : "memory");
}
__device__ __forceinline__ void tma_load_5d(uint32_t dst, const CUtensorMap* map, uint32_t bar, int c0, int c4) {
  asm volatile(
      "cp.async.bulk.tensor.5d.shared::cluster.global.mbarrier::complete_tx::bytes [%0], [%1, {%3, %5, %5, %5, %4}], [%2];" ::"r"(dst),
      "l"(map), "r"(bar), "r"(c0), "r"(c4), "r"(0)
      : "memory");
}
__device__ __forceinline__ void bulk_load(uint32_t dst, const void* src, uint32_t bytes, uint32_t bar) {
  asm volatile("cp.async.bulk.shared::cluster.global.mbarrier::complete_tx::bytes [%0], [%1], %2, [%3];" ::"r"(dst),
               "l"(src), "r"(bytes), "r"(bar)
               : "memory");
}
__device__ __forceinline__ void bulk_store(void* dst, uint32_t src, uint32_t bytes) {
  asm volatile("cp.async.bulk.global.shared::cta.bulk_group [%0], [%1], %2;" ::"l"(dst), "r"(src), "r"(bytes) : "memory");
}
__device__ __forceinline__ void tma_store_2d(const CUtensorMap* map, uint32_t src, int c0, int c1) {
  asm volatile("cp.async.bulk.tensor.2d.global.shared::cta.bulk_group [%0, {%2, %3}], [%1];" ::"l"(map), "r"(src),
               "r"(c0), "r"(c1)
               : "memory");
}
__device__ __forceinline__ void bulk_announce(unsigned* p) {
  asm volatile("cp.reduce.async.bulk.global.shared::cta.bulk_group.add.u32 [%0], [%1], 16;" ::"l"(p), "r"(SBASE + OFF_ONE) : "memory");
}
__device__ __forceinline__ void bulk_commit() { asm volatile("cp.async.bulk.commit_group;" ::: "memory"); }
__device__ __forceinline__ void bulk_wait_read0() { asm volatile("cp.async.bulk.wait_group.read 0;" ::: "memory"); }
__device__ __forceinline__ void bulk_wait0() { asm volatile("cp.async.bulk.wait_group 0;" ::: "memory"); }
__device__ __forceinline__ void named_bar_sync(int id, int nthreads) {
  asm volatile("bar.sync %0, %1;" ::"r"(id), "r"(nthreads) : "memory");
}
__device__ __forceinline__ void named_bar_arrive(int id, int nthreads) {
  asm volatile("bar.arrive %0, %1;" ::"r"(id), "r"(nthreads) : "memory");
}

__device__ __forceinline__ void wgmma_fence() { asm volatile("wgmma.fence.sync.aligned;\n" ::: "memory"); }
__device__ __forceinline__ void wgmma_commit() { asm volatile("wgmma.commit_group.sync.aligned;\n" ::: "memory"); }
template <int N>
__device__ __forceinline__ void wgmma_wait() {
  asm volatile("wgmma.wait_group.sync.aligned %0;\n" ::"n"(N) : "memory");
}
template <int R>
__device__ __forceinline__ void setmaxnreg_inc() { asm volatile("setmaxnreg.inc.sync.aligned.u32 %0;\n" ::"n"(R)); }
template <int R>
__device__ __forceinline__ void setmaxnreg_dec() { asm volatile("setmaxnreg.dec.sync.aligned.u32 %0;\n" ::"n"(R)); }
template <int N>
__device__ __forceinline__ void reg_fence(float* r) {
#pragma unroll
  for (int i = 0; i < N; i++) asm volatile("" : "+f"(r[i])::"memory");
}

template <int N>
__device__ __forceinline__ void reg_define(float* r) {
#pragma unroll
  for (int i = 0; i < N; i++) r[i] = 0.f;
}

__device__ __forceinline__ uint64_t desc_lo(uint32_t lo) {
  uint64_t d;
  asm("mov.b64 %0, {%1, %2};" : "=l"(d) : "r"(lo), "r"(0x40000040u));
  return d;
}
__device__ __forceinline__ uint64_t make_desc(uint32_t addr, uint32_t lbo_bytes) {
  return desc_lo((addr >> 4) + ((lbo_bytes >> 4) << 16));
}

__device__ __forceinline__ void wgmma_n192_ss_ta0_tb1(float* d, uint64_t descA, uint64_t descB, int scaleD) {
  asm volatile("{\n.reg .pred p;\nsetp.ne.b32 p, %98, 0;\n"
    "wgmma.mma_async.sync.aligned.m64n192k16.f32.bf16.bf16 {%0, %1, %2, %3, %4, %5, %6, %7, %8, %9, %10, %11, %12, %13, %14, %15, %16, %17, %18, %19, %20, %21, %22, %23, %24, %25, %26, %27, %28, %29, %30, %31, %32, %33, %34, %35, %36, %37, %38, %39, %40, %41, %42, %43, %44, %45, %46, %47, %48, %49, %50, %51, %52, %53, %54, %55, %56, %57, %58, %59, %60, %61, %62, %63, %64, %65, %66, %67, %68, %69, %70, %71, %72, %73, %74, %75, %76, %77, %78, %79, %80, %81, %82, %83, %84, %85, %86, %87, %88, %89, %90, %91, %92, %93, %94, %95}, %96, %97, p, 1, 1, 0, 1;\n}\n"
    : "+f"(d[0]), "+f"(d[1]), "+f"(d[2]), "+f"(d[3]), "+f"(d[4]), "+f"(d[5]), "+f"(d[6]), "+f"(d[7]), "+f"(d[8]), "+f"(d[9]), "+f"(d[10]), "+f"(d[11]), "+f"(d[12]), "+f"(d[13]), "+f"(d[14]), "+f"(d[15]), "+f"(d[16]), "+f"(d[17]), "+f"(d[18]), "+f"(d[19]), "+f"(d[20]), "+f"(d[21]), "+f"(d[22]), "+f"(d[23]), "+f"(d[24]), "+f"(d[25]), "+f"(d[26]), "+f"(d[27]), "+f"(d[28]), "+f"(d[29]), "+f"(d[30]), "+f"(d[31]), "+f"(d[32]), "+f"(d[33]), "+f"(d[34]), "+f"(d[35]), "+f"(d[36]), "+f"(d[37]), "+f"(d[38]), "+f"(d[39]), "+f"(d[40]), "+f"(d[41]), "+f"(d[42]), "+f"(d[43]), "+f"(d[44]), "+f"(d[45]), "+f"(d[46]), "+f"(d[47]), "+f"(d[48]), "+f"(d[49]), "+f"(d[50]), "+f"(d[51]), "+f"(d[52]), "+f"(d[53]), "+f"(d[54]), "+f"(d[55]), "+f"(d[56]), "+f"(d[57]), "+f"(d[58]), "+f"(d[59]), "+f"(d[60]), "+f"(d[61]), "+f"(d[62]), "+f"(d[63]), "+f"(d[64]), "+f"(d[65]), "+f"(d[66]), "+f"(d[67]), "+f"(d[68]), "+f"(d[69]), "+f"(d[70]), "+f"(d[71]), "+f"(d[72]), "+f"(d[73]), "+f"(d[74]), "+f"(d[75]), "+f"(d[76]), "+f"(d[77]), "+f"(d[78]), "+f"(d[79]), "+f"(d[80]), "+f"(d[81]), "+f"(d[82]), "+f"(d[83]), "+f"(d[84]), "+f"(d[85]), "+f"(d[86]), "+f"(d[87]), "+f"(d[88]), "+f"(d[89]), "+f"(d[90]), "+f"(d[91]), "+f"(d[92]), "+f"(d[93]), "+f"(d[94]), "+f"(d[95])
    : "l"(descA), "l"(descB), "r"(scaleD));
}

__device__ __forceinline__ void wgmma_n128_ss_ta0_tb1(float* d, uint64_t descA, uint64_t descB, int scaleD) {
  asm volatile("{\n.reg .pred p;\nsetp.ne.b32 p, %66, 0;\n"
    "wgmma.mma_async.sync.aligned.m64n128k16.f32.bf16.bf16 {%0, %1, %2, %3, %4, %5, %6, %7, %8, %9, %10, %11, %12, %13, %14, %15, %16, %17, %18, %19, %20, %21, %22, %23, %24, %25, %26, %27, %28, %29, %30, %31, %32, %33, %34, %35, %36, %37, %38, %39, %40, %41, %42, %43, %44, %45, %46, %47, %48, %49, %50, %51, %52, %53, %54, %55, %56, %57, %58, %59, %60, %61, %62, %63}, %64, %65, p, 1, 1, 0, 1;\n}\n"
    : "+f"(d[0]), "+f"(d[1]), "+f"(d[2]), "+f"(d[3]), "+f"(d[4]), "+f"(d[5]), "+f"(d[6]), "+f"(d[7]), "+f"(d[8]), "+f"(d[9]), "+f"(d[10]), "+f"(d[11]), "+f"(d[12]), "+f"(d[13]), "+f"(d[14]), "+f"(d[15]), "+f"(d[16]), "+f"(d[17]), "+f"(d[18]), "+f"(d[19]), "+f"(d[20]), "+f"(d[21]), "+f"(d[22]), "+f"(d[23]), "+f"(d[24]), "+f"(d[25]), "+f"(d[26]), "+f"(d[27]), "+f"(d[28]), "+f"(d[29]), "+f"(d[30]), "+f"(d[31]), "+f"(d[32]), "+f"(d[33]), "+f"(d[34]), "+f"(d[35]), "+f"(d[36]), "+f"(d[37]), "+f"(d[38]), "+f"(d[39]), "+f"(d[40]), "+f"(d[41]), "+f"(d[42]), "+f"(d[43]), "+f"(d[44]), "+f"(d[45]), "+f"(d[46]), "+f"(d[47]), "+f"(d[48]), "+f"(d[49]), "+f"(d[50]), "+f"(d[51]), "+f"(d[52]), "+f"(d[53]), "+f"(d[54]), "+f"(d[55]), "+f"(d[56]), "+f"(d[57]), "+f"(d[58]), "+f"(d[59]), "+f"(d[60]), "+f"(d[61]), "+f"(d[62]), "+f"(d[63])
    : "l"(descA), "l"(descB), "r"(scaleD));
}

__device__ __forceinline__ void wgmma_n192_ssz_ta0_tb1(float* d, uint64_t descA, uint64_t descB) {
  asm volatile("{\n.reg .pred p;\nsetp.ne.b32 p, 0, 0;\n"
    "wgmma.mma_async.sync.aligned.m64n192k16.f32.bf16.bf16 {%0, %1, %2, %3, %4, %5, %6, %7, %8, %9, %10, %11, %12, %13, %14, %15, %16, %17, %18, %19, %20, %21, %22, %23, %24, %25, %26, %27, %28, %29, %30, %31, %32, %33, %34, %35, %36, %37, %38, %39, %40, %41, %42, %43, %44, %45, %46, %47, %48, %49, %50, %51, %52, %53, %54, %55, %56, %57, %58, %59, %60, %61, %62, %63, %64, %65, %66, %67, %68, %69, %70, %71, %72, %73, %74, %75, %76, %77, %78, %79, %80, %81, %82, %83, %84, %85, %86, %87, %88, %89, %90, %91, %92, %93, %94, %95}, %96, %97, p, 1, 1, 0, 1;\n}\n"
    : "=f"(d[0]), "=f"(d[1]), "=f"(d[2]), "=f"(d[3]), "=f"(d[4]), "=f"(d[5]), "=f"(d[6]), "=f"(d[7]), "=f"(d[8]), "=f"(d[9]), "=f"(d[10]), "=f"(d[11]), "=f"(d[12]), "=f"(d[13]), "=f"(d[14]), "=f"(d[15]), "=f"(d[16]), "=f"(d[17]), "=f"(d[18]), "=f"(d[19]), "=f"(d[20]), "=f"(d[21]), "=f"(d[22]), "=f"(d[23]), "=f"(d[24]), "=f"(d[25]), "=f"(d[26]), "=f"(d[27]), "=f"(d[28]), "=f"(d[29]), "=f"(d[30]), "=f"(d[31]), "=f"(d[32]), "=f"(d[33]), "=f"(d[34]), "=f"(d[35]), "=f"(d[36]), "=f"(d[37]), "=f"(d[38]), "=f"(d[39]), "=f"(d[40]), "=f"(d[41]), "=f"(d[42]), "=f"(d[43]), "=f"(d[44]), "=f"(d[45]), "=f"(d[46]), "=f"(d[47]), "=f"(d[48]), "=f"(d[49]), "=f"(d[50]), "=f"(d[51]), "=f"(d[52]), "=f"(d[53]), "=f"(d[54]), "=f"(d[55]), "=f"(d[56]), "=f"(d[57]), "=f"(d[58]), "=f"(d[59]), "=f"(d[60]), "=f"(d[61]), "=f"(d[62]), "=f"(d[63]), "=f"(d[64]), "=f"(d[65]), "=f"(d[66]), "=f"(d[67]), "=f"(d[68]), "=f"(d[69]), "=f"(d[70]), "=f"(d[71]), "=f"(d[72]), "=f"(d[73]), "=f"(d[74]), "=f"(d[75]), "=f"(d[76]), "=f"(d[77]), "=f"(d[78]), "=f"(d[79]), "=f"(d[80]), "=f"(d[81]), "=f"(d[82]), "=f"(d[83]), "=f"(d[84]), "=f"(d[85]), "=f"(d[86]), "=f"(d[87]), "=f"(d[88]), "=f"(d[89]), "=f"(d[90]), "=f"(d[91]), "=f"(d[92]), "=f"(d[93]), "=f"(d[94]), "=f"(d[95])
    : "l"(descA), "l"(descB));
}

__device__ __forceinline__ void wgmma_n8_ss_ta1_tb0(float* d, uint64_t descA, uint64_t descB, int scaleD) {
  asm volatile("{\n.reg .pred p;\nsetp.ne.b32 p, %6, 0;\n"
    "wgmma.mma_async.sync.aligned.m64n8k16.f32.bf16.bf16 {%0, %1, %2, %3}, %4, %5, p, 1, 1, 1, 0;\n}\n"
    : "+f"(d[0]), "+f"(d[1]), "+f"(d[2]), "+f"(d[3])
    : "l"(descA), "l"(descB), "r"(scaleD));
}

__device__ __forceinline__ void wgmma_n8_ssz_ta1_tb0(float* d, uint64_t descA, uint64_t descB) {
  asm volatile("{\n.reg .pred p;\nsetp.ne.b32 p, 0, 0;\n"
    "wgmma.mma_async.sync.aligned.m64n8k16.f32.bf16.bf16 {%0, %1, %2, %3}, %4, %5, p, 1, 1, 1, 0;\n}\n"
    : "=f"(d[0]), "=f"(d[1]), "=f"(d[2]), "=f"(d[3])
    : "l"(descA), "l"(descB));
}

__device__ __forceinline__ void wgmma_n192_rs_tb1(float* d, const uint32_t* a, uint64_t descB, int scaleD) {
  asm volatile("{\n.reg .pred p;\nsetp.ne.b32 p, %101, 0;\n"
    "wgmma.mma_async.sync.aligned.m64n192k16.f32.bf16.bf16 {%0, %1, %2, %3, %4, %5, %6, %7, %8, %9, %10, %11, %12, %13, %14, %15, %16, %17, %18, %19, %20, %21, %22, %23, %24, %25, %26, %27, %28, %29, %30, %31, %32, %33, %34, %35, %36, %37, %38, %39, %40, %41, %42, %43, %44, %45, %46, %47, %48, %49, %50, %51, %52, %53, %54, %55, %56, %57, %58, %59, %60, %61, %62, %63, %64, %65, %66, %67, %68, %69, %70, %71, %72, %73, %74, %75, %76, %77, %78, %79, %80, %81, %82, %83, %84, %85, %86, %87, %88, %89, %90, %91, %92, %93, %94, %95}, {%96, %97, %98, %99}, %100, p, 1, 1, 1;\n}\n"
    : "+f"(d[0]), "+f"(d[1]), "+f"(d[2]), "+f"(d[3]), "+f"(d[4]), "+f"(d[5]), "+f"(d[6]), "+f"(d[7]), "+f"(d[8]), "+f"(d[9]), "+f"(d[10]), "+f"(d[11]), "+f"(d[12]), "+f"(d[13]), "+f"(d[14]), "+f"(d[15]), "+f"(d[16]), "+f"(d[17]), "+f"(d[18]), "+f"(d[19]), "+f"(d[20]), "+f"(d[21]), "+f"(d[22]), "+f"(d[23]), "+f"(d[24]), "+f"(d[25]), "+f"(d[26]), "+f"(d[27]), "+f"(d[28]), "+f"(d[29]), "+f"(d[30]), "+f"(d[31]), "+f"(d[32]), "+f"(d[33]), "+f"(d[34]), "+f"(d[35]), "+f"(d[36]), "+f"(d[37]), "+f"(d[38]), "+f"(d[39]), "+f"(d[40]), "+f"(d[41]), "+f"(d[42]), "+f"(d[43]), "+f"(d[44]), "+f"(d[45]), "+f"(d[46]), "+f"(d[47]), "+f"(d[48]), "+f"(d[49]), "+f"(d[50]), "+f"(d[51]), "+f"(d[52]), "+f"(d[53]), "+f"(d[54]), "+f"(d[55]), "+f"(d[56]), "+f"(d[57]), "+f"(d[58]), "+f"(d[59]), "+f"(d[60]), "+f"(d[61]), "+f"(d[62]), "+f"(d[63]), "+f"(d[64]), "+f"(d[65]), "+f"(d[66]), "+f"(d[67]), "+f"(d[68]), "+f"(d[69]), "+f"(d[70]), "+f"(d[71]), "+f"(d[72]), "+f"(d[73]), "+f"(d[74]), "+f"(d[75]), "+f"(d[76]), "+f"(d[77]), "+f"(d[78]), "+f"(d[79]), "+f"(d[80]), "+f"(d[81]), "+f"(d[82]), "+f"(d[83]), "+f"(d[84]), "+f"(d[85]), "+f"(d[86]), "+f"(d[87]), "+f"(d[88]), "+f"(d[89]), "+f"(d[90]), "+f"(d[91]), "+f"(d[92]), "+f"(d[93]), "+f"(d[94]), "+f"(d[95])
    : "r"(a[0]), "r"(a[1]), "r"(a[2]), "r"(a[3]), "l"(descB), "r"(scaleD));
}

__device__ __forceinline__ void wgmma_n80_rs_tb0(float* d, const uint32_t* a, uint64_t descB, int scaleD) {
  asm volatile("{\n.reg .pred p;\nsetp.ne.b32 p, %45, 0;\n"
    "wgmma.mma_async.sync.aligned.m64n80k16.f32.bf16.bf16 {%0, %1, %2, %3, %4, %5, %6, %7, %8, %9, %10, %11, %12, %13, %14, %15, %16, %17, %18, %19, %20, %21, %22, %23, %24, %25, %26, %27, %28, %29, %30, %31, %32, %33, %34, %35, %36, %37, %38, %39}, {%40, %41, %42, %43}, %44, p, 1, 1, 0;\n}\n"
    : "+f"(d[0]), "+f"(d[1]), "+f"(d[2]), "+f"(d[3]), "+f"(d[4]), "+f"(d[5]), "+f"(d[6]), "+f"(d[7]), "+f"(d[8]), "+f"(d[9]), "+f"(d[10]), "+f"(d[11]), "+f"(d[12]), "+f"(d[13]), "+f"(d[14]), "+f"(d[15]), "+f"(d[16]), "+f"(d[17]), "+f"(d[18]), "+f"(d[19]), "+f"(d[20]), "+f"(d[21]), "+f"(d[22]), "+f"(d[23]), "+f"(d[24]), "+f"(d[25]), "+f"(d[26]), "+f"(d[27]), "+f"(d[28]), "+f"(d[29]), "+f"(d[30]), "+f"(d[31]), "+f"(d[32]), "+f"(d[33]), "+f"(d[34]), "+f"(d[35]), "+f"(d[36]), "+f"(d[37]), "+f"(d[38]), "+f"(d[39])
    : "r"(a[0]), "r"(a[1]), "r"(a[2]), "r"(a[3]), "l"(descB), "r"(scaleD));
}

__device__ __forceinline__ void wgmma_n80_rsz_tb0(float* d, const uint32_t* a, uint64_t descB) {
  asm volatile("{\n.reg .pred p;\nsetp.ne.b32 p, 0, 0;\n"
    "wgmma.mma_async.sync.aligned.m64n80k16.f32.bf16.bf16 {%0, %1, %2, %3, %4, %5, %6, %7, %8, %9, %10, %11, %12, %13, %14, %15, %16, %17, %18, %19, %20, %21, %22, %23, %24, %25, %26, %27, %28, %29, %30, %31, %32, %33, %34, %35, %36, %37, %38, %39}, {%40, %41, %42, %43}, %44, p, 1, 1, 0;\n}\n"
    : "=f"(d[0]), "=f"(d[1]), "=f"(d[2]), "=f"(d[3]), "=f"(d[4]), "=f"(d[5]), "=f"(d[6]), "=f"(d[7]), "=f"(d[8]), "=f"(d[9]), "=f"(d[10]), "=f"(d[11]), "=f"(d[12]), "=f"(d[13]), "=f"(d[14]), "=f"(d[15]), "=f"(d[16]), "=f"(d[17]), "=f"(d[18]), "=f"(d[19]), "=f"(d[20]), "=f"(d[21]), "=f"(d[22]), "=f"(d[23]), "=f"(d[24]), "=f"(d[25]), "=f"(d[26]), "=f"(d[27]), "=f"(d[28]), "=f"(d[29]), "=f"(d[30]), "=f"(d[31]), "=f"(d[32]), "=f"(d[33]), "=f"(d[34]), "=f"(d[35]), "=f"(d[36]), "=f"(d[37]), "=f"(d[38]), "=f"(d[39])
    : "r"(a[0]), "r"(a[1]), "r"(a[2]), "r"(a[3]), "l"(descB));
}

__device__ __forceinline__ void wgmma_n32_rs_tb1(float* d, const uint32_t* a, uint64_t descB, int scaleD) {
  asm volatile("{\n.reg .pred p;\nsetp.ne.b32 p, %21, 0;\n"
    "wgmma.mma_async.sync.aligned.m64n32k16.f32.bf16.bf16 {%0, %1, %2, %3, %4, %5, %6, %7, %8, %9, %10, %11, %12, %13, %14, %15}, {%16, %17, %18, %19}, %20, p, 1, 1, 1;\n}\n"
    : "+f"(d[0]), "+f"(d[1]), "+f"(d[2]), "+f"(d[3]), "+f"(d[4]), "+f"(d[5]), "+f"(d[6]), "+f"(d[7]), "+f"(d[8]), "+f"(d[9]), "+f"(d[10]), "+f"(d[11]), "+f"(d[12]), "+f"(d[13]), "+f"(d[14]), "+f"(d[15])
    : "r"(a[0]), "r"(a[1]), "r"(a[2]), "r"(a[3]), "l"(descB), "r"(scaleD));
}

__device__ __forceinline__ void wgmma_n32_rsz_tb1(float* d, const uint32_t* a, uint64_t descB) {
  asm volatile("{\n.reg .pred p;\nsetp.ne.b32 p, 0, 0;\n"
    "wgmma.mma_async.sync.aligned.m64n32k16.f32.bf16.bf16 {%0, %1, %2, %3, %4, %5, %6, %7, %8, %9, %10, %11, %12, %13, %14, %15}, {%16, %17, %18, %19}, %20, p, 1, 1, 1;\n}\n"
    : "=f"(d[0]), "=f"(d[1]), "=f"(d[2]), "=f"(d[3]), "=f"(d[4]), "=f"(d[5]), "=f"(d[6]), "=f"(d[7]), "=f"(d[8]), "=f"(d[9]), "=f"(d[10]), "=f"(d[11]), "=f"(d[12]), "=f"(d[13]), "=f"(d[14]), "=f"(d[15])
    : "r"(a[0]), "r"(a[1]), "r"(a[2]), "r"(a[3]), "l"(descB));
}

__device__ __forceinline__ void wgmma_n32_rs_tb0(float* d, const uint32_t* a, uint64_t descB, int scaleD) {
  asm volatile("{\n.reg .pred p;\nsetp.ne.b32 p, %21, 0;\n"
    "wgmma.mma_async.sync.aligned.m64n32k16.f32.bf16.bf16 {%0, %1, %2, %3, %4, %5, %6, %7, %8, %9, %10, %11, %12, %13, %14, %15}, {%16, %17, %18, %19}, %20, p, 1, 1, 0;\n}\n"
    : "+f"(d[0]), "+f"(d[1]), "+f"(d[2]), "+f"(d[3]), "+f"(d[4]), "+f"(d[5]), "+f"(d[6]), "+f"(d[7]), "+f"(d[8]), "+f"(d[9]), "+f"(d[10]), "+f"(d[11]), "+f"(d[12]), "+f"(d[13]), "+f"(d[14]), "+f"(d[15])
    : "r"(a[0]), "r"(a[1]), "r"(a[2]), "r"(a[3]), "l"(descB), "r"(scaleD));
}

__device__ __forceinline__ void wgmma_n32_rsz_tb0(float* d, const uint32_t* a, uint64_t descB) {
  asm volatile("{\n.reg .pred p;\nsetp.ne.b32 p, 0, 0;\n"
    "wgmma.mma_async.sync.aligned.m64n32k16.f32.bf16.bf16 {%0, %1, %2, %3, %4, %5, %6, %7, %8, %9, %10, %11, %12, %13, %14, %15}, {%16, %17, %18, %19}, %20, p, 1, 1, 0;\n}\n"
    : "=f"(d[0]), "=f"(d[1]), "=f"(d[2]), "=f"(d[3]), "=f"(d[4]), "=f"(d[5]), "=f"(d[6]), "=f"(d[7]), "=f"(d[8]), "=f"(d[9]), "=f"(d[10]), "=f"(d[11]), "=f"(d[12]), "=f"(d[13]), "=f"(d[14]), "=f"(d[15])
    : "r"(a[0]), "r"(a[1]), "r"(a[2]), "r"(a[3]), "l"(descB));
}

__device__ __forceinline__ uint32_t pack_bf16x2(float lo, float hi) {
  uint32_t r;
  asm("cvt.rn.bf16x2.f32 %0, %1, %2;" : "=r"(r) : "f"(hi), "f"(lo));
  return r;
}
__device__ __forceinline__ float bf_lo(uint32_t p) { return __uint_as_float(p << 16); }
__device__ __forceinline__ float bf_hi(uint32_t p) { return __uint_as_float(p & 0xffff0000u); }
__device__ __forceinline__ float bf16_round(float v) { return __bfloat162float(__float2bfloat16_rn(v)); }
__device__ __forceinline__ float ex2_approx(float x) {
  float r;
  asm("ex2.approx.ftz.f32 %0, %1;" : "=f"(r) : "f"(x));
  return r;
}
__device__ __forceinline__ float rcp_fast(float x) {
  float r;
  asm("rcp.approx.ftz.f32 %0, %1;" : "=f"(r) : "f"(x));
  return r;
}
__device__ __forceinline__ void ldmatrix_x4(uint32_t (&r)[4], uint32_t addr) {
  asm volatile("ldmatrix.sync.aligned.m8n8.x4.shared.b16 {%0,%1,%2,%3}, [%4];"
               : "=r"(r[0]), "=r"(r[1]), "=r"(r[2]), "=r"(r[3])
               : "r"(addr)
               : "memory");
}
__device__ __forceinline__ void stmatrix_x4(uint32_t addr, uint32_t r0, uint32_t r1, uint32_t r2, uint32_t r3) {
  asm volatile("stmatrix.sync.aligned.m8n8.x4.shared.b16 [%0], {%1,%2,%3,%4};" ::"r"(addr), "r"(r0), "r"(r1), "r"(r2),
               "r"(r3));
}
__device__ __forceinline__ uint32_t add_bf16x2(uint32_t a, uint32_t b) {
  uint32_t r;
  asm("add.rn.bf16x2 %0, %1, %2;" : "=r"(r) : "r"(a), "r"(b));
  return r;
}
__device__ __forceinline__ uint4 lds128(uint32_t addr) {
  uint4 v;
  asm volatile("ld.shared.v4.b32 {%0,%1,%2,%3}, [%4];" : "=r"(v.x), "=r"(v.y), "=r"(v.z), "=r"(v.w) : "r"(addr) : "memory");
  return v;
}
__device__ __forceinline__ uint32_t lds32(uint32_t addr) {
  uint32_t v;
  asm volatile("ld.shared.b32 %0, [%1];" : "=r"(v) : "r"(addr) : "memory");
  return v;
}
__device__ __forceinline__ void sts32(uint32_t addr, uint32_t v) {
  asm volatile("st.shared.b32 [%0], %1;" ::"r"(addr), "r"(v) : "memory");
}

__device__ __forceinline__ int fresh_tid() {
  int t;
  asm volatile("mov.u32 %0, %%tid.x;" : "=r"(t));
  return t;
}
__device__ __forceinline__ unsigned ld_relaxed_u32(const void* p) {
  unsigned v;
  asm volatile("ld.relaxed.gpu.global.u32 %0, [%1];" : "=r"(v) : "l"(p) : "memory");
  return v;
}
__device__ __forceinline__ unsigned launch_epoch() { return (*(volatile unsigned*)g_done) / NCTA + 1u; }
__device__ __forceinline__ uint32_t set_tag(uint32_t w, uint32_t m, uint32_t tag) { return (w & ~m) | (tag & m); }
__device__ __forceinline__ uint32_t o_tag(int L) { return (L + 1) & 1; }
__device__ __forceinline__ uint32_t x_tag(int L) { return L & 1; }
__device__ __forceinline__ uint32_t kv_tag(int L) { return L < 2; }

template <class F>
__device__ __forceinline__ void fix_lines(uint32_t bar, uint32_t par, uint32_t ta, uint32_t tag, uint32_t mask, int bar_id, F line) {
  mbar_wait(bar, par);
  uint32_t m = __ballot_sync(0xffffffffu, (lds32(ta) ^ tag) & mask);
  if (m == 0u) return;
#pragma unroll 1
  for (uint32_t it = 0; it < (1u << 17) && m != 0u; ++it) {
    const int l = __ffs(m) - 1, j = fresh_tid() & 7;
    uint4 v;
    asm volatile("ld.relaxed.gpu.global.v4.b32 {%0,%1,%2,%3}, [%4];" : "=r"(v.x), "=r"(v.y), "=r"(v.z), "=r"(v.w) : "l"(line(l) + j * 8) : "memory");
    const uint32_t a = __shfl_sync(0xffffffffu, ta, l) ^ (j << 4);
    if (((__shfl_sync(0xffffffffu, v.x, 0) ^ tag) & 1u) == 0u) {
      asm volatile("st.shared.v4.b32 [%0], {%1,%2,%3,%4};" ::"r"(a), "r"(v.x), "r"(v.y), "r"(v.z), "r"(v.w) : "memory");
      m &= m - 1u;
    }
  }
  fence_proxy_async_smem();
  named_bar_sync(bar_id, 32);
}
__device__ __forceinline__ uint32_t peek_counts(const unsigned* f, unsigned target, int lane) {
  return __ballot_sync(0xffffffffu, (int)(ld_relaxed_u32(f + (lane & 15) * 4) - target) >= 0);
}
__device__ __forceinline__ void wait_count(const unsigned* f, unsigned target, int i, uint32_t& seen, int lane) {
  if ((seen >> i) & 1u) return;
#pragma unroll 1
  for (uint32_t it = 0; it < (1u << 17); ++it) {
    seen = peek_counts(f, target, lane);
    if ((seen >> i) & 1u) break;
  }
}
__device__ __forceinline__ float4 ld_rec(const float4* p) {
  float4 v;
  asm volatile("ld.relaxed.gpu.global.v4.f32 {%0,%1,%2,%3}, [%4];" : "=f"(v.x), "=f"(v.y), "=f"(v.z), "=f"(v.w) : "l"(p) : "memory");
  return v;
}
__device__ __forceinline__ void st_rec(float4* p, float a, float b, float c, unsigned tag) {
  asm volatile("st.relaxed.gpu.global.v4.f32 [%0], {%1,%2,%3,%4};" ::"l"(p), "f"(a), "f"(b), "f"(c), "f"(__uint_as_float(tag)) : "memory");
}
template <int N>
__device__ __forceinline__ float4 sum_recs(const float4* p, int stride, unsigned tag) {
  float4 s;
#pragma unroll 1
  for (uint32_t it = 0; it < (1u << 17); ++it) {
    float4 v[N];
#pragma unroll
    for (int t = 0; t < N; t++) v[t] = ld_rec(p + t * stride);
    bool ok = true;
    s = make_float4(0.f, 0.f, 0.f, 0.f);
#pragma unroll
    for (int t = 0; t < N; t++) {
      ok &= __float_as_uint(v[t].w) == tag;
      s.x += v[t].x;
      s.y += v[t].y;
      s.z += v[t].z;
    }
    if (ok) break;
    __nanosleep(200);
  }
  return s;
}

#define PHASE_IDS                                  \
  const int tid_ = fresh_tid();                    \
  const int lane = tid_ & 31, wwarp = __shfl_sync(0xffffffffu, (tid_ >> 5) & 3, 0), tid = tid_ & 127; \
  const int g = lane >> 2, c = lane & 3;           \
  (void)tid; (void)g; (void)c; (void)wwarp;

#define PHASE_IDS_W                                \
  const int lane = fresh_tid() & 31, wwarp = warp & 3; \
  const int g = lane >> 2, c = lane & 3;

#define GTL(i) do { } while (0)
#define TGET(v) do { } while (0)
#define TPUT(c, i, v) do { } while (0)

constexpr float SM_C = 0.17677669529663687f * 1.4426950408889634f;

__device__ __forceinline__ void stmatrix_x4_if(bool ok, uint32_t addr, uint32_t r0, uint32_t r1, uint32_t r2, uint32_t r3) {
  asm volatile("{\n.reg .pred p;\nsetp.ne.b32 p, %5, 0;\n@p stmatrix.sync.aligned.m8n8.x4.shared.b16 [%0], {%1,%2,%3,%4};\n}\n" ::"r"(addr),
               "r"(r0), "r"(r1), "r"(r2), "r"(r3), "r"((int)ok));
}

__device__ __forceinline__ void attn_a_slow(const uint8_t* __restrict__ kvimg, int L, int gb, int hp, uint32_t bad,
                                            int row0, int lane) {
  constexpr uint32_t sq = SBASE + OFF_SLOT + 3 * 16384;
#pragma unroll 1
  for (int j = 0; j < 8; j++) {
    const uint8_t* tp = kvimg + (size_t)(gb * 16 + hp) * 32768 + (j * 32 + lane) * 128 + ((lane & 7) << 4);
#pragma unroll 1
    for (uint32_t it = 0; it < (1u << 17); ++it)
      if (((ld_relaxed_u32(tp) ^ kv_tag(L)) & 1u) == 0u) break;
  }
  __syncwarp();
#pragma unroll 1
  for (int t = 0; t < 32; t++) {
    const int hh = t >> 4, row = row0 + (t & 7) + (t & 8) * 4;
    if (!((bad >> hh) & 1u)) continue;
    const int qpos = gb * 128 + row;
    const uint32_t qaddr = sq + row * 128;
    float mx = -INFINITY, sum = 0.f, acc = 0.f;
#pragma unroll 1
    for (int pass = 0; pass < 2; pass++) {
#pragma unroll 1
      for (int j = 0; j < 8; j++) {
        const int kp = qpos - (lane + 32 * j);
        const uint8_t* kr = kvimg + ((size_t)((kp >> 7) * 16 + hp) * 2 + ((kp >> 6) & 1)) * 16384 + (kp & 63) * 128;
        float d = -INFINITY;
        if (kp >= 0) {
          d = 0.f;
#pragma unroll 1
          for (int q = 0; q < 4; q++) {
            const uint4 kv = __ldcg(reinterpret_cast<const uint4*>(kr + (((hh * 4 + q) ^ (kp & 7)) << 4)));
            const uint4 qv = lds128(qaddr + (((hh * 4 + q) ^ (row & 7)) << 4));
            const uint32_t kw[4] = {kv.x, kv.y, kv.z, kv.w}, qw[4] = {qv.x, qv.y, qv.z, qv.w};
#pragma unroll
            for (int e = 0; e < 4; e++) d = fmaf(bf_lo(kw[e]), bf_lo(qw[e]), fmaf(bf_hi(kw[e]), bf_hi(qw[e]), d));
          }
        }
        if (pass == 0) {
          mx = fmaxf(mx, d);
        } else {
          const float ev = ex2_approx(d - mx);
          sum += ev;
          const float pv = bf16_round(ev);
#pragma unroll 1
          for (int kk = 0; kk < 32; kk++) {
            const float pk = __shfl_sync(0xffffffffu, pv, kk);
            const int k2 = qpos - (kk + 32 * j);
            if (k2 >= 0) {
              const uint8_t* vr = kvimg + ((size_t)((k2 >> 7) * 16 + hp) * 2 + ((k2 >> 6) & 1)) * 16384 + 8192 + (k2 & 63) * 128;
              const unsigned short vv =
                  __ldcg(reinterpret_cast<const unsigned short*>(vr + (((hh * 4 + (lane >> 3)) ^ (k2 & 7)) << 4) + (lane & 7) * 2));
              acc = fmaf(pk, __uint_as_float((uint32_t)vv << 16), acc);
            }
          }
        }
      }
      if (pass == 0) {
#pragma unroll
        for (int o = 16; o > 0; o >>= 1) mx = fmaxf(mx, __shfl_xor_sync(0xffffffffu, mx, o));
      }
    }
#pragma unroll
    for (int o = 16; o > 0; o >>= 1) sum += __shfl_xor_sync(0xffffffffu, sum, o);
    acc *= rcp_fast(sum);
    const float hi = __shfl_down_sync(0xffffffffu, acc, 1);
    __syncwarp();
    if ((lane & 1) == 0) sts32(qaddr + (((hh * 4 + (lane >> 3)) ^ (row & 7)) << 4) + (lane & 7) * 2,
                               set_tag(pack_bf16x2(acc, hi), hh == 0 && lane == 0, o_tag(L)));
    __syncwarp();
  }
}

template <int HH>
__device__ __forceinline__ void store_o(const float (&o)[16], const float (&inv)[2], uint32_t ra, uint32_t tag, bool ok) {
  const uint32_t m = HH == 0 && (fresh_tid() & 3) == 0;
#pragma unroll
  for (int jp = 0; jp < 2; jp++) {
    uint32_t w0 = pack_bf16x2(o[8 * jp] * inv[0], o[8 * jp + 1] * inv[0]);
    uint32_t w1 = pack_bf16x2(o[8 * jp + 2] * inv[1], o[8 * jp + 3] * inv[1]);
    if (HH == 0 && jp == 0) {
      w0 = set_tag(w0, m, tag);
      w1 = set_tag(w1, m, tag);
    }
    stmatrix_x4_if(ok, ra ^ ((HH * 4 + 2 * jp) << 4), w0, w1, pack_bf16x2(o[8 * jp + 4] * inv[0], o[8 * jp + 5] * inv[0]),
                   pack_bf16x2(o[8 * jp + 6] * inv[1], o[8 * jp + 7] * inv[1]));
  }
}
__device__ __forceinline__ int tile_row(bool B, int w, int r, int g) { return (B ? 16 * w + 8 * r : 8 * w + 32 * r) + g; }
__device__ __forceinline__ uint32_t q_row_addr(bool B, int R, int w, int lane) {
  return SBASE + OFF_SLOT + 3 * 16384 + R * 8192 + tile_row(B, w, (lane >> 3) & 1, lane & 7) * 128 + (((lane >> 4) ^ (lane & 7)) << 4);
}

struct AttnA {
  float s[2][16], o[2][16], l[2][2], sh[2][3];
  uint32_t p[2][4], t[2], me[4], ra, bad, zero;
};
#define ATS_(i) do { } while (0)
template <int V>
__device__ __forceinline__ void attn_sum(AttnA& a, int nv) {
  constexpr int hh = (V >> 1) & 1, kh = V & 1, i = V >> 2;
#pragma unroll
  for (int r = 0; r < 2; r++) {
    const uint32_t t1 = add_bf16x2(add_bf16x2(a.p[0][r], a.p[0][2 + r]), add_bf16x2(a.p[1][r], a.p[1][2 + r]));
    if (kh == 0) {
      a.t[r] = t1;
    } else {
      uint32_t tt = add_bf16x2(a.t[r], t1);
      if (i > 0) tt = i <= nv ? tt : 0u;
      const float v = bf_lo(tt) + bf_hi(tt);
      a.l[hh][r] = i == 0 ? v : a.l[hh][r] + v;
    }
  }
}
template <int HH>
__device__ __forceinline__ void attn_shfl(AttnA& a) {
#pragma unroll
  for (int r = 0; r < 2; r++)
#pragma unroll
    for (int j = 0; j < 3; j++) a.sh[r][j] = __shfl_xor_sync(0xffffffffu, a.l[HH][r], j + 1);
}
template <int HH>
__device__ __forceinline__ void attn_fin(AttnA& a) {
  bool bad = false;
  float inv[2];
#pragma unroll
  for (int r = 0; r < 2; r++) {
    const float v = (a.l[HH][r] + a.sh[r][0]) + (a.sh[r][1] + a.sh[r][2]);
    bad |= !(v <= 1.152921504606846976e18f && v >= 8.673617379884035e-19f);
    inv[r] = rcp_fast(v);
  }
  bad = __any_sync(0xffffffffu, bad);
  if (HH == 1) wgmma_wait<0>();
  reg_fence<16>(a.o[HH]);
  store_o<HH>(a.o[HH], inv, a.ra, o_tag(0), !bad);
  a.bad = (HH == 0 ? 0u : a.bad) | (bad ? 1u << HH : 0u);
}
__device__ __forceinline__ void attn_masks(AttnA& a, int wr) {
  const int lane = fresh_tid() & 31, d = (lane >> 2) - 2 * (lane & 3);
  const uint32_t tri = d >= 1 ? 0xffffffffu : (d == 0 ? 0xffffu : 0u);
#pragma unroll
  for (int t = 0; t < 4; t++) a.me[t] = wr > t ? 0xffffffffu : (wr == t ? tri : 0u);
}
template <int V, int K>
__device__ __forceinline__ uint32_t attn_exp(AttnA& a) {
  constexpr int i = V >> 2, kh = V & 1, r = K & 1;
  if ((i == 0 && kh > r) || (i == 4 && kh < r)) return 0u;
  const uint32_t w = pack_bf16x2(ex2_approx(a.s[V & 1][2 * K]), ex2_approx(a.s[V & 1][2 * K + 1]));
  if (i == 0 && kh == r) return w & a.me[K >> 1];
  if (i == 4 && kh == r) return w & ~a.me[K >> 1];
  return w;
}
template <int V>
__device__ __forceinline__ void attn_unit(AttnA& a, const uint32_t (&q)[2][2][4], uint64_t dcur, uint64_t dnext, int R, int wr, int nv,
                                          uint32_t hbar, uint32_t hpar, uint32_t rbar, bool rel) {
  constexpr int hh = (V >> 1) & 1, kh = V & 1, i = V >> 2;
  ATS_(V + 1);
  asm volatile("" : "+l"(dcur), "+l"(dnext));
  wgmma_wait<1>();
  reg_fence<16>(a.s[V & 1]);
  bool hok = true;
  if (V == 4) hbar = SBASE + OFF_BAR + 8u * (R ? B_LOC : B_HV);
  if (((V & 3) == 2 && V < 16) || V == 4) hok = mbar_test(hbar, hpar);
  const uint64_t d0 = ((V & 3) >= 2 ? dnext : dcur) + ((hh ^ 1) * 4 + kh * 256), d1 = ((V & 3) >= 2 ? dnext : dcur) + ((hh ^ 1) * 4 + kh * 256 + 2);
  const uint64_t d2 = dcur + (512 + hh * 4 + kh * 256), d3 = dcur + (640 + hh * 4 + kh * 256);
  if ((V & 3) == 1 && V > 4 && rel) mbar_arrive(rbar);
  if (V > 0) attn_sum<V - 1>(a, nv);
  if (V == 15) attn_masks(a, wr);
  if (V == 18) {
    attn_shfl<0>(a);
    a.ra = q_row_addr(false, R, wr, fresh_tid() & 31);
  }
  if (V == 19) attn_fin<0>(a);
  uint32_t p[2][4];
  p[0][0] = attn_exp<V, 0>(a);
  p[0][1] = attn_exp<V, 1>(a);
  p[0][2] = attn_exp<V, 2>(a);
  p[0][3] = attn_exp<V, 3>(a);
  p[1][0] = attn_exp<V, 4>(a);
  p[1][1] = attn_exp<V, 5>(a);
  p[1][2] = attn_exp<V, 6>(a);
  p[1][3] = attn_exp<V, 7>(a);
  if (V > 0) {
#pragma unroll
    for (int r = 0; r < 2; r++) p[1][r] ^= (kh ? a.t[r] : __float_as_uint(a.l[hh ^ 1][r])) & a.zero;
  }
#pragma unroll
  for (int k = 0; k < 8; k++) {
    asm volatile("" : "+r"(p[k >> 2][k & 3]));
    a.p[k >> 2][k & 3] = p[k >> 2][k & 3];
  }
  if (!hok) mbar_wait(hbar, hpar);
  wgmma_fence();
  if (V < 18) wgmma_n32_rsz_tb0(a.s[V & 1], q[hh ^ 1][0], d0);
  if (i == 0 && kh == 0) wgmma_n32_rsz_tb1(a.o[hh], a.p[0], d2);
  else wgmma_n32_rs_tb1(a.o[hh], a.p[0], d2, 1);
  if (V < 18) wgmma_n32_rs_tb0(a.s[V & 1], q[hh ^ 1][1], d1, 1);
  wgmma_n32_rs_tb1(a.o[hh], a.p[1], d3, 1);
  wgmma_commit();
}
template <int I>
__device__ __forceinline__ void attn_step(AttnA& a, const uint32_t (&q)[2][2][4], uint64_t dcur, uint64_t dnext, int R, int wr, int nv,
                                          uint32_t hbar, uint32_t hpar, uint32_t rbar, bool rel) {
  attn_unit<4 * I>(a, q, dcur, dnext, R, wr, nv, hbar, hpar, rbar, rel);
  attn_unit<4 * I + 1>(a, q, dcur, dnext, R, wr, nv, hbar, hpar, rbar, rel);
  attn_unit<4 * I + 2>(a, q, dcur, dnext, R, wr, nv, hbar, hpar, rbar, rel);
  attn_unit<4 * I + 3>(a, q, dcur, dnext, R, wr, nv, hbar, hpar, rbar, rel);
}

__device__ __forceinline__ void attention_a(const uint32_t (&q)[2][2][4], int R, int L, int gb, int hp, uint32_t par, int wr,
                                            uint32_t zero) {
  constexpr uint32_t bars = SBASE + OFF_BAR;
  constexpr uint32_t dslot = ((SBASE + OFF_SLOT) >> 4) + 0x10000u;
  auto next = [&](uint64_t d) { return desc_lo((uint32_t)d == dslot ? dslot + 2048 : (uint32_t)d - 1024) + zero; };
  uint64_t d0 = desc_lo(dslot + R * 1024) + zero, d1 = next(d0);
  AttnA a;
  ATS_(0);
  wgmma_fence();
#pragma unroll
  for (int v = 0; v < 2; v++) {
    wgmma_n32_rsz_tb0(a.s[v], q[0][0], d0 + v * 256);
    wgmma_n32_rs_tb0(a.s[v], q[0][1], d0 + (v * 256 + 2), 1);
    wgmma_commit();
  }
  a.zero = zero;
  const bool lane0 = (fresh_tid() & 31) == 0;
  attn_masks(a, wr);
  const int nv = 2 * gb + R;
  const uint32_t hb = bars + 8u * (B_HALO - R), rb = bars + 8u * (B_REL - R);
  attn_step<0>(a, q, d0, d1, R, wr, nv, hb, par, 0, false);
  d0 = next(d1);
  attn_step<1>(a, q, d1, d0, R, wr, nv, R ? bars + 8u * B_HV : hb + 8, par, rb + 8, lane0);
  d1 = next(d0);
  attn_step<2>(a, q, d0, d1, R, wr, nv, hb + 16, par, rb + 16, lane0);
  d0 = next(d1);
  attn_step<3>(a, q, d1, d0, R, wr, nv, hb + 24, par, rb + 24, lane0 && R);
  attn_step<4>(a, q, d0, d0, R, wr, nv, 0, 0, rb, false);
  ATS_(21);
  attn_sum<19>(a, nv);
  attn_shfl<1>(a);
  attn_fin<1>(a);
  ATS_(22);
  if (a.bad != 0u) {
    attn_a_slow(g_kvA[0][0][0], L, gb, hp, a.bad, R * 64 + wr * 8, fresh_tid() & 31);
    named_bar_sync(7, 32);
  }
}

constexpr uint32_t KB_ROW0 = SBASE + OFF_SLOT + 2048, VB_ROW0 = SBASE + OFF_SLOT + 24576 + 2048;

__device__ __forceinline__ void attention_b(const uint32_t (&q)[2][2][4], int R, int gb, uint32_t par0, int wr) {
  constexpr uint32_t bars = SBASE + OFF_BAR;
  const uint32_t dk = ((KB_ROW0 - 2048) >> 4) + 0x10000u + R * 512, dv = dk + ((VB_ROW0 - KB_ROW0) >> 4);
  float s[2][40];
  mbar_wait(bars + 8u * (B_HALO - R), par0);
  wgmma_fence();
#pragma unroll
  for (int hh = 0; hh < 2; hh++) {
    wgmma_n80_rsz_tb0(s[hh], q[hh][0], desc_lo(dk + hh * 4));
    wgmma_n80_rs_tb0(s[hh], q[hh][1], desc_lo(dk + hh * 4 + 2), 1);
  }
  wgmma_commit();
  const int lane = fresh_tid() & 31, g = lane >> 2;
  const bool odd = g & 1, edge = R == 0 && gb == 0 && wr == 0;
  const int D = 2 * (lane & 3) + (g & 1) - g;
  const uint32_t ra = q_row_addr(true, R, wr, lane);
  wgmma_wait<0>();
  reg_fence<40>(s[0]);
  reg_fence<40>(s[1]);
  float z[2][2], y[2][2];
#define GATHER_(W)                                                                                          \
  _Pragma("unroll") for (int hh = 0; hh < 2; hh++) _Pragma("unroll") for (int r = 0; r < 2; r++) {          \
    const float* e = &s[hh][4 * (2 * W + r) + 2 * r];                                                       \
    z[hh][r] = odd ? e[5] : e[4];                                                                           \
    y[hh][r] = D >= 2 ? (odd ? e[1] : e[0]) : (odd ? e[9] : e[8]);                                          \
  }
  if (wr < 2) {
    if (wr == 0) { GATHER_(0) } else { GATHER_(1) }
  } else {
    if (wr == 2) { GATHER_(2) } else { GATHER_(3) }
  }
#undef GATHER_
  float o[2][16], inv[2][2];
  uint32_t p[2][5][4];
  const int sh = odd ? 16 : 0, kb = wr + (D >= 2 ? 0 : 1);
#pragma unroll
  for (int hh = 0; hh < 2; hh++) {
    if (edge) {
      z[hh][0] = -INFINITY;
      if (D >= 2) y[hh][0] = y[hh][1] = -INFINITY;
    }
    uint32_t ab[2][2];
#pragma unroll
    for (int r = 0; r < 2; r++) {
      float m = fmaxf(z[hh][r], y[hh][r]);
      m = fmaxf(m, __shfl_xor_sync(0xffffffffu, m, 1));
      m = fmaxf(m, __shfl_xor_sync(0xffffffffu, m, 2));
      const float e0 = ex2_approx(z[hh][r] - m), e1 = ex2_approx(y[hh][r] - m);
      inv[hh][r] = e0 + e1;
      ab[r][0] = pack_bf16x2(e0, 0.f) << sh;
      ab[r][1] = pack_bf16x2(e1, 0.f) << sh;
    }
#pragma unroll
    for (int k = 0; k < 5; k++) {
      p[hh][k][0] = k == kb ? ab[0][1] : 0u;
      p[hh][k][1] = k == wr + 1 ? ab[1][0] : 0u;
      p[hh][k][2] = k == wr ? ab[0][0] : 0u;
      p[hh][k][3] = k == kb ? ab[1][1] : 0u;
#pragma unroll
      for (int j = 0; j < 4; j++) asm volatile("" : "+r"(p[hh][k][j]));
    }
  }
  wgmma_fence();
#pragma unroll
  for (int hh = 0; hh < 2; hh++) {
    wgmma_n32_rsz_tb1(o[hh], p[hh][0], desc_lo(dv + hh * 4));
#pragma unroll
    for (int k = 1; k < 5; k++) wgmma_n32_rs_tb1(o[hh], p[hh][k], desc_lo(dv + hh * 4 + k * 128), 1);
  }
  wgmma_commit();
#pragma unroll
  for (int hh = 0; hh < 2; hh++)
#pragma unroll
    for (int r = 0; r < 2; r++) {
      inv[hh][r] += __shfl_xor_sync(0xffffffffu, inv[hh][r], 1);
      inv[hh][r] += __shfl_xor_sync(0xffffffffu, inv[hh][r], 2);
      inv[hh][r] = rcp_fast(inv[hh][r]);
    }
  wgmma_wait<0>();
  reg_fence<16>(o[0]);
  reg_fence<16>(o[1]);
  store_o<0>(o[0], inv[0], ra, o_tag(1), true);
  store_o<1>(o[1], inv[1], ra, o_tag(1), true);
}

#define TRICKLE 300
#define QREL 5
#define PRESLEEP 200
#define CSA 5
#define PN1 4
#define PN2 5
#define TLAZY 100
#define SDLY 1500
#define HTS(i) do { } while (0)
struct Params {
  CUtensorMap x[5], xq[4], o, wqkv[2], wqkv3[2], wo3[2];
  const __nv_bfloat16* in_x;
  const __nv_bfloat16* wqkv_p[2];
  const __nv_bfloat16* wo_p[2];
  uint32_t zero;
};

__device__ __forceinline__ void colsum_part(const CUtensorMap* wmap, int ty, int qr, int hp) {
  constexpr uint32_t bars = SBASE + OFF_BAR, slots = SBASE + OFF_SLOT;
  PHASE_IDS
  const unsigned ep1 = launch_epoch();
  if (wwarp == 0 && elect_one()) {
    mbar_expect_tx(bars + 8u * B_CS, 6 * UNIT);
#pragma unroll 1
    for (int j = 0; j < 6; j++) {
      if (ty == 0) mbar_pace(bars + 8u * (B_QF + B_E + ((j * CSA / 6) & 3)), (j * CSA / 6) >> 2, j ? PN1 : 30);
      else mbar_wait_lazy<100>(bars + 8u * (B_WF + B_E + ((2 * j + 3 - (j & 1)) & 7)), j >= 3);
      tma_load_2d(slots + j * UNIT, wmap, bars + 8u * B_CS, (j >> 1) * 1024 + hp * 64, qr * 128 + (j & 1) * 64);
    }
  }
  constexpr uint64_t ones = (SBASE + OFF_LSB + 32) >> 4;
  float s[3][4];
  mbar_wait_lazy<100>(bars + 8u * B_CS, ty);
  wgmma_fence();
#pragma unroll
  for (int p = 0; p < 3; p++) {
    wgmma_n8_ssz_ta1_tb0(s[p], make_desc(slots + p * 2 * UNIT, 16), ones);
#pragma unroll
    for (int k = 1; k < 8; k++) wgmma_n8_ss_ta1_tb0(s[p], make_desc(slots + p * 2 * UNIT + k * 2048, 16), ones, 1);
  }
  wgmma_commit();
  wgmma_wait<0>();
  reg_fence<12>(&s[0][0]);
  if (lane == 0) mbar_arrive(bars + 8u * (ty ? B_CSD : B_RDONE));
  if (c == 0) {
#pragma unroll
    for (int r = 0; r < 2; r++) st_rec(&g_cs[ty][hp][qr][wwarp * 16 + 8 * r + g], s[0][2 * r], s[1][2 * r], s[2][2 * r], ep1);
  }
}

__device__ __forceinline__ void put_colsums(int ty, int col, const float4& s) {
  const float v[3] = {s.x, s.y, s.z};
#pragma unroll
  for (int p = 0; p < 3; p++) {
    const uint32_t a = SBASE + OFF_CS + (p * 8 + (col >> 3)) * 64 + ty * 32 + (col & 7) * 2;
    const float hi = bf16_round(v[p]);
    const uint32_t w = pack_bf16x2(hi, v[p] - hi);
    asm volatile("st.shared.b16 [%0], %1;" ::"r"(a), "h"((unsigned short)w) : "memory");
    asm volatile("st.shared.b16 [%0], %1;" ::"r"(a + 16), "h"((unsigned short)(w >> 16)) : "memory");
  }
}

__device__ __forceinline__ uint32_t ln_params(float s1, float s2) {
  const float mean = s1 * (1.0f / DM);
  const float var = fmaxf(fmaf(-mean, mean, s2 * (1.0f / DM)), 0.f);
  float sd;
  asm("sqrt.approx.f32 %0, %1;" : "=f"(sd) : "f"(bf16_round(bf16_round(var) + 1e-5f)));
  return pack_bf16x2(mean, sd);
}

__host__ __device__ constexpr uint32_t w_rel(int kt) { return ((B_WF + (kt & 7)) << 1) | (kt >> 3); }
__host__ __device__ constexpr uint32_t w_rel4(int a, int b, int c, int d) { return w_rel(a) | (w_rel(b) << 8) | (w_rel(c) << 16) | (w_rel(d) << 24); }
__device__ __forceinline__ void ring_wait(uint32_t e) { mbar_wait(SBASE + OFF_BAR + 8u * B_E + ((e << 2) & 0x3f8u), e & 1u); }
struct RingProd {
  uint32_t rel = ((B_QF << 1) | 1) * 0x01010101u + 0x06040200u;
  __device__ __forceinline__ void q_step(int kt) {
    const int sh = 8 * (kt & 3);
    const uint32_t e = rel >> sh;
    rel ^= ((e ^ (((B_QF + (kt & 3)) << 1) | ((kt >> 2) & 1))) & 255u) << sh;
    ring_wait(e);
  }
  __device__ __forceinline__ void w_job(int st, bool pre, uint32_t sel0, uint32_t sel1, uint32_t last, uint32_t& w0, uint32_t& w1) {
    const uint32_t r = __funnelshift_r(rel, rel, 8 * st);
    w0 = __byte_perm(r, 0u, sel0);
    w1 = __byte_perm(r, w_rel4(0, 1, 2, 3), pre ? sel1 : 0x6543u);
    const uint32_t n = pre ? (w_rel4(9, 11, 13, 0) & 0xffffffu) | (last << 24) : (w_rel4(11, 13, 0, 15) & 0xff00ffffu) | (last << 16);
    rel = __funnelshift_l(n, n, 8 * st);
  }
};

#define SP1 15
#define SP2 13
#define SP3 11
#define SP4 11
#define SP5 15
#define SP6 13
#define SP7 16
__device__ __forceinline__ int q_split(int inst) {
  constexpr uint32_t T = 15u | ((SP1 - 1) << 4) | ((SP2 - 1) << 8) | ((SP3 - 1) << 12) | ((SP4 - 1) << 16) | ((SP5 - 1) << 20) |
                         ((SP6 - 1) << 24) | ((uint32_t)(SP7 - 1) << 28);
  return (int)((T >> (4 * inst)) & 15u) + 1;
}
#define QROT 4
#define WROT 2
__device__ __forceinline__ int qk(int kt) { return (((kt & 12) | ((kt & 1) << 1) | ((kt >> 1) & 1)) + QROT) & 15; }
__device__ __forceinline__ int wk(int kt) { return (kt + WROT) & 15; }
__host__ __device__ constexpr uint32_t turn_par(int kind) {
  const int sp[8] = {16, SP1, SP2, SP3, SP4, SP5, SP6, SP7};
  int cnt[2] = {0, 0};
  uint32_t m = 0;
  for (int i = 0; i < 8; i++)
    for (int k = 0; k < 3; k++) {
      if (k == kind) m |= (uint32_t)(cnt[i & 1] & 1) << i;
      if (k == 0 ? (i == 1 || (i > 1 && sp[i - 1] < 16)) : (k == 2 || sp[i] < 16)) cnt[i & 1]++;
    }
  return m;
}
#define PREMASK 0xBFu
__device__ __forceinline__ bool w_pre(int inst) { return (PREMASK >> inst) & 1u; }
#define STGMASK 0x2Eu
__device__ __forceinline__ bool w_stg(int inst) { return (STGMASK >> inst) & 1u; }
__device__ __forceinline__ uint32_t w_out(int inst) {
  return w_stg(inst) ? SBASE + OFF_SLOT : SBASE + (((inst < 7 ? q_split(inst + 1) : 0) + (w_pre(inst) ? 3 : 2)) & 3) * 5 * UNIT;
}
__host__ __device__ constexpr unsigned long long bar_counts(int i0) {
  unsigned long long t = 0;
  for (int i = i0; i < i0 + 32; i++) {
    int l = 0;
    if (i < B_RF) l = 1;
    if ((i >= B_E && i < B_E + B_RF) || i == B_LOC || i == B_REL || i == B_OS0 || i == B_TURN || i == B_TURN + 1 || i == B_XS ||
        i == B_XS + 1 || i == B_CSD || i == B_OS1 || i == B_RDONE || i == B_KV)
      l = 2;
    if (i == B_REL + 1 || i == B_REL + 2) l = 3;
    t |= (unsigned long long)l << (2 * (i - i0));
  }
  return t;
}

__global__ void __launch_bounds__(512, 1) fused_kernel(const __grid_constant__ Params P) {
  extern __shared__ __align__(1024) uint8_t smem_raw[];
  constexpr uint32_t base = SBASE, bars = base + OFF_BAR, slots = base + OFF_SLOT;
  if (smem_u32(smem_raw) != base) __trap();
  const int warp = __shfl_sync(0xffffffffu, threadIdx.x >> 5, 0), lane = threadIdx.x & 31;
  const int b = blockIdx.x;
#define QS 1
#define WS 1
  const int qr = ((b & ((8 << QS) - 1)) >> QS) ^ (((b >> (3 + QS)) & 1) * 7);
  const int hp = ((b >> (3 + QS)) << QS) + (b & ((1 << QS) - 1));
  const int rt = ((b & ((16 << WS) - 1)) >> WS) ^ (((b >> (4 + WS)) & 1) * 15);
  const int ct = ((b >> (4 + WS)) << WS) + (b & ((1 << WS) - 1));

  if (warp < 12) {
    if (warp >= 4) {
      if (elect_one()) {
#pragma unroll 1
        for (int i = warp; i <= B_KV; i += 8) mbar_init(bars + 8u * i, 1u << (((i < 32 ? bar_counts(0) : bar_counts(32)) >> (2 * (i & 31))) & 3u));
        sts32(warp < 8 ? base + OFF_ONE - 16 + 4 * warp : base + OFF_LSB + 4 * warp, warp < 8 ? warp == 4 : 0x3f803f80u);
        fence_proxy_async_smem();
        fence_barrier_init();
      }
      __syncwarp();
    }
    const bool asst = warp >= 8;
    GTL(0);
    if (warp >= 4) named_bar_sync(0, 512);
    if (warp >= 4 && !asst) {
      PHASE_IDS
      {
        const unsigned ep1 = launch_epoch();
        const int row = b * 16 + (tid >> 3);
        const uint4* src = reinterpret_cast<const uint4*>(P.in_x + (size_t)row * DM) + (tid & 7);
        float s1 = 0.f, s2 = 0.f;
#pragma unroll 1
        for (int k = 0; k < 4; k++) {
          mbar_pace(bars + 8u * (B_QF + B_E + ((2 * k) & 3)), k >> 1, k ? PN2 : 30);
          uint4 v[4];
#pragma unroll
          for (int j = 0; j < 4; j++) v[j] = __ldg(src + (k * 4 + j) * 8);
#pragma unroll
          for (int j = 0; j < 4; j++) {
            const uint32_t w[4] = {v[j].x, v[j].y, v[j].z, v[j].w};
#pragma unroll
            for (int e = 0; e < 4; e++) {
              const float x0 = bf_lo(w[e]), x1 = bf_hi(w[e]);
              s1 += x0 + x1;
              s2 = fmaf(x0, x0, fmaf(x1, x1, s2));
            }
          }
        }
#pragma unroll
        for (int o = 1; o < 8; o <<= 1) {
          s1 += __shfl_xor_sync(0xffffffffu, s1, o);
          s2 += __shfl_xor_sync(0xffffffffu, s2, o);
        }
        if ((tid & 7) == 0) st_rec(&g_stats[0][row], s1, s2, 0.f, 4u * ep1);
        if (tid == 0) sts32(base + OFF_EPOCH, ep1);
        if (tid < 64) {
          const float4 s0 = sum_recs<8>(&g_cs[0][hp][0][tid], 64, ep1);
          put_colsums(0, tid, s0);
        } else {
          put_colsums(1, tid - 64, make_float4(0.f, 0.f, 0.f, 0.f));
        }
#pragma unroll 1
        for (int cc = 0; cc < 2; cc++) {
          const float4 s0 = sum_recs<1>(&g_stats[0][(cc * 8 + qr) * 128 + tid], 0, 4u * ep1);
          sts32(base + OFF_RS + (cc * 128 + tid) * 4, ln_params(s0.x, s0.y));
        }
        fence_proxy_async_smem();
        named_bar_sync(2, 128);
        if (tid < 2) mbar_arrive(bars + 8u * (B_PREP + tid));
      }
    }
#pragma unroll 1
    for (int inst = asst ? 0 : warp >> 2; inst < 8; inst += asst ? 1 : 2) {
      const int L = inst >> 1, ch = inst & 1, gb = ch * 8 + qr;
      uint32_t q[2][2][4];
      if (asst) {
        if (inst < 2) colsum_part(&P.wqkv[inst], inst, qr, hp);
        setmaxnreg_dec<24>();
        named_bar_sync(4, 256);
        setmaxnreg_inc<128>();
        const uint32_t ra = q_row_addr(L & 1, 1, warp & 3, fresh_tid() & 31);
#pragma unroll
        for (int j = 0; j < 4; j++) ldmatrix_x4(q[j >> 1][j & 1], ra ^ (j << 5));
      } else {
      setmaxnreg_inc<224>();
      {
        float acc[2][96];
        const int ksp = q_split(inst);
        constexpr uint32_t STG = 5 * (UNIT >> 4), D0 = ((base + 3 * UNIT) >> 4) + 0x10000u;
        constexpr uint32_t DB = ((UNIT >> 4) << 16) - 0x10000u - 3 * (UNIT >> 4);
        const uint32_t toff = ((fresh_tid() & 127) << 7) + ((fresh_tid() & 7) << 4);
        const bool lane0 = (toff & 0xf80u) == 0u;
        uint32_t xt = x_tag(L), tro = (warp & 3) * 2048 + (toff & 0x7f0u) + ((toff << 2) & 0x2000u);
        auto check_x = [&](uint32_t bar, uint32_t par, uint32_t ta, int kt, uint32_t mask) {
          fix_lines(bar, par, ta, xt, mask, 7, [&](int l) {
            return g_x + (size_t)(gb * 128 + (l >> 4) * 64 + tile_row(L & 1, warp & 3, (l >> 3) & 1, l & 7)) * DM + qk(kt) * 64;
          });
        };
        uint32_t rsa = base + OFF_RS + (ch * 128 + tile_row(L & 1, warp & 3, 0, (toff >> 9) & 7)) * 4;
        uint32_t rsb = rsa + ((L & 1) ? 32 : 128);
        uint32_t lnm = ((toff >> 7) & 3) == (L & 1) ? 0xffffffffu : 0u, tmk = L > 0;
        uint32_t soff = tile_row(L & 1, warp & 3, (toff >> 10) & 1, (toff >> 7) & 7) * 128 + ((toff ^ (toff >> 7)) & 0x10u) + (toff & 0x60u);
        uint32_t bprep = bars + 8u * (B_PREP + ch), bturn = bars + 8u * (B_TURN + (ch ^ 1));
        const bool stg = inst > 0 && w_stg(inst - 1);
        uint32_t bfree = bars + 8u * (inst == 1 ? B_CSD : (stg ? B_RF + B_E : B_RDONE));
        uint32_t pfree = inst == 1 ? 0 : (inst & 1) ^ stg, pprep = L & 1;
        asm volatile("" : "+r"(rsa), "+r"(rsb), "+r"(lnm), "+r"(soff), "+r"(xt), "+r"(tmk), "+r"(tro));
        asm volatile("" : "+r"(bprep), "+r"(bturn), "+r"(bfree), "+r"(pfree), "+r"(pprep));
        if (inst == 0) named_bar_sync(0, 512);
        if (inst == 1 || (inst > 1 && q_split(inst - 1) < 16)) mbar_wait_lazy<TLAZY>(bars + 8u * (B_TURN + ch), (turn_par(0) >> inst) & 1u);
        if (L == 3) GTL(37);
        check_x(bars + 8u * B_QF, 0, base + 3 * UNIT + tro, 0, tmk);
        GTL(1 + L * 8);
        {
          const uint64_t da = desc_lo(D0) + P.zero;
          wgmma_fence();
          wgmma_n192_ssz_ta0_tb1(acc[1], da + (UNIT >> 4), da + DB);
          wgmma_commit();
          wgmma_n192_ssz_ta0_tb1(acc[0], da, da + DB);
          wgmma_commit();
        }
        int left = ksp;
        asm volatile("" : "+r"(left));
        const uint64_t d0 = desc_lo(D0) + P.zero;
#pragma unroll 1
        for (int k4 = 0;; k4++) {
#pragma unroll
          for (int ks = 0; ks < 4; ks++) {
            const uint64_t da = d0 + ks * STG, dn = d0 + ((ks + 1) & 3) * STG;
            const uint32_t fn = bars + 8u * (B_QF + ((ks + 1) & 3)), pn = (k4 + (ks == 3)) & 1;
            const uint32_t ta = base + (3 + ((ks + 1) & 3) * 5) * UNIT + tro;
            bool ok, last;
            uint32_t tw;
#pragma unroll
            for (int k16 = 1; k16 < 4; k16++) {
              if (k16 > 1 || ks > 0) wgmma_wait<1>();
              else wgmma_fence();
              wgmma_n192_ss_ta0_tb1(acc[1], da + ((UNIT >> 4) + k16 * 2), da + (DB + k16 * 128), 1);
              wgmma_commit();
              if (k16 == 1) last = --left == 0;
              if (k16 == 2) {
                ok = mbar_test(fn, pn);
                tw = lds32(ta);
              }
              wgmma_wait<1>();
              wgmma_n192_ss_ta0_tb1(acc[0], da + k16 * 2, da + (DB + k16 * 128), 1);
              wgmma_commit();
              if (k16 == 2) {
                if (last && lane0) mbar_arrive(bturn);
                ok = !__any_sync(0xffffffffu, !ok || ((tw ^ xt) & tmk)) && !last;
              }
            }
            if (!ok) {
              if (last) {
                wgmma_wait<0>();
                if (lane0) mbar_arrive(bars + 8u * (B_QF + B_E + ks));
                mbar_wait_lazy<TLAZY>(bars + 8u * (B_TURN + ch), (turn_par(1) >> inst) & 1u);
              }
              check_x(fn, pn, ta, 4 * k4 + ks + 1, tmk);
            }
            if (ks == 2 && k4 == 3) goto q_last;
            wgmma_fence();
            wgmma_wait<1>();
            wgmma_n192_ss_ta0_tb1(acc[1], dn + (UNIT >> 4), dn + DB, 1);
            wgmma_commit();
            wgmma_wait<1>();
            wgmma_n192_ss_ta0_tb1(acc[0], dn, dn + DB, 1);
            wgmma_commit();
            if (lane0 && !last) mbar_arrive(bars + 8u * (B_QF + B_E + ks));
          }
        }
      q_last:
        constexpr uint32_t DL = D0 + 3 * STG;
        wgmma_fence();
#pragma unroll
        for (int k16 = 0; k16 < 4; k16++) wgmma_n192_ss_ta0_tb1(acc[1], desc_lo(DL + (UNIT >> 4) + k16 * 2), desc_lo(DL + DB + k16 * 128), 1);
        wgmma_commit();
        mbar_wait(bprep, pprep);
        uint32_t rs[2][2];
        constexpr uint64_t DCS = (uint64_t)((base + OFF_CS) >> 4) | (4ull << 32);
        auto ln_mma = [&](float (&d)[96], uint32_t (&r)[2], int h) {
          uint32_t a[4];
#pragma unroll
          for (int i = 0; i < 2; i++) {
            if (h) r[i] = lds32((i ? rsb : rsa) + 256);
            a[i] = (__byte_perm(r[i], 0u, 0x1010) ^ 0x80008000u) & lnm;
            a[i + 2] = r[i] & P.zero;
          }
#pragma unroll
          for (int i = 0; i < 4; i++) asm volatile("" : "+r"(a[i]));
          wgmma_fence();
          wgmma_n192_rs_tb1(d, a, DCS, 1);
          wgmma_commit();
        };
        ln_mma(acc[1], rs[1], 1);
        wgmma_wait<2>();
        if (lane0 && ksp != 15) mbar_arrive(bars + 8u * (B_QF + B_E + 2));
        wgmma_fence();
#pragma unroll
        for (int k16 = 0; k16 < 4; k16++) wgmma_n192_ss_ta0_tb1(acc[0], desc_lo(DL + k16 * 2), desc_lo(DL + DB + k16 * 128), 1);
        wgmma_commit();
        if (lane0) mbar_arrive(bturn);
        rs[0][0] = lds32(rsa);
        rs[0][1] = lds32(rsb);
        static_assert(SP1 < 16 && SP5 < 16 && (PREMASK & 1u) && !(STGMASK & 1u), "column sums of B");
        const bool afree = mbar_test(bfree, pfree) & (mbar_test(bars + 8u * (B_WF + B_E + 7), 1) | (ksp == 16));
        float rinv[2];
#pragma unroll
        for (int r = 0; r < 2; r++) {
          rinv[r] = rcp_fast(bf_hi(rs[1][r]));
          asm volatile("" : "+f"(rinv[r]));
        }
        const uint32_t kdst = ((L & 1) ? KB_ROW0 : slots) + soff, vdst = ((L & 1) ? VB_ROW0 : slots + 8192) + soff;
        const uint32_t hs = (L & 1) ? 8192 : 16384, c0 = (toff & 0x180u) == 0u;
        wgmma_wait<1>();
        ln_mma(acc[0], rs[0], 0);
        reg_fence<96>(acc[1]);
        GTL(2 + L * 8);
        if (!afree) {
          mbar_wait(bfree, pfree);
          if (ksp < 16) mbar_wait(bars + 8u * (B_WF + B_E + 7), 1);
        }
#pragma unroll
        for (int t = 0; t < 24; t++) {
          const int h = t < 12 ? 1 : 0, p = ((t % 12) / 4 + 1) % 3, jp = t & 3;
          if (t == QREL) {
            wgmma_wait<0>();
            reg_fence<96>(acc[0]);
            if (lane0) mbar_arrive(bars + 8u * (B_QF + B_E + 3));
          }
          if (t == 8 || t == 20) {
            rinv[0] *= SM_C;
            rinv[1] *= SM_C;
          }
          const float* a = &acc[h][4 * (p * 8 + 2 * jp)];
          uint32_t r0 = pack_bf16x2(a[0] * rinv[0], a[1] * rinv[0]);
          uint32_t r1 = pack_bf16x2(a[2] * rinv[1], a[3] * rinv[1]);
          if (p != 0 && jp == 0) {
            r0 = set_tag(r0, c0, kv_tag(L));
            r1 = set_tag(r1, c0, kv_tag(L));
          }
          const uint32_t r2 = pack_bf16x2(a[4] * rinv[0], a[5] * rinv[0]);
          const uint32_t r3 = pack_bf16x2(a[6] * rinv[1], a[7] * rinv[1]);
          const uint32_t dst = p == 0 ? slots + 3 * 16384 + soff + h * 8192 : (p == 1 ? kdst : vdst) + h * hs;
          stmatrix_x4(dst ^ (jp << 5), r0, r1, r2, r3);
          if (t >= 20) {
            q[jp >> 1][jp & 1][0] = r0;
            q[jp >> 1][jp & 1][1] = r1;
            q[jp >> 1][jp & 1][2] = r2;
            q[jp >> 1][jp & 1][3] = r3;
          }
          if (t == 7 || t == 19) signal_async(bars + 8u * (t == 7 ? B_KV : B_LOC), lane0);
          if (t == 11) {
            setmaxnreg_dec<128>();
            named_bar_arrive(4, 256);
#pragma unroll
            for (int r = 0; r < 2; r++) rinv[r] = rcp_fast(bf_hi(rs[0][r]));
          }
        }
        mbar_wait(bars + 8u * B_LOC, inst & 1);
      }
      }
      GTL(3 + L * 8);
      if ((L & 1) == 0) attention_a(q, asst, L, gb, hp, ch, warp & 3, P.zero);
      else attention_b(q, asst, gb, inst & 1, warp & 3);
      GTL(4 + L * 8);
      signal_async(bars + 8u * (asst ? B_OS1 : B_OS0), (fresh_tid() & 31) == 0);
      if (asst) continue;
      GTL(5 + L * 8);

      {
        float acc[64];
        const int sp = inst < 7 ? q_split(inst + 1) : 0;
        const int st = sp & 3;
        const bool pre = w_pre(inst);
        const uint32_t toff = ((fresh_tid() & 63) << 7) + ((fresh_tid() & 7) << 4);
        uint32_t tro = (warp & 3) * 2048 + (toff & 0x7f0u);
        auto check_o = [&](uint32_t bar, uint32_t par, uint32_t sa, int kt) {
          fix_lines(bar, par, sa + tro, o_tag(L), 1u, 7, [&](int l) {
            return g_o + (size_t)(ch * 1024 + rt * 64 + (warp & 3) * 16 + (l & 15)) * DM + wk(kt) * 64;
          });
        };
        const bool lane0 = (toff & 0xf80u) == 0u;
        constexpr uint32_t U4 = UNIT >> 4, LA = 0x10000u, LB = U4 << 16;
        reg_define<64>(acc);
        reg_fence<64>(acc);
        uint32_t xv[8][4];
        {
          PHASE_IDS_W
          const uint32_t xr = slots + 6 * UNIT + (wwarp * 16 + (lane & 15)) * 128 + (((lane >> 4) ^ (lane & 7)) << 4);
          mbar_wait(bars + 8u * B_RF, inst & 1);
#pragma unroll
          for (int jp = 0; jp < 8; jp++) ldmatrix_x4(xv[jp], (xr ^ ((jp & 3) << 5)) + (jp >> 2) * UNIT);
          signal_async(bars + 8u * B_RDONE, lane0);
          if (L > 0) {
            uint32_t lsb;
            asm volatile("ld.shared.u8 %0, [%1];" : "=r"(lsb) : "r"(base + OFF_LSB + ch * 32 + wwarp * 8 + g) : "memory");
#pragma unroll
            for (int k = 0; k < 4; k++) xv[(k >> 1) * 4][k & 1] = set_tag(xv[(k >> 1) * 4][k & 1], c == 0, lsb >> k);
          }
        }
        uint32_t tmx = L < 3 && (toff & 0x180u) == 0u, xt = x_tag(L + 1);
        uint32_t xrow = w_out(inst) + (warp & 3) * 2048 + (toff & 0x7e0u) + ((toff ^ (toff >> 7)) & 0x10u);
        asm volatile("" : "+r"(tmx), "+r"(xt), "+r"(xrow), "+r"(tro));
        const uint64_t dz = desc_lo(0) + P.zero;
        auto nexts = [&](uint32_t a) { return a == base + 15 * UNIT ? base : a + 5 * UNIT; };
        uint32_t s0 = base + st * 5 * UNIT, sp3 = slots, fb = bars + 8u * B_WF;
        int turn = lane0 && (sp < 16 || inst == 6) ? 3 : -1;
        asm volatile("" : "+r"(turn));
        if (inst < 7 || SP7 == 16) mbar_wait_lazy<TLAZY>(bars + 8u * (B_TURN + ch), (turn_par(2) >> inst) & 1u);
        check_o(bars + 8u * B_WF, 0, s0, 0);
        GTL(6 + L * 8);
#pragma unroll 1
        for (int m = 0; m < 4; m++) {
          uint32_t s1, s2;
#pragma unroll
          for (int i = 0; i < 4; i++) {
            const uint64_t da = dz + ((i == 0 ? s0 : s1) >> 4) + (LA + (i == 2 ? 1 : (i == 3 ? 4 : 0)) * U4);
            const uint64_t db = dz + ((i < 2 ? s0 : (i == 2 ? s1 : s2)) >> 4) + (LB + (i == 0 ? 1 : (i == 1 ? 3 : (i == 2 ? 2 : 0))) * U4);
            wgmma_fence();
#pragma unroll
            for (int k16 = 0; k16 < 4; k16++) wgmma_n128_ss_ta0_tb1(acc, da + 2 * k16, db + 128 * k16, 1);
            wgmma_commit();
            if (i == 0) s1 = nexts(s0);
            if (i == 1) s0 = nexts(s1);
            if (i == 2) {
              s2 = pre ? sp3 : s0;
              s0 = pre ? s0 : nexts(s0);
              sp3 += 2 * UNIT;
            }
            const uint32_t fn = i < 3 ? fb + 8u * (i + 1) : fb ^ 96u;
            const uint32_t pn = i < 3 ? m >> 1 : m > 0;
            const uint32_t an = i < 3 ? s1 + (i == 1 ? 1 : (i == 2 ? 4 : 0)) * UNIT : s0;
            bool ok = mbar_test(fn, pn);
            const uint32_t tw = lds32(an + tro);
            ok = !__any_sync(0xffffffffu, (!ok || ((tw ^ o_tag(L)) & 1u)) && (i < 3 || m < 3));
            wgmma_wait<1>();
            if (lane0 && (i > 0 || m > 0)) mbar_arrive((i > 0 ? fb + 8u * (i - 1) : (fb ^ 96u) + 24u) + 8u * B_E);
            if (i == 2 && m == turn) mbar_arrive(bars + 8u * (B_TURN + (ch ^ 1)));
            if (!ok) check_o(fn, pn, an, 4 * m + i + 1);
          }
          fb ^= 96u;
        }
        wgmma_wait<0>();
        reg_fence<64>(acc);
        if (lane0) mbar_arrive(bars + 8u * (B_WF + B_E + 7));
        GTL(7 + L * 8);
#pragma unroll
        for (int jp = 0; jp < 8; jp++) {
#pragma unroll
          for (int q = 0; q < 4; q++) xv[jp][q] = add_bf16x2(xv[jp][q], pack_bf16x2(acc[8 * jp + 2 * q], acc[8 * jp + 2 * q + 1]));
          const bool tg = (jp & 3) == 0;
          stmatrix_x4((xrow ^ ((jp & 3) << 5)) + (jp >> 2) * UNIT,
                      tg ? set_tag(xv[jp][0], tmx, xt) : xv[jp][0], tg ? set_tag(xv[jp][1], tmx, xt) : xv[jp][1], xv[jp][2], xv[jp][3]);
          if ((jp & 3) == 3) signal_async(bars + 8u * (B_XS + (jp >> 2)), lane0);
        }
        if (L < 3) {
          PHASE_IDS_W
          const int grow = ch * 1024 + rt * 64;
          const unsigned ep1 = lds32(base + OFF_EPOCH);
          if (c == 0)
            asm volatile("st.shared.u8 [%0], %1;" ::"r"(base + OFF_LSB + ch * 32 + wwarp * 8 + g),
                         "r"((xv[0][0] & 1u) | ((xv[0][1] & 1u) << 1) | ((xv[4][0] & 1u) << 2) | ((xv[4][1] & 1u) << 3)) : "memory");
          float s1[2] = {0.f, 0.f}, s2[2] = {0.f, 0.f};
#pragma unroll
          for (int jp = 0; jp < 8; jp++)
#pragma unroll
            for (int q = 0; q < 4; q++) {
              const float x0 = bf_lo(xv[jp][q]), x1 = bf_hi(xv[jp][q]);
              s1[q & 1] += x0 + x1;
              s2[q & 1] = fmaf(x0, x0, fmaf(x1, x1, s2[q & 1]));
            }
#pragma unroll
          for (int r = 0; r < 2; r++) {
            s1[r] += __shfl_xor_sync(0xffffffffu, s1[r], 1);
            s2[r] += __shfl_xor_sync(0xffffffffu, s2[r], 1);
            s1[r] += __shfl_xor_sync(0xffffffffu, s1[r], 2);
            s2[r] += __shfl_xor_sync(0xffffffffu, s2[r], 2);
            if (c == 0) st_rec(&g_stats[ct][grow + wwarp * 16 + g + 8 * r], s1[r], s2[r], 0.f, 4u * ep1 + L + 1);
          }
        }
        GTL(8 + L * 8);
      }
    }
    if (threadIdx.x == 128) atomicAdd(g_done, 1u);
  } else {
    setmaxnreg_dec<32>();
    if (warp == 13) {
      RingProd rp;
      unsigned ep1 = 0;
      uint32_t seenx = 0;
      named_bar_sync(0, 512);
      mbar_wait(bars + 8u * B_GO, 0);
#pragma unroll 1
      for (int sg = 4; sg < 34; sg++) {
        const int part = sg & 3, inst = (sg >> 2) - (part & 1);
        if (part == 3 || inst == 8) continue;
        const int L = inst >> 1, ch = inst & 1;
        if (part != 1) {
          const CUtensorMap* tx = &P.xq[L];
          const int k0 = part ? q_split(inst) : 0, k1 = part ? 16 : q_split(inst);
          if (sg == 4) ep1 = launch_epoch();
          if (part == 0) seenx = L == 0 ? 0xffffffffu : peek_counts(g_fx[ch * 8 + qr][0], 6u * ep1 - 6u + 2u * L, lane);
          const int m0 = ch * 16 + qr * 2;
#pragma unroll 1
          for (int kt = k0; kt < k1; kt++) {
            const uint32_t fb = bars + 8u * (B_QF + (kt & 3));
            rp.q_step(kt);
            if (lane == 0) mbar_expect_tx(fb, 2 * UNIT);
            wait_count(g_fx[ch * 8 + qr][0], 6u * ep1 - 6u + 2u * L, qk(kt), seenx, lane);
            TGET(t38);
            if (elect_one()) tma_load_5d(base + ((kt & 3) * 5 + 3) * UNIT, tx, fb, qk(kt) * 64, m0);
            TGET(t39);
            if (L == 3 && kt == 0 && lane == 0) { TPUT(ch, 38, t38); TPUT(ch, 39, t39); }
          }
        } else {
          const int m0 = ch * 1024 + rt * 64;
          const bool pre = w_pre(inst);
          int st = inst < 7 ? q_split(inst + 1) & 3 : 0;
          uint32_t w0, w1;
          uint32_t seen = peek_counts(g_fo[ch * 16 + rt][0], 4u * ep1 - 3u + L, lane);
          rp.w_job(st, pre, 0x1110u, 0x3332u, inst == 6 && SP7 == 16 ? B_RF << 1 : w_rel(15), w0, w1);
#pragma unroll 1
          for (int m = 0; m < 4; m++) {
            const uint32_t fb = bars + 8u * (B_WF + 4 * (m & 1));
#pragma unroll
            for (int i = 0; i < 4; i++) {
              ring_wait(w0 >> (8 * i));
              if (lane == 0) mbar_expect_tx(fb + 8u * i, UNIT);
              wait_count(g_fo[ch * 16 + rt][0], 4u * ep1 - 3u + L, wk(4 * m + i), seen, lane);
              if (elect_one())
                tma_load_2d(base + ((st + (i > 0)) & 3) * 5 * UNIT + (i == 2 ? 1 : (i == 3 ? 4 : 0)) * UNIT, &P.o, fb + 8u * i, wk(4 * m + i) * 64, m0);
            }
            st += pre ? 2 : 3;
            w0 = w1;
            w1 = m == 0 ? (pre ? w_rel4(0, 1, 2, 3) : w_rel4(3, 4, 5, 6)) : (pre ? w_rel4(4, 5, 6, 7) : w_rel4(7, 8, 9, 10));
          }
        }
      }
#pragma unroll 1
      for (int j = 0; j < 8; j++)
        g_x[(size_t)((j >> 2) * 1024 + rt * 64 + (j & 3) * 16 + (lane >> 1)) * DM + ct * 128 + (lane & 1) * 64] = __ushort_as_bfloat16(0);
    } else if (warp == 14) {
      const unsigned ep1 = launch_epoch();
      uint32_t hpar = 0;
      named_bar_sync(0, 512);
#pragma unroll 1
      for (int inst = 0; inst < 8; inst++) {
        const int L = inst >> 1, ch = inst & 1, gb = ch * 8 + qr;
        const unsigned kv0 = 8u * ep1 - 8u + 2u * L + (L & 1);
        const uint32_t tag = kv_tag(L);
        if (L >= 2) {
#pragma unroll 1
          for (uint32_t it = 0; it < (1u << 17); ++it)
            if (__all_sync(0xffffffffu, (int)(ld_relaxed_u32(g_fk[hp][min(gb + 1 + (lane & 1), 15)]) - kv0) >= 0)) break;
        }
        if ((L & 1) == 0) {
          uint8_t* img = g_kvA[gb][hp][0];
          const uint8_t* s1 = gb > 0 ? img - 16 * 32768 : g_zero;
          const uint8_t* s2 = gb > 1 ? img - 32 * 32768 : g_zero;
          const uint32_t h1 = gb > 0 ? 16384 : 0, h2 = gb > 1 ? 16384 : 0;
          const unsigned* cp = g_fk[hp][max(gb - 1 - (lane >= 3), 0)];
          const unsigned ct0 = kv0 + ((0x32321u >> (4 * (lane & 7))) & 3u);
          uint32_t fr = gb == 0 ? 31u : (gb == 1 ? 24u : 0u);
          const uint32_t toff = slots + lane * 128 + ((lane & 7) << 4);
          auto seen = [&](uint32_t m) {
#pragma unroll 1
            for (uint32_t it = 0; it < (1u << 17) && !(fr & m); ++it)
              fr |= __ballot_sync(0xffffffffu, (int)(ld_relaxed_u32(cp) - ct0) >= 0);
          };
          auto load = [&](uint32_t off, const uint8_t* src, uint32_t bytes, int bi) {
            if (elect_one()) {
              mbar_expect_tx(bars + 8u * (B_HL + bi), bytes);
              bulk_load(slots + off, src, bytes, bars + 8u * (B_HL + bi));
            }
          };
          auto check = [&](uint32_t off, const uint8_t* src, uint32_t bytes, int bi, bool real, int done) {
#pragma unroll 1
            for (int tries = 0; tries < 4096; tries++) {
              mbar_wait(bars + 8u * (B_HL + bi), (hpar >> bi) & 1u);
              hpar ^= 1u << bi;
              uint32_t t = (lds32(toff + off) ^ tag) | (lds32(toff + off + 4096) ^ tag);
              if (bytes > 8192) t |= (lds32(toff + off + 8192) ^ tag) | (lds32(toff + off + 12288) ^ tag);
              if (!__any_sync(0xffffffffu, real && (t & 1u))) break;
              fence_proxy_async_smem();
              load(off, src, bytes, bi);
            }
            if (lane == 0) mbar_arrive(bars + 8u * done);
          };
          uint8_t *pk = img + 16384, *pv = img + 24576;
          unsigned* f = g_fk[hp][gb];
          pin64(pk), pin64(pv), pin64(f);
          mbar_wait(bars + 8u * B_KV, inst & 1);
          if (ch) mbar_wait(bars + 8u * (B_RF + B_E), 0);
          if (elect_one()) {
            bulk_store(pk, slots + 16384, 8192);
            bulk_announce(f);
            bulk_store(pv, slots + 24576, 8192);
            bulk_announce(f);
            bulk_commit();
          }
          HTS(44);
          seen(1);
          HTS(46);
          load(32768, s1 + h1, 8192, 0);
          seen(2);
          HTS(47);
          load(40960, s1 + h1 + 8192, 8192, 1);
          mbar_wait(bars + 8u * B_LOC, inst & 1);
          HTS(45);
          if (elect_one()) {
            bulk_store(img, slots, 16384);
            bulk_announce(g_fk[hp][gb]);
            bulk_commit();
            asm volatile("cp.async.bulk.wait_group.read 1;" ::: "memory");
          }
          check(32768, s1 + h1, 8192, 0, gb > 0, B_HALO);
          HTS(52);
          check(40960, s1 + h1 + 8192, 8192, 1, gb > 0, B_HV);
          HTS(53);
#pragma unroll 1
          for (int n = 1; n < 4; n++) {
            const uint8_t* src = n == 1 ? s1 : (n == 2 ? s2 + h2 : s2);
            const uint32_t off = n == 3 ? 32768 : 32768 - n * 16384;
            seen(2u << n);
            if (n == 2 && elect_one()) bulk_wait_read0();
            mbar_wait(bars + 8u * (B_REL - 1) + 8u * n, ch);
            HTS(47 + n);
            load(off, src, 16384, 0);
            check(off, src, 16384, 0, gb > (n >> 1), B_HALO + n);
            HTS(53 + n);
          }
        } else {
          uint8_t *pk = g_kvB[gb][hp], *pv = pk + 2048;
          const uint8_t* src = gb >= 1 ? pk - 16 * 4096 : g_zero;
          unsigned* f = g_fk[hp][gb];
          pin64(pk), pin64(pv), pin64(f), pin64(src);
          mbar_wait(bars + 8u * B_KV, inst & 1);
          if (elect_one()) {
            bulk_store(pk, KB_ROW0 + 112 * 128, 2048);
            bulk_store(pv, VB_ROW0 + 112 * 128, 2048);
            bulk_announce(f);
            bulk_commit();
          }
          HTS(44);
          if (gb > 0) {
#pragma unroll 1
            for (uint32_t it = 0; it < (1u << 17); ++it)
              if (__any_sync(0xffffffffu, (int)(ld_relaxed_u32(f - 4) - kv0) > 0)) break;
          }
          HTS(46);
#pragma unroll 1
          for (uint32_t it = 0; it < (1u << 17); ++it) {
            if (elect_one()) {
              mbar_expect_tx(bars + 8u * B_HL, 4096);
              bulk_load(KB_ROW0 - 2048, src, 2048, bars + 8u * B_HL);
              bulk_load(VB_ROW0 - 2048, src + 2048, 2048, bars + 8u * B_HL);
            }
            mbar_wait(bars + 8u * B_HL, hpar & 1u);
            hpar ^= 1u;
            const uint32_t t = lds32((lane < 16 ? KB_ROW0 - 2048 : VB_ROW0 - 4096) + lane * 128 + ((lane & 7) << 4)) ^ tag;
            if (!__any_sync(0xffffffffu, gb > 0 && (t & 1u))) break;
            fence_proxy_async_smem();
          }
          if (lane == 0) mbar_arrive(bars + 8u * B_HALO);
          HTS(52);
        }
        if (elect_one()) {
          const CUtensorMap* mo = &P.o;
          unsigned *f1 = g_fo[gb * 2 + 1][hp], *f0 = g_fo[gb * 2][hp];
          int c0 = hp * 64, r0 = gb * 128, r1 = r0 + 64;
          pin64(mo), pin64(f1), pin64(f0);
          asm volatile("" : "+r"(c0), "+r"(r0), "+r"(r1));
          mbar_wait(bars + 8u * B_OS1, inst & 1);
          tma_store_2d(mo, slots + 7 * UNIT, c0, r1);
          bulk_announce(f1);
          bulk_commit();
          mbar_wait(bars + 8u * B_OS0, inst & 1);
          tma_store_2d(mo, slots + 6 * UNIT, c0, r0);
          bulk_announce(f0);
          bulk_commit();
          HTS(57);
          const bool pre = w_pre(inst);
          bulk_wait_read0();
          HTS(58 - 15);
          mbar_expect_tx(bars + 8u * B_RF, 2 * UNIT);
          tma_load_2d(slots + 6 * UNIT, &P.x[L], bars + 8u * B_RF, ct * 128, ch * 1024 + rt * 64);
          tma_load_2d(slots + 7 * UNIT, &P.x[L], bars + 8u * B_RF, ct * 128 + 64, ch * 1024 + rt * 64);
          if (pre) {
            const uint32_t pp = __popc(PREMASK & ((1u << inst) - 1u)) & 1;
            mbar_expect_tx(bars + 8u * B_PRE, 2 * UNIT);
            mbar_expect_tx(bars + 8u * B_PRE2, 6 * UNIT);
#pragma unroll 1
            for (int j = 0; j < 4; j++) {
              __nanosleep(PRESLEEP);
              if (j == 3) mbar_wait(bars + 8u * B_RDONE, (inst & 1) ^ 1);
              tma_load_3d(slots + j * 2 * UNIT, &P.wo3[L & 1], bars + 8u * (j ? B_PRE2 : B_PRE), ct * 128, wk(4 * j + 3) * 64);
            }
#pragma unroll 1
            for (int j = 0; j < 4; j++) {
              const uint32_t fb = bars + 8u * (B_WF + 3 + 4 * (j & 1));
              if (j < 2) mbar_wait(bars + 8u * (j ? B_PRE2 : B_PRE), pp);
              if (j < 2 && inst == 7 && SP7 == 16) mbar_wait(bars + 8u * (B_TURN + 1), (turn_par(2) >> 7) & 1u);
              mbar_wait(fb + 8u * B_E, j < 2);
              mbar_arrive(fb);
            }
          }
        }
        __syncwarp();
      }
    } else if (warp == 15) {
      const unsigned ep1 = launch_epoch();
      named_bar_sync(0, 512);
      mbar_wait(bars + 8u * B_GO, 0);
#pragma unroll 1
      for (int i = 0; i < 20; i++) {
        const char* src = i < 4 ? reinterpret_cast<const char*>(P.wo_p[0]) + (size_t)b * 16384 + i * 4096
                                : (i < 16 ? reinterpret_cast<const char*>(P.wqkv_p[1]) + (size_t)b * 49152 + (i - 4) * 4096
                                          : reinterpret_cast<const char*>(P.wo_p[1]) + (size_t)b * 16384 + (i - 16) * 4096);
        asm volatile("prefetch.global.L2 [%0];" ::"l"(src + lane * 128));
        __nanosleep(TRICKLE);
      }
#pragma unroll 1
      for (int inst = 2; inst < 10; inst++) {
        const int L = inst >> 1, ch = inst & 1, gb = ch * 8 + qr;
        {
          uint32_t xb = w_out(inst - 2);
          unsigned* f = g_fx[ch * 8 + (rt >> 1)][ct * 2];
          const CUtensorMap* mx = &P.x[L];
          int c0 = ct * 128, r0 = ch * 1024 + rt * 64;
          pin64(f), pin64(mx);
          asm volatile("" : "+r"(xb), "+r"(c0), "+r"(r0));
#pragma unroll
          for (int h = 0; h < 2; h++) {
            mbar_wait(bars + 8u * (B_XS + h), ch);
            if (elect_one()) {
              tma_store_2d(mx, xb + h * UNIT, c0 + h * 64, r0);
              if (L < 4) bulk_announce(f + 4 * h);
              bulk_commit();
              if (h == 1) {
                bulk_wait_read0();
                mbar_arrive(bars + 8u * (B_RF + B_E));
                bulk_wait0();
              }
            }
          }
          if (L == 4) continue;
          __nanosleep(SDLY);
        }
#pragma unroll 1
        for (int h = 0; h < 4; h++) {
          const float4* sp = &g_stats[0][gb * 128 + h * 32 + lane];
          const float4 s0 = sum_recs<4>(sp, S_LEN, 4u * ep1 + L), s1 = sum_recs<4>(sp + 4 * S_LEN, S_LEN, 4u * ep1 + L);
          sts32(base + OFF_RS + (ch * 128 + h * 32 + lane) * 4, ln_params(s0.x + s1.x, s0.y + s1.y));
        }
        if (inst == 2) {
#pragma unroll 1
          for (int hf = 0; hf < 2; hf++) {
            const float4* cp = &g_cs[1][hp][0][hf * 32 + lane];
            const float4 s0 = sum_recs<4>(cp, 64, ep1), s1 = sum_recs<4>(cp + 4 * 64, 64, ep1);
            put_colsums(1, hf * 32 + lane, make_float4(s0.x + s1.x, s0.y + s1.y, s0.z + s1.z, 0.f));
          }
        }
        fence_proxy_async_smem();
        __syncwarp();
        if (lane == 0) mbar_arrive(bars + 8u * (B_PREP + ch));
      }
    } else {
      if (elect_one()) {
#pragma unroll 1
        for (int s = 0; s < 4; s++) {
          const uint32_t fb = bars + 8u * (B_QF + s), sa = base + s * 5 * UNIT;
          mbar_init(fb, 2);
          fence_barrier_init();
          mbar_expect_tx(fb, 5 * UNIT);
          mbar_arrive(fb);
          tma_load_5d(sa + 3 * UNIT, &P.xq[0], fb, s * 64, qr * 2);
          tma_load_3d(sa, &P.wqkv3[0], fb, hp * 64, s * 64);
        }
      }
      __syncwarp();
      named_bar_sync(0, 512);
      if (elect_one()) {
#pragma unroll 1
        for (int s = 4; s < 16; s++) {
          const uint32_t fb = bars + 8u * (B_QF + (s & 3)), sa = base + (s & 3) * 5 * UNIT;
          mbar_wait(fb + 8u * B_E, ((s >> 2) & 1) ^ 1);
          mbar_expect_tx(fb, 5 * UNIT);
          mbar_arrive(fb);
          tma_load_5d(sa + 3 * UNIT, &P.xq[0], fb, s * 64, qr * 2);
          tma_load_3d(sa, &P.wqkv3[0], fb, hp * 64, s * 64);
        }
        mbar_arrive(bars + 8u * B_GO);
        RingProd rp;
#pragma unroll 1
        for (int sg = 4; sg < 34; sg++) {
          const int part = sg & 3, inst = (sg >> 2) - (part & 1);
          if (part == 3 || inst == 8) continue;
          const int ty = (inst >> 1) & 1;
          if (part != 1) {
            const int k0 = part ? q_split(inst) : 0, k1 = part ? 16 : q_split(inst);
#pragma unroll 1
            for (int kt = k0; kt < k1; kt++) {
              const uint32_t sa = base + (kt & 3) * 5 * UNIT, fb = bars + 8u * (B_QF + (kt & 3));
              rp.q_step(kt);
              mbar_expect_tx(fb, 3 * UNIT);
              tma_load_3d(sa, &P.wqkv3[ty], fb, hp * 64, qk(kt) * 64);
            }
          } else {
            const bool pre = w_pre(inst);
            int st = inst < 7 ? q_split(inst + 1) & 3 : 0;
            uint32_t w0, w1;
            rp.w_job(st, pre, pre ? 0x1100u : 0x2100u, 0x3322u, w_stg(inst) ? w_rel(15) : (B_RF << 1) | (inst & 1), w0, w1);
#pragma unroll 1
            for (int m = 0; m < 4; m++) {
              const uint32_t fb = bars + 8u * (B_WF + 4 * (m & 1));
#pragma unroll
              for (int i = 0; i < 4; i++) {
                if (i < 3 || !pre) {
                  ring_wait(w0 >> (8 * i));
                  mbar_expect_tx(fb + 8u * i, 2 * UNIT);
                  tma_load_3d(base + ((st + (i ? i - 1 : 0)) & 3) * 5 * UNIT + ((0x2d >> (2 * i)) & 3) * UNIT, &P.wo3[ty], fb + 8u * i,
                              ct * 128, wk(4 * m + i) * 64);
                }
              }
              st += pre ? 2 : 3;
              w0 = w1;
              w1 = m == 0 ? (pre ? w_rel4(0, 1, 2, 3) : w_rel4(3, 4, 5, 6)) : (pre ? w_rel4(4, 5, 6, 7) : w_rel4(7, 8, 9, 10));
            }
          }
        }
      }
    }
  }
}

typedef CUresult (*PFN_tmEncode)(CUtensorMap*, CUtensorMapDataType, cuuint32_t, void*, const cuuint64_t*,
                                 const cuuint64_t*, const cuuint32_t*, const cuuint32_t*, CUtensorMapInterleave,
                                 CUtensorMapSwizzle, CUtensorMapL2promotion, CUtensorMapFloatOOBfill);

PFN_tmEncode get_encode_fn() {
  static PFN_tmEncode fn = nullptr;
  if (!fn) {
    cudaDriverEntryPointQueryResult qr;
    void* p = nullptr;
    cudaGetDriverEntryPoint("cuTensorMapEncodeTiled", &p, cudaEnableDefault, &qr);
    fn = (PFN_tmEncode)p;
  }
  return fn;
}

CUtensorMap make_map(const void* ptr, int rows, int cols) {
  CUtensorMap m;
  cuuint64_t gdim[2] = {(cuuint64_t)cols, (cuuint64_t)rows};
  cuuint64_t gstr[1] = {(cuuint64_t)cols * 2};
  cuuint32_t box[2] = {64, 64};
  cuuint32_t estr[2] = {1, 1};
  get_encode_fn()(&m, CU_TENSOR_MAP_DATA_TYPE_BFLOAT16, 2, const_cast<void*>(ptr), gdim, gstr, box, estr,
                  CU_TENSOR_MAP_INTERLEAVE_NONE, CU_TENSOR_MAP_SWIZZLE_128B, CU_TENSOR_MAP_L2_PROMOTION_L2_128B,
                  CU_TENSOR_MAP_FLOAT_OOB_FILL_NONE);
  return m;
}

CUtensorMap make_map3(const void* ptr, int rows, int cols, int n, int step) {
  CUtensorMap m;
  cuuint64_t gdim[3] = {(cuuint64_t)(cols - (n - 1) * step), (cuuint64_t)rows, (cuuint64_t)n};
  cuuint64_t gstr[2] = {(cuuint64_t)cols * 2, (cuuint64_t)step * 2};
  cuuint32_t box[3] = {64, 64, (cuuint32_t)n};
  cuuint32_t estr[3] = {1, 1, 1};
  get_encode_fn()(&m, CU_TENSOR_MAP_DATA_TYPE_BFLOAT16, 3, const_cast<void*>(ptr), gdim, gstr, box, estr,
                  CU_TENSOR_MAP_INTERLEAVE_NONE, CU_TENSOR_MAP_SWIZZLE_128B, CU_TENSOR_MAP_L2_PROMOTION_L2_128B,
                  CU_TENSOR_MAP_FLOAT_OOB_FILL_NONE);
  return m;
}

CUtensorMap make_map_q(const void* ptr, int sw, int sr) {
  CUtensorMap m;
  cuuint64_t gdim[5] = {DM, 8, 2, 4, S_LEN / 64};
  cuuint64_t gstr[4] = {DM * 2, (cuuint64_t)sr * DM * 2, (cuuint64_t)sw * DM * 2, 64 * DM * 2};
  cuuint32_t box[5] = {64, 8, 2, 4, 2};
  cuuint32_t estr[5] = {1, 1, 1, 1, 1};
  get_encode_fn()(&m, CU_TENSOR_MAP_DATA_TYPE_BFLOAT16, 5, const_cast<void*>(ptr), gdim, gstr, box, estr,
                  CU_TENSOR_MAP_INTERLEAVE_NONE, CU_TENSOR_MAP_SWIZZLE_128B, CU_TENSOR_MAP_L2_PROMOTION_L2_128B,
                  CU_TENSOR_MAP_FLOAT_OOB_FILL_NONE);
  return m;
}

}

extern "C" void kernel_launch(void* const* d_in, const int* in_sizes, int n_in, void* d_out, int out_size) {
  (void)in_sizes; (void)n_in; (void)out_size;
  void *p_o, *p_x;
  cudaGetSymbolAddress(&p_o, g_o);
  cudaGetSymbolAddress(&p_x, g_x);
  static bool attr_done = false;
  if (!attr_done) {
    cudaFuncSetAttribute(fused_kernel, cudaFuncAttributeMaxDynamicSharedMemorySize, SMEM_BYTES);
    attr_done = true;
  }
  Params P;
  P.in_x = (const __nv_bfloat16*)d_in[0];
  P.wqkv_p[0] = (const __nv_bfloat16*)d_in[1];
  P.wo_p[0] = (const __nv_bfloat16*)d_in[2];
  P.wqkv_p[1] = (const __nv_bfloat16*)d_in[4];
  P.wo_p[1] = (const __nv_bfloat16*)d_in[5];
  P.zero = 0;
  for (int L = 0; L < 5; L++) {
    const void* px = L == 0 ? (const void*)P.in_x : (L == 4 ? d_out : p_x);
    P.x[L] = make_map(px, S_LEN, DM);
    if (L < 4) P.xq[L] = (L & 1) ? make_map_q(px, 16, 8) : make_map_q(px, 8, 32);
  }
  P.o = make_map(p_o, S_LEN, DM);
  for (int t = 0; t < 2; t++) {
    P.wqkv[t] = make_map(P.wqkv_p[t], DM, NQKV);
    P.wqkv3[t] = make_map3(P.wqkv_p[t], DM, NQKV, 3, 1024);
    P.wo3[t] = make_map3(P.wo_p[t], DM, DM, 2, 64);
  }
    fused_kernel<<<NCTA, 512, SMEM_BYTES>>>(P);
}
```
